```python
import torch

def _softmax(x, axis=-1):
    return torch.softmax(x, dim=axis)
def _gelu(x):
    return torch.nn.functional.gelu(x, approximate="tanh")
def _silu(x):
    return torch.nn.functional.silu(x)
def _sigmoid(x):
    return torch.sigmoid(x)
def _layernorm(x, axis=-1, eps=1e-5):
    m = x.mean(dim=axis, keepdim=True)
    v = x.var(dim=axis, keepdim=True, unbiased=False)
    return (x - m) / torch.sqrt(v + eps)
def _scatter_add(tgt, idx, src, axis=0):
    return tgt.clone().index_add_(axis, idx, src)
def _segment_sum(src, seg, n):
    out = torch.zeros((n,) + src.shape[1:], dtype=src.dtype)
    return out.index_add_(0, seg, src)
def _pad(x, pw):
    flat = tuple(v for pair in reversed(pw) for v in pair)
    return torch.nn.functional.pad(x, flat)

kernel_name = 'standalone__w8a8_smoothquant_per_tensor_per_channel_int8_activations_weights__prompt'

def setup_inputs():

    _w = (lambda a: (lambda t: t.to(torch.bfloat16) if t.is_floating_point() else t)(torch.as_tensor(a)))
    B, S, D, F = 1, 2048, 1024, 3584
    x = abs((lambda *s: torch.randn(*s, dtype=torch.bfloat16) * 0.05)(B, S, D))
    w = (lambda *s: torch.randn(*s, dtype=torch.bfloat16) * 0.05)(D, F)
    x_min, x_max = float(x.min()), float(x.max())
    sx = (x_max - x_min) / 255.0 + 1e-6
    zx = int(torch.as_tensor(-128.0 - x_min / sx).round())
    qx = torch.clamp(torch.as_tensor(x / sx).round() + zx, -128, 127).to(torch.int32)
    sw = (torch.abs(w).amax(dim=0) / 127.0 + 1e-6).to(float)
    qw = torch.clamp(torch.as_tensor(w / sw[None, :]).round(), -127, 127).to(torch.int32)
    return {
        "qx": _w(qx),
        "qw": _w(qw),
        "scale_x": _w(torch.tensor(sx, dtype=float)),
        "zero_x": _w(torch.tensor(zx, dtype=torch.int32)),
        "scale_w": _w(sw),
        "bias": _w((lambda *s: torch.randn(*s, dtype=torch.bfloat16) * 0.05)(F)),
    }

def reference(qx, qw, scale_x, zero_x, scale_w, bias):
    dt = scale_w.dtype
    acc = torch.einsum("bsd,df->bsf", (lambda x, dt: x.to(dt))(qx, dt), (lambda x, dt: x.to(dt))(qw, dt))
    w_colsum = torch.sum((lambda x, dt: x.to(dt))(qw, dt), axis=0)
    acc = acc - (lambda x, dt: x.to(dt))(zero_x, dt) * w_colsum[None, None, :]
    return acc * scale_x * scale_w[None, None, :] + bias[None, None, :]
```

```cpp
#include <cuda_runtime.h>
#include <cuda.h>
#include <cuda_bf16.h>
#include <stdint.h>

namespace ra {

constexpr int CFG_D = 3;
constexpr int CFG_AMASK = 0x555F;
constexpr int CFG_PC0 = 0x44568AC;
constexpr int CFG_PC1 = 21;
constexpr int CFG_P0 = 650;
constexpr int CFG_P1 = 570;
constexpr int CFG_PX = 10;
constexpr int CFG_PF0 = 0;
constexpr int CFG_SLEEP = 200;
constexpr int CFG_NINIT = 4;
constexpr int CFG_WIN = 0;
constexpr int CFG_UNR = 1;
constexpr int CFG_FS = 32;
constexpr int CFG_FH = 8;
constexpr int CFG_PSL = 0;
constexpr int CFG_LW = 8;

constexpr int M_ = 2048, K_ = 1024, N_ = 3584;
constexpr int CS = 16, NCTA = 112, TN = 448;
constexpr int NRING = 7, NPERM = 3, NCONV = 4, NJOB = 26, NG = 56, NOUT = 4, D_ = CFG_D;

constexpr int SM_A = 0;
constexpr int SM_RING = 131072;
constexpr int SM_STG = SM_RING + NRING * 8192;
constexpr int SM_OUT = SM_STG + NPERM * 8192;
constexpr int SM_PAR = SM_OUT + NOUT * 4096;
constexpr int SM_SUM = SM_PAR + 1024;
constexpr int SM_BAR = SM_SUM + 256;
constexpr int B_FULL = 0, B_PAR = 64, B_AFREE = 72, B_OFREE = 76, B_SUM = 108, B_GO = 112, B_RAW = 128, B_FREE = 136, B_OFULL = 144, B_END = 148;
constexpr int SM_TOTAL = SM_BAR + B_END * 8;

constexpr int FS = CFG_FS;
struct __align__(2048) Scratch {
    uint4 a8[M_ * K_ / 16];
    uint4 b8[N_ * K_ / 16];
    unsigned cs[32 * TN / 2];
    unsigned flag[CS * FS + 64];
    unsigned epoch[128];
};
__device__ Scratch g_scratch;
constexpr int SM_ALLOC = SM_TOTAL;
static_assert(SM_ALLOC <= 232448, "");

__device__ __forceinline__ void mbar_init(uint32_t bar, uint32_t cnt) {
    asm volatile("mbarrier.init.shared::cta.b64 [%0], %1;" :: "r"(bar), "r"(cnt) : "memory");
}
__device__ __forceinline__ void mbar_expect_tx(uint32_t bar, uint32_t bytes) {
    asm volatile("mbarrier.arrive.expect_tx.shared::cta.b64 _, [%0], %1;" :: "r"(bar), "r"(bytes) : "memory");
}
__device__ __forceinline__ void mbar_arrive(uint32_t bar) {
    asm volatile("mbarrier.arrive.shared::cta.b64 _, [%0];" :: "r"(bar) : "memory");
}
__device__ __forceinline__ void mbar_arrive_cluster(uint32_t bar) {
    asm volatile("mbarrier.arrive.shared::cluster.b64 _, [%0];" :: "r"(bar) : "memory");
}
__device__ __forceinline__ void mbar_wait(uint32_t bar, uint32_t parity = 0) {
    asm volatile("{\n.reg .pred p;\n.reg .u32 c;\nmov.u32 c, 0;\n"
                 "WAIT_LOOP:\n"
                 "mbarrier.try_wait.parity.shared::cta.b64 p, [%0], %1;\n"
                 "@p bra WAIT_DONE;\n"
                 "add.u32 c, c, 1;\nsetp.lt.u32 p, c, 0x100000;\n"
                 "@p bra WAIT_LOOP;\n"
                 "trap;\n"
                 "WAIT_DONE:\n}" :: "r"(bar), "r"(parity) : "memory");
}
__device__ __forceinline__ void mbar_wait_cluster(uint32_t bar) {
    asm volatile("{\n.reg .pred p;\n.reg .u32 c;\nmov.u32 c, 0;\n"
                 "WAIT_LOOP:\n"
                 "mbarrier.try_wait.parity.relaxed.cluster.shared::cta.b64 p, [%0], 0;\n"
                 "@p bra WAIT_DONE;\n"
                 "add.u32 c, c, 1;\nsetp.lt.u32 p, c, 0x100000;\n"
                 "@p bra WAIT_LOOP;\n"
                 "trap;\n"
                 "WAIT_DONE:\n"
                 "fence.acquire.sync_restrict::shared::cluster.cluster;\n}" :: "r"(bar) : "memory");
}
__device__ __forceinline__ void mbar_wait2(uint32_t bar0, uint32_t bar1) {
    asm volatile("{\n.reg .pred p, q;\n.reg .u32 c;\nmov.u32 c, 0;\n"
                 "WAIT_LOOP:\n"
                 "mbarrier.try_wait.parity.shared::cta.b64 p, [%0], 0;\n"
                 "mbarrier.try_wait.parity.shared::cta.b64 q, [%1], 0;\n"
                 "and.pred p, p, q;\n"
                 "@p bra WAIT_DONE;\n"
                 "add.u32 c, c, 1;\nsetp.lt.u32 p, c, 0x100000;\n"
                 "@p bra WAIT_LOOP;\n"
                 "trap;\n"
                 "WAIT_DONE:\n}" :: "r"(bar0), "r"(bar1) : "memory");
}
__device__ __forceinline__ bool mbar_test(uint32_t bar) {
    uint32_t ok;
    asm volatile("{\n.reg .pred p;\nmbarrier.test_wait.parity.shared::cta.b64 p, [%1], 0;\nselp.u32 %0, 1, 0, p;\n}" : "=r"(ok) : "r"(bar) : "memory");
    return ok;
}
__device__ __forceinline__ bool mbar_test2(uint32_t bar0, uint32_t bar1) {
    uint32_t ok;
    asm volatile("{\n.reg .pred p, q;\nmbarrier.test_wait.parity.shared::cta.b64 p, [%1], 0;\n"
                 "mbarrier.test_wait.parity.shared::cta.b64 q, [%2], 0;\nand.pred p, p, q;\nselp.u32 %0, 1, 0, p;\n}"
                 : "=r"(ok) : "r"(bar0), "r"(bar1) : "memory");
    return ok;
}
__device__ __forceinline__ bool elect_one() {
    uint32_t ok;
    asm volatile("{\n.reg .pred p;\nelect.sync _|p, 0xffffffff;\nselp.u32 %0, 1, 0, p;\n}" : "=r"(ok));
    return ok;
}
__device__ __forceinline__ uint32_t mapa(uint32_t a, uint32_t cta) {
    uint32_t r;
    asm("mapa.shared::cluster.u32 %0, %1, %2;" : "=r"(r) : "r"(a), "r"(cta));
    return r;
}
__device__ __forceinline__ void st_async32(uint32_t a, uint32_t v, uint32_t bar) {
    asm volatile("st.async.shared::cluster.mbarrier::complete_tx::bytes.b32 [%0], %1, [%2];" :: "r"(a), "r"(v), "r"(bar) : "memory");
}
__device__ __forceinline__ unsigned ld_flag(const unsigned* p) {
    unsigned v;
    asm volatile("ld.relaxed.gpu.global.u32 %0, [%1];" : "=r"(v) : "l"(p) : "memory");
    return v;
}
__device__ __forceinline__ unsigned clk() { unsigned t; asm volatile("mov.u32 %0, %clock;" : "=r"(t)); return t; }
__device__ __forceinline__ uint4 lds128(uint32_t a) {
    uint4 v;
    asm volatile("ld.shared.v4.b32 {%0,%1,%2,%3}, [%4];" : "=r"(v.x), "=r"(v.y), "=r"(v.z), "=r"(v.w) : "r"(a) : "memory");
    return v;
}
__device__ __forceinline__ void sts128(uint32_t a, uint4 v) {
    asm volatile("st.shared.v4.b32 [%0], {%1,%2,%3,%4};" :: "r"(a), "r"(v.x), "r"(v.y), "r"(v.z), "r"(v.w) : "memory");
}
__device__ __forceinline__ uint32_t lds32(uint32_t a) {
    uint32_t v;
    asm volatile("ld.shared.b32 %0, [%1];" : "=r"(v) : "r"(a) : "memory");
    return v;
}
__device__ __forceinline__ uint2 lds64(uint32_t a) {
    uint2 v;
    asm volatile("ld.shared.v2.b32 {%0,%1}, [%2];" : "=r"(v.x), "=r"(v.y) : "r"(a) : "memory");
    return v;
}
__device__ __forceinline__ void sts32(uint32_t a, uint32_t v) {
    asm volatile("st.shared.b32 [%0], %1;" :: "r"(a), "r"(v) : "memory");
}
__device__ __forceinline__ void stg128(void* p, uint4 v) {
    asm volatile("st.global.v4.b32 [%0], {%1,%2,%3,%4};" :: "l"(p), "r"(v.x), "r"(v.y), "r"(v.z), "r"(v.w) : "memory");
}
__device__ __forceinline__ unsigned pack4(unsigned a, unsigned b, unsigned c, unsigned d) {
    unsigned lo, r;
    asm("cvt.pack.sat.s8.s32.b32 %0, %1, %2, 0;" : "=r"(lo) : "r"(d), "r"(c));
    asm("cvt.pack.sat.s8.s32.b32 %0, %1, %2, %3;" : "=r"(r) : "r"(b), "r"(a), "r"(lo));
    return r;
}
constexpr uint32_t DESC_A_HI = 256 >> 4;
constexpr uint32_t DESC_B_HI = 0x80000000u | (512 >> 4);
__device__ __forceinline__ void mma_unit2(int (&d)[64], int (&e)[64], uint32_t alo, uint32_t blo, int scale_d) {
    asm volatile("{\n.reg .pred p;\n.reg .b64 da, db;\nsetp.ne.b32 p, %130, 0;\n"
        "mov.b64 da, {%128, %131};\nmov.b64 db, {%129, %132};\n"
        "wgmma.mma_async.sync.aligned.m64n128k32.s32.s8.s8 "
        "{%0, %1, %2, %3, %4, %5, %6, %7, %8, %9, %10, %11, %12, %13, %14, %15, "
        "%16, %17, %18, %19, %20, %21, %22, %23, %24, %25, %26, %27, %28, %29, %30, %31, "
        "%32, %33, %34, %35, %36, %37, %38, %39, %40, %41, %42, %43, %44, %45, %46, %47, "
        "%48, %49, %50, %51, %52, %53, %54, %55, %56, %57, %58, %59, %60, %61, %62, %63}, "
        "da, db, p;\n"
        "add.s64 da, da, 128;\n"
        "wgmma.mma_async.sync.aligned.m64n128k32.s32.s8.s8 "
        "{%64, %65, %66, %67, %68, %69, %70, %71, %72, %73, %74, %75, %76, %77, %78, %79, "
        "%80, %81, %82, %83, %84, %85, %86, %87, %88, %89, %90, %91, %92, %93, %94, %95, "
        "%96, %97, %98, %99, %100, %101, %102, %103, %104, %105, %106, %107, %108, %109, %110, %111, "
        "%112, %113, %114, %115, %116, %117, %118, %119, %120, %121, %122, %123, %124, %125, %126, %127}, "
        "da, db, p;\n"
        "add.s64 da, da, 128;\nadd.s64 db, db, 2;\n"
        "wgmma.mma_async.sync.aligned.m64n128k32.s32.s8.s8 "
        "{%0, %1, %2, %3, %4, %5, %6, %7, %8, %9, %10, %11, %12, %13, %14, %15, "
        "%16, %17, %18, %19, %20, %21, %22, %23, %24, %25, %26, %27, %28, %29, %30, %31, "
        "%32, %33, %34, %35, %36, %37, %38, %39, %40, %41, %42, %43, %44, %45, %46, %47, "
        "%48, %49, %50, %51, %52, %53, %54, %55, %56, %57, %58, %59, %60, %61, %62, %63}, "
        "da, db, 1;\n"
        "add.s64 da, da, 128;\n"
        "wgmma.mma_async.sync.aligned.m64n128k32.s32.s8.s8 "
        "{%64, %65, %66, %67, %68, %69, %70, %71, %72, %73, %74, %75, %76, %77, %78, %79, "
        "%80, %81, %82, %83, %84, %85, %86, %87, %88, %89, %90, %91, %92, %93, %94, %95, "
        "%96, %97, %98, %99, %100, %101, %102, %103, %104, %105, %106, %107, %108, %109, %110, %111, "
        "%112, %113, %114, %115, %116, %117, %118, %119, %120, %121, %122, %123, %124, %125, %126, %127}, "
        "da, db, 1;\n"
        "wgmma.commit_group.sync.aligned;\n}\n"
        : "+r"(d[0]), "+r"(d[1]), "+r"(d[2]), "+r"(d[3]), "+r"(d[4]), "+r"(d[5]), "+r"(d[6]), "+r"(d[7]),
          "+r"(d[8]), "+r"(d[9]), "+r"(d[10]), "+r"(d[11]), "+r"(d[12]), "+r"(d[13]), "+r"(d[14]), "+r"(d[15]),
          "+r"(d[16]), "+r"(d[17]), "+r"(d[18]), "+r"(d[19]), "+r"(d[20]), "+r"(d[21]), "+r"(d[22]), "+r"(d[23]),
          "+r"(d[24]), "+r"(d[25]), "+r"(d[26]), "+r"(d[27]), "+r"(d[28]), "+r"(d[29]), "+r"(d[30]), "+r"(d[31]),
          "+r"(d[32]), "+r"(d[33]), "+r"(d[34]), "+r"(d[35]), "+r"(d[36]), "+r"(d[37]), "+r"(d[38]), "+r"(d[39]),
          "+r"(d[40]), "+r"(d[41]), "+r"(d[42]), "+r"(d[43]), "+r"(d[44]), "+r"(d[45]), "+r"(d[46]), "+r"(d[47]),
          "+r"(d[48]), "+r"(d[49]), "+r"(d[50]), "+r"(d[51]), "+r"(d[52]), "+r"(d[53]), "+r"(d[54]), "+r"(d[55]),
          "+r"(d[56]), "+r"(d[57]), "+r"(d[58]), "+r"(d[59]), "+r"(d[60]), "+r"(d[61]), "+r"(d[62]), "+r"(d[63]),
          "+r"(e[0]), "+r"(e[1]), "+r"(e[2]), "+r"(e[3]), "+r"(e[4]), "+r"(e[5]), "+r"(e[6]), "+r"(e[7]),
          "+r"(e[8]), "+r"(e[9]), "+r"(e[10]), "+r"(e[11]), "+r"(e[12]), "+r"(e[13]), "+r"(e[14]), "+r"(e[15]),
          "+r"(e[16]), "+r"(e[17]), "+r"(e[18]), "+r"(e[19]), "+r"(e[20]), "+r"(e[21]), "+r"(e[22]), "+r"(e[23]),
          "+r"(e[24]), "+r"(e[25]), "+r"(e[26]), "+r"(e[27]), "+r"(e[28]), "+r"(e[29]), "+r"(e[30]), "+r"(e[31]),
          "+r"(e[32]), "+r"(e[33]), "+r"(e[34]), "+r"(e[35]), "+r"(e[36]), "+r"(e[37]), "+r"(e[38]), "+r"(e[39]),
          "+r"(e[40]), "+r"(e[41]), "+r"(e[42]), "+r"(e[43]), "+r"(e[44]), "+r"(e[45]), "+r"(e[46]), "+r"(e[47]),
          "+r"(e[48]), "+r"(e[49]), "+r"(e[50]), "+r"(e[51]), "+r"(e[52]), "+r"(e[53]), "+r"(e[54]), "+r"(e[55]),
          "+r"(e[56]), "+r"(e[57]), "+r"(e[58]), "+r"(e[59]), "+r"(e[60]), "+r"(e[61]), "+r"(e[62]), "+r"(e[63])
        : "r"(alo), "r"(blo), "r"(scale_d), "n"(DESC_A_HI), "n"(DESC_B_HI) : "memory");
}
__device__ __forceinline__ void mma_unit1(int (&d)[64], uint32_t alo, uint32_t blo, int scale_d) {
    asm volatile("{\n.reg .pred p;\n.reg .b64 da, db;\nsetp.ne.b32 p, %66, 0;\n"
        "mov.b64 da, {%64, %67};\nmov.b64 db, {%65, %68};\n"
        "wgmma.mma_async.sync.aligned.m64n128k32.s32.s8.s8 "
        "{%0, %1, %2, %3, %4, %5, %6, %7, %8, %9, %10, %11, %12, %13, %14, %15, "
        "%16, %17, %18, %19, %20, %21, %22, %23, %24, %25, %26, %27, %28, %29, %30, %31, "
        "%32, %33, %34, %35, %36, %37, %38, %39, %40, %41, %42, %43, %44, %45, %46, %47, "
        "%48, %49, %50, %51, %52, %53, %54, %55, %56, %57, %58, %59, %60, %61, %62, %63}, "
        "da, db, p;\n"
        "add.s64 da, da, 128;\nadd.s64 db, db, 2;\n"
        "wgmma.mma_async.sync.aligned.m64n128k32.s32.s8.s8 "
        "{%0, %1, %2, %3, %4, %5, %6, %7, %8, %9, %10, %11, %12, %13, %14, %15, "
        "%16, %17, %18, %19, %20, %21, %22, %23, %24, %25, %26, %27, %28, %29, %30, %31, "
        "%32, %33, %34, %35, %36, %37, %38, %39, %40, %41, %42, %43, %44, %45, %46, %47, "
        "%48, %49, %50, %51, %52, %53, %54, %55, %56, %57, %58, %59, %60, %61, %62, %63}, "
        "da, db, 1;\n"
        "add.s64 da, da, 128;\nadd.s64 db, db, 510;\n"
        "wgmma.mma_async.sync.aligned.m64n128k32.s32.s8.s8 "
        "{%0, %1, %2, %3, %4, %5, %6, %7, %8, %9, %10, %11, %12, %13, %14, %15, "
        "%16, %17, %18, %19, %20, %21, %22, %23, %24, %25, %26, %27, %28, %29, %30, %31, "
        "%32, %33, %34, %35, %36, %37, %38, %39, %40, %41, %42, %43, %44, %45, %46, %47, "
        "%48, %49, %50, %51, %52, %53, %54, %55, %56, %57, %58, %59, %60, %61, %62, %63}, "
        "da, db, 1;\n"
        "add.s64 da, da, 128;\nadd.s64 db, db, 2;\n"
        "wgmma.mma_async.sync.aligned.m64n128k32.s32.s8.s8 "
        "{%0, %1, %2, %3, %4, %5, %6, %7, %8, %9, %10, %11, %12, %13, %14, %15, "
        "%16, %17, %18, %19, %20, %21, %22, %23, %24, %25, %26, %27, %28, %29, %30, %31, "
        "%32, %33, %34, %35, %36, %37, %38, %39, %40, %41, %42, %43, %44, %45, %46, %47, "
        "%48, %49, %50, %51, %52, %53, %54, %55, %56, %57, %58, %59, %60, %61, %62, %63}, "
        "da, db, 1;\n"
        "wgmma.commit_group.sync.aligned;\n}\n"
        : "+r"(d[0]), "+r"(d[1]), "+r"(d[2]), "+r"(d[3]), "+r"(d[4]), "+r"(d[5]), "+r"(d[6]), "+r"(d[7]),
          "+r"(d[8]), "+r"(d[9]), "+r"(d[10]), "+r"(d[11]), "+r"(d[12]), "+r"(d[13]), "+r"(d[14]), "+r"(d[15]),
          "+r"(d[16]), "+r"(d[17]), "+r"(d[18]), "+r"(d[19]), "+r"(d[20]), "+r"(d[21]), "+r"(d[22]), "+r"(d[23]),
          "+r"(d[24]), "+r"(d[25]), "+r"(d[26]), "+r"(d[27]), "+r"(d[28]), "+r"(d[29]), "+r"(d[30]), "+r"(d[31]),
          "+r"(d[32]), "+r"(d[33]), "+r"(d[34]), "+r"(d[35]), "+r"(d[36]), "+r"(d[37]), "+r"(d[38]), "+r"(d[39]),
          "+r"(d[40]), "+r"(d[41]), "+r"(d[42]), "+r"(d[43]), "+r"(d[44]), "+r"(d[45]), "+r"(d[46]), "+r"(d[47]),
          "+r"(d[48]), "+r"(d[49]), "+r"(d[50]), "+r"(d[51]), "+r"(d[52]), "+r"(d[53]), "+r"(d[54]), "+r"(d[55]),
          "+r"(d[56]), "+r"(d[57]), "+r"(d[58]), "+r"(d[59]), "+r"(d[60]), "+r"(d[61]), "+r"(d[62]), "+r"(d[63])
        : "r"(alo), "r"(blo), "r"(scale_d), "n"(DESC_A_HI), "n"(DESC_B_HI) : "memory");
}

__device__ __forceinline__ void wg_fence() { asm volatile("wgmma.fence.sync.aligned;" ::: "memory"); }
__device__ __forceinline__ void wg_commit() { asm volatile("wgmma.commit_group.sync.aligned;" ::: "memory"); }
template <int N> __device__ __forceinline__ void wg_wait() { asm volatile("wgmma.wait_group.sync.aligned %0;" :: "n"(N) : "memory"); }

struct Maps { CUtensorMap m[3]; };

constexpr int W0 = 16, C0 = 30;
static_assert(__builtin_popcount(CFG_AMASK) == 10 && (CFG_AMASK & 15) == 15 && CFG_AMASK < 1 << 15 && CFG_PC1 - 5 >= 16, "");
__host__ __device__ constexpr int unit_of(int wg, int s) { return wg ? (s < 16 - D_ ? D_ + 2 * s : s + 16) : (s < D_ ? s : 2 * s - D_ + 1); }

__host__ __device__ constexpr int bar_of(int u) { return u < D_ || u >= 32 - D_ ? u : ((u - D_) & 1) ? D_ + ((u - D_) >> 1) : 16 + ((u - D_) >> 1); }
constexpr uint32_t step_table(int wg) {
    uint32_t t = 0;
    for (int s = 0; s < 15; s++) t |= (uint32_t)(unit_of(wg, s + 1) - unit_of(wg, s) - 1) << s;
    return t;
}
constexpr uint32_t STEPS0 = step_table(0), STEPS1 = step_table(1);
__device__ __forceinline__ int sum_owner(int g) { return g < 8 ? (g & 4) | (g & 1) << 1 | (~g >> 1 & 1) : g; }
__device__ __forceinline__ int sum_group(int r) { return r < 8 ? (r & 4) | (~r & 1) << 1 | (r >> 1 & 1) : r; }
__device__ __forceinline__ int job_code(int p, int c) {
    const int p0 = (CFG_PC0 >> (4 * c)) & 15, p1 = c == 6 ? 99 : CFG_PC1 - c, q = p - (p > p0) - (p > p1);
    const int na = __popc(CFG_AMASK & ((1u << q) - 1)), code = (CFG_AMASK >> q & 1) ? na : W0 + q - na;
    return p == p0 ? C0 : p == p1 || (c == 6 && code == 9) ? C0 + 1 : code;
}
__device__ __forceinline__ uint32_t stg_slot(int sl) { return sl < 4 ? SM_STG + sl * 8192 : SM_A + (8 + sl) * 8192; }
static_assert(SM_OUT == SM_STG + 3 * 8192, "");
__device__ __forceinline__ int wjob(int code, int b) { return code < C0 ? (code - W0) * 16 + (b & 15) : 96 - (b & ~15) + (b & 15) + (code - C0) * NCTA; }
__device__ __forceinline__ int job_src(int code, int b) {
    const int r = b & 15, c = b >> 4;
    if (code < W0) {
        const int g = 7 * code + c - 5;
        return (r * 128 + (g & 3) * 32) | (g >> 2) << 13;
    }
    const int G = wjob(code, b), u = G >> 2, q = G & 3, f = bar_of(u);
    const int blk = u < 32 ? (f >> 4) * 2 + (q & 1) : u >> 3, step = u < 32 ? (f & 15) * 2 + (q >> 1) : G & 31;
    return ((code < C0 ? c : 7) * TN + blk * 64) | step << 17 | blk << 22;
}

__device__ __forceinline__ unsigned read_back(const void* p) {
    unsigned v = 0;
    asm volatile("ld.relaxed.gpu.global.u32 %0, [%1];" : "=r"(v) : "l"(p) : "memory");
    return v;
}
__device__ __forceinline__ void publish(unsigned* flag, unsigned seen, unsigned zero) {
    asm volatile("{\n.reg .pred p;\n.reg .u32 t;\nredux.sync.or.b32 t, %1, 0xffffffff;\nand.b32 t, t, %2;\nadd.u32 t, t, 1;\n"
                 "elect.sync _|p, 0xffffffff;\n@p red.relaxed.gpu.global.add.u32 [%0], t;\n}" :: "l"(flag), "r"(seen), "r"(zero) : "memory");
}
__device__ __forceinline__ int x_flag(int r, int g) { return r * FS + (g >> 3) + (g >> 2 & 1) * CFG_FH; }
__device__ __forceinline__ int job_due(int p, int code, int b) {
    const int phase = code < W0 ? b : (b & 15) * 7 + (b >> 4);
    return p < CFG_PX ? (p - 1) * CFG_P0 + phase * (CFG_P0 * 16 / NCTA) / 16
                      : (CFG_PX - 1) * CFG_P0 + (p - CFG_PX) * CFG_P1 + phase * (CFG_P1 * 16 / NCTA) / 16;
}

__device__ __forceinline__ void raw_load(const CUtensorMap* maps, int code, int src, uint32_t dst, uint32_t bar) {
    const bool w = code >= W0;
    const int c0 = src & 0xFFF, y = (src >> 12) & 0x3FF;
    asm volatile("cp.async.bulk.tensor.3d.shared::cluster.global.tile.mbarrier::complete_tx::bytes [%0], [%1, {%2, %3, %4}], [%5];"
                 :: "r"(dst), "l"(maps + (w ? 1 : 0)), "r"(w ? c0 : 0), "r"(y), "r"(w ? 0 : c0), "r"(bar) : "memory");
}

__device__ __forceinline__ uint32_t bf2_op_epi(int a, int b, uint32_t zc, uint32_t sx, uint32_t sw, uint32_t bi) {
    uint32_t v;
    float fa = __int2float_rn(a), fb = __int2float_rn(b);
    asm("cvt.rn.bf16x2.f32 %0, %1, %2;" : "=r"(v) : "f"(fb), "f"(fa));
    asm("sub.rn.bf16x2 %0, %0, %1;" : "+r"(v) : "r"(zc));
    asm("mul.rn.bf16x2 %0, %0, %1;" : "+r"(v) : "r"(sx));
    asm("mul.rn.bf16x2 %0, %0, %1;" : "+r"(v) : "r"(sw));
    asm("add.rn.bf16x2 %0, %0, %1;" : "+r"(v) : "r"(bi));
    return v;
}
__device__ __forceinline__ uint32_t zero_term(const unsigned (&sv)[4], float zxf) {
    int lo = 0, hi = 0;
#pragma unroll
    for (int h = 0; h < 4; h++) {
        const int l = (int)(short)(sv[h] & 0xFFFF);
        lo += l; hi += ((int)(sv[h] - (unsigned)l)) >> 16;
    }
    const float fl = __bfloat162float(__float2bfloat16_rn((float)lo)) * zxf, fh = __bfloat162float(__float2bfloat16_rn((float)hi)) * zxf;
    uint32_t z;
    asm("cvt.rn.bf16x2.f32 %0, %1, %2;" : "=r"(z) : "f"(fh), "f"(fl));
    return z;
}

template <bool SIDE>
__device__ __forceinline__ void load_x(Scratch* scr, uint32_t sb, int b, int h, int lane) {
    const uint32_t bars = sb + SM_BAR;
    const int r = b & 15;
    const unsigned tgt = (*(volatile unsigned*)&scr->epoch[b] + 1) * 4;
    const unsigned* f = scr->flag + r * FS + (lane & 7) + h * CFG_FH;
    unsigned todo = 0xFF, v = ld_flag(f);
    asm volatile("barrier.cluster.wait.aligned;" ::: "memory");
#pragma unroll 1
    for (int it = 0; todo; it++) {
        unsigned m = __ballot_sync(~0u, (int)(v - tgt) >= 0) & todo;
        if (CFG_PSL) __nanosleep(CFG_PSL);
        v = ld_flag(f);
        todo &= ~m;
        while (m) {
            const int sl = (__ffs(m) - 1) * 2 + h;
            m &= m - 1;
            if (!SIDE && sl >= 12) mbar_wait(bars + (B_AFREE - 12 + sl) * 8);
            if (elect_one()) {
                asm volatile("cp.async.bulk.shared::cluster.global.mbarrier::complete_tx::bytes [%0], [%1], %2, [%3];"
                             :: "r"(sb + SM_A + sl * 8192), "l"((const char*)scr->a8 + (r * 16 + sl) * 8192),
                                "r"(8192), "r"(bars + (B_FULL + sl) * 8) : "memory");
            }
        }
        if (it > (1 << 20)) __trap();
    }
}

__device__ __forceinline__ void store_out(const CUtensorMap* map, uint32_t sb, int b, int agent, int lane) {
    const uint32_t bars = sb + SM_BAR;
    const int r = b & 15, c = b >> 4;
    const uint32_t buf = sb + SM_OUT + agent * 4096, full = bars + (B_OFULL + agent) * 8;
    const int row = r * 128 + agent * 32;
#pragma unroll 1
    for (int t = 0; t < 7; t++) {
        asm volatile("{\n.reg .pred p;\n.reg .u32 c;\nmov.u32 c, 0;\n"
                     "WAIT_LOOP:\n"
                     "mbarrier.try_wait.parity.shared::cta.b64 p, [%4], %5;\n"
                     "@p bra WAIT_DONE;\n"
                     "add.u32 c, c, 1;\nsetp.lt.u32 p, c, 0x100000;\n"
                     "@p bra WAIT_LOOP;\n"
                     "trap;\n"
                     "WAIT_DONE:\n"
                     "fence.proxy.async.shared::cta;\n"
                     "elect.sync _|p, 0xffffffff;\n"
                     "@p cp.async.bulk.tensor.2d.global.shared::cta.tile.bulk_group [%0, {%1, %2}], [%3];\n"
                     "cp.async.bulk.commit_group;\n}"
                     :: "l"(map), "r"(c * TN + (((agent < 2 ? 0x6534120 : 0x6541230) >> (t * 4)) & 7) * 64), "r"(row), "r"(buf), "r"(full), "r"(t & 1) : "memory");
        asm volatile("cp.async.bulk.wait_group.read 0;" ::: "memory");
        if (t < 6 && elect_one()) mbar_arrive(bars + (B_OFREE + t * 4 + 4 + agent) * 8);
    }
}

template <int V> struct I { static constexpr int v = V; };
template <bool SIDE>
__device__ __forceinline__ void consume(Scratch* scr, const __nv_bfloat16* __restrict__ scale_w, const __nv_bfloat16* __restrict__ bias,
                                        const __nv_bfloat16* __restrict__ scale_x, uint32_t sb, int b, int warp, int lane) {
    constexpr int NR = SIDE ? NRING + NPERM : NRING;
    const uint32_t bars = sb + SM_BAR;
    const int c = b >> 4;
    constexpr uint32_t SD = 0x400 >> 4;
    if ((sb & 0xFFFFFF) != 0x400) __trap();
    const int wg = warp >> 2;
    const unsigned short sxr = __ldg((const unsigned short*)scale_x);
    const uint32_t sx2 = (uint32_t)sxr * 0x10001u;
    const int c0 = (warp & 3) * 16 + (lane >> 2) * 2;
    uint32_t sw[4], bi[4];
#pragma unroll
    for (int i = 0; i < 4; i++) {
        const int col = c * TN + (i < 2 ? wg * 2 + i : i == 2 ? 4 + wg : 6) * 64 + c0;
        sw[i] = __ldg((const uint32_t*)(scale_w + col));
        bi[i] = __ldg((const uint32_t*)(bias + col));
    }
    const uint32_t st0 = sb + SM_OUT + (lane & 3) * 256 + (((c0 >> 3) ^ ((lane & 3) * 2)) << 4) + (c0 & 7) * 2;
    constexpr uint32_t DX0 = (SD + (SM_A >> 4)) | (1 << 16), DW0 = (SD + (SM_RING >> 4)) | (8 << 16);
    asm volatile("barrier.cluster.wait.aligned;" ::: "memory");
    int a0[64], a1[64];
    constexpr int MUL = SIDE ? 4 : 2, NONE = 64 * MUL, BIAS = NR + 64 - NG;
    const uint32_t go = mapa(bars + B_GO * 8, lane & (SIDE ? 1 : 15)) - (64 - NG) * MUL;
    const int key = SIDE ? (lane < 2 ? lane * 4 : 1) : (lane < 16 ? (lane >> 2) * 2 : 1);
    int pend = NONE;
    uint32_t bb = bars + (B_FULL + wg * 16) * 8;
#define RELEASE() { if ((pend & (NONE + 8 - MUL)) == key) mbar_arrive_cluster(go + (pend & ~7)); }
    struct Par { uint32_t a, b, c, d; };
    auto load_par = [&](int blk, uint32_t swv, uint32_t biv) {
        mbar_wait_cluster(bars + (B_PAR + blk) * 8);
        const uint32_t zc = lds32(sb + SM_PAR + (blk * 64 + c0) * 2);
        const float sxf = __uint_as_float(sx2 << 16);
        const float s0 = sxf * __uint_as_float(swv << 16), s1 = sxf * __uint_as_float(swv & 0xFFFF0000u);
        Par P = {__float_as_uint(s0), __float_as_uint(s1), __float_as_uint(fmaf(-__uint_as_float(zc << 16), s0, __uint_as_float(biv << 16))),
                 __float_as_uint(fmaf(-__uint_as_float(zc & 0xFFFF0000u), s1, __uint_as_float(biv & 0xFFFF0000u)))};
        asm volatile("" : "+r"(P.a), "+r"(P.b), "+r"(P.c), "+r"(P.d));
        return P;
    };
    auto drain = [&](const int (&a)[64], auto Q, int t, const Par& P) {
#pragma unroll
        for (int q = Q.v; q < Q.v + 2; q++) {
            const bool free = mbar_test(bars + (B_OFREE + t * 4 + q) * 8);
            uint32_t v[8];
#pragma unroll
            for (int j = 0; j < 8; j++) {
                const int o = q * 16 + (j >> 1) * 4 + (j & 1);
                asm("cvt.rn.bf16x2.f32 %0, %1, %2;" : "=r"(v[j]) : "f"(fmaf(__int2float_rn(a[o + 2]), __uint_as_float(P.b), __uint_as_float(P.d))),
                    "f"(fmaf(__int2float_rn(a[o]), __uint_as_float(P.a), __uint_as_float(P.c))));
            }
            if (!free) mbar_wait(bars + (B_OFREE + t * 4 + q) * 8);
#pragma unroll
            for (int j = 0; j < 8; j++) sts32((st0 ^ ((j & 1) * 16)) + q * 4096 + (j >> 1) * 1024 + (j & 1) * 128, v[j]);
            __syncwarp();
            if (lane == 0) mbar_arrive(bars + (B_OFULL + q) * 8);
        }
    };
    wg_fence();
    {
        uint32_t tbl = wg ? STEPS1 : STEPS0;
        uint32_t ba = bars + B_FULL * 8;
        int u = MUL * (wg * D_ + BIAS);
        uint32_t dw = DW0 + wg * D_ * 512;
        static_assert(D_ < NR, "");
        mbar_wait2(ba, bb);
#pragma unroll 1
        for (uint32_t dx = DX0;;) {
            mma_unit2(a0, a1, dw, dx, dx - DX0);
            dx += 512; ba += 8; bb += 8;
            const bool ready = mbar_test2(ba, bb);
            wg_wait<1>();
            RELEASE()
            pend = u;
            if (dx == DX0 + 16 * 512) break;
            u += MUL + (tbl & 1) * MUL;
            dw += 512 + (tbl & 1) * 512;
            if (dw >= DW0 + NR * 512) dw -= NR * 512;
            tbl >>= 1;
            if (!ready && !mbar_test2(ba, bb)) {
                wg_wait<0>();
                RELEASE()
                pend = NONE;
                mbar_wait2(ba, bb);
            }
        }
    }
    Par P0 = load_par(2 * wg, sw[0], bi[0]);
    const Par P1 = load_par(2 * wg + 1, sw[1], bi[1]);
    wg_wait<0>();
    RELEASE()
#pragma unroll 1
    for (int ph = 0; ph < 3; ph++) {
        if (ph == 1) drain(a1, I<0>(), 2 + 2 * wg, P1);
        if (ph + wg == 1) drain(a1, I<2>(), 3 - 2 * wg, P1);
        drain(a0, I<0>(), wg ? 4 * ph + 1 : 3 * ph, P0);
        const int u0 = 32 + ph * 16 + wg * 8;
        uint32_t dw = DW0 + (ph ? 48 % NR : wg ? 40 % NR : 32 % NR) * 512;
        bb = bars + (B_FULL + u0) * 8;
        const bool first = mbar_test(bb);
        drain(a0, I<2>(), ph ? 2 * ph + 2 + wg : 2 * wg, P0);
        if (ph + wg == 2) break;
        pend = NONE;
        if (!first) mbar_wait(bb);
        wg_fence();
        constexpr int UNR = CFG_UNR;
#pragma unroll UNR
        for (int n = 0; n < 8; n++) {
            mma_unit1(a0, dw, DX0 + n * 1024, n);
            const bool ready = mbar_test(bb + n * 8 + 8) || n == 7;
            wg_wait<1>();
            RELEASE()
            pend = MUL * (u0 + BIAS + n);
            dw += 512;
            if (dw == DW0 + NR * 512) dw = DW0;
            if (!ready && !mbar_test(bb + n * 8 + 8)) {
                wg_wait<0>();
                RELEASE()
                pend = NONE;
                mbar_wait(bb + n * 8 + 8);
            }
        }
        P0 = load_par(4 + 2 * ph + wg, ph ? sw[3] : sw[2], ph ? bi[3] : bi[2]);
        wg_wait<0>();
        RELEASE()
    }
    if (threadIdx.x == 128) asm volatile("red.relaxed.gpu.global.add.u32 [%0], 1;" :: "l"(scr->epoch + b) : "memory");
}

__global__ void __cluster_dims__(CS, 1, 1) __launch_bounds__(512, 1)
w8a8_kernel(const char* __restrict__ qx, Scratch* scr, const __nv_bfloat16* __restrict__ scale_w,
            const __nv_bfloat16* __restrict__ bias, const __nv_bfloat16* __restrict__ scale_x, const int* __restrict__ zero_x,
            const __grid_constant__ Maps maps) {
    extern __shared__ __align__(1024) unsigned char smem_raw[];
    const uint32_t sb = (uint32_t)__cvta_generic_to_shared(smem_raw);
    const uint32_t bars = sb + SM_BAR;
    const int warp = __shfl_sync(~0u, threadIdx.x >> 5, 0), lane = threadIdx.x & 31;
    const int b = blockIdx.x, r = b & 15, c = b >> 4;
    const unsigned t0 = clk() + CFG_PF0;
    if (warp >= 4 && warp < 8) {
        static_assert(CFG_NINIT <= 4, "");
        asm volatile("barrier.cluster.arrive.relaxed.aligned;" ::: "memory");
        const int g = 7 * (warp - 4) + c - 5;
        if (g >= 0) {
            const char* src = qx + (r * 128 + (g & 3) * 32 + (lane >> 4)) * (K_ * 4) + (g >> 2) * 256 + (lane & 15) * 16;
            unsigned* d = (unsigned*)(scr->a8 + (r * 64 + g) * 128) + lane;
            while ((int)(clk() - t0) < job_due(warp - 4, 0, b)) ;
            uint4 v[16];
            unsigned o[16];
#pragma unroll
            for (int i = 0; i < 16; i++)
                asm volatile("ld.global.nc.L1::no_allocate.v4.b32 {%0,%1,%2,%3}, [%4];" : "=r"(v[i].x), "=r"(v[i].y), "=r"(v[i].z), "=r"(v[i].w) : "l"(src + i * (2 * K_ * 4)));
#pragma unroll
            for (int i = 0; i < 16; i++) {
                o[i] = pack4(v[i].x, v[i].y, v[i].z, v[i].w);
                asm volatile("st.global.b32 [%0], %1;" :: "l"((unsigned*)((uintptr_t)d ^ ((i & 3) * 16)) + i * 32), "r"(o[i]) : "memory");
            }
            asm volatile("fence.proxy.async.global;" ::: "memory");
            __syncwarp();
            publish(scr->flag + x_flag(r, g), read_back(d + lane * 15), blockIdx.y);
        }
    } else if (warp == 11) {
        if (elect_one()) {
#pragma unroll
            for (int i = 0; i < 16; i++) mbar_init(bars + (B_RAW + i) * 8, 1);
            asm volatile("fence.mbarrier_init.release.cluster;" ::: "memory");
        }
        __syncwarp();
        if (lane < 12) mbar_expect_tx(bars + (B_RAW + lane) * 8, lane >> 2 == 1 ? 8192 : 0);
        __syncwarp();
        asm volatile("bar.arrive 1, 384;" ::: "memory");
    } else {
        if (warp == 12) asm volatile("griddepcontrol.launch_dependents;");
        if (warp == 13 && elect_one()) {
#pragma unroll
            for (int i = 0; i < 3; i++) asm volatile("prefetch.tensormap [%0];" :: "l"(maps.m + i) : "memory");
        }
        asm volatile("bar.sync 1, 384;" ::: "memory");
        if (warp < CFG_NINIT) {
#pragma unroll 1
            for (int w = warp; w < B_RAW / 16; w += CFG_NINIT) {
                if (elect_one()) {
                    const uint32_t cnt = w < B_GO / 16 ? 1 : 4 * CS + 1;
#pragma unroll
                    for (int i = 0; i < 16; i++) mbar_init(bars + (w * 16 + i) * 8, cnt);
                }
                __syncwarp();
                const int i = w * 16 + lane;
                if (lane < 16 && i < B_AFREE) mbar_expect_tx(bars + i * 8, i < 16 ? 16384 : i < B_PAR ? 8192 : 128);
                if (w == B_GO / 16 && 4 * lane + (r >> 2) < NRING)
                    asm volatile("mbarrier.arrive.shared::cta.b64 _, [%0], %1;" :: "r"(bars + i * 8), "r"(4 * CS) : "memory");
            }
            if (warp == (B_SUM / 16) % CFG_NINIT) {
                if (elect_one()) {
#pragma unroll
                    for (int i = 0; i < NOUT; i++) mbar_init(bars + (B_OFULL + i) * 8, 4);
                    mbar_init(bars + B_SUM * 8, r < 8 ? 1 : 3);
                    mbar_expect_tx(bars + B_SUM * 8, r < 8 ? 32 * 64 : 30 * 64);
                }
                asm volatile("st.shared.v2.b32 [%0], {%1, %1};" :: "r"(sb + SM_SUM + lane * 8), "r"(0) : "memory");
                asm volatile("fence.release.sync_restrict::shared::cta.cluster;" ::: "memory");
            }
            asm volatile("fence.mbarrier_init.release.cluster;" ::: "memory");
        }
    }
    if (warp < 4 || warp >= 8) asm volatile("barrier.cluster.arrive.relaxed.aligned;" ::: "memory");

    if (warp >= 8) {
        asm volatile("setmaxnreg.dec.sync.aligned.u32 88;");
        int agent = -1;
        int mcode = 0, msrc = 0;
        if (warp >= 11) { mcode = job_code(min(lane, NJOB - 1), c); msrc = job_src(mcode, b) | mcode << 25; }
        if (warp >= 16 - NCONV) {
            const int cw = warp - (16 - NCONV);
            const int njob = NJOB - (c == 6);
            const int mdst = mcode < W0 ? (r * 64 + 7 * mcode + c - 5) | x_flag(r, 7 * mcode + c - 5) << 12
                                        : (1024 + (mcode < C0 ? c : 7) * 224 + wjob(mcode, b)) | (CS * FS + (wjob(mcode, b) >> 2)) << 12;
            const int c4 = lane & 3, ln = (lane >> 2) * 2 + (c4 >> 1);
            const uint32_t rdA = ln * 128 + ((((c4 & 1) << 2) ^ (ln & 7)) << 4);
            const int wrA = ((lane >> 2) * 4 + (c4 ^ ((lane >> 3) & 3))) * 16;
            const int wrB = ((lane >> 3) * 32 + (lane & 7)) * 16;
            const unsigned zero = blockIdx.y;
            asm volatile("barrier.cluster.wait.aligned;" ::: "memory");
#pragma unroll 1
            for (int p = 4 + cw; p < njob; p += p < 16 ? 4 : 3) {
                const int src = __shfl_sync(~0u, msrc, p), dst = __shfl_sync(~0u, mdst, p), nsrc = __shfl_sync(~0u, msrc, p + 3);
                const int code = src >> 25, sl = p < 16 ? p & 7 : cw;
                const uint32_t s = sb + stg_slot(sl);
                char* const tile = (char*)scr + (dst & 0xFFF) * 2048;
                char* d = tile + (code < W0 ? wrA : wrB);
                const char* rb = tile + lane * 64;
                unsigned* flag = scr->flag + (dst >> 12);
                uint32_t a0 = s + (code < W0 ? rdA : lane * 8);
                uint32_t sig = lane == 0 ? (code >= W0 && code < C0 ? B_GO - W0 + code : 0)
                             : p == 11 ? (lane <= NOUT ? B_OFREE - 1 + lane : 0)
                             : p < 16 && lane == 1 ? ((p >> 2) == 3 ? B_AFREE + cw : B_FREE + sl) : 0;
                if (sig) sig = bars + sig * 8;
                asm volatile("" : "+l"(d), "+l"(rb), "+l"(flag), "+r"(a0), "+r"(sig));
                mbar_wait(bars + (B_RAW + sl) * 8, p < 16 ? p >> 3 : (p - cw) & 1);
                if (code < W0) {
                    unsigned o[16];
#pragma unroll
                    for (int i = 0; i < 16; i += 2) {
                        const uint32_t a = i >= 2 * CFG_LW ? a0 | (o[i - 2 * CFG_LW + 1] & zero) : a0;
                        const uint4 u = lds128((a ^ ((i & 3) * 16)) + (i >> 2) * 2048), w = lds128((a ^ ((i & 3) * 16 + 16)) + (i >> 2) * 2048);
                        o[i] = pack4(u.x, u.y, u.z, u.w);
                        o[i + 1] = pack4(w.x, w.y, w.z, w.w);
                        if (i & 2) stg128(d + (i >> 2) * 512, make_uint4(o[i - 2], o[i - 1], o[i], o[i + 1]));
                    }
                    asm volatile("fence.proxy.async.global;" ::: "memory");
                    __syncwarp();
                    const unsigned seen = read_back(rb);
                    if (sig) mbar_arrive(sig);
                    publish(flag, seen, zero);
                } else {
                    unsigned o[16];
#pragma unroll
                    for (int i = 0; i < 8; i++) {
                        const uint32_t a = (i >= CFG_LW ? a0 | (o[i - CFG_LW] & zero) : a0) + i * 1024;
                        const uint2 v0 = lds64(a), v1 = lds64(a + 256), v2 = lds64(a + 512), v3 = lds64(a + 768);
                        o[i] = pack4(v0.x, v1.x, v2.x, v3.x);
                        o[8 + i] = pack4(v0.y, v1.y, v2.y, v3.y);
                        if ((i & 3) == 3) {
                            stg128(d + (i >> 2) * 128, make_uint4(o[i - 3], o[i - 2], o[i - 1], o[i]));
                            stg128(d + (i >> 2) * 128 + 256, make_uint4(o[i + 5], o[i + 6], o[i + 7], o[i + 8]));
                        }
                    }
                    asm volatile("fence.proxy.async.global;" ::: "memory");
                    __syncwarp();
                    if (sig) mbar_arrive(sig);
                    if (p >= 16 && p + 3 < njob && elect_one()) {
                        mbar_expect_tx(bars + (B_RAW + sl) * 8, 8192);
                        raw_load(maps.m, W0, nsrc, s, bars + (B_RAW + sl) * 8);
                    }
                    int cs[4];
#pragma unroll
                    for (int i = 0; i < 4; i++)
                        cs[i] = __dp4a((int)o[4 * i], 0x01010101, __dp4a((int)o[4 * i + 1], 0x01010101,
                                __dp4a((int)o[4 * i + 2], 0x01010101, __dp4a((int)o[4 * i + 3], 0x01010101, 0))));
                    const unsigned csv = cs[0] + cs[1] + (cs[2] + cs[3]) * 65536;
                    const int blk = (src >> 22) & 7;
                    if (code < C0) {
                        const int own = sum_owner(blk * 2 + (lane >> 4));
                        const uint32_t so = SM_SUM + ((src >> 20) & 3) * 64 + (lane & 15) * 4;
                        if (own != r) {
                            const uint32_t ro = mapa(sb, own);
                            asm volatile("red.async.relaxed.cluster.shared::cluster.mbarrier::complete_tx::bytes.add.u32 [%0], %1, [%2];"
                                         :: "r"(ro + so), "r"(csv), "r"(ro + SM_BAR + B_SUM * 8) : "memory");
                        } else asm volatile("red.relaxed.cluster.shared::cta.add.u32 [%0], %1;" :: "r"(sb + so), "r"(csv) : "memory");
                        __syncwarp();
                        if (own == r && (lane & 15) == 0) mbar_arrive(bars + B_SUM * 8);
                    } else {
                        unsigned* csp = scr->cs + ((src >> 17) & 31) * (TN / 2) + blk * 32 + lane;
                        asm volatile("st.global.u32 [%0], %1;" :: "l"(csp), "r"(csv) : "memory");
                        publish(flag, read_back(rb) | read_back(csp), zero);
                    }
                }
                __syncwarp();
                if (p == 15) break;
            }
            if (cw == 3) agent = 3;
        } else if (warp == 11) {
            const int tau = job_due(lane, mcode, b);
#pragma unroll 1
            for (int p = 4; p < 19; p++) {
                const int desc = __shfl_sync(~0u, msrc, p), due = __shfl_sync(~0u, tau, p), sl = p & 7;
                if (p >= 8) {
                    mbar_wait(bars + (B_FREE + sl) * 8, p >> 4);
                    if (elect_one()) mbar_expect_tx(bars + (B_RAW + sl) * 8, 8192);
                }
                if (CFG_WIN && p >= CFG_WIN) mbar_wait(bars + (B_RAW + ((p - CFG_WIN) & 7)) * 8, (p - CFG_WIN) >> 3);
                for (int rem; (rem = due - (int)(clk() - t0)) > 0;) if (rem > CFG_SLEEP) __nanosleep(CFG_SLEEP / 4);
                if (elect_one()) raw_load(maps.m, desc >> 25, desc, sb + stg_slot(sl), bars + (B_RAW + sl) * 8);
            }
            asm volatile("barrier.cluster.wait.aligned;" ::: "memory");
            agent = 2;
        } else if (warp == 9) {
            const float zxf = __bfloat162float(__float2bfloat16_rn((float)__ldg(zero_x)));
            const int grp = sum_group(r), zi = r < 8 ? 7 : r | 1;
            asm volatile("barrier.cluster.wait.aligned;" ::: "memory");
            const char* src = (const char*)scr->b8 + (c * 224 + r) * 2048;
#pragma unroll 1
            for (int i = 0, slot = r >> 2; i < NG / 4; i++) {
                asm volatile("{\n.reg .pred p;\n.reg .u32 c;\nmov.u32 c, 0;\n"
                             "WAIT_LOOP:\n"
                             "mbarrier.try_wait.parity.shared::cta.b64 p, [%4], 0;\n"
                             "@p bra WAIT_DONE;\n"
                             "add.u32 c, c, 1;\nsetp.lt.u32 p, c, 0x100000;\n"
                             "@p bra WAIT_LOOP;\n"
                             "trap;\n"
                             "WAIT_DONE:\n"
                             "elect.sync _|p, 0xffffffff;\n"
                             "@p cp.async.bulk.shared::cluster.global.mbarrier::complete_tx::bytes.multicast::cluster [%0], [%1], 2048, [%2], %3;\n}"
                             :: "r"(sb + SM_RING + slot * 8192 + (r & 3) * 2048), "l"(src + i * 32768),
                                "r"(bars + (B_FULL + bar_of(4 * i + (r >> 2))) * 8), "h"((uint16_t)0xFFFF), "r"(bars + (B_GO + i) * 8) : "memory");
                slot += slot >= NRING - 4 ? 4 - NRING : 4;
                if (i == zi) {
                    mbar_wait_cluster(bars + B_SUM * 8);
                    unsigned sv[4];
#pragma unroll
                    for (int h = 0; h < 4; h++) sv[h] = lds32(sb + SM_SUM + h * 64 + (lane & 15) * 4);
                    const uint32_t z = zero_term(sv, zxf);
#pragma unroll 1
                    for (int k = 0; k < 8; k++) {
                        const uint32_t rb = mapa(sb, k * 2 + (lane >> 4));
                        st_async32(rb + SM_PAR + grp * 64 + (lane & 15) * 4, z, rb + SM_BAR + (B_PAR + (grp >> 1)) * 8);
                    }
                }
            }
        } else {
            const int h = (warp >> 1) & 1;
            load_x<false>(scr, sb, b, h, lane);
            agent = h;
        }
        if (agent >= 0) {
            store_out(maps.m + 2, sb, b, agent, lane);
        }
    } else {
        asm volatile("setmaxnreg.inc.sync.aligned.u32 168;");
        consume<false>(scr, scale_w, bias, scale_x, sb, b, warp, lane);
    }
}

__global__ void __cluster_dims__(2, 1, 1) __launch_bounds__(512, 1)
w8a8_side(Scratch* scr, const __nv_bfloat16* __restrict__ scale_w, const __nv_bfloat16* __restrict__ bias,
          const __nv_bfloat16* __restrict__ scale_x, const int* __restrict__ zero_x, const __grid_constant__ CUtensorMap map) {
    extern __shared__ __align__(1024) unsigned char smem_raw[];
    const uint32_t sb = (uint32_t)__cvta_generic_to_shared(smem_raw);
    const uint32_t bars = sb + SM_BAR;
    const int warp = __shfl_sync(~0u, threadIdx.x >> 5, 0), lane = threadIdx.x & 31;
    const int b = NCTA + blockIdx.x, rank = b & 1;
    constexpr int NR = NRING + NPERM;
    if (warp < B_OFULL / 16) {
        if (elect_one()) {
            const uint32_t cnt = warp < B_GO / 16 ? 1 : 9;
#pragma unroll
            for (int i = 0; i < 16; i++) mbar_init(bars + (warp * 16 + i) * 8, cnt);
        }
        __syncwarp();
        const int i = warp * 16 + lane;
        if (lane < 16 && i < B_PAR) mbar_expect_tx(bars + i * 8, i < 16 ? 16384 : 8192);
        if (lane < 16 && i >= B_OFREE && i < B_OFREE + NOUT) mbar_arrive(bars + i * 8);
        if (warp == B_GO / 16 && 2 * lane + rank < NR)
            asm volatile("mbarrier.arrive.shared::cta.b64 _, [%0], %1;" :: "r"(bars + i * 8), "r"(8) : "memory");
        asm volatile("fence.mbarrier_init.release.cluster;" ::: "memory");
    } else if (warp == B_OFULL / 16) {
        if (elect_one()) {
#pragma unroll
            for (int i = 0; i < NOUT; i++) mbar_init(bars + (B_OFULL + i) * 8, 4);
            asm volatile("fence.mbarrier_init.release.cluster;" ::: "memory");
        }
        __syncwarp();
    } else if (warp == 13 && elect_one()) asm volatile("prefetch.tensormap [%0];" :: "l"(&map) : "memory");
    asm volatile("barrier.cluster.arrive.relaxed.aligned;" ::: "memory");

    if (warp >= 8) {
        asm volatile("setmaxnreg.dec.sync.aligned.u32 88;");
        int agent = -1;
        if (warp == 8 || warp == 10) {
            const int h = (warp >> 1) & 1;
            load_x<true>(scr, sb, b, h, lane);
            agent = h;
        } else if (warp == 11) {
            const unsigned tgt = (*(volatile unsigned*)&scr->epoch[b] + 1) * 4;
            const unsigned* f = scr->flag + CS * FS + lane;
            unsigned todo0 = ~0u, todo1 = 0xFFFFFF, v0 = ld_flag(f), v1 = ld_flag(f + 32);
            bool par = lane >= 3;
            asm volatile("barrier.cluster.wait.aligned;" ::: "memory");
#pragma unroll 1
            for (int it = 0; todo0 | todo1; it++) {
                const unsigned m0 = __ballot_sync(~0u, (int)(v0 - tgt) >= 0) & todo0, m1 = __ballot_sync(~0u, (int)(v1 - tgt) >= 0) & todo1;
                v0 = ld_flag(f); v1 = ld_flag(f + 32);
                todo0 &= ~m0; todo1 &= ~m1;
                if ((lane & 1) == rank) {
                    if (m0 >> lane & 1) mbar_arrive(bars + (B_GO + (lane >> 1)) * 8);
                    if (m1 >> lane & 1) mbar_arrive(bars + (B_GO + 16 + (lane >> 1)) * 8);
                }
                if (!par && !(lane ? todo1 << (32 - lane * 16) : todo0)) { par = true; mbar_arrive(bars + (B_AFREE + lane) * 8); }
                if (it > (1 << 20)) __trap();
            }
        } else if (warp == 9) {
            asm volatile("barrier.cluster.wait.aligned;" ::: "memory");
            const char* src = (const char*)scr->b8 + (7 * NG + rank) * 8192;
#pragma unroll 1
            for (int i = 0, slot = rank; i < NG / 2; i++) {
                asm volatile("{\n.reg .pred p;\n.reg .u32 c;\nmov.u32 c, 0;\n"
                             "WAIT_LOOP:\n"
                             "mbarrier.try_wait.parity.shared::cta.b64 p, [%4], 0;\n"
                             "@p bra WAIT_DONE;\n"
                             "add.u32 c, c, 1;\nsetp.lt.u32 p, c, 0x100000;\n"
                             "@p bra WAIT_LOOP;\n"
                             "trap;\n"
                             "WAIT_DONE:\n"
                             "elect.sync _|p, 0xffffffff;\n"
                             "@p cp.async.bulk.shared::cluster.global.mbarrier::complete_tx::bytes.multicast::cluster [%0], [%1], 8192, [%2], %3;\n}"
                             :: "r"(sb + SM_RING + slot * 8192), "l"(src + i * 16384),
                                "r"(bars + (B_FULL + bar_of(2 * i + rank)) * 8), "h"((uint16_t)3), "r"(bars + (B_GO + i) * 8) : "memory");
                slot += slot >= NR - 2 ? 2 - NR : 2;
            }
        } else if (warp == 12 || warp == 15) {
            const float zxf = __bfloat162float(__float2bfloat16_rn((float)__ldg(zero_x)));
            asm volatile("barrier.cluster.wait.aligned;" ::: "memory");
#pragma unroll 1
            for (int blk = warp & 2; blk < 7; blk += 4) {
                const int w = min(blk * 32 + lane * 2, TN / 2 - 2);
                mbar_wait(bars + (B_AFREE + max(blk / 2 - 1, 0)) * 8);
                uint2 v[32];
                unsigned s0[4], s1[4];
#pragma unroll
                for (int k = 0; k < 32; k++) v[k] = __ldcg((const uint2*)(scr->cs + k * (TN / 2) + w));
#pragma unroll
                for (int h = 0; h < 4; h++) {
                    s0[h] = s1[h] = 0;
#pragma unroll
                    for (int k = 0; k < 8; k++) { s0[h] += v[8 * h + k].x; s1[h] += v[8 * h + k].y; }
                }
                sts32(sb + SM_PAR + w * 4, zero_term(s0, zxf));
                sts32(sb + SM_PAR + w * 4 + 4, zero_term(s1, zxf));
                __syncwarp();
                if (lane < 2) mbar_arrive(bars + (B_PAR + blk + lane) * 8);
            }
        } else {
            asm volatile("barrier.cluster.wait.aligned;" ::: "memory");
            agent = warp - 11;
        }
        if (agent >= 0) store_out(&map, sb, b, agent, lane);
    } else {
        asm volatile("setmaxnreg.inc.sync.aligned.u32 168;");
        consume<true>(scr, scale_w, bias, scale_x, sb, b, warp, lane);
    }
}

}

typedef CUresult (*EncodeFn)(CUtensorMap*, CUtensorMapDataType, cuuint32_t, void*, const cuuint64_t*, const cuuint64_t*,
                             const cuuint32_t*, const cuuint32_t*, CUtensorMapInterleave, CUtensorMapSwizzle,
                             CUtensorMapL2promotion, CUtensorMapFloatOOBfill);

namespace w8 {

constexpr int M_ = 2048, K_ = 1024, N_ = 3584;
constexpr int WA = 160, WB = 64;
constexpr int TN = 2 * WA + 2 * WB;
static_assert(TN == 448, "");
constexpr int X1 = 13;
constexpr int NSLOT = 7, SLOT = WA * 64;
constexpr int NSTG = 3, PFD = 700, NCONV = 5;
constexpr int NU = 48;
constexpr int UX = 32 + NSLOT;
constexpr int NJOB = 22;
constexpr int NCTA = 128;

constexpr int nA = 64, nWA = WA / 4, nWB = WB / 4;
constexpr int SEG1 = X1 * (nA + 2 * nWA);
constexpr int SEG2 = SEG1 + (16 - X1) * (nA + nWA);
constexpr int SEG3 = SEG2 + (16 - X1) * nWA;
constexpr int SEG4 = SEG3 + 16 * nWB;
constexpr int SEG5 = SEG4 + 16 * nWB;
static_assert(SEG5 == NJOB * NCTA, "");

constexpr int SM_A = 0;
constexpr int SM_RING = 131072;
constexpr int SM_STG = SM_RING + NSLOT * SLOT;
constexpr int SM_PAR = SM_STG + NSTG * 8192;
constexpr int SM_BAR = SM_PAR + 3 * TN * 2;
constexpr int B_FULLB = 0, B_FULLA = 48, B_GO = 64, B_PAR = 88, B_PSTEP = 92, B_AFREE = 100, B_NINIT = 102, B_FULLS = 102, B_END = 108;
constexpr int SM_TOTAL = SM_BAR + B_END * 8;
static_assert(SM_TOTAL <= 232448, "");

__device__ uint4 g_a8[M_ * K_ / 16];
__device__ uint4 g_b8[N_ * K_ / 16];
__device__ uint4 g_cs[16 * N_ * 2 / 16];
__device__ unsigned g_flag[16 * 16 + 8 * 64];
__device__ unsigned g_epoch[NCTA];
__device__ unsigned g_sink;
constexpr int SM_ALLOC = SM_TOTAL;

__device__ __forceinline__ void mbar_init(uint32_t bar, uint32_t cnt) {
    asm volatile("mbarrier.init.shared::cta.b64 [%0], %1;" :: "r"(bar), "r"(cnt) : "memory");
}
__device__ __forceinline__ void mbar_expect_tx(uint32_t bar, uint32_t bytes) {
    asm volatile("mbarrier.arrive.expect_tx.shared::cta.b64 _, [%0], %1;" :: "r"(bar), "r"(bytes) : "memory");
}
__device__ __forceinline__ void mbar_arrive(uint32_t bar) {
    asm volatile("mbarrier.arrive.shared::cta.b64 _, [%0];" :: "r"(bar) : "memory");
}
__device__ __forceinline__ void mbar_arrive_cluster(uint32_t bar) {
    asm volatile("mbarrier.arrive.shared::cluster.b64 _, [%0];" :: "r"(bar) : "memory");
}
__device__ __forceinline__ void mbar_wait(uint32_t bar, uint32_t parity = 0) {
    asm volatile("{\n.reg .pred p;\n.reg .u32 c;\n"
                 "mbarrier.try_wait.parity.shared::cta.b64 p, [%0], %1;\n"
                 "@p bra WAIT_DONE;\n"
                 "mov.u32 c, 0;\n"
                 "WAIT_LOOP:\n"
                 "mbarrier.try_wait.parity.shared::cta.b64 p, [%0], %1;\n"
                 "@p bra WAIT_DONE;\n"
                 "add.u32 c, c, 1;\nsetp.lt.u32 p, c, 0x100000;\n"
                 "@p bra WAIT_LOOP;\n"
                 "trap;\n"
                 "WAIT_DONE:\n}" :: "r"(bar), "r"(parity) : "memory");
}
__device__ __forceinline__ void mbar_wait2(uint32_t bar0, uint32_t bar1) {
    asm volatile("{\n.reg .pred p, q;\n.reg .u32 c;\nmov.u32 c, 0;\n"
                 "WAIT_LOOP:\n"
                 "mbarrier.try_wait.parity.shared::cta.b64 p, [%0], 0;\n"
                 "mbarrier.try_wait.parity.shared::cta.b64 q, [%1], 0;\n"
                 "and.pred p, p, q;\n"
                 "@p bra WAIT_DONE;\n"
                 "add.u32 c, c, 1;\nsetp.lt.u32 p, c, 0x100000;\n"
                 "@p bra WAIT_LOOP;\n"
                 "trap;\n"
                 "WAIT_DONE:\n}" :: "r"(bar0), "r"(bar1) : "memory");
}
__device__ __forceinline__ bool mbar_test(uint32_t bar) {
    uint32_t ok;
    asm volatile("{\n.reg .pred p;\nmbarrier.test_wait.parity.shared::cta.b64 p, [%1], 0;\nselp.u32 %0, 1, 0, p;\n}" : "=r"(ok) : "r"(bar) : "memory");
    return ok;
}
__device__ __forceinline__ bool mbar_test2(uint32_t bar0, uint32_t bar1) {
    uint32_t ok;
    asm volatile("{\n.reg .pred p, q;\nmbarrier.test_wait.parity.shared::cta.b64 p, [%1], 0;\n"
                 "mbarrier.test_wait.parity.shared::cta.b64 q, [%2], 0;\nand.pred p, p, q;\nselp.u32 %0, 1, 0, p;\n}"
                 : "=r"(ok) : "r"(bar0), "r"(bar1) : "memory");
    return ok;
}
__device__ __forceinline__ bool elect_one() {
    uint32_t ok;
    asm volatile("{\n.reg .pred p;\nelect.sync _|p, 0xffffffff;\nselp.u32 %0, 1, 0, p;\n}" : "=r"(ok));
    return ok;
}
__device__ __forceinline__ unsigned ld_acquire(const unsigned* p) {
    unsigned v;
    asm volatile("ld.acquire.gpu.global.u32 %0, [%1];" : "=r"(v) : "l"(p) : "memory");
    return v;
}
__device__ __forceinline__ unsigned ld_flag(const unsigned* p) {
    unsigned v;
    asm volatile("ld.relaxed.gpu.global.u32 %0, [%1];" : "=r"(v) : "l"(p) : "memory");
    return v;
}
__device__ __forceinline__ uint4 lds128(uint32_t a) {
    uint4 v;
    asm volatile("ld.shared.v4.b32 {%0,%1,%2,%3}, [%4];" : "=r"(v.x), "=r"(v.y), "=r"(v.z), "=r"(v.w) : "r"(a) : "memory");
    return v;
}
__device__ __forceinline__ void sts128(uint32_t a, uint4 v) {
    asm volatile("st.shared.v4.b32 [%0], {%1,%2,%3,%4};" :: "r"(a), "r"(v.x), "r"(v.y), "r"(v.z), "r"(v.w) : "memory");
}
__device__ __forceinline__ uint32_t lds32(uint32_t a) {
    uint32_t v;
    asm volatile("ld.shared.b32 %0, [%1];" : "=r"(v) : "r"(a) : "memory");
    return v;
}
__device__ __forceinline__ void sts32(uint32_t a, uint32_t v) {
    asm volatile("st.shared.b32 [%0], %1;" :: "r"(a), "r"(v) : "memory");
}
__device__ __forceinline__ void stg128(void* p, uint4 v) {
    asm volatile("st.global.v4.b32 [%0], {%1,%2,%3,%4};" :: "l"(p), "r"(v.x), "r"(v.y), "r"(v.z), "r"(v.w) : "memory");
}
__device__ __forceinline__ unsigned pack4(unsigned a, unsigned b, unsigned c, unsigned d) {
    unsigned lo, r;
    asm("cvt.pack.sat.s8.s32.b32 %0, %1, %2, 0;" : "=r"(lo) : "r"(d), "r"(c));
    asm("cvt.pack.sat.s8.s32.b32 %0, %1, %2, %3;" : "=r"(r) : "r"(b), "r"(a), "r"(lo));
    return r;
}
__device__ __forceinline__ void cpasync16(uint32_t dst, const void* src) {
    asm volatile("cp.async.cg.shared.global [%0], [%1], 16;" :: "r"(dst), "l"(src) : "memory");
}
__device__ __forceinline__ unsigned pf_l2(const void* p) {
    unsigned v;
    asm volatile("ld.global.cg.L2::128B.u32 %0, [%1];" : "=r"(v) : "l"(p) : "memory");
    return v;
}

constexpr uint32_t DESC_A_HI = 0x80000000u | (512 >> 4);
constexpr uint32_t DESC_B_HI = 128 >> 4;
template <int NR> __device__ __forceinline__ void wgmma_n160(int (&d)[NR], uint32_t alo, uint32_t blo, int scale_d) {
    asm volatile("{\n.reg .pred p;\n.reg .b64 da, db;\nsetp.ne.b32 p, %82, 0;\n"
        "mov.b64 da, {%80, %83};\nmov.b64 db, {%81, %84};\n"
        "wgmma.mma_async.sync.aligned.m64n160k32.s32.s8.s8 "
        "{%0, %1, %2, %3, %4, %5, %6, %7, %8, %9, %10, %11, %12, %13, %14, %15, "
        "%16, %17, %18, %19, %20, %21, %22, %23, %24, %25, %26, %27, %28, %29, %30, %31, "
        "%32, %33, %34, %35, %36, %37, %38, %39, %40, %41, %42, %43, %44, %45, %46, %47, "
        "%48, %49, %50, %51, %52, %53, %54, %55, %56, %57, %58, %59, %60, %61, %62, %63, "
        "%64, %65, %66, %67, %68, %69, %70, %71, %72, %73, %74, %75, %76, %77, %78, %79}, "
        "da, db, p;\n}\n"
        : "+r"(d[0]), "+r"(d[1]), "+r"(d[2]), "+r"(d[3]), "+r"(d[4]), "+r"(d[5]), "+r"(d[6]), "+r"(d[7]),
          "+r"(d[8]), "+r"(d[9]), "+r"(d[10]), "+r"(d[11]), "+r"(d[12]), "+r"(d[13]), "+r"(d[14]), "+r"(d[15]),
          "+r"(d[16]), "+r"(d[17]), "+r"(d[18]), "+r"(d[19]), "+r"(d[20]), "+r"(d[21]), "+r"(d[22]), "+r"(d[23]),
          "+r"(d[24]), "+r"(d[25]), "+r"(d[26]), "+r"(d[27]), "+r"(d[28]), "+r"(d[29]), "+r"(d[30]), "+r"(d[31]),
          "+r"(d[32]), "+r"(d[33]), "+r"(d[34]), "+r"(d[35]), "+r"(d[36]), "+r"(d[37]), "+r"(d[38]), "+r"(d[39]),
          "+r"(d[40]), "+r"(d[41]), "+r"(d[42]), "+r"(d[43]), "+r"(d[44]), "+r"(d[45]), "+r"(d[46]), "+r"(d[47]),
          "+r"(d[48]), "+r"(d[49]), "+r"(d[50]), "+r"(d[51]), "+r"(d[52]), "+r"(d[53]), "+r"(d[54]), "+r"(d[55]),
          "+r"(d[56]), "+r"(d[57]), "+r"(d[58]), "+r"(d[59]), "+r"(d[60]), "+r"(d[61]), "+r"(d[62]), "+r"(d[63]),
          "+r"(d[64]), "+r"(d[65]), "+r"(d[66]), "+r"(d[67]), "+r"(d[68]), "+r"(d[69]), "+r"(d[70]), "+r"(d[71]),
          "+r"(d[72]), "+r"(d[73]), "+r"(d[74]), "+r"(d[75]), "+r"(d[76]), "+r"(d[77]), "+r"(d[78]), "+r"(d[79])
        : "r"(alo), "r"(blo), "r"(scale_d), "r"(DESC_A_HI), "r"(DESC_B_HI));
}
template <int NR> __device__ __forceinline__ void wgmma_t128(int (&d)[NR], uint32_t alo, uint32_t blo, int scale_d) {
    asm volatile("{\n.reg .pred p;\n.reg .b64 da, db;\nsetp.ne.b32 p, %66, 0;\n"
        "mov.b64 da, {%64, %67};\nmov.b64 db, {%65, %68};\n"
        "wgmma.mma_async.sync.aligned.m64n128k32.s32.s8.s8 "
        "{%0, %1, %2, %3, %4, %5, %6, %7, %8, %9, %10, %11, %12, %13, %14, %15, "
        "%16, %17, %18, %19, %20, %21, %22, %23, %24, %25, %26, %27, %28, %29, %30, %31, "
        "%32, %33, %34, %35, %36, %37, %38, %39, %40, %41, %42, %43, %44, %45, %46, %47, "
        "%48, %49, %50, %51, %52, %53, %54, %55, %56, %57, %58, %59, %60, %61, %62, %63}, "
        "da, db, p;\n}\n"
        : "+r"(d[0]), "+r"(d[1]), "+r"(d[2]), "+r"(d[3]), "+r"(d[4]), "+r"(d[5]), "+r"(d[6]), "+r"(d[7]),
          "+r"(d[8]), "+r"(d[9]), "+r"(d[10]), "+r"(d[11]), "+r"(d[12]), "+r"(d[13]), "+r"(d[14]), "+r"(d[15]),
          "+r"(d[16]), "+r"(d[17]), "+r"(d[18]), "+r"(d[19]), "+r"(d[20]), "+r"(d[21]), "+r"(d[22]), "+r"(d[23]),
          "+r"(d[24]), "+r"(d[25]), "+r"(d[26]), "+r"(d[27]), "+r"(d[28]), "+r"(d[29]), "+r"(d[30]), "+r"(d[31]),
          "+r"(d[32]), "+r"(d[33]), "+r"(d[34]), "+r"(d[35]), "+r"(d[36]), "+r"(d[37]), "+r"(d[38]), "+r"(d[39]),
          "+r"(d[40]), "+r"(d[41]), "+r"(d[42]), "+r"(d[43]), "+r"(d[44]), "+r"(d[45]), "+r"(d[46]), "+r"(d[47]),
          "+r"(d[48]), "+r"(d[49]), "+r"(d[50]), "+r"(d[51]), "+r"(d[52]), "+r"(d[53]), "+r"(d[54]), "+r"(d[55]),
          "+r"(d[56]), "+r"(d[57]), "+r"(d[58]), "+r"(d[59]), "+r"(d[60]), "+r"(d[61]), "+r"(d[62]), "+r"(d[63])
        : "r"(alo), "r"(blo), "r"(scale_d), "r"(DESC_B_HI), "r"(DESC_A_HI));
}

__device__ __forceinline__ void wg_fence() { asm volatile("wgmma.fence.sync.aligned;" ::: "memory"); }
__device__ __forceinline__ void wg_commit() { asm volatile("wgmma.commit_group.sync.aligned;" ::: "memory"); }
template <int N> __device__ __forceinline__ void wg_wait() { asm volatile("wgmma.wait_group.sync.aligned %0;" :: "n"(N) : "memory"); }

struct Job { int src; int dst; };
__host__ __device__ constexpr int unit_of(int piece, int slab) {
    return piece < 2 ? (slab < X1 ? 2 * slab + piece : (piece ? 16 : X1) + slab) : 32 + (piece - 2) * 8 + (slab >> 1);
}
__device__ __forceinline__ Job decode_job(int g) {
    int slab, idx, piece;
    if (g < SEG2) {
        int r;
        if (g < SEG1) { slab = g / (nA + 2 * nWA); r = g - slab * (nA + 2 * nWA); }
        else { g -= SEG1; slab = g / (nA + nWA); r = g - slab * (nA + nWA); slab += X1; }
        piece = r < nA ? -1 : (r < nA + nWA ? 0 : 1);
        idx = r < nA ? r : r - nA - piece * nWA;
    } else if (g < SEG3) {
        g -= SEG2; slab = g / nWA; idx = g - slab * nWA; slab += X1; piece = 1;
    } else {
        g -= SEG3; piece = 2 + (g >> 8); slab = (g >> 4) & 15; idx = g & 15;
        static_assert(nWB == 16, "");
    }
    Job j;
    if (piece < 0) {
        const int flag = (idx >> 2) * 16 + slab;
        j.src = idx * 32 + (slab << 12);
        j.dst = (flag * 512 + (idx & 3) * 128) | (flag << 18);
    } else {
        const bool wide = piece < 2;
        const int w = wide ? WA : WB;
        const int nb = wide ? idx / (WA / 32) : idx / (WB / 32);
        const int J = idx - nb * (w / 32);
        const int cb = nb * TN + (wide ? piece * WA : 2 * WA - 2 * WB + piece * WB);
        j.src = cb + J * 32 + (slab << 12) + (wide ? 1 << 16 : 2 << 16);
        j.dst = (cb * (K_ / 16) + slab * w * 4 + J * 32) | ((256 + nb * 64 + unit_of(piece, slab)) << 18);
    }
    return j;
}
struct Coord { const CUtensorMap* m; int x, y, z; };
__device__ __forceinline__ Coord job_coord(const CUtensorMap* maps, int src) {
    const bool w = src >> 16;
    const int c0 = src & 0xFFF, slab = (src >> 12) & 15;
    return {maps + (w ? 1 : 0), w ? c0 : 0, w ? slab * 64 : slab * 2, w ? 0 : c0};
}
__device__ __forceinline__ void raw_load(const Coord& c, uint32_t dst, uint32_t bar) {
    mbar_expect_tx(bar, 8192);
    asm volatile("cp.async.bulk.tensor.3d.shared::cluster.global.tile.mbarrier::complete_tx::bytes [%0], [%1, {%2, %3, %4}], [%5];"
                 :: "r"(dst), "l"(c.m), "r"(c.x), "r"(c.y), "r"(c.z), "r"(bar) : "memory");
}
__device__ __forceinline__ void raw_prefetch(const Coord& c) {
    asm volatile("cp.async.bulk.prefetch.tensor.3d.L2.global.tile [%0, {%1, %2, %3}];"
                 :: "l"(c.m), "r"(c.x), "r"(c.y), "r"(c.z) : "memory");
}
__host__ __device__ constexpr unsigned unit_mask(int piece, int s0, int s1) {
    unsigned m = 0;
    for (int s = s0; s < s1; s++) m |= 1u << (unit_of(piece, s) & 31);
    return m;
}
__host__ __device__ constexpr int slot_of(int u) {
    return u < UX ? (u % NSLOT) * (SLOT / 2048) : u < UX + NSTG ? NSLOT * (SLOT / 2048) + (u - UX) * 4 : ((u - NSTG) % NSLOT) * (SLOT / 2048);
}
__host__ __device__ constexpr uint64_t slot_table(int piece) {
    uint64_t t = 0;
    if (piece < 2) for (int s = 0; s < 16; s++) t |= (uint64_t)(unit_of(piece, s) % NSLOT) << (4 * s);
    else for (int s = 0; s < 8; s++) t |= (uint64_t)slot_of(unit_of(piece, 2 * s)) << (8 * s);
    return t;
}
struct Maps { CUtensorMap m[3]; };

__device__ __forceinline__ uint32_t bf2_op_epi(int a, int b, uint32_t zc, uint32_t sx, uint32_t sw, uint32_t bi) {
    uint32_t v;
    float fa = __int2float_rn(a), fb = __int2float_rn(b);
    asm("cvt.rn.bf16x2.f32 %0, %1, %2;" : "=r"(v) : "f"(fb), "f"(fa));
    asm("sub.rn.bf16x2 %0, %0, %1;" : "+r"(v) : "r"(zc));
    asm("mul.rn.bf16x2 %0, %0, %1;" : "+r"(v) : "r"(sx));
    asm("mul.rn.bf16x2 %0, %0, %1;" : "+r"(v) : "r"(sw));
    asm("add.rn.bf16x2 %0, %0, %1;" : "+r"(v) : "r"(bi));
    return v;
}

struct Par { uint4 zc, sw, bi; };
__device__ __forceinline__ Par ld_par(uint32_t p) { return {lds128(p), lds128(p + TN * 2), lds128(p + TN * 4)}; }
__device__ __forceinline__ void epi_row(const int (&a)[WA / 2], int o, const Par& p, uint32_t sx2, char* out) {
    uint4 r;
    r.x = bf2_op_epi(a[o + 0], a[o + 4], p.zc.x, sx2, p.sw.x, p.bi.x);
    r.y = bf2_op_epi(a[o + 8], a[o + 12], p.zc.y, sx2, p.sw.y, p.bi.y);
    r.z = bf2_op_epi(a[o + 1], a[o + 5], p.zc.z, sx2, p.sw.z, p.bi.z);
    r.w = bf2_op_epi(a[o + 9], a[o + 13], p.zc.w, sx2, p.sw.w, p.bi.w);
    stg128(out, r);
}
template <int J, int JN>
__device__ __forceinline__ void epilogue(const int (&a)[WA / 2], Par& p, uint32_t par, uint32_t sx2, char* out) {
    epi_row(a, J * 16, p, sx2, out + J * 64);
    Par n = p;
    if (JN != J) n = ld_par(par + JN * 64);
    epi_row(a, J * 16 + 2, p, sx2, out + 8 * (N_ * 2) + J * 64);
    p = n;
}

__global__ void __cluster_dims__(2, 1, 1) __launch_bounds__(512, 1)
w8a8_kernel(const __grid_constant__ Maps maps, const char* __restrict__ qx, const char* __restrict__ qw, const __nv_bfloat16* __restrict__ scale_x, const int* __restrict__ zero_x,
            const __nv_bfloat16* __restrict__ scale_w, const __nv_bfloat16* __restrict__ bias,
            __nv_bfloat16* __restrict__ out) {
    extern __shared__ __align__(1024) unsigned char smem_raw[];
    const uint32_t sb = (uint32_t)__cvta_generic_to_shared(smem_raw);
    const uint32_t bars = sb + SM_BAR;
    const int warp = __shfl_sync(~0u, threadIdx.x >> 5, 0), lane = threadIdx.x & 31;
    const int b = blockIdx.x, rank = b & 1, nb = (b >> 1) & 7, mb = (b >> 4) * 2 + rank;

    if (warp >= 8) {
        asm volatile("setmaxnreg.dec.sync.aligned.u32 56;");
        if (warp >= 16 - NCONV) {
            const int cw = warp - (16 - NCONV);
            unsigned t0;
            asm volatile("mov.u32 %0, %clock;" : "=r"(t0));
            t0 += 100;
            asm volatile("barrier.cluster.arrive.relaxed.aligned;" ::: "memory");
            const Job mj = decode_job(min(lane, NJOB - 1) * NCTA + b);
            static_assert(NCONV == NSTG + 2 && NJOB == 22, "");
            const uint32_t s = sb + (cw < NSTG ? SM_STG + cw * 8192 : SM_A + (14 - NSTG + cw) * 8192);
            const uint32_t sbar = bars + (B_FULLS + cw) * 8;
            {
                const Coord c = job_coord(maps.m, __shfl_sync(~0u, mj.src, cw));
                if (elect_one()) {
                    mbar_init(sbar, 1);
                    asm volatile("fence.mbarrier_init.release.cluster;" ::: "memory");
                    unsigned t;
                    do { asm volatile("mov.u32 %0, %clock;" : "=r"(t)); } while ((int)(t - t0) < cw * PFD + (cw ? b * 88 : b * 0) / 16);
                    raw_load(c, s, sbar);
                }
                __syncwarp();
            }
            asm volatile("barrier.cluster.wait.aligned;" ::: "memory");
            t0 += b * 88 / 16;
            const int c4 = lane & 3, ln = (lane >> 2) * 2 + (c4 >> 1);
            const uint32_t rdA = ln * 128 + ((((c4 & 1) << 2) ^ (ln & 7)) << 4);
            const uint32_t rdB = (lane >> 3) * 2048 + (lane & 7) * 16;
            const int wrA = (lane >> 2) * 4 + (c4 ^ ((lane >> 3) & 3));
            uint32_t par = 0;
#pragma unroll 1
            for (int j = cw, jn; j < NJOB; j = jn, par ^= 1) {
                jn = j < 13 ? j + NCONV : (j < 15 ? 31 : j + NSTG);
                const int src = __shfl_sync(~0u, mj.src, j), dst = __shfl_sync(~0u, mj.dst, j);
                const int nsrc = __shfl_sync(~0u, mj.src, jn);
                const int kind = src >> 16;
                uint4 o[4];
                uint4* d;
                int dstep;
                mbar_wait(sbar, par);
                if (kind == 0) {
                    const uint32_t a0 = s + rdA;
                    d = g_a8 + (dst & 0x3FFFF) + wrA;
                    dstep = 32;
#pragma unroll
                    for (int i = 0; i < 4; i++) {
                        uint4 v0 = lds128(a0 + i * 2048), v1 = lds128((a0 ^ 16) + i * 2048);
                        uint4 v2 = lds128((a0 ^ 32) + i * 2048), v3 = lds128((a0 ^ 48) + i * 2048);
                        o[i].x = pack4(v0.x, v0.y, v0.z, v0.w); o[i].y = pack4(v1.x, v1.y, v1.z, v1.w);
                        o[i].z = pack4(v2.x, v2.y, v2.z, v2.w); o[i].w = pack4(v3.x, v3.y, v3.z, v3.w);
                    }
                } else {
                    const uint32_t a0 = s + rdB;
                    d = g_b8 + (dst & 0x3FFFF) + (lane >> 3) * (kind == 1 ? WA : WB) + (lane & 7);
                    dstep = 8;
#define CV_B(m, f)                                                                                    \
                    {                                                                                 \
                        uint4 v0 = lds128(a0 + m * 512), v1 = lds128(a0 + m * 512 + 128);             \
                        uint4 v2 = lds128(a0 + m * 512 + 256), v3 = lds128(a0 + m * 512 + 384);       \
                        o[0].f = pack4(v0.x, v1.x, v2.x, v3.x); o[1].f = pack4(v0.y, v1.y, v2.y, v3.y); \
                        o[2].f = pack4(v0.z, v1.z, v2.z, v3.z); o[3].f = pack4(v0.w, v1.w, v2.w, v3.w); \
                    }
                    CV_B(0, x) CV_B(1, y) CV_B(2, z) CV_B(3, w)
                }
#pragma unroll
                for (int i = 0; i < 4; i++) stg128(d + i * dstep, o[i]);
                unsigned tn;
                asm volatile("mov.u32 %0, %clock;" : "=r"(tn));
                const bool late = jn < NJOB && (int)(tn - t0) < jn * PFD;
                if (!late && elect_one()) {
                    if (jn < NJOB) { raw_load(job_coord(maps.m, nsrc), s, sbar); }
                    else if (jn == 31) mbar_arrive(bars + (B_AFREE - NSTG + cw) * 8);
                    else if (0 != 1) {
                        uint32_t ra;
                        asm("mapa.shared::cluster.u32 %0, %1, %2;" : "=r"(ra) : "r"(bars + (B_GO + ((UX + cw) >> 1)) * 8), "r"((UX + cw) & 1));
                        mbar_arrive_cluster(ra);
                    }
                }
                const int* csp = (const int*)d;
                unsigned csv = o[0].x;
                if (kind != 0) {
                    int cs[4];
#pragma unroll
                    for (int i = 0; i < 4; i++)
                        cs[i] = __dp4a((int)o[i].x, 0x01010101, __dp4a((int)o[i].y, 0x01010101,
                                __dp4a((int)o[i].z, 0x01010101, __dp4a((int)o[i].w, 0x01010101, 0))));
                    const int p01 = cs[0] + cs[1] * 65536, p23 = cs[2] + cs[3] * 65536;
                    const bool odd = lane & 8;
                    int v = (odd ? p23 : p01) + __shfl_xor_sync(~0u, odd ? p01 : p23, 8);
                    v += __shfl_xor_sync(~0u, v, 16);
                    int* p = (int*)g_cs + ((src >> 12) & 15) * (N_ / 2) + ((src & 0xFFF) >> 1) + (lane & 15);
                    if (lane < 16) *p = v;
                    csp = p; csv = v;
                }
#pragma unroll 1
                for (int it = 0; it < 1000; it++) {
                    bool ok = true;
                    if ((lane & 3) == 0) {
                        unsigned rb[5];
#pragma unroll
                        for (int i = 0; i < 4; i++)
                            asm volatile("ld.relaxed.gpu.global.u32 %0, [%1];" : "=r"(rb[i]) : "l"(d + i * dstep) : "memory");
                        asm volatile("ld.relaxed.gpu.global.u32 %0, [%1];" : "=r"(rb[4]) : "l"(csp) : "memory");
                        ok = rb[0] == o[0].x && rb[1] == o[1].x && rb[2] == o[2].x && rb[3] == o[3].x && rb[4] == csv;
                    }
                    if (__all_sync(~0u, ok)) break;
                }
                if (elect_one()) asm volatile("red.relaxed.gpu.global.add.u32 [%0], 1;" :: "l"(g_flag + ((unsigned)dst >> 18)) : "memory");
                __syncwarp();
                if (late && elect_one()) {
                    do { asm volatile("mov.u32 %0, %clock;" : "=r"(tn)); } while ((int)(tn - t0) < jn * PFD);
                    raw_load(job_coord(maps.m, nsrc), s, sbar);
                }
                __syncwarp();
            }
        } else if (warp == 8) {
            asm volatile("barrier.cluster.arrive.relaxed.aligned;" ::: "memory");
            const unsigned ep = *(volatile unsigned*)&g_epoch[b] + 1;
            const unsigned* f1 = g_flag + 256 + nb * 64 + lane;
            const unsigned* f2 = lane < 16 ? f1 + 32 : g_flag + mb * 16 + lane - 16;
            const unsigned t1 = ep * (WA / 32), t2 = ep * 4;
            static_assert(WB / 16 == 4, "");
            const unsigned n1 = lane == 0 ? unit_mask(0, 0, 8) : lane == 1 ? unit_mask(1, 0, 8) : lane == 2 ? unit_mask(0, 8, 16)
                              : lane == 3 ? unit_mask(1, 8, 16) : 0u;
            const unsigned n2 = lane < 4 ? 0u : 0xFFFFu;
            bool d1 = false, d2 = false, d3 = lane >= 5, fr = lane < 30;
            asm volatile("barrier.cluster.wait.aligned;" ::: "memory");
            for (int it = 0; 0 != 1; it++) {
                unsigned v1 = t1, v2 = t2;
                if (!d1) v1 = ld_flag(f1);
                if (!d2) v2 = ld_flag(f2);
                if (!fr) fr = mbar_test(bars + (B_AFREE - 30 + lane) * 8);
                if (!d2 && fr && (int)(v2 - t2) >= 0) {
                    d2 = true;
                    if (lane >= 16) {
                        asm volatile("fence.proxy.async.global;" ::: "memory");
                        asm volatile("cp.async.bulk.shared::cluster.global.mbarrier::complete_tx::bytes [%0], [%1], %2, [%3];"
                                     :: "r"(sb + SM_A + (lane - 16) * 8192), "l"((const char*)g_a8 + (mb * 16 + lane - 16) * 8192),
                                        "r"(8192), "r"(bars + (B_FULLA + lane - 16) * 8) : "memory");
                    } else if ((lane & 1) == rank) mbar_arrive(bars + (B_GO + 16 + (lane >> 1)) * 8);
                }
                if (!d1 && (int)(v1 - t1) >= 0) {
                    d1 = true;
                    if ((lane & 1) == rank) mbar_arrive(bars + (B_GO + (lane >> 1)) * 8);
                }
                const unsigned m1 = __ballot_sync(~0u, d1), m2 = __ballot_sync(~0u, d2);
                if (!d3 && (m1 & n1) == n1 && (m2 & n2) == n2) { d3 = true; mbar_arrive(bars + (B_PSTEP + lane) * 8); }
                if ((m1 & m2) == ~0u) break;
                if (it > (1 << 22)) __trap();
            }
        } else if (warp == 9) {
            asm volatile("barrier.cluster.arrive.relaxed.aligned;" ::: "memory");
            const int u = 2 * lane + rank;
            int so, fb;
            if (u < 2 * X1) { so = (u & 1) * (WA * K_) + (u >> 1) * (WA * 64); fb = (u & 1) * 24 + (u >> 1); }
            else if (u < X1 + 16) { so = (u - X1) * (WA * 64); fb = u - X1; }
            else if (u < 32) { so = WA * K_ + (u - 16) * (WA * 64); fb = 24 + u - 16; }
            else { so = 2 * WA * K_ + (u - 32) * (WB * 128); fb = u < 40 ? u - 16 : u; }
            const char* srcB = (const char*)g_b8 + nb * TN * K_ + so;
            const uint32_t dstB = sb + SM_RING + slot_of(u) * 2048;
            asm volatile("barrier.cluster.wait.aligned;" ::: "memory");
#pragma unroll 1
            for (int i = 0; i < NU / 2 && 0 != 1; i++) {
                mbar_wait(bars + (B_GO + i) * 8);
                if (lane == i) {
                    asm volatile("fence.proxy.async.global;" ::: "memory");
                    asm volatile("cp.async.bulk.shared::cluster.global.mbarrier::complete_tx::bytes.multicast::cluster [%0], [%1], %2, [%3], %4;"
                                 :: "r"(dstB), "l"(srcB), "r"(u < 32 ? WA * 64 : WB * 128), "r"(bars + (B_FULLB + fb) * 8), "h"((uint16_t)3) : "memory");
                }
                __syncwarp();
            }
        } else if (warp == 10) {
            unsigned pv, pv2;
            {
                static_assert(X1 > 0 && nA == 64 && nWA == 40, "");
                const int i = b - (b < 104 ? 64 : 104), q = i / 5;
                const char* p = b < 64 ? qx + (b * 32 + (lane >> 1)) * (K_ * 4) + (lane & 1) * 128
                                       : qw + lane * (N_ * 4) + (q * TN + (b < 104 ? 0 : WA) + (i - q * 5) * 32) * 4;
                pv = pf_l2(p);
                pv2 = pf_l2(p + (b < 64 ? 16 * K_ * 4 : 32 * N_ * 4));
                if (lane < 3) asm volatile("prefetch.tensormap [%0];" :: "l"(maps.m + lane) : "memory");
            }
            asm volatile("barrier.cluster.arrive.relaxed.aligned;" ::: "memory");
            if ((pv ^ pv2) == 0x40000000u) g_sink = pv;
            const float zxf = __bfloat162float(__float2bfloat16_rn((float)__ldg(zero_x)));
#pragma unroll 1
            for (int i = lane; i < TN / 4; i += 32) {
                const bool hi = i >= TN / 8;
                sts128(sb + SM_PAR + TN * 2 + i * 16, __ldg((const uint4*)((hi ? bias : scale_w) + nb * TN) + (hi ? i - TN / 8 : i)));
            }
            asm volatile("barrier.cluster.wait.aligned;" ::: "memory");
            int c[8], cs[8];
#pragma unroll
            for (int i = 0; i < 8; i++) { c[i] = 0; cs[i] = 0; }
#pragma unroll 1
            for (int st = 0; st < 5 && 0 != 1; st++) {
                const bool wide = st < 4;
                const int half = wide ? (st >> 1) : (lane >> 4);
                const int col = wide ? (st & 1) * WA + min(lane, WA / 8 - 1) * 8 : 2 * WA + (lane & 15) * 8;
                const uint4* src = g_cs + (half * 8 * N_ + nb * TN + col) / 8;
                mbar_wait(bars + (B_PSTEP + st) * 8);
                uint4 v[8];
#pragma unroll
                for (int i = 0; i < 8; i++) v[i] = __ldcg(src + i * (N_ / 8));
#pragma unroll
                for (int h = 0; h < 8; h += 4) {
                    const unsigned sv[4] = {v[h].x + v[h + 1].x + v[h + 2].x + v[h + 3].x, v[h].y + v[h + 1].y + v[h + 2].y + v[h + 3].y,
                                            v[h].z + v[h + 1].z + v[h + 2].z + v[h + 3].z, v[h].w + v[h + 1].w + v[h + 2].w + v[h + 3].w};
#pragma unroll
                    for (int i = 0; i < 4; i++) {
                        const int lo = (int)(short)(sv[i] & 0xFFFF);
                        c[2 * i] += lo; c[2 * i + 1] += ((int)(sv[i] - (unsigned)lo)) >> 16;
                    }
                }
                if (st >= 2) {
                    uint32_t z[4];
#pragma unroll
                    for (int i = 0; i < 8; i++) {
                        const int o = __shfl_xor_sync(~0u, c[i], 16);
                        if (!wide) c[i] += o;
                    }
#pragma unroll
                    for (int i = 0; i < 4; i++) {
                        const float lo = __bfloat162float(__float2bfloat16_rn((float)c[2 * i])) * zxf;
                        const float hi = __bfloat162float(__float2bfloat16_rn((float)c[2 * i + 1])) * zxf;
                        asm("cvt.rn.bf16x2.f32 %0, %1, %2;" : "=r"(z[i]) : "f"(hi), "f"(lo));
                    }
                    const uint32_t za = sb + SM_PAR + ((col & ~31) + (col & 8) * 2 + ((col >> 3) & 2)) * 2;
#pragma unroll
                    for (int i = 0; i < 4; i++) sts32(za + i * 8, z[i]);
                    __syncwarp();
                    if (lane == 0) { mbar_arrive(bars + (B_PAR + st - 2) * 8); }
#pragma unroll
                    for (int i = 0; i < 8; i++) c[i] = 0;
                }
#pragma unroll
                for (int i = 0; i < 8; i++) { const int t = c[i]; c[i] = cs[i]; cs[i] = t; }
            }
        } else {
            asm volatile("barrier.cluster.arrive.relaxed.aligned;" ::: "memory");
            asm volatile("barrier.cluster.wait.aligned;" ::: "memory");
        }
    } else {
        asm volatile("setmaxnreg.inc.sync.aligned.u32 200;");
        {
            constexpr int PER = (B_NINIT + 7) / 8;
            if (elect_one()) {
#pragma unroll 1
                for (int i = warp * PER; i < min(warp * PER + PER, B_NINIT); i++)
                    {
                    const int u = 2 * (i - B_GO) + rank;
                    mbar_init(bars + i * 8, (i < B_GO || i >= B_PAR || u < NSLOT) ? 1 : (u >= UX && u < UX + NSTG) ? 3 : 9);
                }
            }
            __syncwarp();
            const int i = warp * PER + lane;
            if (lane < PER && i < B_GO) mbar_expect_tx(bars + i * 8, (i < 16 || (i >= 24 && i < 40)) ? WA * 64 : 8192);
            static_assert(WB * 128 == 8192, "");
            asm volatile("fence.mbarrier_init.release.cluster;" ::: "memory");
        }
        asm volatile("barrier.cluster.arrive.relaxed.aligned;" ::: "memory");
        const int wg = warp >> 2;
        const uint32_t sd = (sb & 0x3FFFF) >> 4;
        const unsigned short sxr = __ldg((const unsigned short*)scale_x);
        const uint32_t sx2 = (uint32_t)sxr * 0x10001u;
        char* orow = (char*)out + (size_t)(mb * 128 + (warp & 3) * 16 + (lane >> 2)) * (N_ * 2) + (nb * TN + (lane & 3) * 8 + wg * WA) * 2;
        const uint32_t par = sb + SM_PAR + (lane & 3) * 16 + wg * WA * 2;
        uint32_t reladdr;
        int rell;
        {
            const int u = lane < 16 ? (lane < X1 ? 2 * lane + wg : (wg ? 16 : X1) + lane) : 16 + wg * 8 + lane;
            const int v = u + (u < 32 ? NSLOT : NSLOT + NSTG);
            rell = (lane < 24 && v < NU) ? lane : 99;
            asm("mapa.shared::cluster.u32 %0, %1, %2;" : "=r"(reladdr) : "r"(bars + (B_GO + (v >> 1)) * 8), "r"(v & 1));
        }
        asm volatile("barrier.cluster.wait.aligned;" ::: "memory");
        int a0[WA / 2], a1[WA / 2];
        uint32_t barB = bars + (B_FULLB + wg * 24) * 8;
        bool ready = false;
#define RELEASE2(done) if (rell <= (done)) { mbar_arrive_cluster(reladdr); rell = 99; }
        if (0 != 1) {
            wg_fence();
            {
                uint64_t tbl = wg ? slot_table(1) : slot_table(0);
                uint32_t da = (sd + (SM_A >> 4)) | (1 << 16);
#pragma unroll 1
                for (int s = 0; s < 16; s++) {
                    const uint32_t db = ((sd + (SM_RING >> 4)) | (WA << 16)) + ((uint32_t)tbl & 15) * (SLOT >> 4);
                    const bool starved = !ready && !mbar_test2(bars + (B_FULLA + s) * 8, barB);
                    if (starved) {
                        wg_wait<0>();
                        RELEASE2(s - 1)
                        mbar_wait2(bars + (B_FULLA + s) * 8, barB);
                    }
                    wgmma_n160(a0, da, db, s);
                    wgmma_n160(a1, da + 256, db, s);
                    wgmma_n160(a0, da + 2, db + 2 * WA, 1);
                    wgmma_n160(a1, da + 258, db + 2 * WA, 1);
                    wg_commit();
                    RELEASE2(s - 2)
                    tbl >>= 4; da += 512; barB += 8;
                    ready = mbar_test2(bars + (B_FULLA + min(s + 1, 15)) * 8, barB);
                    wg_wait<1>();
                }
            }
            RELEASE2(14)
            wg_wait<0>();
            RELEASE2(15)
            mbar_wait(bars + (B_PAR + wg) * 8);
            Par P = ld_par(par);
            char* const orow1 = orow + 64 * (N_ * 2);
            epilogue<0, 1>(a0, P, par, sx2, orow); epilogue<1, 2>(a0, P, par, sx2, orow);
            epilogue<2, 3>(a0, P, par, sx2, orow); epilogue<3, 0>(a0, P, par, sx2, orow);
            int t[64];
            wg_fence();
            {
                uint64_t tbl = wg ? slot_table(3) : slot_table(2);
                uint32_t da = (sd + (SM_A >> 4)) | (1 << 16);
#pragma unroll
                for (int i = 16; i < 24; i++) {
                    const uint32_t db = ((sd + (SM_RING >> 4)) | (WB << 16)) + ((uint32_t)tbl & 255) * 128;
                    const bool starved = !ready && !mbar_test(barB);
                    if (starved) {
                        wg_wait<0>();
                        RELEASE2(i - 1)
                        mbar_wait(barB);
                    }
#pragma unroll
                    for (int k = 0; k < 4; k++) wgmma_t128(t, db + k * 2 * WB, da + (k >> 1) * 512 + (k & 1) * 2, k ? 1 : i - 16);
                    wg_commit();
                    RELEASE2(i - 2)
                    tbl >>= 8; da += 1024; barB += 8;
                    ready = mbar_test(barB);
                    switch (i) {
                        case 16: epilogue<0, 0>(a1, P, par, sx2, orow1); break;
                        case 17: epilogue<1, 1>(a1, P, par, sx2, orow1); break;
                        case 18: epilogue<2, 2>(a1, P, par, sx2, orow1); break;
                        case 19: epilogue<3, 3>(a1, P, par, sx2, orow1); break;
                        case 20: epilogue<4, 4>(a1, P, par, sx2, orow1); break;
                        case 21: epilogue<4, 4>(a0, P, par, sx2, orow); break;
                        default: break;
                    }
                    if (i < 20) P = ld_par(par + (i - 15) * 64);
                    wg_wait<1>();
                }
            }
            RELEASE2(22)
            mbar_wait(bars + (B_PAR + 2) * 8);
            const int w = warp & 3, q = lane >> 2, c0 = (w >> 1) * 32 + q * 4 + (w & 1) * 2;
            const uint32_t pp = sb + SM_PAR + (2 * WA + wg * WB + c0) * 2;
            const uint32_t zc = lds32(pp), sw = lds32(pp + TN * 2), bi = lds32(pp + TN * 4);
            const int r0 = (lane & 3) * 2;
            const uint32_t st0 = r0 * 128 + (((c0 >> 3) ^ r0) << 4) + (c0 & 7) * 2, st1 = (st0 ^ 16) + 128;
            wg_wait<0>();
            asm volatile("bar.sync %0, 128;" :: "r"(3 + wg) : "memory");
#pragma unroll
            for (int h = 0; h < 2; h++) {
                const uint32_t buf = sb + SM_RING + (wg ? slot_of(UX + 1 + h) : slot_of(UX - 1 + h)) * 2048;
#pragma unroll
                for (int j = 0; j < 8; j++) {
                    const int o = h * 32 + j * 4;
                    sts32(buf + st0 + j * 1024, bf2_op_epi(t[o], t[o + 2], zc, sx2, sw, bi));
                    sts32(buf + st1 + j * 1024, bf2_op_epi(t[o + 1], t[o + 3], zc, sx2, sw, bi));
                }
                asm volatile("fence.proxy.async.shared::cta;" ::: "memory");
                asm volatile("bar.sync %0, 128;" :: "r"(3 + wg) : "memory");
                if (w == 0 && elect_one())
                    asm volatile("cp.async.bulk.tensor.2d.global.shared::cta.tile.bulk_group [%0, {%1, %2}], [%3];"
                                 :: "l"(maps.m + 2), "r"(nb * TN + 2 * WA + wg * WB), "r"(mb * 128 + h * 64), "r"(buf) : "memory");
            }
            if (w == 0) {
                asm volatile("cp.async.bulk.commit_group;" ::: "memory");
                asm volatile("cp.async.bulk.wait_group.read 0;" ::: "memory");
            }
        }
        if (threadIdx.x == 128) asm volatile("red.relaxed.gpu.global.add.u32 [%0], 1;" :: "l"(g_epoch + b) : "memory");
    }
}

static void launch(EncodeFn encode, void* const* d_in, void* d_out) {
    Maps maps;
    CUtensorMap &mx = maps.m[0], &mw = maps.m[1];
    {
        const cuuint64_t dim[3] = {32, K_ / 32, M_}, str[2] = {128, K_ * 4};
        const cuuint32_t box[3] = {32, 2, 32}, es[3] = {1, 1, 1};
        encode(&mx, CU_TENSOR_MAP_DATA_TYPE_INT32, 3, d_in[0], dim, str, box, es, CU_TENSOR_MAP_INTERLEAVE_NONE,
               CU_TENSOR_MAP_SWIZZLE_128B, CU_TENSOR_MAP_L2_PROMOTION_NONE, CU_TENSOR_MAP_FLOAT_OOB_FILL_NONE);
    }
    {
        const cuuint64_t dim[3] = {N_, K_, 1}, str[2] = {N_ * 4, (cuuint64_t)N_ * K_ * 4};
        const cuuint32_t box[3] = {32, 64, 1}, es[3] = {1, 1, 1};
        encode(&mw, CU_TENSOR_MAP_DATA_TYPE_INT32, 3, d_in[1], dim, str, box, es, CU_TENSOR_MAP_INTERLEAVE_NONE,
               CU_TENSOR_MAP_SWIZZLE_NONE, CU_TENSOR_MAP_L2_PROMOTION_NONE, CU_TENSOR_MAP_FLOAT_OOB_FILL_NONE);
    }
    {
        const cuuint64_t dim[2] = {N_, M_}, str[1] = {N_ * 2};
        const cuuint32_t box[2] = {WB, 64}, es[2] = {1, 1};
        encode(&maps.m[2], CU_TENSOR_MAP_DATA_TYPE_BFLOAT16, 2, d_out, dim, str, box, es, CU_TENSOR_MAP_INTERLEAVE_NONE,
               CU_TENSOR_MAP_SWIZZLE_128B, CU_TENSOR_MAP_L2_PROMOTION_NONE, CU_TENSOR_MAP_FLOAT_OOB_FILL_NONE);
    }
    w8a8_kernel<<<NCTA, 512, SM_ALLOC>>>(maps, (const char*)d_in[0], (const char*)d_in[1], (const __nv_bfloat16*)d_in[2], (const int*)d_in[3],
                                         (const __nv_bfloat16*)d_in[4], (const __nv_bfloat16*)d_in[5],
                                         (__nv_bfloat16*)d_out);
}

}

extern "C" void kernel_launch(void* const* d_in, const int* in_sizes, int n_in, void* d_out, int out_size) {
    using namespace ra;
    static EncodeFn encode = nullptr;
    static Scratch* scr = nullptr;
    static bool fits = false;
    if (!encode) {
        void* fn = nullptr;
        cudaDriverEntryPointQueryResult qr;
        cudaGetDriverEntryPoint("cuTensorMapEncodeTiled", &fn, cudaEnableDefault, &qr);
        encode = (EncodeFn)fn;
        cudaGetSymbolAddress((void**)&scr, g_scratch);
        cudaFuncSetAttribute(w8a8_kernel, cudaFuncAttributeMaxDynamicSharedMemorySize, SM_ALLOC);
        cudaFuncSetAttribute(w8a8_kernel, cudaFuncAttributeNonPortableClusterSizeAllowed, 1);
        cudaFuncSetAttribute(w8a8_side, cudaFuncAttributeMaxDynamicSharedMemorySize, SM_ALLOC);
        cudaFuncSetAttribute(w8::w8a8_kernel, cudaFuncAttributeMaxDynamicSharedMemorySize, w8::SM_ALLOC);
        cudaLaunchConfig_t oc = {};
        oc.gridDim = dim3(NCTA); oc.blockDim = dim3(512); oc.dynamicSmemBytes = SM_ALLOC;
        cudaLaunchAttribute oa[1];
        oa[0].id = cudaLaunchAttributeClusterDimension; oa[0].val.clusterDim.x = CS; oa[0].val.clusterDim.y = 1; oa[0].val.clusterDim.z = 1;
        oc.attrs = oa; oc.numAttrs = 1;
        int nc = 0;
        fits = cudaOccupancyMaxActiveClusters(&nc, w8a8_kernel, &oc) == cudaSuccess && nc >= NCTA / CS;
        cudaGetLastError();
    }
    if (!fits) { w8::launch(encode, d_in, d_out); return; }
    Maps maps;
    {
        const cuuint64_t dim[3] = {32, K_ / 32, M_}, str[2] = {128, K_ * 4};
        const cuuint32_t box[3] = {32, 2, 32}, es[3] = {1, 1, 1};
        encode(&maps.m[0], CU_TENSOR_MAP_DATA_TYPE_INT32, 3, d_in[0], dim, str, box, es, CU_TENSOR_MAP_INTERLEAVE_NONE,
               CU_TENSOR_MAP_SWIZZLE_128B, CU_TENSOR_MAP_L2_PROMOTION_NONE, CU_TENSOR_MAP_FLOAT_OOB_FILL_NONE);
    }
    {
        const cuuint64_t dim[3] = {N_, K_, 1}, str[2] = {N_ * 4, (cuuint64_t)N_ * K_ * 4};
        const cuuint32_t box[3] = {64, 32, 1}, es[3] = {1, 1, 1};
        encode(&maps.m[1], CU_TENSOR_MAP_DATA_TYPE_INT32, 3, d_in[1], dim, str, box, es, CU_TENSOR_MAP_INTERLEAVE_NONE,
               CU_TENSOR_MAP_SWIZZLE_NONE, CU_TENSOR_MAP_L2_PROMOTION_NONE, CU_TENSOR_MAP_FLOAT_OOB_FILL_NONE);
    }
    {
        const cuuint64_t dim[2] = {N_, M_}, str[1] = {N_ * 2};
        const cuuint32_t box[2] = {64, 32}, es[2] = {1, 1};
        encode(&maps.m[2], CU_TENSOR_MAP_DATA_TYPE_BFLOAT16, 2, d_out, dim, str, box, es, CU_TENSOR_MAP_INTERLEAVE_NONE,
               CU_TENSOR_MAP_SWIZZLE_128B, CU_TENSOR_MAP_L2_PROMOTION_NONE, CU_TENSOR_MAP_FLOAT_OOB_FILL_NONE);
    }
    w8a8_kernel<<<NCTA, 512, SM_ALLOC, cudaStreamPerThread>>>((const char*)d_in[0], scr, (const __nv_bfloat16*)d_in[4],
                                                             (const __nv_bfloat16*)d_in[5], (const __nv_bfloat16*)d_in[2], (const int*)d_in[3], maps);
    cudaLaunchConfig_t cfg = {};
    cfg.gridDim = dim3(16); cfg.blockDim = dim3(512); cfg.dynamicSmemBytes = SM_ALLOC; cfg.stream = cudaStreamPerThread;
    cudaLaunchAttribute at[1];
    at[0].id = cudaLaunchAttributeProgrammaticStreamSerialization; at[0].val.programmaticStreamSerializationAllowed = 1;
    cfg.attrs = at; cfg.numAttrs = 1;
    cudaLaunchKernelEx(&cfg, w8a8_side, scr, (const __nv_bfloat16*)d_in[4], (const __nv_bfloat16*)d_in[5], (const __nv_bfloat16*)d_in[2],
                       (const int*)d_in[3], maps.m[2]);
}
```

```cpp
#include <cuda_runtime.h>
#include <cuda.h>
#include <cuda_bf16.h>
#include <stdint.h>

namespace ra {

constexpr int CFG_D = 3;
constexpr int CFG_P0 = 650;
constexpr int CFG_PF0 = 0;
constexpr int CFG_SLEEP = 200;
constexpr int CFG_NINIT = 2;
constexpr int CFG_NR = 10;
constexpr int CFG_PZ = 17;

constexpr int M_ = 2048, K_ = 1024, N_ = 3584;
constexpr int CS = 16, NCTA = 112, TN = 448;
constexpr int NRING = CFG_NR, NCONV = 6, NJOB = 26, NG = 56, NOUT = 4, D_ = CFG_D;

constexpr int SM_A = 0;
constexpr int SM_RING = 131072;
constexpr int SM_OUT = SM_RING + NRING * 8192;
constexpr int SM_PAR = SM_OUT + NOUT * 4096;
constexpr int SM_SUM = SM_PAR + 1024;
constexpr int SM_BAR = SM_SUM + 256;
constexpr int B_FULL = 0, B_PAR = 64, B_AFREE = 72, B_OFREE = 76, B_SUM = 108, B_GO = 112, B_OFULL = 144, B_END = 148;
constexpr int SM_TOTAL = SM_BAR + B_END * 8;

constexpr int FS = 32;
struct __align__(2048) Scratch {
    uint4 a8[M_ * K_ / 16];
    uint4 b8[N_ * K_ / 16];
    unsigned cs[32 * TN / 2];
    unsigned flag[CS * FS + 64];
    unsigned epoch[128];
};
__device__ Scratch g_scratch;
constexpr int SM_ALLOC = SM_TOTAL;
static_assert(SM_ALLOC <= 232448, "");

__device__ __forceinline__ void mbar_init(uint32_t bar, uint32_t cnt) {
    asm volatile("mbarrier.init.shared::cta.b64 [%0], %1;" :: "r"(bar), "r"(cnt) : "memory");
}
__device__ __forceinline__ void mbar_expect_tx(uint32_t bar, uint32_t bytes) {
    asm volatile("mbarrier.arrive.expect_tx.shared::cta.b64 _, [%0], %1;" :: "r"(bar), "r"(bytes) : "memory");
}
__device__ __forceinline__ void mbar_arrive(uint32_t bar) {
    asm volatile("mbarrier.arrive.shared::cta.b64 _, [%0];" :: "r"(bar) : "memory");
}
__device__ __forceinline__ void mbar_arrive_cluster(uint32_t bar) {
    asm volatile("mbarrier.arrive.shared::cluster.b64 _, [%0];" :: "r"(bar) : "memory");
}
__device__ __forceinline__ void mbar_wait(uint32_t bar) {
    asm volatile("{\n.reg .pred p;\nWAIT_LOOP:\nmbarrier.try_wait.parity.shared::cta.b64 p, [%0], 0;\n@!p bra WAIT_LOOP;\n}" :: "r"(bar) : "memory");
}
__device__ __forceinline__ void mbar_wait_cluster(uint32_t bar) {
    asm volatile("{\n.reg .pred p;\nWAIT_LOOP:\nmbarrier.try_wait.parity.relaxed.cluster.shared::cta.b64 p, [%0], 0;\n@!p bra WAIT_LOOP;\n"
                 "fence.acquire.sync_restrict::shared::cluster.cluster;\n}" :: "r"(bar) : "memory");
}
__device__ __forceinline__ void mbar_wait2(uint32_t bar0, uint32_t bar1) { mbar_wait(bar0); mbar_wait(bar1); }
__device__ __forceinline__ bool mbar_test(uint32_t bar) {
    uint32_t ok;
    asm volatile("{\n.reg .pred p;\nmbarrier.test_wait.parity.shared::cta.b64 p, [%1], 0;\nselp.u32 %0, 1, 0, p;\n}" : "=r"(ok) : "r"(bar) : "memory");
    return ok;
}
__device__ __forceinline__ bool mbar_test2(uint32_t bar0, uint32_t bar1) {
    uint32_t ok;
    asm volatile("{\n.reg .pred p, q;\nmbarrier.test_wait.parity.shared::cta.b64 p, [%1], 0;\n"
                 "mbarrier.test_wait.parity.shared::cta.b64 q, [%2], 0;\nand.pred p, p, q;\nselp.u32 %0, 1, 0, p;\n}"
                 : "=r"(ok) : "r"(bar0), "r"(bar1) : "memory");
    return ok;
}
__device__ __forceinline__ bool elect_one() {
    uint32_t ok;
    asm volatile("{\n.reg .pred p;\nelect.sync _|p, 0xffffffff;\nselp.u32 %0, 1, 0, p;\n}" : "=r"(ok));
    return ok;
}
__device__ __forceinline__ uint32_t mapa(uint32_t a, uint32_t cta) {
    uint32_t r;
    asm("mapa.shared::cluster.u32 %0, %1, %2;" : "=r"(r) : "r"(a), "r"(cta));
    return r;
}
__device__ __forceinline__ void st_async32(uint32_t a, uint32_t v, uint32_t bar) {
    asm volatile("st.async.shared::cluster.mbarrier::complete_tx::bytes.b32 [%0], %1, [%2];" :: "r"(a), "r"(v), "r"(bar) : "memory");
}
__device__ __forceinline__ unsigned ld_flag(const unsigned* p) {
    unsigned v;
    asm volatile("ld.relaxed.gpu.global.u32 %0, [%1];" : "=r"(v) : "l"(p) : "memory");
    return v;
}
__device__ __forceinline__ unsigned clk() { unsigned t; asm volatile("mov.u32 %0, %clock;" : "=r"(t)); return t; }
__device__ __forceinline__ uint32_t lds32(uint32_t a) {
    uint32_t v;
    asm volatile("ld.shared.b32 %0, [%1];" : "=r"(v) : "r"(a) : "memory");
    return v;
}
__device__ __forceinline__ void sts32(uint32_t a, uint32_t v) {
    asm volatile("st.shared.b32 [%0], %1;" :: "r"(a), "r"(v) : "memory");
}
__device__ __forceinline__ void stg128(void* p, uint4 v) {
    asm volatile("st.global.v4.b32 [%0], {%1,%2,%3,%4};" :: "l"(p), "r"(v.x), "r"(v.y), "r"(v.z), "r"(v.w) : "memory");
}
__device__ __forceinline__ unsigned pack4(unsigned a, unsigned b, unsigned c, unsigned d) {
    unsigned lo, r;
    asm("cvt.pack.sat.s8.s32.b32 %0, %1, %2, 0;" : "=r"(lo) : "r"(d), "r"(c));
    asm("cvt.pack.sat.s8.s32.b32 %0, %1, %2, %3;" : "=r"(r) : "r"(b), "r"(a), "r"(lo));
    return r;
}
constexpr uint32_t DESC_A_HI = 256 >> 4;
constexpr uint32_t DESC_B_HI = 0x80000000u | (512 >> 4);
__device__ __forceinline__ void mma_unit2(int (&d)[64], int (&e)[64], uint32_t alo, uint32_t blo, int scale_d) {
    asm volatile("{\n.reg .pred p;\n.reg .b64 da, db;\nsetp.ne.b32 p, %130, 0;\n"
        "mov.b64 da, {%128, %131};\nmov.b64 db, {%129, %132};\n"
        "wgmma.mma_async.sync.aligned.m64n128k32.s32.s8.s8 "
        "{%0, %1, %2, %3, %4, %5, %6, %7, %8, %9, %10, %11, %12, %13, %14, %15, "
        "%16, %17, %18, %19, %20, %21, %22, %23, %24, %25, %26, %27, %28, %29, %30, %31, "
        "%32, %33, %34, %35, %36, %37, %38, %39, %40, %41, %42, %43, %44, %45, %46, %47, "
        "%48, %49, %50, %51, %52, %53, %54, %55, %56, %57, %58, %59, %60, %61, %62, %63}, "
        "da, db, p;\n"
        "add.s64 da, da, 128;\n"
        "wgmma.mma_async.sync.aligned.m64n128k32.s32.s8.s8 "
        "{%64, %65, %66, %67, %68, %69, %70, %71, %72, %73, %74, %75, %76, %77, %78, %79, "
        "%80, %81, %82, %83, %84, %85, %86, %87, %88, %89, %90, %91, %92, %93, %94, %95, "
        "%96, %97, %98, %99, %100, %101, %102, %103, %104, %105, %106, %107, %108, %109, %110, %111, "
        "%112, %113, %114, %115, %116, %117, %118, %119, %120, %121, %122, %123, %124, %125, %126, %127}, "
        "da, db, p;\n"
        "add.s64 da, da, 128;\nadd.s64 db, db, 2;\n"
        "wgmma.mma_async.sync.aligned.m64n128k32.s32.s8.s8 "
        "{%0, %1, %2, %3, %4, %5, %6, %7, %8, %9, %10, %11, %12, %13, %14, %15, "
        "%16, %17, %18, %19, %20, %21, %22, %23, %24, %25, %26, %27, %28, %29, %30, %31, "
        "%32, %33, %34, %35, %36, %37, %38, %39, %40, %41, %42, %43, %44, %45, %46, %47, "
        "%48, %49, %50, %51, %52, %53, %54, %55, %56, %57, %58, %59, %60, %61, %62, %63}, "
        "da, db, 1;\n"
        "add.s64 da, da, 128;\n"
        "wgmma.mma_async.sync.aligned.m64n128k32.s32.s8.s8 "
        "{%64, %65, %66, %67, %68, %69, %70, %71, %72, %73, %74, %75, %76, %77, %78, %79, "
        "%80, %81, %82, %83, %84, %85, %86, %87, %88, %89, %90, %91, %92, %93, %94, %95, "
        "%96, %97, %98, %99, %100, %101, %102, %103, %104, %105, %106, %107, %108, %109, %110, %111, "
        "%112, %113, %114, %115, %116, %117, %118, %119, %120, %121, %122, %123, %124, %125, %126, %127}, "
        "da, db, 1;\n"
        "wgmma.commit_group.sync.aligned;\n}\n"
        : "+r"(d[0]), "+r"(d[1]), "+r"(d[2]), "+r"(d[3]), "+r"(d[4]), "+r"(d[5]), "+r"(d[6]), "+r"(d[7]),
          "+r"(d[8]), "+r"(d[9]), "+r"(d[10]), "+r"(d[11]), "+r"(d[12]), "+r"(d[13]), "+r"(d[14]), "+r"(d[15]),
          "+r"(d[16]), "+r"(d[17]), "+r"(d[18]), "+r"(d[19]), "+r"(d[20]), "+r"(d[21]), "+r"(d[22]), "+r"(d[23]),
          "+r"(d[24]), "+r"(d[25]), "+r"(d[26]), "+r"(d[27]), "+r"(d[28]), "+r"(d[29]), "+r"(d[30]), "+r"(d[31]),
          "+r"(d[32]), "+r"(d[33]), "+r"(d[34]), "+r"(d[35]), "+r"(d[36]), "+r"(d[37]), "+r"(d[38]), "+r"(d[39]),
          "+r"(d[40]), "+r"(d[41]), "+r"(d[42]), "+r"(d[43]), "+r"(d[44]), "+r"(d[45]), "+r"(d[46]), "+r"(d[47]),
          "+r"(d[48]), "+r"(d[49]), "+r"(d[50]), "+r"(d[51]), "+r"(d[52]), "+r"(d[53]), "+r"(d[54]), "+r"(d[55]),
          "+r"(d[56]), "+r"(d[57]), "+r"(d[58]), "+r"(d[59]), "+r"(d[60]), "+r"(d[61]), "+r"(d[62]), "+r"(d[63]),
          "+r"(e[0]), "+r"(e[1]), "+r"(e[2]), "+r"(e[3]), "+r"(e[4]), "+r"(e[5]), "+r"(e[6]), "+r"(e[7]),
          "+r"(e[8]), "+r"(e[9]), "+r"(e[10]), "+r"(e[11]), "+r"(e[12]), "+r"(e[13]), "+r"(e[14]), "+r"(e[15]),
          "+r"(e[16]), "+r"(e[17]), "+r"(e[18]), "+r"(e[19]), "+r"(e[20]), "+r"(e[21]), "+r"(e[22]), "+r"(e[23]),
          "+r"(e[24]), "+r"(e[25]), "+r"(e[26]), "+r"(e[27]), "+r"(e[28]), "+r"(e[29]), "+r"(e[30]), "+r"(e[31]),
          "+r"(e[32]), "+r"(e[33]), "+r"(e[34]), "+r"(e[35]), "+r"(e[36]), "+r"(e[37]), "+r"(e[38]), "+r"(e[39]),
          "+r"(e[40]), "+r"(e[41]), "+r"(e[42]), "+r"(e[43]), "+r"(e[44]), "+r"(e[45]), "+r"(e[46]), "+r"(e[47]),
          "+r"(e[48]), "+r"(e[49]), "+r"(e[50]), "+r"(e[51]), "+r"(e[52]), "+r"(e[53]), "+r"(e[54]), "+r"(e[55]),
          "+r"(e[56]), "+r"(e[57]), "+r"(e[58]), "+r"(e[59]), "+r"(e[60]), "+r"(e[61]), "+r"(e[62]), "+r"(e[63])
        : "r"(alo), "r"(blo), "r"(scale_d), "n"(DESC_A_HI), "n"(DESC_B_HI) : "memory");
}
__device__ __forceinline__ bool mma_pair(int (&d)[64], uint32_t alo, uint32_t blo, int scale_d, uint32_t bar) {
    uint32_t ok;
    asm volatile("{\n.reg .pred p, q;\n.reg .b64 da, db;\nsetp.ne.b32 p, %67, 0;\n"
        "mov.b64 da, {%65, %68};\nmov.b64 db, {%66, %69};\n"
        "wgmma.mma_async.sync.aligned.m64n128k32.s32.s8.s8 "
        "{%0, %1, %2, %3, %4, %5, %6, %7, %8, %9, %10, %11, %12, %13, %14, %15, "
        "%16, %17, %18, %19, %20, %21, %22, %23, %24, %25, %26, %27, %28, %29, %30, %31, "
        "%32, %33, %34, %35, %36, %37, %38, %39, %40, %41, %42, %43, %44, %45, %46, %47, "
        "%48, %49, %50, %51, %52, %53, %54, %55, %56, %57, %58, %59, %60, %61, %62, %63}, "
        "da, db, p;\n"
        "add.s64 da, da, 128;\nadd.s64 db, db, 2;\n"
        "wgmma.mma_async.sync.aligned.m64n128k32.s32.s8.s8 "
        "{%0, %1, %2, %3, %4, %5, %6, %7, %8, %9, %10, %11, %12, %13, %14, %15, "
        "%16, %17, %18, %19, %20, %21, %22, %23, %24, %25, %26, %27, %28, %29, %30, %31, "
        "%32, %33, %34, %35, %36, %37, %38, %39, %40, %41, %42, %43, %44, %45, %46, %47, "
        "%48, %49, %50, %51, %52, %53, %54, %55, %56, %57, %58, %59, %60, %61, %62, %63}, "
        "da, db, 1;\n"
        "add.s64 da, da, 128;\nadd.s64 db, db, 510;\n"
        "wgmma.mma_async.sync.aligned.m64n128k32.s32.s8.s8 "
        "{%0, %1, %2, %3, %4, %5, %6, %7, %8, %9, %10, %11, %12, %13, %14, %15, "
        "%16, %17, %18, %19, %20, %21, %22, %23, %24, %25, %26, %27, %28, %29, %30, %31, "
        "%32, %33, %34, %35, %36, %37, %38, %39, %40, %41, %42, %43, %44, %45, %46, %47, "
        "%48, %49, %50, %51, %52, %53, %54, %55, %56, %57, %58, %59, %60, %61, %62, %63}, "
        "da, db, 1;\n"
        "add.s64 da, da, 128;\nadd.s64 db, db, 2;\n"
        "wgmma.mma_async.sync.aligned.m64n128k32.s32.s8.s8 "
        "{%0, %1, %2, %3, %4, %5, %6, %7, %8, %9, %10, %11, %12, %13, %14, %15, "
        "%16, %17, %18, %19, %20, %21, %22, %23, %24, %25, %26, %27, %28, %29, %30, %31, "
        "%32, %33, %34, %35, %36, %37, %38, %39, %40, %41, %42, %43, %44, %45, %46, %47, "
        "%48, %49, %50, %51, %52, %53, %54, %55, %56, %57, %58, %59, %60, %61, %62, %63}, "
        "da, db, 1;\n"
        "add.s64 da, da, 128;\nadd.s64 db, db, 510;\n"
        "wgmma.mma_async.sync.aligned.m64n128k32.s32.s8.s8 "
        "{%0, %1, %2, %3, %4, %5, %6, %7, %8, %9, %10, %11, %12, %13, %14, %15, "
        "%16, %17, %18, %19, %20, %21, %22, %23, %24, %25, %26, %27, %28, %29, %30, %31, "
        "%32, %33, %34, %35, %36, %37, %38, %39, %40, %41, %42, %43, %44, %45, %46, %47, "
        "%48, %49, %50, %51, %52, %53, %54, %55, %56, %57, %58, %59, %60, %61, %62, %63}, "
        "da, db, 1;\n"
        "add.s64 da, da, 128;\nadd.s64 db, db, 2;\n"
        "mbarrier.test_wait.parity.shared::cta.b64 q, [%70], 0;\n"
        "wgmma.mma_async.sync.aligned.m64n128k32.s32.s8.s8 "
        "{%0, %1, %2, %3, %4, %5, %6, %7, %8, %9, %10, %11, %12, %13, %14, %15, "
        "%16, %17, %18, %19, %20, %21, %22, %23, %24, %25, %26, %27, %28, %29, %30, %31, "
        "%32, %33, %34, %35, %36, %37, %38, %39, %40, %41, %42, %43, %44, %45, %46, %47, "
        "%48, %49, %50, %51, %52, %53, %54, %55, %56, %57, %58, %59, %60, %61, %62, %63}, "
        "da, db, 1;\n"
        "add.s64 da, da, 128;\nadd.s64 db, db, 510;\n"
        "wgmma.mma_async.sync.aligned.m64n128k32.s32.s8.s8 "
        "{%0, %1, %2, %3, %4, %5, %6, %7, %8, %9, %10, %11, %12, %13, %14, %15, "
        "%16, %17, %18, %19, %20, %21, %22, %23, %24, %25, %26, %27, %28, %29, %30, %31, "
        "%32, %33, %34, %35, %36, %37, %38, %39, %40, %41, %42, %43, %44, %45, %46, %47, "
        "%48, %49, %50, %51, %52, %53, %54, %55, %56, %57, %58, %59, %60, %61, %62, %63}, "
        "da, db, 1;\n"
        "add.s64 da, da, 128;\nadd.s64 db, db, 2;\n"
        "wgmma.mma_async.sync.aligned.m64n128k32.s32.s8.s8 "
        "{%0, %1, %2, %3, %4, %5, %6, %7, %8, %9, %10, %11, %12, %13, %14, %15, "
        "%16, %17, %18, %19, %20, %21, %22, %23, %24, %25, %26, %27, %28, %29, %30, %31, "
        "%32, %33, %34, %35, %36, %37, %38, %39, %40, %41, %42, %43, %44, %45, %46, %47, "
        "%48, %49, %50, %51, %52, %53, %54, %55, %56, %57, %58, %59, %60, %61, %62, %63}, "
        "da, db, 1;\n"
        "wgmma.commit_group.sync.aligned;\nselp.u32 %64, 1, 0, q;\n}\n"
        : "+r"(d[0]), "+r"(d[1]), "+r"(d[2]), "+r"(d[3]), "+r"(d[4]), "+r"(d[5]), "+r"(d[6]), "+r"(d[7]),
          "+r"(d[8]), "+r"(d[9]), "+r"(d[10]), "+r"(d[11]), "+r"(d[12]), "+r"(d[13]), "+r"(d[14]), "+r"(d[15]),
          "+r"(d[16]), "+r"(d[17]), "+r"(d[18]), "+r"(d[19]), "+r"(d[20]), "+r"(d[21]), "+r"(d[22]), "+r"(d[23]),
          "+r"(d[24]), "+r"(d[25]), "+r"(d[26]), "+r"(d[27]), "+r"(d[28]), "+r"(d[29]), "+r"(d[30]), "+r"(d[31]),
          "+r"(d[32]), "+r"(d[33]), "+r"(d[34]), "+r"(d[35]), "+r"(d[36]), "+r"(d[37]), "+r"(d[38]), "+r"(d[39]),
          "+r"(d[40]), "+r"(d[41]), "+r"(d[42]), "+r"(d[43]), "+r"(d[44]), "+r"(d[45]), "+r"(d[46]), "+r"(d[47]),
          "+r"(d[48]), "+r"(d[49]), "+r"(d[50]), "+r"(d[51]), "+r"(d[52]), "+r"(d[53]), "+r"(d[54]), "+r"(d[55]),
          "+r"(d[56]), "+r"(d[57]), "+r"(d[58]), "+r"(d[59]), "+r"(d[60]), "+r"(d[61]), "+r"(d[62]), "+r"(d[63]), "=r"(ok)
        : "r"(alo), "r"(blo), "r"(scale_d), "n"(DESC_A_HI), "n"(DESC_B_HI), "r"(bar) : "memory");
    return ok;
}

__device__ __forceinline__ void wg_fence() { asm volatile("wgmma.fence.sync.aligned;" ::: "memory"); }
template <int N> __device__ __forceinline__ void wg_wait() { asm volatile("wgmma.wait_group.sync.aligned %0;" :: "n"(N) : "memory"); }

constexpr int W0 = 16, C0 = 30;
__host__ __device__ constexpr int unit_of(int wg, int s) { return wg ? (s < 16 - D_ ? D_ + 2 * s : s + 16) : (s < D_ ? s : 2 * s - D_ + 1); }

__host__ __device__ constexpr int bar_of(int u) { return u >= 32 ? u & ~1 : u < D_ || u >= 32 - D_ ? u : ((u - D_) & 1) ? D_ + ((u - D_) >> 1) : 16 + ((u - D_) >> 1); }
constexpr uint32_t step_table(int wg) {
    uint32_t t = 0;
    for (int s = 0; s < 15; s++) t |= (uint32_t)(unit_of(wg, s + 1) - unit_of(wg, s) - 1) << s;
    return t;
}
constexpr uint32_t STEPS0 = step_table(0), STEPS1 = step_table(1);
__host__ __device__ constexpr int sum_owner(int g) { return g < 8 ? (g & 4) | (g & 1) << 1 | (~g >> 1 & 1) : g; }
__device__ __forceinline__ int sum_group(int r) { return r < 8 ? (r & 4) | (~r & 1) << 1 | (r >> 1 & 1) : r; }
struct JobTable { uint2 e[NCTA][NJOB + NCONV]; };
__device__ const JobTable g_jobs = {{
    {{0x0, 0x0}, {0x20400, 0x1000000}, {0x90202, 0x20080a2}, {0x100004, 0x3010144}, {0x14000000, 0x31000221}, {0x2a506231, 0x62830288}, {0x14102a00, 0x31004322}, {0x5d0a07, 0x409c3af}, {0x14204600, 0x31048495}, {0x3646809, 0x56a4516}, {0x14306200, 0x3104c5ff}, {0x2ac500b, 0x752c668}, {0x14407e00, 0x31090744}, {0x34000d, 0x8034794}, {0x37060d, 0x803480f}, {0x14509a00, 0x3109488a}, {0x33c600f, 0x963c8f9}, {0x1460b600, 0x310d89a6}, {0x2aaf6935, 0x6d88c9f6}, {0x1470d200, 0x310dca49}, {0x14800004, 0x98020aeb}, {0x14907004, 0x980a4b8e}, {0x14a00005, 0xba028c6d}, {0x14b07005, 0xba0acd60}, {0x14c00006, 0xdc030e44}, {0x14d07006, 0xdc0b4f18}, {0x30000000, 0x0}, {0x30000000, 0x0}, {0x30000000, 0x0}, {0x30000000, 0x0}, {0x30000000, 0x0}, {0x30000000, 0x0}},
    {{0x0, 0x0}, {0x420c00, 0x1080001}, {0x490a02, 0x20880a3}, {0x500804, 0x3090145}, {0x14010001, 0x2000022d}, {0x1572e05, 0x42942a4}, {0x14112a01, 0x20004339}, {0x2a5e5b33, 0x5d83c3c1}, {0x14214601, 0x200484ac}, {0x1252209, 0x622452b}, {0x14316201, 0x2004c613}, {0x2d020b, 0x702c677}, {0x32f660b, 0x762c6e7}, {0x14417e01, 0x20090759}, {0x2a8eaf33, 0xb186c7d0}, {0x14519a01, 0x2009489e}, {0x2a9dd234, 0xd587c902}, {0x1461b601, 0x200d89b0}, {0x2ab07035, 0x74890a00}, {0x1471d201, 0x200dca53}, {0x14810704, 0x98020af6}, {0x14917704, 0x980a4b98}, {0x14a10705, 0xba028c7c}, {0x14b17705, 0xba0acd6f}, {0x14c10706, 0xdc030e51}, {0x14d17706, 0xdc0b4f25}, {0x30000000, 0x0}, {0x30000000, 0x0}, {0x30000000, 0x0}, {0x30000000, 0x0}, {0x30000000, 0x0}, {0x30000000, 0x0}},
    {{0x0, 0x0}, {0x821400, 0x1100002}, {0x891202, 0x21080a4}, {0x901004, 0x3110146}, {0x14020700, 0x31000238}, {0x2d75e05, 0x45942b5}, {0x14123100, 0x31004350}, {0x39d7207, 0x471c3d4}, {0x1e03808, 0x53a044a}, {0x14224d00, 0x310484c4}, {0x3e57a09, 0x67a4549}, {0x14326900, 0x3104c627}, {0x22d420b, 0x742c68c}, {0x14428500, 0x3109076d}, {0x36040d, 0x80347e6}, {0x1452a100, 0x310948b3}, {0x1bd320f, 0x933c912}, {0x1462bd00, 0x310d89ba}, {0x2ab17735, 0x7b890a0a}, {0x1472d900, 0x310dca5d}, {0x14820e04, 0x98020b00}, {0x14927e04, 0x980a4ba3}, {0x14a20e05, 0xba028c8b}, {0x14b27e05, 0xba0acd7e}, {0x14c20e06, 0xdc030e5e}, {0x14d27e06, 0xdc0b4f33}, {0x30000000, 0x0}, {0x30000000, 0x0}, {0x30000000, 0x0}, {0x30000000, 0x0}, {0x30000000, 0x0}, {0x30000000, 0x0}},
    {{0x0, 0x0}, {0xc21c00, 0x1180004}, {0xc91a02, 0x21880a6}, {0xd01804, 0x3190148}, {0x14030701, 0x20000244}, {0x580806, 0x40982c6}, {0x14133101, 0x20004367}, {0x11e2407, 0x521c3e6}, {0x3e07808, 0x57a0461}, {0x14234d01, 0x200484db}, {0x1e63c09, 0x63a4560}, {0x14336901, 0x2004c63c}, {0xae140b, 0x712c6a5}, {0x14438501, 0x20090781}, {0x2b6540d, 0x85347ff}, {0x1453a101, 0x200948c7}, {0x37d6a0f, 0x96bc924}, {0x1463bd01, 0x200d89c4}, {0x2ab27e35, 0x82890a14}, {0x1473d901, 0x200dca67}, {0x14831504, 0x98020b0a}, {0x14938504, 0x980a4bad}, {0x14a31505, 0xba028c9b}, {0x14b38505, 0xba0acd8e}, {0x14c31506, 0xdc030e6b}, {0x14d38506, 0xdc0b4f40}, {0x30000000, 0x0}, {0x30000000, 0x0}, {0x30000000, 0x0}, {0x30000000, 0x0}, {0x30000000, 0x0}, {0x30000000, 0x0}},
    {{0x0, 0x0}, {0x1022400, 0x1200005}, {0x1092202, 0x22080a7}, {0x1102004, 0x3210149}, {0x14040e00, 0x3100024f}, {0x2a544633, 0x488342d9}, {0x14140e02, 0x7500437f}, {0x29e5407, 0x551c3f7}, {0x14242a02, 0x750084f2}, {0xe61c09, 0x61a4556}, {0x368680a, 0x66a85cd}, {0x14344602, 0x7504c650}, {0x2ee5c0b, 0x75ac6bc}, {0x14446202, 0x75050796}, {0x770e0d, 0x80b4811}, {0x14547e02, 0x750948db}, {0x1be340f, 0x933c93b}, {0x14649a02, 0x750989ce}, {0x2ab38535, 0x89890a1f}, {0x1474b602, 0x750dca71}, {0x14841c04, 0x98020b14}, {0x14948c04, 0x980a4bb7}, {0x14a41c05, 0xba028caa}, {0x14b48c05, 0xba0acd9d}, {0x14c41c06, 0xdc030e79}, {0x14d48c06, 0xdc0b4f4d}, {0x30000000, 0x0}, {0x30000000, 0x0}, {0x30000000, 0x0}, {0x30000000, 0x0}, {0x30000000, 0x0}, {0x30000000, 0x0}},
    {{0x0, 0x0}, {0x1422c00, 0x1280007}, {0x1492a02, 0x22880a9}, {0x1502804, 0x329014b}, {0x14050e01, 0x2000025b}, {0x3987006, 0x47182ec}, {0x14150e03, 0x64004396}, {0x1f0607, 0x501c409}, {0x3216208, 0x5620488}, {0x14252a03, 0x64008509}, {0x1672e09, 0x62a458a}, {0x14354603, 0x6404c664}, {0x12f260b, 0x722c6d3}, {0x14456203, 0x640507aa}, {0x237460d, 0x8434823}, {0x2a97bd34, 0xc0874887}, {0x14557e03, 0x640948f0}, {0xff1e0f, 0x91bc95c}, {0x14659a03, 0x640989d9}, {0x1475b603, 0x640dca7b}, {0x14852304, 0x98020b1e}, {0x14959304, 0x980a4bc6}, {0x14a52305, 0xba028cb9}, {0x14b59305, 0xba0acdac}, {0x14c52306, 0xdc030e86}, {0x14d59306, 0xdc0b4f5b}, {0x30000000, 0x0}, {0x30000000, 0x0}, {0x30000000, 0x0}, {0x30000000, 0x0}, {0x30000000, 0x0}, {0x30000000, 0x0}},
    {{0x0, 0x0}, {0x1823400, 0x1300008}, {0x1893202, 0x23080aa}, {0x1903004, 0x331014c}, {0x14061500, 0x31000267}, {0x1192206, 0x42182fe}, {0x14161502, 0x750043ad}, {0x1df3e07, 0x539c41b}, {0xe21c08, 0x51a049d}, {0x14263102, 0x75008521}, {0x2674e09, 0x64a4596}, {0x14364d02, 0x7504c679}, {0x36f6e0b, 0x76ac6ea}, {0x14466902, 0x750507be}, {0x3f77e0d, 0x87b4833}, {0x2a98c433, 0xc687889c}, {0x14568502, 0x75094904}, {0x1ff3e0f, 0x93bc965}, {0x1466a102, 0x750989e3}, {0x1476bd02, 0x750dca86}, {0x14862a04, 0x98020b28}, {0x14969a04, 0x980a4bd5}, {0x14a62a05, 0xba028cc8}, {0x14b69a05, 0xba0acdbb}, {0x14c62a06, 0xdc030e93}, {0x14d69a06, 0xdc0b4f68}, {0x30000000, 0x0}, {0x30000000, 0x0}, {0x30000000, 0x0}, {0x30000000, 0x0}, {0x30000000, 0x0}, {0x30000000, 0x0}},
    {{0x0, 0x0}, {0x1c23c00, 0x138000a}, {0x1c93a02, 0x23880ac}, {0x1d03804, 0x339014e}, {0x14071501, 0x20000272}, {0x2995206, 0x451830f}, {0x14171503, 0x640043c4}, {0x35f6e07, 0x569c42e}, {0x2e25c08, 0x55a04b4}, {0x14273103, 0x64008538}, {0x68080a, 0x60a85ad}, {0x14374d03, 0x6404c68d}, {0xb0100c, 0x71306f7}, {0x14476903, 0x640507d3}, {0xf8180e, 0x81b883f}, {0x3ba740e, 0x97388ac}, {0x14578503, 0x64094918}, {0x3ff7e0f, 0x97bc979}, {0x1467a103, 0x640989ed}, {0x1477bd03, 0x640dca90}, {0x14873104, 0x98020b33}, {0x1497a104, 0x980a4be5}, {0x14a73105, 0xba028cd7}, {0x14b7a105, 0xba0acdca}, {0x14c73106, 0xdc030ea1}, {0x14d7a106, 0xdc0b4f75}, {0x30000000, 0x0}, {0x30000000, 0x0}, {0x30000000, 0x0}, {0x30000000, 0x0}, {0x30000000, 0x0}, {0x30000000, 0x0}},
    {{0x0, 0x0}, {0x2024400, 0x140000b}, {0x2094202, 0x24080ad}, {0x2104004, 0x341014f}, {0x2a271532, 0x168041f1}, {0x14081c00, 0x3100027e}, {0x11a2406, 0x421832c}, {0x14183800, 0x310443dc}, {0x2a05008, 0x5520454}, {0x14285400, 0x3104854f}, {0x2a8500a, 0x65285c5}, {0x14387000, 0x3108c6a1}, {0x230400c, 0x7430706}, {0x14488c00, 0x310907e7}, {0x1b8300e, 0x8338847}, {0xfb1e0e, 0x91b88b9}, {0x1458a800, 0x310d492d}, {0x1468c400, 0x310d89f7}, {0x2ab7a135, 0xa5894a47}, {0x1478c402, 0x750dca9a}, {0x14883804, 0x98060b3d}, {0x1498a804, 0x980e4bf4}, {0x14a83805, 0xba068ce7}, {0x14b8a805, 0xba0ecdd9}, {0x14c83806, 0xdc070eae}, {0x14d8a806, 0xdc0f4f82}, {0x30000000, 0x0}, {0x30000000, 0x0}, {0x30000000, 0x0}, {0x30000000, 0x0}, {0x30000000, 0x0}, {0x30000000, 0x0}},
    {{0x0, 0x0}, {0x2424c00, 0x148000c}, {0x2494a02, 0x24880ae}, {0x2504804, 0x3490150}, {0x2a200031, 0x8001e7}, {0x14091c01, 0x2000028a}, {0x21a4406, 0x4418338}, {0x14193801, 0x200443f3}, {0xe11a08, 0x51a046e}, {0x14295401, 0x20048566}, {0xe91a0a, 0x61a85dc}, {0x14397001, 0x2008c6b6}, {0x3f0780c, 0x77b0716}, {0x2f35e0c, 0x85b0788}, {0x14498c01, 0x200907fb}, {0x239420e, 0x8438874}, {0x1459a801, 0x200d4941}, {0x1469c401, 0x200d8a01}, {0x2ab8a835, 0xac898a51}, {0x1479c403, 0x640dcaa4}, {0x14893f04, 0x98060b47}, {0x1499af04, 0x980e4c03}, {0x14a93f05, 0xba068cf6}, {0x14b9af05, 0xba0ecde7}, {0x14c93f06, 0xdc070ebb}, {0x14d9af06, 0xdc0f4f90}, {0x30000000, 0x0}, {0x30000000, 0x0}, {0x30000000, 0x0}, {0x30000000, 0x0}, {0x30000000, 0x0}, {0x30000000, 0x0}},
    {{0x0, 0x0}, {0x2825400, 0x150000e}, {0x2895202, 0x25080b0}, {0x2905004, 0x3510152}, {0x2a210032, 0x18001e8}, {0x140a2300, 0x31000297}, {0x35a6c06, 0x4698346}, {0x141a3f00, 0x3104440a}, {0x3616a08, 0x56a048b}, {0x142a5b00, 0x3104857d}, {0x3e97a0a, 0x67a85f9}, {0x143a7700, 0x3108c6ca}, {0x1712a0c, 0x72b0727}, {0x144a9300, 0x31090810}, {0x1792a0e, 0x82b886d}, {0x145aaf00, 0x310d4956}, {0x2aab4d35, 0x518889cd}, {0x146acb00, 0x310d8a0b}, {0x147acb02, 0x750dcaae}, {0x2ac93f36, 0x448a8afe}, {0x148a4604, 0x98060b51}, {0x149ab604, 0x980e4c12}, {0x14aa4605, 0xba068d05}, {0x14bab605, 0xba0ecdf4}, {0x14ca4606, 0xdc070ec8}, {0x14dab606, 0xdc0f4f9d}, {0x30000000, 0x0}, {0x30000000, 0x0}, {0x30000000, 0x0}, {0x30000000, 0x0}, {0x30000000, 0x0}, {0x30000000, 0x0}},
    {{0x0, 0x0}, {0x2c25c00, 0x158000f}, {0x2c95a02, 0x25880b1}, {0x2d05804, 0x3590153}, {0x2a220731, 0x78001ea}, {0x140b2301, 0x200002ae}, {0xdb1e06, 0x4198358}, {0x141b3f01, 0x20044421}, {0x1a23408, 0x53204a5}, {0x142b5b01, 0x20048595}, {0x26a4c0a, 0x64a8614}, {0x6d0a0b, 0x70ac67a}, {0x143b7701, 0x2008c6de}, {0x1722c0c, 0x72b0750}, {0x144b9301, 0x20090824}, {0x3a040e, 0x9038889}, {0x145baf01, 0x200d496a}, {0x146bcb01, 0x200d8a16}, {0x2abab635, 0xba898a66}, {0x147bcb03, 0x640dcab9}, {0x148b4d04, 0x98060b5b}, {0x149bbd04, 0x980e4c21}, {0x14ab4d05, 0xba068d14}, {0x14bbbd05, 0xba0ece01}, {0x14cb4d06, 0xdc070ed6}, {0x14dbbd06, 0xdc0f4faa}, {0x30000000, 0x0}, {0x30000000, 0x0}, {0x30000000, 0x0}, {0x30000000, 0x0}, {0x30000000, 0x0}, {0x30000000, 0x0}},
    {{0x0, 0x0}, {0x3026400, 0x1600011}, {0x3096202, 0x26080b3}, {0x3106004, 0x3610155}, {0x2a230732, 0x88001eb}, {0x140c0002, 0x750002c5}, {0x25b4e06, 0x4498369}, {0x141c1c02, 0x75004438}, {0x3e27c08, 0x57a04be}, {0x142c3802, 0x750485ac}, {0x2b060a, 0x6028626}, {0x2a7e9333, 0x9585c68a}, {0x143c5402, 0x7504c6f3}, {0x332640c, 0x7630761}, {0x144c7002, 0x75090839}, {0x2ba540e, 0x95388a2}, {0x145c8c02, 0x7509497d}, {0x146ca802, 0x750d8a20}, {0x2abbbd35, 0xc1898a70}, {0x147cd202, 0x750dcac3}, {0x148c5404, 0x98060b66}, {0x149cc404, 0x980e4c30}, {0x14ac5405, 0xba068d23}, {0x14bcc405, 0xba0ece0f}, {0x14cc5406, 0xdc070ee3}, {0x14dcc406, 0xdc0f4fb8}, {0x30000000, 0x0}, {0x30000000, 0x0}, {0x30000000, 0x0}, {0x30000000, 0x0}, {0x30000000, 0x0}, {0x30000000, 0x0}},
    {{0x0, 0x0}, {0x3426c00, 0x1680012}, {0x3496a02, 0x26880b4}, {0x3506804, 0x3690156}, {0x2a240e31, 0xe8041ed}, {0x140d0003, 0x640002dc}, {0x2a5b7732, 0x7883837c}, {0x141d1c03, 0x64004450}, {0x2a6a9331, 0x938484d8}, {0x142d3803, 0x640485c1}, {0x2a7aaf31, 0xaf858639}, {0x2e040b, 0x702c6a0}, {0x143d5403, 0x6404c707}, {0x1b3360c, 0x833077b}, {0x144d7003, 0x6409084d}, {0x1fb3e0e, 0x93b88c2}, {0x145d8c03, 0x64094987}, {0x146da803, 0x640d8a2a}, {0x2abcc435, 0xc889ca7a}, {0x147dd203, 0x640dcacd}, {0x148d5b04, 0x98060b70}, {0x149dcb04, 0x980e4c40}, {0x14ad5b05, 0xba068d32}, {0x14bdcb05, 0xba0ece1c}, {0x14cd5b06, 0xdc070ef0}, {0x14ddcb06, 0xdc0f4fc5}, {0x30000000, 0x0}, {0x30000000, 0x0}, {0x30000000, 0x0}, {0x30000000, 0x0}, {0x30000000, 0x0}, {0x30000000, 0x0}},
    {{0x0, 0x0}, {0x3827400, 0x1700014}, {0x3897202, 0x27080b6}, {0x3907004, 0x3710158}, {0x2a250e32, 0xf8041ee}, {0x140e0702, 0x750002f3}, {0x15c2807, 0x429c38c}, {0x141e2302, 0x75004467}, {0x3e37e08, 0x57a04ec}, {0x142e3f02, 0x750485d6}, {0x3ab760a, 0x672864a}, {0x2a80b631, 0xb68606b3}, {0x143e5b02, 0x7504c71c}, {0x3f37e0c, 0x87b0791}, {0x144e7702, 0x75090861}, {0x2a9bcb34, 0xce8788d9}, {0x145e9302, 0x75094991}, {0x146eaf02, 0x750d8a34}, {0x2abdcb35, 0xcf89ca84}, {0x147ed902, 0x750dcad7}, {0x148e6204, 0x98060b7a}, {0x149ed204, 0x980e4c4f}, {0x14ae6205, 0xba068d42}, {0x14bed205, 0xba0ece29}, {0x14ce6206, 0xdc070efe}, {0x14ded206, 0xdc0f4fd2}, {0x30000000, 0x0}, {0x30000000, 0x0}, {0x30000000, 0x0}, {0x30000000, 0x0}, {0x30000000, 0x0}, {0x30000000, 0x0}},
    {{0x0, 0x0}, {0x3c27c00, 0x1780015}, {0x3c97a02, 0x27880b7}, {0x3d07804, 0x3790159}, {0x2a261531, 0x158041f0}, {0x140f0703, 0x6400030b}, {0x2dc5807, 0x459c39d}, {0x141f2303, 0x6400447e}, {0x1a43009, 0x5324502}, {0x142f3f03, 0x640485ea}, {0x12c200b, 0x722c659}, {0x143f5b03, 0x6404c730}, {0x2a8acb31, 0xcb86877f}, {0x236440d, 0x84347fa}, {0x144f7703, 0x64090876}, {0x2a9cd233, 0xd487c8ed}, {0x145f9303, 0x6409499b}, {0x2aae6235, 0x6688c9ec}, {0x146faf03, 0x640d8a3e}, {0x147fd903, 0x640dcae1}, {0x148f6904, 0x98060b84}, {0x149fd904, 0x980e4c5e}, {0x14af6905, 0xba068d51}, {0x14bfd905, 0xba0ece36}, {0x14cf6906, 0xdc070f0b}, {0x14dfd906, 0xdc0f4fdf}, {0x30000000, 0x0}, {0x30000000, 0x0}, {0x30000000, 0x0}, {0x30000000, 0x0}, {0x30000000, 0x0}, {0x30000000, 0x0}},
    {{0x0, 0x0}, {0x30600, 0x1000017}, {0xa0402, 0x20080b9}, {0x110204, 0x301015b}, {0x14e00007, 0x31000222}, {0x2a516232, 0x63830294}, {0x14f02a07, 0x31004325}, {0x9d1207, 0x411c3b1}, {0x15004607, 0x31048498}, {0x3a47009, 0x5724519}, {0x15106207, 0x3104c601}, {0x2ec580b, 0x75ac66b}, {0x1ef3e0b, 0x73ac6d9}, {0x15207e07, 0x31090747}, {0x35020d, 0x80347bd}, {0x15309a07, 0x3109488c}, {0x37c680f, 0x96bc8fb}, {0x1540b607, 0x310d89a7}, {0x1550d207, 0x310dca4a}, {0x1560000b, 0x98020aed}, {0x2acf6936, 0x6e8acb3c}, {0x1570700b, 0x980a4b90}, {0x1580000c, 0xba028c6f}, {0x1590700c, 0xba0acd62}, {0x15a0000d, 0xdc030e46}, {0x15b0700d, 0xdc0b4f1a}, {0x30000000, 0x0}, {0x30000000, 0x0}, {0x30000000, 0x0}, {0x30000000, 0x0}, {0x30000000, 0x0}, {0x30000000, 0x0}},
    {{0x0, 0x0}, {0x430e00, 0x1080018}, {0x4a0c02, 0x20880ba}, {0x510a04, 0x309015c}, {0x14e10008, 0x2000022e}, {0x1973605, 0x43142a7}, {0x14f12a08, 0x2000433c}, {0x21d4207, 0x441c3c3}, {0x15014608, 0x200484af}, {0x1652a09, 0x62a452e}, {0x3676e09, 0x66a45a2}, {0x15116208, 0x2004c615}, {0xad120b, 0x712c67c}, {0x15217e08, 0x2009075b}, {0x2754a0d, 0x84b47d4}, {0x15319a08, 0x200948a1}, {0x3d020f, 0x903c903}, {0x1541b608, 0x200d89b1}, {0x1551d208, 0x200dca54}, {0x1561070b, 0x98020af7}, {0x2ad07036, 0x758b0b46}, {0x1571770b, 0x980a4b9a}, {0x1581070c, 0xba028c7e}, {0x1591770c, 0xba0acd71}, {0x15a1070d, 0xdc030e53}, {0x15b1770d, 0xdc0b4f27}, {0x30000000, 0x0}, {0x30000000, 0x0}, {0x30000000, 0x0}, {0x30000000, 0x0}, {0x30000000, 0x0}, {0x30000000, 0x0}},
    {{0x0, 0x0}, {0x831600, 0x1100019}, {0x8a1402, 0x21080bb}, {0x911204, 0x311015d}, {0x14e20707, 0x3100023a}, {0x3176605, 0x46142b8}, {0x14f23107, 0x31004353}, {0x3dd7a07, 0x479c3d6}, {0x2a646233, 0x6484444d}, {0x15024d07, 0x310484c7}, {0x260409, 0x602454e}, {0x15126907, 0x3104c62a}, {0x2ad520b, 0x752c691}, {0x15228507, 0x3109076f}, {0xb6140d, 0x81347eb}, {0x1532a107, 0x310948b5}, {0x1fd3a0f, 0x93bc913}, {0x1542bd07, 0x310d89bb}, {0x1552d907, 0x310dca5e}, {0x15620e0b, 0x98020b01}, {0x2ad17736, 0x7c8b0b50}, {0x15727e0b, 0x980a4ba4}, {0x15820e0c, 0xba028c8d}, {0x15927e0c, 0xba0acd80}, {0x15a20e0d, 0xdc030e60}, {0x15b27e0d, 0xdc0b4f35}, {0x30000000, 0x0}, {0x30000000, 0x0}, {0x30000000, 0x0}, {0x30000000, 0x0}, {0x30000000, 0x0}, {0x30000000, 0x0}},
    {{0x0, 0x0}, {0xc31e00, 0x118001b}, {0xca1c02, 0x21880bd}, {0xd11a04, 0x319015f}, {0x14e30708, 0x20000245}, {0x981006, 0x41182c9}, {0x14f33108, 0x2000436a}, {0x15e2c07, 0x529c3e9}, {0x15034d08, 0x200484de}, {0x3656a09, 0x66a4545}, {0x2a747e33, 0x808545bf}, {0x15136908, 0x2004c63e}, {0xee1c0b, 0x71ac6a8}, {0x15238508, 0x20090784}, {0x2f65c0d, 0x85b4802}, {0x1533a108, 0x200948ca}, {0x3bd720f, 0x973c926}, {0x1543bd08, 0x200d89c5}, {0x1553d908, 0x200dca68}, {0x1563150b, 0x98020b0b}, {0x2ad27e36, 0x838b0b5a}, {0x1573850b, 0x980a4bae}, {0x1583150c, 0xba028c9d}, {0x1593850c, 0xba0acd8f}, {0x15a3150d, 0xdc030e6d}, {0x15b3850d, 0xdc0b4f42}, {0x30000000, 0x0}, {0x30000000, 0x0}, {0x30000000, 0x0}, {0x30000000, 0x0}, {0x30000000, 0x0}, {0x30000000, 0x0}},
    {{0x0, 0x0}, {0x1032600, 0x120001c}, {0x10a2402, 0x22080be}, {0x1112204, 0x3210160}, {0x14e40e07, 0x31000251}, {0x2184006, 0x44182db}, {0x14f40e09, 0x75004382}, {0x2de5c07, 0x559c3fa}, {0x15042a09, 0x750084f5}, {0x1262409, 0x6224559}, {0x3e8780a, 0x67a85d1}, {0x15144609, 0x7504c652}, {0x32e640b, 0x762c6bf}, {0x15246209, 0x75050798}, {0xb7160d, 0x8134814}, {0x15347e09, 0x750948de}, {0x1fe3c0f, 0x93bc93c}, {0x15449a09, 0x750989d0}, {0x1554b609, 0x750dca73}, {0x15641c0b, 0x98020b15}, {0x2ad38536, 0x8a8b0b64}, {0x15748c0b, 0x980a4bb9}, {0x15841c0c, 0xba028cac}, {0x15948c0c, 0xba0acd9f}, {0x15a41c0d, 0xdc030e7b}, {0x15b48c0d, 0xdc0b4f4f}, {0x30000000, 0x0}, {0x30000000, 0x0}, {0x30000000, 0x0}, {0x30000000, 0x0}, {0x30000000, 0x0}, {0x30000000, 0x0}},
    {{0x0, 0x0}, {0x1432e00, 0x128001e}, {0x14a2c02, 0x22880c0}, {0x1512a04, 0x3290162}, {0x14e50e08, 0x2000025d}, {0x3d87806, 0x47982ee}, {0x14f50e0a, 0x64004399}, {0x5f0e07, 0x509c40b}, {0x15052a0a, 0x6400850c}, {0x2a65409, 0x652456b}, {0x1692a0a, 0x62a85e1}, {0x1515460a, 0x6404c667}, {0x16f2e0b, 0x72ac6d6}, {0x1525620a, 0x640507ad}, {0x2774e0d, 0x84b4825}, {0x7a0c0e, 0x90b888b}, {0x15357e0a, 0x640948f2}, {0x13f260f, 0x923c95e}, {0x15459a0a, 0x640989da}, {0x1555b60a, 0x640dca7d}, {0x1565230b, 0x98020b20}, {0x1575930b, 0x980a4bc8}, {0x1585230c, 0xba028cbb}, {0x1595930c, 0xba0acdae}, {0x15a5230d, 0xdc030e88}, {0x15b5930d, 0xdc0b4f5c}, {0x30000000, 0x0}, {0x30000000, 0x0}, {0x30000000, 0x0}, {0x30000000, 0x0}, {0x30000000, 0x0}, {0x30000000, 0x0}},
    {{0x0, 0x0}, {0x1833600, 0x130001f}, {0x18a3402, 0x23080c1}, {0x1913204, 0x3310163}, {0x14e61507, 0x31000268}, {0x1592a06, 0x4298300}, {0x14f61509, 0x750043b0}, {0x2a628531, 0x8584041e}, {0x1222408, 0x522049f}, {0x15063109, 0x75008523}, {0x2a75609, 0x6524599}, {0x15164d09, 0x7504c67b}, {0x3af760b, 0x772c6ec}, {0x15266909, 0x750507c1}, {0x2a93d932, 0xda870836}, {0x15368509, 0x75094907}, {0x3f060f, 0x903c954}, {0x1546a109, 0x750989e4}, {0x2ab59335, 0x97894a33}, {0x1556bd09, 0x750dca87}, {0x15662a0b, 0x98020b2a}, {0x15769a0b, 0x980a4bd7}, {0x15862a0c, 0xba028cca}, {0x15969a0c, 0xba0acdbd}, {0x15a62a0d, 0xdc030e95}, {0x15b69a0d, 0xdc0b4f6a}, {0x30000000, 0x0}, {0x30000000, 0x0}, {0x30000000, 0x0}, {0x30000000, 0x0}, {0x30000000, 0x0}, {0x30000000, 0x0}},
    {{0x0, 0x0}, {0x1c33e00, 0x1380021}, {0x1ca3c02, 0x23880c3}, {0x1d13a04, 0x3390165}, {0x14e71508, 0x20000274}, {0x2d95a06, 0x4598312}, {0x14f7150a, 0x640043c7}, {0x39f7607, 0x571c431}, {0x1507310a, 0x6400853b}, {0x2a72a131, 0xa1850592}, {0x2a78a831, 0xa8858610}, {0x15174d0a, 0x6404c690}, {0xf0180c, 0x71b06f9}, {0x3b2740c, 0x7730767}, {0x1527690a, 0x640507d5}, {0x378680e, 0x86b8858}, {0x1537850a, 0x6409491b}, {0x2aa31535, 0x1988097c}, {0x1547a10a, 0x640989ee}, {0x1557bd0a, 0x640dca91}, {0x1567310b, 0x98020b34}, {0x1577a10b, 0x980a4be6}, {0x1587310c, 0xba028cd9}, {0x1597a10c, 0xba0acdcc}, {0x15a7310d, 0xdc030ea3}, {0x15b7a10d, 0xdc0b4f77}, {0x30000000, 0x0}, {0x30000000, 0x0}, {0x30000000, 0x0}, {0x30000000, 0x0}, {0x30000000, 0x0}, {0x30000000, 0x0}},
    {{0x0, 0x0}, {0x2034600, 0x1400022}, {0x20a4402, 0x24080c4}, {0x2114204, 0x3410166}, {0x2a281c31, 0x1c8081f3}, {0x14e81c07, 0x3100027f}, {0x15a2c06, 0x429832f}, {0x14f83807, 0x310443de}, {0x3206008, 0x562045a}, {0x15085407, 0x31048552}, {0x2e8580a, 0x65a85c8}, {0x15187007, 0x3108c6a4}, {0x270480c, 0x74b0708}, {0x15288c07, 0x310907ea}, {0x2a94b633, 0xb887484a}, {0x1538a807, 0x310d492f}, {0x23f460f, 0x943c969}, {0x1548c407, 0x310d89f8}, {0x1558c409, 0x750dca9b}, {0x1568380b, 0x98060b3e}, {0x2ad8a836, 0xad8b8b97}, {0x1578a80b, 0x980e4bf6}, {0x1588380c, 0xba068ce8}, {0x1598a80c, 0xba0ecddb}, {0x15a8380d, 0xdc070eb0}, {0x15b8a80d, 0xdc0f4f84}, {0x30000000, 0x0}, {0x30000000, 0x0}, {0x30000000, 0x0}, {0x30000000, 0x0}, {0x30000000, 0x0}, {0x30000000, 0x0}},
    {{0x0, 0x0}, {0x2434e00, 0x1480023}, {0x24a4c02, 0x24880c5}, {0x2514a04, 0x3490167}, {0x2a291c32, 0x1d8081f4}, {0x14e91c08, 0x2000028b}, {0x25a4c06, 0x449833b}, {0x14f93808, 0x200443f6}, {0x1612a08, 0x52a0474}, {0x15095408, 0x20048569}, {0x129220a, 0x62285df}, {0x15197008, 0x2008c6b8}, {0x2a859a34, 0x9d864719}, {0x15298c08, 0x200907fe}, {0x3f8780e, 0x87b885c}, {0x1539a808, 0x200d4944}, {0x2aa52335, 0x27884990}, {0x1549c408, 0x200d8a03}, {0x1559c40a, 0x640dcaa5}, {0x15693f0b, 0x98060b48}, {0x1579af0b, 0x980e4c05}, {0x2ae83837, 0x3e8c8c7a}, {0x15893f0c, 0xba068cf8}, {0x1599af0c, 0xba0ecde9}, {0x15a93f0d, 0xdc070ebd}, {0x15b9af0d, 0xdc0f4f92}, {0x30000000, 0x0}, {0x30000000, 0x0}, {0x30000000, 0x0}, {0x30000000, 0x0}, {0x30000000, 0x0}, {0x30000000, 0x0}},
    {{0x0, 0x0}, {0x2835600, 0x1500025}, {0x28a5402, 0x25080c7}, {0x2915204, 0x3510169}, {0x2a2a2331, 0x238081f6}, {0x14ea2307, 0x31000299}, {0x39a7406, 0x4718349}, {0x14fa3f07, 0x3104440d}, {0x3a17208, 0x572048e}, {0x150a5b07, 0x31048580}, {0x2a778534, 0x888545fc}, {0x151a7707, 0x3108c6cd}, {0x1b1320c, 0x733072a}, {0x152a9307, 0x31090812}, {0x1b9320e, 0x833886f}, {0x153aaf07, 0x310d4958}, {0x2aaa4635, 0x4a8889c3}, {0x154acb07, 0x310d8a0d}, {0x155acb09, 0x750dcab0}, {0x156a460b, 0x98060b52}, {0x157ab60b, 0x980e4c14}, {0x2ae93f37, 0x458c8c8a}, {0x158a460c, 0xba068d07}, {0x159ab60c, 0xba0ecdf6}, {0x15aa460d, 0xdc070eca}, {0x15bab60d, 0xdc0f4f9f}, {0x30000000, 0x0}, {0x30000000, 0x0}, {0x30000000, 0x0}, {0x30000000, 0x0}, {0x30000000, 0x0}, {0x30000000, 0x0}},
    {{0x0, 0x0}, {0x2c35e00, 0x1580026}, {0x2ca5c02, 0x25880c8}, {0x2d15a04, 0x359016a}, {0x2a2b2332, 0x248081f7}, {0x14eb2308, 0x200002b1}, {0x11b2606, 0x421835a}, {0x14fb3f08, 0x20044424}, {0x1e23c08, 0x53a04a7}, {0x150b5b08, 0x20048598}, {0x2aa540a, 0x6528617}, {0x151b7708, 0x2008c6e1}, {0x331620c, 0x7630739}, {0x2f4580d, 0x85b47b0}, {0x152b9308, 0x20090827}, {0xba140e, 0x913888e}, {0x153baf08, 0x200d496c}, {0x154bcb08, 0x200d8a17}, {0x155bcb0a, 0x640dcaba}, {0x156b4d0b, 0x98060b5d}, {0x157bbd0b, 0x980e4c23}, {0x2aea4637, 0x4c8c8c99}, {0x158b4d0c, 0xba068d16}, {0x159bbd0c, 0xba0ece03}, {0x15ab4d0d, 0xdc070ed8}, {0x15bbbd0d, 0xdc0f4fac}, {0x30000000, 0x0}, {0x30000000, 0x0}, {0x30000000, 0x0}, {0x30000000, 0x0}, {0x30000000, 0x0}, {0x30000000, 0x0}},
    {{0x0, 0x0}, {0x3036600, 0x1600028}, {0x30a6402, 0x26080ca}, {0x3116204, 0x361016c}, {0x2a2c0033, 0x280c1f8}, {0x14ec0009, 0x750002c8}, {0x29b5606, 0x451836c}, {0x14fc1c09, 0x7500443b}, {0x230608, 0x50204c2}, {0x150c3809, 0x750485af}, {0x6b0e0a, 0x60a8629}, {0x26d4a0b, 0x74ac68e}, {0x151c5409, 0x7504c6f5}, {0x3726c0c, 0x76b0764}, {0x152c7009, 0x7509083b}, {0x33a640e, 0x96388a7}, {0x153c8c09, 0x7509497e}, {0x154ca809, 0x750d8a21}, {0x155cd209, 0x750dcac4}, {0x156c540b, 0x98060b67}, {0x157cc40b, 0x980e4c32}, {0x2aeb4d37, 0x538c8ca8}, {0x158c540c, 0xba068d25}, {0x159cc40c, 0xba0ece10}, {0x15ac540d, 0xdc070ee5}, {0x15bcc40d, 0xdc0f4fb9}, {0x30000000, 0x0}, {0x30000000, 0x0}, {0x30000000, 0x0}, {0x30000000, 0x0}, {0x30000000, 0x0}, {0x30000000, 0x0}},
    {{0x0, 0x0}, {0x3436e00, 0x1680029}, {0x34a6c02, 0x26880cb}, {0x3516a04, 0x369016d}, {0x2a2d0034, 0x380c1fa}, {0x14ed000a, 0x640002df}, {0x1c0007, 0x401c37d}, {0x14fd1c0a, 0x64004453}, {0x2234608, 0x54204d9}, {0x150d380a, 0x640485c4}, {0x22b460a, 0x642863a}, {0x6e0c0b, 0x70ac6a3}, {0x151d540a, 0x6404c70a}, {0x1f33e0c, 0x83b077c}, {0x152d700a, 0x6409084f}, {0x2a9acb33, 0xcd8788c4}, {0x153d8c0a, 0x64094988}, {0x154da80a, 0x640d8a2b}, {0x155dd20a, 0x640dcace}, {0x156d5b0b, 0x98060b71}, {0x157dcb0b, 0x980e4c41}, {0x2aec5437, 0x5a8cccb7}, {0x158d5b0c, 0xba068d34}, {0x159dcb0c, 0xba0ece1e}, {0x15ad5b0d, 0xdc070ef2}, {0x15bdcb0d, 0xdc0f4fc7}, {0x30000000, 0x0}, {0x30000000, 0x0}, {0x30000000, 0x0}, {0x30000000, 0x0}, {0x30000000, 0x0}, {0x30000000, 0x0}},
    {{0x0, 0x0}, {0x3837600, 0x170002b}, {0x38a7402, 0x27080cd}, {0x3917204, 0x371016f}, {0x2a2e0733, 0x980c1fb}, {0x14ee0709, 0x750002f6}, {0x19c3007, 0x431c38f}, {0x14fe2309, 0x7500446a}, {0x2a6b9332, 0x948484ef}, {0x150e3f09, 0x750485d8}, {0x3eb7e0a, 0x67a864b}, {0x22e440b, 0x742c6b4}, {0x151e5b09, 0x7504c71e}, {0x2a8bcb32, 0xcc868793}, {0x152e7709, 0x75090864}, {0x3c000f, 0x903c8da}, {0x153e9309, 0x75094993}, {0x154eaf09, 0x750d8a35}, {0x155ed909, 0x750dcad8}, {0x2acd5b36, 0x608acb27}, {0x156e620b, 0x98060b7b}, {0x157ed20b, 0x980e4c51}, {0x158e620c, 0xba068d44}, {0x159ed20c, 0xba0ece2b}, {0x15ae620d, 0xdc070eff}, {0x15bed20d, 0xdc0f4fd4}, {0x30000000, 0x0}, {0x30000000, 0x0}, {0x30000000, 0x0}, {0x30000000, 0x0}, {0x30000000, 0x0}, {0x30000000, 0x0}},
    {{0x0, 0x0}, {0x3c37e00, 0x178002c}, {0x3ca7c02, 0x27880ce}, {0x3d17a04, 0x3790170}, {0x2a2f0734, 0xa80c1fd}, {0x14ef070a, 0x6400030e}, {0x31c6007, 0x461c3a0}, {0x14ff230a, 0x64004481}, {0x1e43809, 0x53a4504}, {0x150f3f0a, 0x640485ed}, {0x16c280b, 0x72ac65b}, {0x2a81b632, 0xb78606c8}, {0x151f5b0a, 0x6404c732}, {0x2a8ca833, 0xaa86c7a7}, {0x152f770a, 0x64090878}, {0x23c400f, 0x943c8ee}, {0x153f930a, 0x6409499d}, {0x154faf0a, 0x640d8a40}, {0x155fd90a, 0x640dcae2}, {0x2ace6236, 0x678acb31}, {0x156f690b, 0x98060b85}, {0x157fd90b, 0x980e4c60}, {0x158f690c, 0xba068d53}, {0x159fd90c, 0xba0ece38}, {0x15af690d, 0xdc070f0d}, {0x15bfd90d, 0xdc0f4fe1}, {0x30000000, 0x0}, {0x30000000, 0x0}, {0x30000000, 0x0}, {0x30000000, 0x0}, {0x30000000, 0x0}, {0x30000000, 0x0}},
    {{0x0, 0x0}, {0x40001, 0x100402e}, {0xb0602, 0x20080d0}, {0x120404, 0x3010172}, {0x15c0000e, 0x31000224}, {0x170605, 0x4014295}, {0x15d02a0e, 0x31004328}, {0xdd1a07, 0x419c3b4}, {0x15e0460e, 0x3104849b}, {0x3e47809, 0x57a451b}, {0x15f0620e, 0x3104c604}, {0x32c600b, 0x762c66d}, {0x16007e0e, 0x31090749}, {0xb4100d, 0x8134799}, {0x16109a0e, 0x3109488f}, {0xfc180f, 0x91bc8e2}, {0x23e440f, 0x943c940}, {0x1620b60e, 0x310d89a8}, {0x1630d20e, 0x310dca4b}, {0x16400012, 0x98020aee}, {0x16507012, 0x980a4b91}, {0x2ae00037, 0x68c0c01}, {0x16600013, 0xba028c71}, {0x16707013, 0xba0acd64}, {0x16800014, 0xdc030e47}, {0x16907014, 0xdc0b4f1c}, {0x30000000, 0x0}, {0x30000000, 0x0}, {0x30000000, 0x0}, {0x30000000, 0x0}, {0x30000000, 0x0}, {0x30000000, 0x0}},
    {{0x0, 0x0}, {0x440801, 0x108402f}, {0x4b0e02, 0x20880d1}, {0x520c04, 0x3090173}, {0x15c1000f, 0x20000230}, {0x1d73e05, 0x43942a8}, {0x15d12a0f, 0x2000433f}, {0x25d4a07, 0x449c3c6}, {0x15e1460f, 0x200484b2}, {0x1a53209, 0x6324531}, {0x3a77609, 0x67245a5}, {0x15f1620f, 0x2004c618}, {0xed1a0b, 0x71ac67f}, {0x16017e0f, 0x2009075e}, {0x2b5520d, 0x85347d7}, {0x16119a0f, 0x200948a3}, {0x7d0a0f, 0x90bc905}, {0x1621b60f, 0x200d89b2}, {0x1631d20f, 0x200dca55}, {0x16410712, 0x98020af8}, {0x16517712, 0x980a4b9b}, {0x16610713, 0xba028c80}, {0x16717713, 0xba0acd73}, {0x16810714, 0xdc030e55}, {0x16917714, 0xdc0b4f29}, {0x30000000, 0x0}, {0x30000000, 0x0}, {0x30000000, 0x0}, {0x30000000, 0x0}, {0x30000000, 0x0}, {0x30000000, 0x0}, {0x30000000, 0x0}},
    {{0x0, 0x0}, {0x841001, 0x1104030}, {0x8b1602, 0x21080d2}, {0x921404, 0x3110174}, {0x15c2070e, 0x3100023b}, {0x3576e05, 0x46942bb}, {0x15d2310e, 0x31004356}, {0x2a5f5b34, 0x5e83c3d9}, {0x2204008, 0x542044e}, {0x15e24d0e, 0x310484ca}, {0x660c09, 0x60a4550}, {0x15f2690e, 0x3104c62c}, {0x2ed5a0b, 0x75ac693}, {0x1602850e, 0x31090772}, {0xf61c0d, 0x81b47ed}, {0x1612a10e, 0x310948b8}, {0x2a9ed933, 0xdb87c916}, {0x1622bd0e, 0x310d89bd}, {0x1632d90e, 0x310dca5f}, {0x16420e12, 0x98020b02}, {0x16527e12, 0x980a4ba5}, {0x16620e13, 0xba028c8f}, {0x16727e13, 0xba0acd82}, {0x16820e14, 0xdc030e62}, {0x16927e14, 0xdc0b4f37}, {0x30000000, 0x0}, {0x30000000, 0x0}, {0x30000000, 0x0}, {0x30000000, 0x0}, {0x30000000, 0x0}, {0x30000000, 0x0}, {0x30000000, 0x0}},
    {{0x0, 0x0}, {0xc41801, 0x1184032}, {0xcb1e02, 0x21880d4}, {0xd21c04, 0x3190176}, {0x15c3070f, 0x20000247}, {0xd81806, 0x41982cc}, {0x15d3310f, 0x2000436d}, {0x19e3407, 0x531c3ec}, {0x210208, 0x5020465}, {0x15e34d0f, 0x200484e1}, {0x2a709a31, 0x9a850563}, {0x15f3690f, 0x2004c641}, {0x12e240b, 0x722c6aa}, {0x1603850f, 0x20090786}, {0x336640d, 0x8634804}, {0x1613a10f, 0x200948cc}, {0x3fd7a0f, 0x97bc928}, {0x1623bd0f, 0x200d89c7}, {0x1633d90f, 0x200dca6a}, {0x16431512, 0x98020b0c}, {0x16538512, 0x980a4baf}, {0x16631513, 0xba028c9e}, {0x2af27e37, 0x848d0d12}, {0x16738513, 0xba0acd91}, {0x16831514, 0xdc030e6f}, {0x16938514, 0xdc0b4f44}, {0x30000000, 0x0}, {0x30000000, 0x0}, {0x30000000, 0x0}, {0x30000000, 0x0}, {0x30000000, 0x0}, {0x30000000, 0x0}},
    {{0x0, 0x0}, {0x1042001, 0x1204033}, {0x10b2602, 0x22080d5}, {0x1122404, 0x3210177}, {0x15c40e0e, 0x31000252}, {0x2584806, 0x44982de}, {0x15d40e10, 0x75004385}, {0x31e6407, 0x561c3fd}, {0x15e42a10, 0x750084f8}, {0x1662c09, 0x62a455c}, {0x29020a, 0x60285d5}, {0x15f44610, 0x7504c655}, {0x36e6c0b, 0x76ac6c1}, {0x16046210, 0x7505079b}, {0xf71e0d, 0x81b4816}, {0x16147e10, 0x750948e0}, {0x2aa00035, 0x488093f}, {0x16249a10, 0x750989d1}, {0x1634b610, 0x750dca74}, {0x16441c12, 0x98020b17}, {0x16548c12, 0x980a4bbb}, {0x2ae52337, 0x298c4c4d}, {0x16641c13, 0xba028cae}, {0x16748c13, 0xba0acda0}, {0x16841c14, 0xdc030e7d}, {0x16948c14, 0xdc0b4f51}, {0x30000000, 0x0}, {0x30000000, 0x0}, {0x30000000, 0x0}, {0x30000000, 0x0}, {0x30000000, 0x0}, {0x30000000, 0x0}},
    {{0x0, 0x0}, {0x1442801, 0x1284035}, {0x14b2e02, 0x22880d7}, {0x1522c04, 0x3290179}, {0x15c50e0f, 0x2000025e}, {0x2a554634, 0x498342f1}, {0x15d50e11, 0x6400439c}, {0x9f1607, 0x511c40e}, {0x15e52a11, 0x6400850f}, {0x2e65c09, 0x65a456d}, {0x1e93a0a, 0x63a85e5}, {0x15f54611, 0x6404c669}, {0x1af360b, 0x732c6d8}, {0x16056211, 0x640507af}, {0x2b7560d, 0x8534828}, {0x16157e11, 0x640948f5}, {0x3be740f, 0x973c94f}, {0x16259a11, 0x640989db}, {0x1635b611, 0x640dca7e}, {0x16452312, 0x98020b21}, {0x16559312, 0x980a4bca}, {0x2ae41c37, 0x228c4c3e}, {0x16652313, 0xba028cbd}, {0x16759313, 0xba0acdb0}, {0x16852314, 0xdc030e8a}, {0x16959314, 0xdc0b4f5e}, {0x30000000, 0x0}, {0x30000000, 0x0}, {0x30000000, 0x0}, {0x30000000, 0x0}, {0x30000000, 0x0}, {0x30000000, 0x0}},
    {{0x0, 0x0}, {0x1843001, 0x1304036}, {0x18b3602, 0x23080d8}, {0x1923404, 0x331017a}, {0x15c6150e, 0x3100026a}, {0x1993206, 0x4318303}, {0x15d61510, 0x750043b3}, {0x21f4607, 0x541c420}, {0x1622c08, 0x52a04a2}, {0x15e63110, 0x75008526}, {0x3276609, 0x662459f}, {0x15f64d10, 0x7504c67e}, {0x3ef7e0b, 0x77ac6ee}, {0x232440c, 0x7430757}, {0x16066910, 0x750507c3}, {0x1f8380e, 0x83b8848}, {0x16168510, 0x75094909}, {0x2aa20e35, 0x12880967}, {0x1626a110, 0x750989e5}, {0x1636bd10, 0x750dca88}, {0x16462a12, 0x98020b2b}, {0x16569a12, 0x980a4bd9}, {0x16662a13, 0xba028ccc}, {0x16769a13, 0xba0acdbf}, {0x16862a14, 0xdc030e97}, {0x16969a14, 0xdc0b4f6c}, {0x30000000, 0x0}, {0x30000000, 0x0}, {0x30000000, 0x0}, {0x30000000, 0x0}, {0x30000000, 0x0}, {0x30000000, 0x0}},
    {{0x0, 0x0}, {0x1c43801, 0x1384038}, {0x1cb3e02, 0x23880da}, {0x1d23c04, 0x339017c}, {0x15c7150f, 0x20000275}, {0x3196206, 0x4618315}, {0x15d71511, 0x640043ca}, {0x3df7e07, 0x579c433}, {0x3626c08, 0x56a04ba}, {0x15e73111, 0x6400853e}, {0x128200a, 0x62285b6}, {0x15f74d11, 0x6404c692}, {0x130200c, 0x72306fc}, {0x2a89c432, 0xc586876a}, {0x16076911, 0x640507d8}, {0x3b8700e, 0x873885b}, {0x16178511, 0x6409491e}, {0x2aa41c35, 0x20884986}, {0x1627a111, 0x640989ef}, {0x1637bd11, 0x640dca92}, {0x16473112, 0x98020b35}, {0x1657a112, 0x980a4be8}, {0x16673113, 0xba028cdb}, {0x1677a113, 0xba0acdce}, {0x16873114, 0xdc030ea4}, {0x1697a114, 0xdc0b4f79}, {0x30000000, 0x0}, {0x30000000, 0x0}, {0x30000000, 0x0}, {0x30000000, 0x0}, {0x30000000, 0x0}, {0x30000000, 0x0}},
    {{0x0, 0x0}, {0x2044001, 0x1404039}, {0x20b4602, 0x24080db}, {0x2124404, 0x341017d}, {0x2a302a31, 0x2a8101fe}, {0x15c81c0e, 0x31000281}, {0x15d8380e, 0x310443e1}, {0xe01808, 0x51a0440}, {0xe31e08, 0x51a04cb}, {0x15e8540e, 0x31048555}, {0x328600a, 0x66285ca}, {0x15f8700e, 0x3108c6a6}, {0x2b0500c, 0x753070b}, {0x16088c0e, 0x310907ec}, {0x238400e, 0x843884c}, {0x17b2e0e, 0x92b88be}, {0x1618a80e, 0x310d4932}, {0x1628c40e, 0x310d89fa}, {0x1638c410, 0x750dca9d}, {0x16483812, 0x98060b3f}, {0x1658a812, 0x980e4bf7}, {0x2ae62a37, 0x308c4c5c}, {0x16683813, 0xba068cea}, {0x1678a813, 0xba0ecddd}, {0x16883814, 0xdc070eb2}, {0x1698a814, 0xdc0f4f86}, {0x30000000, 0x0}, {0x30000000, 0x0}, {0x30000000, 0x0}, {0x30000000, 0x0}, {0x30000000, 0x0}, {0x30000000, 0x0}},
    {{0x0, 0x0}, {0x2444801, 0x148403a}, {0x24b4e02, 0x24880dc}, {0x2524c04, 0x349017e}, {0x2a312a32, 0x2b810200}, {0x15c91c0f, 0x2000028c}, {0x29a5406, 0x451833d}, {0x15d9380f, 0x200443f9}, {0x1e13a08, 0x53a0478}, {0x15e9540f, 0x2004856c}, {0x1a9320a, 0x63285e4}, {0x15f9700f, 0x2008c6bb}, {0x31020c, 0x703071a}, {0x3736e0c, 0x86b078d}, {0x16098c0f, 0x20090801}, {0x2794a0e, 0x84b8877}, {0x1619a80f, 0x200d4946}, {0x1629c40f, 0x200d8a04}, {0x1639c411, 0x640dcaa7}, {0x16493f12, 0x98060b4a}, {0x1659af12, 0x980e4c07}, {0x16693f13, 0xba068cfa}, {0x2af69a37, 0xa08d4d4f}, {0x1679af13, 0xba0ecdea}, {0x16893f14, 0xdc070ebf}, {0x1699af14, 0xdc0f4f93}, {0x30000000, 0x0}, {0x30000000, 0x0}, {0x30000000, 0x0}, {0x30000000, 0x0}, {0x30000000, 0x0}, {0x30000000, 0x0}},
    {{0x0, 0x0}, {0x2845001, 0x150403c}, {0x28b5602, 0x25080de}, {0x2925404, 0x3510180}, {0x2a323131, 0x31810201}, {0x15ca230e, 0x3100029c}, {0x2a597032, 0x7183834d}, {0x15da3f0e, 0x31044410}, {0x2a676934, 0x6c844492}, {0x15ea5b0e, 0x31048583}, {0x6a0c0a, 0x60a8600}, {0x15fa770e, 0x3108c6cf}, {0x2a86a133, 0xa386472d}, {0x174280d, 0x82b47a1}, {0x160a930e, 0x31090815}, {0x2f95a0e, 0x85b887c}, {0x161aaf0e, 0x310d495b}, {0x162acb0e, 0x310d8a0e}, {0x163acb10, 0x750dcab1}, {0x164a4612, 0x98060b54}, {0x165ab612, 0x980e4c16}, {0x166a4613, 0xba068d09}, {0x2af9af37, 0xb58d8d7c}, {0x167ab613, 0xba0ecdf8}, {0x168a4614, 0xdc070ecc}, {0x169ab614, 0xdc0f4fa1}, {0x30000000, 0x0}, {0x30000000, 0x0}, {0x30000000, 0x0}, {0x30000000, 0x0}, {0x30000000, 0x0}, {0x30000000, 0x0}},
    {{0x0, 0x0}, {0x2c45801, 0x158403d}, {0x2cb5e02, 0x25880df}, {0x2d25c04, 0x3590181}, {0x2a333132, 0x32810203}, {0x15cb230f, 0x200002b4}, {0x19b3606, 0x4318360}, {0x15db3f0f, 0x20044427}, {0x2224408, 0x54204ab}, {0x15eb5b0f, 0x2004859a}, {0x2ea5c0a, 0x65a8619}, {0x15fb770f, 0x2008c6e4}, {0x3716a0c, 0x76b073b}, {0x334600d, 0x86347b3}, {0x160b930f, 0x20090829}, {0xfa1c0e, 0x91b8890}, {0x161baf0f, 0x200d496f}, {0x162bcb0f, 0x200d8a18}, {0x163bcb11, 0x640dcabb}, {0x164b4d12, 0x98060b5e}, {0x165bbd12, 0x980e4c25}, {0x166b4d13, 0xba068d18}, {0x2afab637, 0xbc8d8d8c}, {0x167bbd13, 0xba0ece05}, {0x168b4d14, 0xdc070eda}, {0x169bbd14, 0xdc0f4fae}, {0x30000000, 0x0}, {0x30000000, 0x0}, {0x30000000, 0x0}, {0x30000000, 0x0}, {0x30000000, 0x0}, {0x30000000, 0x0}},
    {{0x0, 0x0}, {0x3046001, 0x160403f}, {0x30b6602, 0x26080e1}, {0x3126404, 0x3610183}, {0x2a340e33, 0x10814204}, {0x15cc0010, 0x750002cb}, {0x31b6606, 0x4618372}, {0x15dc1c10, 0x7500443e}, {0xa31608, 0x51204c8}, {0x15ec3810, 0x750485b2}, {0xeb1e0a, 0x61a862e}, {0x15fc5410, 0x7504c6f8}, {0x720c0c, 0x70b0746}, {0x2a8da834, 0xab86c7bc}, {0x160c7010, 0x7509083e}, {0x37a6c0e, 0x96b88aa}, {0x161c8c10, 0x75094980}, {0x162ca810, 0x750d8a22}, {0x163cd210, 0x750dcac5}, {0x164c5412, 0x98060b68}, {0x165cc412, 0x980e4c34}, {0x166c5413, 0xba068d27}, {0x2afbbd37, 0xc38d8d9b}, {0x167cc413, 0xba0ece12}, {0x168c5414, 0xdc070ee7}, {0x169cc414, 0xdc0f4fbb}, {0x30000000, 0x0}, {0x30000000, 0x0}, {0x30000000, 0x0}, {0x30000000, 0x0}, {0x30000000, 0x0}, {0x30000000, 0x0}},
    {{0x0, 0x0}, {0x3446801, 0x1684040}, {0x34b6e02, 0x26880e2}, {0x3526c04, 0x3690184}, {0x2a350e34, 0x11814205}, {0x15cd0011, 0x640002e2}, {0x5c0807, 0x409c380}, {0x15dd1c11, 0x64004455}, {0x2634e08, 0x54a04dc}, {0x15ed3811, 0x640485c7}, {0x26b4e0a, 0x64a863d}, {0x15fd5411, 0x6404c70c}, {0x1b2340c, 0x7330752}, {0x1752a0d, 0x82b47ca}, {0x160d7011, 0x64090852}, {0x23b460e, 0x94388c6}, {0x161d8c11, 0x6409498a}, {0x162da811, 0x640d8a2d}, {0x163dd211, 0x640dcacf}, {0x164d5b12, 0x98060b72}, {0x165dcb12, 0x980e4c43}, {0x166d5b13, 0xba068d36}, {0x2afcc437, 0xca8dcdaa}, {0x167dcb13, 0xba0ece20}, {0x168d5b14, 0xdc070ef4}, {0x169dcb14, 0xdc0f4fc9}, {0x30000000, 0x0}, {0x30000000, 0x0}, {0x30000000, 0x0}, {0x30000000, 0x0}, {0x30000000, 0x0}, {0x30000000, 0x0}},
    {{0x0, 0x0}, {0x3847001, 0x1704042}, {0x38b7602, 0x27080e4}, {0x3927404, 0x3710186}, {0x2a361533, 0x17814207}, {0x15ce0710, 0x750002f9}, {0x1dc3807, 0x439c390}, {0x15de2310, 0x7500446d}, {0x240009, 0x50244f1}, {0x15ee3f10, 0x750485db}, {0x2a7baf32, 0xb085864d}, {0x15fe5b10, 0x7504c721}, {0x3f27c0c, 0x77b0768}, {0x3f57a0d, 0x87b47e2}, {0x160e7710, 0x75090866}, {0x7c080f, 0x90bc8dd}, {0x161e9310, 0x75094994}, {0x162eaf10, 0x750d8a37}, {0x163ed910, 0x750dcada}, {0x164e6212, 0x98060b7c}, {0x165ed212, 0x980e4c53}, {0x2aed5b37, 0x618cccc6}, {0x166e6213, 0xba068d45}, {0x167ed213, 0xba0ece2d}, {0x168e6214, 0xdc070f01}, {0x169ed214, 0xdc0f4fd6}, {0x30000000, 0x0}, {0x30000000, 0x0}, {0x30000000, 0x0}, {0x30000000, 0x0}, {0x30000000, 0x0}, {0x30000000, 0x0}},
    {{0x0, 0x0}, {0x3c47801, 0x1784043}, {0x3cb7e02, 0x27880e5}, {0x3d27c04, 0x3790187}, {0x2a371534, 0x18814208}, {0x15cf0711, 0x64000310}, {0x35c6807, 0x469c3a3}, {0x15df2311, 0x64004484}, {0x2a6c7033, 0x7284c506}, {0x15ef3f11, 0x640485ef}, {0x1ac300b, 0x732c65e}, {0x15ff5b11, 0x6404c735}, {0x233460c, 0x8430780}, {0x2764c0d, 0x84b47fd}, {0x160f7711, 0x6409087b}, {0x2bc500f, 0x953c8f4}, {0x161f9311, 0x6409499e}, {0x162faf11, 0x640d8a41}, {0x163fd911, 0x640dcae4}, {0x164f6912, 0x98060b87}, {0x2adfd936, 0xde8bcbf2}, {0x165fd912, 0x980e4c62}, {0x166f6913, 0xba068d55}, {0x167fd913, 0xba0ece3a}, {0x168f6914, 0xdc070f0f}, {0x169fd914, 0xdc0f4fe3}, {0x30000000, 0x0}, {0x30000000, 0x0}, {0x30000000, 0x0}, {0x30000000, 0x0}, {0x30000000, 0x0}, {0x30000000, 0x0}},
    {{0x0, 0x0}, {0x50201, 0x1004045}, {0xc0003, 0x200c0e7}, {0x130604, 0x3010189}, {0x16a00015, 0x31000225}, {0x570e05, 0x4094298}, {0x16b02a15, 0x3100432b}, {0x11d2207, 0x421c3b7}, {0x16c04615, 0x3104849e}, {0x2a6d7034, 0x7384c51e}, {0x16d06215, 0x3104c606}, {0x36c680b, 0x76ac670}, {0x16e07e15, 0x3109074c}, {0xf4180d, 0x81b479c}, {0x16f09a15, 0x31094892}, {0x17c280f, 0x92bc8e7}, {0x2be540f, 0x953c945}, {0x1700b615, 0x310d89a9}, {0x1710d215, 0x310dca4c}, {0x17200019, 0x98020aef}, {0x17307019, 0x980a4b92}, {0x1740001a, 0xba028c73}, {0x1750701a, 0xba0acd66}, {0x2affd937, 0xdf8dcdd7}, {0x1760001b, 0xdc030e49}, {0x1770701b, 0xdc0b4f1e}, {0x30000000, 0x0}, {0x30000000, 0x0}, {0x30000000, 0x0}, {0x30000000, 0x0}, {0x30000000, 0x0}, {0x30000000, 0x0}},
    {{0x0, 0x0}, {0x450a01, 0x1084046}, {0x4c0803, 0x208c0e8}, {0x530e04, 0x309018a}, {0x16a10016, 0x20000231}, {0x2a526931, 0x698302ab}, {0x16b12a16, 0x20004342}, {0x29d5207, 0x451c3c9}, {0x16c14616, 0x200484b5}, {0x1e53a09, 0x63a4532}, {0x3e77e09, 0x67a45a6}, {0x16d16216, 0x2004c61b}, {0x12d220b, 0x722c682}, {0x16e17e16, 0x20090760}, {0x335620d, 0x86347dc}, {0x16f19a16, 0x200948a6}, {0xbd120f, 0x913c908}, {0x1701b616, 0x200d89b4}, {0x1711d216, 0x200dca57}, {0x17210719, 0x98020af9}, {0x17317719, 0x980a4b9c}, {0x1741071a, 0xba028c82}, {0x1751771a, 0xba0acd75}, {0x1761071b, 0xdc030e57}, {0x1771771b, 0xdc0b4f2b}, {0x30000000, 0x0}, {0x30000000, 0x0}, {0x30000000, 0x0}, {0x30000000, 0x0}, {0x30000000, 0x0}, {0x30000000, 0x0}, {0x30000000, 0x0}},
    {{0x0, 0x0}, {0x851201, 0x1104047}, {0x8c1003, 0x210c0e9}, {0x931604, 0x311018b}, {0x16a20715, 0x3100023d}, {0x3977605, 0x47142be}, {0x16b23115, 0x31004359}, {0x1e0407, 0x501c3da}, {0x2604808, 0x54a0451}, {0x16c24d15, 0x310484cc}, {0xa61409, 0x6124553}, {0x16d26915, 0x3104c62f}, {0x32d620b, 0x762c696}, {0x16e28515, 0x31090775}, {0x1762c0d, 0x82b47f3}, {0x16f2a115, 0x310948ba}, {0x23d420f, 0x943c917}, {0x1702bd15, 0x310d89be}, {0x1712d915, 0x310dca61}, {0x17220e19, 0x98020b04}, {0x17327e19, 0x980a4ba6}, {0x17420e1a, 0xba028c91}, {0x17527e1a, 0xba0acd84}, {0x17620e1b, 0xdc030e64}, {0x17727e1b, 0xdc0b4f38}, {0x30000000, 0x0}, {0x30000000, 0x0}, {0x30000000, 0x0}, {0x30000000, 0x0}, {0x30000000, 0x0}, {0x30000000, 0x0}, {0x30000000, 0x0}},
    {{0x0, 0x0}, {0xc51a01, 0x1184049}, {0xcc1803, 0x218c0eb}, {0xd31e04, 0x319018d}, {0x16a30716, 0x20000248}, {0x1182006, 0x42182cf}, {0x16b33116, 0x20004370}, {0x1de3c07, 0x539c3ed}, {0x610a08, 0x50a0468}, {0x16c34d16, 0x200484e4}, {0x2264409, 0x6424565}, {0x16d36916, 0x2004c643}, {0x16e2c0b, 0x72ac6ad}, {0x16e38516, 0x20090789}, {0x3766c0d, 0x86b4807}, {0x16f3a116, 0x200948cf}, {0x2a9fd934, 0xdc87c92a}, {0x1703bd16, 0x200d89c8}, {0x1713d916, 0x200dca6b}, {0x17231519, 0x98020b0e}, {0x17338519, 0x980a4bb1}, {0x1743151a, 0xba028ca0}, {0x2af48c37, 0x928d4d31}, {0x1753851a, 0xba0acd93}, {0x1763151b, 0xdc030e71}, {0x1773851b, 0xdc0b4f46}, {0x30000000, 0x0}, {0x30000000, 0x0}, {0x30000000, 0x0}, {0x30000000, 0x0}, {0x30000000, 0x0}, {0x30000000, 0x0}},
    {{0x0, 0x0}, {0x1052201, 0x120404a}, {0x10c2003, 0x220c0ec}, {0x1132604, 0x321018e}, {0x16a40e15, 0x31000254}, {0x2985006, 0x45182e1}, {0x16b40e17, 0x75004387}, {0x35e6c07, 0x569c400}, {0x16c42a17, 0x750084fb}, {0x1a63409, 0x632455f}, {0x690a0a, 0x60a85d7}, {0x16d44617, 0x7504c658}, {0x3ae740b, 0x772c6c4}, {0x16e46217, 0x7505079d}, {0x137260d, 0x8234819}, {0x16f47e17, 0x750948e3}, {0x27e4c0f, 0x94bc942}, {0x17049a17, 0x750989d2}, {0x1714b617, 0x750dca75}, {0x17241c19, 0x98020b18}, {0x2ad48c36, 0x918b4b6e}, {0x17348c19, 0x980a4bbd}, {0x17441c1a, 0xba028cb0}, {0x17548c1a, 0xba0acda2}, {0x17641c1b, 0xdc030e7e}, {0x17748c1b, 0xdc0b4f53}, {0x30000000, 0x0}, {0x30000000, 0x0}, {0x30000000, 0x0}, {0x30000000, 0x0}, {0x30000000, 0x0}, {0x30000000, 0x0}},
    {{0x0, 0x0}, {0x1452a01, 0x128404c}, {0x14c2803, 0x228c0ee}, {0x1532e04, 0x3290190}, {0x16a50e16, 0x2000025f}, {0x190206, 0x40182f2}, {0x16b50e18, 0x6400439f}, {0xdf1e07, 0x519c411}, {0x16c52a18, 0x64008512}, {0x3266409, 0x6624570}, {0x229420a, 0x64285e9}, {0x16d54618, 0x6404c66c}, {0x2a82bd31, 0xbd8606dc}, {0x16e56218, 0x640507b2}, {0x2f75e0d, 0x85b482b}, {0x16f57e18, 0x640948f7}, {0x3fe7c0f, 0x97bc950}, {0x17059a18, 0x640989dc}, {0x1715b618, 0x640dca7f}, {0x17252319, 0x98020b22}, {0x2ad59336, 0x988b4b79}, {0x17359319, 0x980a4bcc}, {0x1745231a, 0xba028cbf}, {0x1755931a, 0xba0acdb2}, {0x1765231b, 0xdc030e8c}, {0x1775931b, 0xdc0b4f60}, {0x30000000, 0x0}, {0x30000000, 0x0}, {0x30000000, 0x0}, {0x30000000, 0x0}, {0x30000000, 0x0}, {0x30000000, 0x0}},
    {{0x0, 0x0}, {0x1853201, 0x130404d}, {0x18c3003, 0x230c0ef}, {0x1933604, 0x3310191}, {0x16a61515, 0x3100026b}, {0x1d93a06, 0x4398305}, {0x16b61517, 0x750043b6}, {0x25f4e07, 0x549c423}, {0x16c63117, 0x75008529}, {0xa71609, 0x6124582}, {0x2a040a, 0x60285fd}, {0x16d64d17, 0x7504c680}, {0x2a83bd32, 0xbe8606f0}, {0x16e66917, 0x750507c6}, {0x38000e, 0x8038837}, {0x27a4c0e, 0x94b88a0}, {0x16f68517, 0x7509490c}, {0x27f4e0f, 0x94bc96b}, {0x1706a117, 0x750989e7}, {0x1716bd17, 0x750dca89}, {0x17262a19, 0x98020b2c}, {0x17369a19, 0x980a4bdb}, {0x17462a1a, 0xba028cce}, {0x17569a1a, 0xba0acdc1}, {0x17662a1b, 0xdc030e99}, {0x17769a1b, 0xdc0b4f6e}, {0x30000000, 0x0}, {0x30000000, 0x0}, {0x30000000, 0x0}, {0x30000000, 0x0}, {0x30000000, 0x0}, {0x30000000, 0x0}},
    {{0x0, 0x0}, {0x1c53a01, 0x138404f}, {0x1cc3803, 0x238c0f1}, {0x1d33e04, 0x3390193}, {0x16a71516, 0x20000277}, {0x3596a06, 0x4698318}, {0x16b71518, 0x640043cd}, {0x2a638532, 0x86840436}, {0x16c73118, 0x64008540}, {0x2274609, 0x6424593}, {0x22a440a, 0x6428612}, {0x16d74d18, 0x6404c695}, {0x170280c, 0x72b06fe}, {0x33060c, 0x803076c}, {0x16e76918, 0x640507da}, {0x2a95b634, 0xb987485f}, {0x16f78518, 0x64094920}, {0x1707a118, 0x640989f1}, {0x1717bd18, 0x640dca94}, {0x2ac62a36, 0x2f8a4ae0}, {0x17273119, 0x98020b36}, {0x1737a119, 0x980a4bea}, {0x1747311a, 0xba028cdd}, {0x1757a11a, 0xba0acdd0}, {0x1767311b, 0xdc030ea6}, {0x1777a11b, 0xdc0b4f7b}, {0x30000000, 0x0}, {0x30000000, 0x0}, {0x30000000, 0x0}, {0x30000000, 0x0}, {0x30000000, 0x0}, {0x30000000, 0x0}},
    {{0x0, 0x0}, {0x2054201, 0x1404050}, {0x20c4003, 0x240c0f2}, {0x2134604, 0x3410194}, {0x2a383831, 0x3881820a}, {0x16a81c15, 0x31000282}, {0x19a3406, 0x4318332}, {0x16b83815, 0x310443e4}, {0x3a07008, 0x5720460}, {0x16c85415, 0x31048558}, {0x3a8700a, 0x67285cf}, {0x16d87015, 0x3108c6a9}, {0x2f0580c, 0x75b070e}, {0x16e88c15, 0x310907ef}, {0x2b8500e, 0x8538851}, {0x16f8a815, 0x310d4934}, {0x2ff5e0f, 0x95bc970}, {0x1708c415, 0x310d89fb}, {0x1718c417, 0x750dca9e}, {0x17283819, 0x98060b41}, {0x1738a819, 0x980e4bf9}, {0x2ae73137, 0x378c4c6b}, {0x1748381a, 0xba068cec}, {0x1758a81a, 0xba0ecddf}, {0x1768381b, 0xdc070eb4}, {0x1778a81b, 0xdc0f4f88}, {0x30000000, 0x0}, {0x30000000, 0x0}, {0x30000000, 0x0}, {0x30000000, 0x0}, {0x30000000, 0x0}, {0x30000000, 0x0}},
    {{0x0, 0x0}, {0x2454a01, 0x1484051}, {0x24c4803, 0x248c0f3}, {0x2534e04, 0x3490195}, {0x2a393832, 0x3981820b}, {0x16a91c16, 0x2000028e}, {0x2da5c06, 0x4598340}, {0x16b93816, 0x200443fb}, {0x2a666933, 0x6b84447b}, {0x16c95416, 0x2004856f}, {0x2a768533, 0x878545e8}, {0x16d97016, 0x2008c6bd}, {0x710a0c, 0x70b071d}, {0x16e98c16, 0x20090803}, {0x39020e, 0x8038860}, {0x16f9a816, 0x200d4949}, {0x2aa62a35, 0x2e88499a}, {0x1709c416, 0x200d8a05}, {0x1719c418, 0x640dcaa8}, {0x17293f19, 0x98060b4b}, {0x1739af19, 0x980e4c09}, {0x17493f1a, 0xba068cfb}, {0x2af7a137, 0xa78d4d5e}, {0x1759af1a, 0xba0ecdec}, {0x17693f1b, 0xdc070ec1}, {0x1779af1b, 0xdc0f4f95}, {0x30000000, 0x0}, {0x30000000, 0x0}, {0x30000000, 0x0}, {0x30000000, 0x0}, {0x30000000, 0x0}, {0x30000000, 0x0}},
    {{0x0, 0x0}, {0x2855201, 0x1504053}, {0x28c5003, 0x250c0f5}, {0x2935604, 0x3510197}, {0x2a3a3f31, 0x3f81820d}, {0x16aa2315, 0x3100029f}, {0x1b0606, 0x401834f}, {0x16ba3f15, 0x31044413}, {0x220408, 0x5020494}, {0x16ca5b15, 0x31048586}, {0xaa140a, 0x6128602}, {0x16da7715, 0x3108c6d2}, {0x231420c, 0x743072f}, {0x16ea9315, 0x31090817}, {0x1f93a0e, 0x83b8871}, {0x16faaf15, 0x310d495d}, {0x2aa93f35, 0x438889b9}, {0x170acb15, 0x310d8a0f}, {0x171acb17, 0x750dcab2}, {0x172a4619, 0x98060b55}, {0x2adbbd36, 0xc28b8bb6}, {0x173ab619, 0x980e4c18}, {0x174a461a, 0xba068d0b}, {0x175ab61a, 0xba0ecdfa}, {0x176a461b, 0xdc070ece}, {0x177ab61b, 0xdc0f4fa3}, {0x30000000, 0x0}, {0x30000000, 0x0}, {0x30000000, 0x0}, {0x30000000, 0x0}, {0x30000000, 0x0}, {0x30000000, 0x0}},
    {{0x0, 0x0}, {0x2c55a01, 0x1584054}, {0x2cc5803, 0x258c0f6}, {0x2d35e04, 0x3590198}, {0x2a3b3f32, 0x4081820e}, {0x16ab2316, 0x200002b6}, {0x1db3e06, 0x4398362}, {0x16bb3f16, 0x2004442a}, {0x2624c08, 0x54a04ae}, {0x16cb5b16, 0x2004859d}, {0x36a6c0a, 0x66a861e}, {0x16db7716, 0x2008c6e6}, {0x3b1720c, 0x773073e}, {0x16eb9316, 0x2009082c}, {0x2b9520e, 0x8538879}, {0x27c480f, 0x94bc8f1}, {0x16fbaf16, 0x200d4972}, {0x170bcb16, 0x200d8a19}, {0x171bcb18, 0x640dcabc}, {0x172b4d19, 0x98060b5f}, {0x173bbd19, 0x980e4c27}, {0x174b4d1a, 0xba068d1a}, {0x175bbd1a, 0xba0ece07}, {0x176b4d1b, 0xdc070edb}, {0x177bbd1b, 0xdc0f4fb0}, {0x30000000, 0x0}, {0x30000000, 0x0}, {0x30000000, 0x0}, {0x30000000, 0x0}, {0x30000000, 0x0}, {0x30000000, 0x0}, {0x30000000, 0x0}},
    {{0x0, 0x0}, {0x3056201, 0x1604056}, {0x30c6003, 0x260c0f8}, {0x3136604, 0x361019a}, {0x2a3c1c33, 0x1e81c210}, {0x16ac0017, 0x750002ce}, {0x35b6e06, 0x4698375}, {0x16bc1c17, 0x75004441}, {0x1232608, 0x52204ce}, {0x16cc3817, 0x750485b5}, {0x12b260a, 0x6228630}, {0x16dc5417, 0x7504c6fa}, {0xb2140c, 0x7130748}, {0x750a0d, 0x80b47c0}, {0x16ec7017, 0x75090840}, {0x3fa7c0e, 0x97b88ae}, {0x16fc8c17, 0x75094981}, {0x170ca817, 0x750d8a24}, {0x171cd217, 0x750dcac6}, {0x172c5419, 0x98060b69}, {0x173cc419, 0x980e4c36}, {0x174c541a, 0xba068d29}, {0x175cc41a, 0xba0ece14}, {0x176c541b, 0xdc070ee9}, {0x177cc41b, 0xdc0f4fbd}, {0x30000000, 0x0}, {0x30000000, 0x0}, {0x30000000, 0x0}, {0x30000000, 0x0}, {0x30000000, 0x0}, {0x30000000, 0x0}, {0x30000000, 0x0}},
    {{0x0, 0x0}, {0x3456a01, 0x1684057}, {0x34c6803, 0x268c0f9}, {0x3536e04, 0x369019b}, {0x2a3d1c34, 0x1f81c211}, {0x16ad0018, 0x640002e5}, {0x9c1007, 0x411c383}, {0x16bd1c18, 0x64004458}, {0x2e35e08, 0x55a04e2}, {0x16cd3818, 0x640485c9}, {0x2ab560a, 0x652863f}, {0x16dd5418, 0x6404c70f}, {0x1f23c0c, 0x73b0754}, {0x1b5320d, 0x83347cc}, {0x16ed7018, 0x64090855}, {0x27b4e0e, 0x94b88c8}, {0x16fd8c18, 0x6409498b}, {0x170da818, 0x640d8a2e}, {0x171dd218, 0x640dcad1}, {0x172d5b19, 0x98060b74}, {0x173dcb19, 0x980e4c45}, {0x174d5b1a, 0xba068d38}, {0x175dcb1a, 0xba0ece21}, {0x176d5b1b, 0xdc070ef6}, {0x177dcb1b, 0xdc0f4fca}, {0x30000000, 0x0}, {0x30000000, 0x0}, {0x30000000, 0x0}, {0x30000000, 0x0}, {0x30000000, 0x0}, {0x30000000, 0x0}, {0x30000000, 0x0}},
    {{0x0, 0x0}, {0x3857201, 0x1704059}, {0x38c7003, 0x270c0fb}, {0x3937604, 0x371019d}, {0x2a3e2333, 0x2581c213}, {0x16ae0717, 0x750002fc}, {0x2a5c5433, 0x5683c393}, {0x16be2317, 0x75004470}, {0x640809, 0x50a44f4}, {0x16ce3f17, 0x750485dd}, {0x2c000b, 0x702c64f}, {0x2ae540b, 0x752c6ba}, {0x16de5b17, 0x7504c723}, {0x74080d, 0x80b4797}, {0x16ee7717, 0x75090869}, {0xbc100f, 0x913c8df}, {0x16fe9317, 0x75094995}, {0x170eaf17, 0x750d8a38}, {0x171ed917, 0x750dcadb}, {0x172e6219, 0x98060b7e}, {0x173ed219, 0x980e4c54}, {0x174e621a, 0xba068d47}, {0x2afdcb37, 0xd18dcdb9}, {0x175ed21a, 0xba0ece2f}, {0x176e621b, 0xdc070f03}, {0x177ed21b, 0xdc0f4fd8}, {0x30000000, 0x0}, {0x30000000, 0x0}, {0x30000000, 0x0}, {0x30000000, 0x0}, {0x30000000, 0x0}, {0x30000000, 0x0}},
    {{0x0, 0x0}, {0x3c57a01, 0x178405a}, {0x3cc7803, 0x278c0fc}, {0x3d37e04, 0x379019e}, {0x2a3f2334, 0x2681c214}, {0x16af0718, 0x64000313}, {0x39c7007, 0x471c3a6}, {0x16bf2318, 0x64004487}, {0x2244009, 0x5424508}, {0x16cf3f18, 0x640485f2}, {0x1ec380b, 0x73ac65f}, {0x6f0e0b, 0x70ac6cb}, {0x16df5b18, 0x6404c738}, {0x2b4500d, 0x85347ae}, {0x16ef7718, 0x6409087d}, {0x2fc580f, 0x95bc8f6}, {0x16ff9318, 0x6409499f}, {0x170faf18, 0x640d8a42}, {0x171fd918, 0x640dcae5}, {0x172f6919, 0x98060b88}, {0x173fd919, 0x980e4c64}, {0x174f691a, 0xba068d56}, {0x2afed237, 0xd88dcdc8}, {0x175fd91a, 0xba0ece3c}, {0x176f691b, 0xdc070f11}, {0x177fd91b, 0xdc0f4fe5}, {0x30000000, 0x0}, {0x30000000, 0x0}, {0x30000000, 0x0}, {0x30000000, 0x0}, {0x30000000, 0x0}, {0x30000000, 0x0}},
    {{0x0, 0x0}, {0x60401, 0x100405c}, {0xd0203, 0x200c0fe}, {0x140005, 0x30141a0}, {0x1780001c, 0x31000227}, {0x971605, 0x411429b}, {0x17902a1c, 0x3100432d}, {0x15d2a07, 0x429c3ba}, {0x17a0461c, 0x310484a1}, {0x250209, 0x602451f}, {0x17b0621c, 0x3104c609}, {0x3ac700b, 0x772c672}, {0x17c07e1c, 0x3109074e}, {0x134200d, 0x823479f}, {0x17d09a1c, 0x31094894}, {0x1fc380f, 0x93bc8eb}, {0x33e640f, 0x963c94a}, {0x17e0b61c, 0x310d89ab}, {0x17f0d21c, 0x310dca4e}, {0x18000020, 0x98020af0}, {0x18107020, 0x980a4b93}, {0x18200021, 0xba028c75}, {0x18307021, 0xba0acd68}, {0x18400022, 0xdc030e4b}, {0x18507022, 0xdc0b4f20}, {0x30000000, 0x0}, {0x30000000, 0x0}, {0x30000000, 0x0}, {0x30000000, 0x0}, {0x30000000, 0x0}, {0x30000000, 0x0}, {0x30000000, 0x0}},
    {{0x0, 0x0}, {0x460c01, 0x108405d}, {0x4d0a03, 0x208c0ff}, {0x540805, 0x30941a1}, {0x1781001d, 0x20000232}, {0x2174605, 0x44142ac}, {0x17912a1d, 0x20004345}, {0x2dd5a07, 0x459c3cc}, {0x17a1461d, 0x200484b8}, {0x2a6e7733, 0x7984c535}, {0x2a73a132, 0xa28505a9}, {0x17b1621d, 0x2004c61d}, {0x16d2a0b, 0x72ac684}, {0x17c17e1d, 0x20090763}, {0x3756a0d, 0x86b47de}, {0x17d19a1d, 0x200948a8}, {0xfd1a0f, 0x91bc90a}, {0x17e1b61d, 0x200d89b5}, {0x17f1d21d, 0x200dca58}, {0x18010720, 0x98020afb}, {0x18117720, 0x980a4b9e}, {0x2ae10737, 0xd8c0c10}, {0x18210721, 0xba028c84}, {0x18317721, 0xba0acd77}, {0x18410722, 0xdc030e59}, {0x18517722, 0xdc0b4f2d}, {0x30000000, 0x0}, {0x30000000, 0x0}, {0x30000000, 0x0}, {0x30000000, 0x0}, {0x30000000, 0x0}, {0x30000000, 0x0}},
    {{0x0, 0x0}, {0x861401, 0x110405e}, {0x8d1203, 0x210c100}, {0x941005, 0x31141a2}, {0x1782071c, 0x3100023e}, {0x3d77e05, 0x47942bf}, {0x1792311c, 0x3100435c}, {0x5e0c07, 0x509c3dd}, {0x17a24d1c, 0x310484cf}, {0x2a55209, 0x652453c}, {0xe8180a, 0x61a85b3}, {0x17b2691c, 0x3104c631}, {0x36d6a0b, 0x76ac698}, {0x17c2851c, 0x31090777}, {0x1b6340d, 0x83347f5}, {0x17d2a11c, 0x310948bd}, {0x27d4a0f, 0x94bc91a}, {0x17e2bd1c, 0x310d89bf}, {0x17f2d91c, 0x310dca62}, {0x18020e20, 0x98020b05}, {0x18127e20, 0x980a4ba8}, {0x18220e21, 0xba028c93}, {0x18327e21, 0xba0acd86}, {0x18420e22, 0xdc030e66}, {0x18527e22, 0xdc0b4f3a}, {0x30000000, 0x0}, {0x30000000, 0x0}, {0x30000000, 0x0}, {0x30000000, 0x0}, {0x30000000, 0x0}, {0x30000000, 0x0}, {0x30000000, 0x0}},
    {{0x0, 0x0}, {0xc61c01, 0x1184060}, {0xcd1a03, 0x218c102}, {0xd41805, 0x31941a4}, {0x1783071d, 0x2000024a}, {0x1582806, 0x42982d2}, {0x1793311d, 0x20004373}, {0x2a607e31, 0x7e8403f0}, {0xa11208, 0x512046b}, {0x17a34d1d, 0x200484e7}, {0x2664c09, 0x64a4568}, {0x17b3691d, 0x2004c646}, {0x1ae340b, 0x732c6af}, {0x17c3851d, 0x2009078b}, {0x3b6740d, 0x8734809}, {0x17d3a11d, 0x200948d1}, {0x7e0c0f, 0x90bc92e}, {0x17e3bd1d, 0x200d89c9}, {0x17f3d91d, 0x200dca6c}, {0x18031520, 0x98020b0f}, {0x18138520, 0x980a4bb2}, {0x18231521, 0xba028ca2}, {0x2af38537, 0x8b8d0d21}, {0x18338521, 0xba0acd95}, {0x18431522, 0xdc030e73}, {0x18538522, 0xdc0b4f48}, {0x30000000, 0x0}, {0x30000000, 0x0}, {0x30000000, 0x0}, {0x30000000, 0x0}, {0x30000000, 0x0}, {0x30000000, 0x0}},
    {{0x0, 0x0}, {0x1062401, 0x1204061}, {0x10d2203, 0x220c103}, {0x1142005, 0x32141a5}, {0x17840e1c, 0x31000255}, {0x2d85806, 0x45982e3}, {0x17940e1e, 0x7500438a}, {0x39e7407, 0x571c403}, {0x2614a08, 0x54a0480}, {0x17a42a1e, 0x750084fe}, {0x270609, 0x602457c}, {0x17b4461e, 0x7504c65a}, {0x3ee7c0b, 0x77ac6c5}, {0x17c4621e, 0x750507a0}, {0x1772e0d, 0x82b481b}, {0x3796a0e, 0x86b8881}, {0x17d47e1e, 0x750948e6}, {0x7f0e0f, 0x90bc957}, {0x17e49a1e, 0x750989d3}, {0x17f4b61e, 0x750dca76}, {0x18041c20, 0x98020b19}, {0x18148c20, 0x980a4bbf}, {0x18241c21, 0xba028cb1}, {0x18348c21, 0xba0acda4}, {0x18441c22, 0xdc030e80}, {0x18548c22, 0xdc0b4f55}, {0x30000000, 0x0}, {0x30000000, 0x0}, {0x30000000, 0x0}, {0x30000000, 0x0}, {0x30000000, 0x0}, {0x30000000, 0x0}},
    {{0x0, 0x0}, {0x1462c01, 0x1284063}, {0x14d2a03, 0x228c105}, {0x1542805, 0x32941a7}, {0x17850e1d, 0x20000261}, {0x590a06, 0x40982f5}, {0x17950e1f, 0x640043a2}, {0x11f2607, 0x521c414}, {0x17a52a1f, 0x64008515}, {0x3a67409, 0x6724576}, {0x2e95a0a, 0x65a85f1}, {0x17b5461f, 0x6404c66e}, {0x22f460b, 0x742c6dd}, {0x17c5621f, 0x640507b4}, {0x337660d, 0x863482d}, {0x13a240e, 0x9238893}, {0x17d57e1f, 0x640948fa}, {0x17f2e0f, 0x92bc961}, {0x17e59a1f, 0x640989de}, {0x17f5b61f, 0x640dca81}, {0x18052320, 0x98020b23}, {0x18159320, 0x980a4bce}, {0x18252321, 0xba028cc1}, {0x18359321, 0xba0acdb3}, {0x18452322, 0xdc030e8e}, {0x18559322, 0xdc0b4f62}, {0x30000000, 0x0}, {0x30000000, 0x0}, {0x30000000, 0x0}, {0x30000000, 0x0}, {0x30000000, 0x0}, {0x30000000, 0x0}},
    {{0x0, 0x0}, {0x1863401, 0x1304064}, {0x18d3203, 0x230c106}, {0x1943005, 0x33141a8}, {0x1786151c, 0x3100026c}, {0x2a564d33, 0x4f834308}, {0x1796151e, 0x750043b9}, {0x29f5607, 0x551c426}, {0x17a6311e, 0x7500852c}, {0x1272609, 0x6224588}, {0xea1c0a, 0x61a8605}, {0x17b64d1e, 0x7504c683}, {0x30000c, 0x70306f2}, {0x2b2540c, 0x753075c}, {0x17c6691e, 0x750507c9}, {0x278480e, 0x84b884e}, {0x17d6851e, 0x7509490e}, {0x2bf560f, 0x953c96e}, {0x17e6a11e, 0x750989e8}, {0x17f6bd1e, 0x750dca8b}, {0x18062a20, 0x98020b2e}, {0x18169a20, 0x980a4bdd}, {0x18262a21, 0xba028cd0}, {0x18369a21, 0xba0acdc3}, {0x18462a22, 0xdc030e9b}, {0x18569a22, 0xdc0b4f6f}, {0x30000000, 0x0}, {0x30000000, 0x0}, {0x30000000, 0x0}, {0x30000000, 0x0}, {0x30000000, 0x0}, {0x30000000, 0x0}},
    {{0x0, 0x0}, {0x1c63c01, 0x1384066}, {0x1cd3a03, 0x238c108}, {0x1d43805, 0x33941aa}, {0x1787151d, 0x20000278}, {0x3997206, 0x471831b}, {0x1797151f, 0x640043d0}, {0x200008, 0x5020437}, {0x3a27408, 0x57204bc}, {0x17a7311f, 0x64008543}, {0x1e8380a, 0x63a85bc}, {0x17b74d1f, 0x6404c697}, {0x1b0300c, 0x7330701}, {0x17c7691f, 0x640507dd}, {0x138200e, 0x8238841}, {0x2a99c434, 0xc78788b0}, {0x17d7851f, 0x64094923}, {0x17e7a11f, 0x640989f2}, {0x17f7bd1f, 0x640dca95}, {0x18073120, 0x98020b38}, {0x2ad69a36, 0x9f8b4b83}, {0x1817a120, 0x980a4bec}, {0x18273121, 0xba028cdf}, {0x1837a121, 0xba0acdd2}, {0x18473122, 0xdc030ea8}, {0x1857a122, 0xdc0b4f7d}, {0x30000000, 0x0}, {0x30000000, 0x0}, {0x30000000, 0x0}, {0x30000000, 0x0}, {0x30000000, 0x0}, {0x30000000, 0x0}},
    {{0x0, 0x0}, {0x2064401, 0x1404067}, {0x20d4203, 0x240c109}, {0x2144005, 0x34141ab}, {0x2a404631, 0x46820215}, {0x17881c1c, 0x31000284}, {0x1da3c06, 0x4398333}, {0x1798381c, 0x310443e7}, {0x2a656234, 0x65844464}, {0x17a8541c, 0x3104855b}, {0x2a757e34, 0x818545d3}, {0x17b8701c, 0x3108c6ac}, {0x330600c, 0x7630710}, {0x17c88c1c, 0x310907f1}, {0x2f8580e, 0x85b8853}, {0x17d8a81c, 0x310d4937}, {0x37f6e0f, 0x96bc975}, {0x17e8c41c, 0x310d89fc}, {0x17f8c41e, 0x750dca9f}, {0x18083820, 0x98060b42}, {0x1818a820, 0x980e4bfb}, {0x18283821, 0xba068cee}, {0x2af59337, 0x998d4d40}, {0x1838a821, 0xba0ecde1}, {0x18483822, 0xdc070eb5}, {0x1858a822, 0xdc0f4f8a}, {0x30000000, 0x0}, {0x30000000, 0x0}, {0x30000000, 0x0}, {0x30000000, 0x0}, {0x30000000, 0x0}, {0x30000000, 0x0}},
    {{0x0, 0x0}, {0x2464c01, 0x1484068}, {0x24d4a03, 0x248c10a}, {0x2544805, 0x34941ac}, {0x2a414632, 0x47820217}, {0x17891c1d, 0x2000028f}, {0x31a6406, 0x4618343}, {0x1799381d, 0x200443fe}, {0x2214208, 0x542047d}, {0x17a9541d, 0x20048572}, {0x2694a0a, 0x64a85eb}, {0x17b9701d, 0x2008c6c0}, {0xb1120c, 0x713071f}, {0x17c98c1d, 0x20090806}, {0xb9120e, 0x8138865}, {0x17d9a81d, 0x200d494b}, {0x2aa73135, 0x358849a4}, {0x17e9c41d, 0x200d8a06}, {0x17f9c41f, 0x640dcaa9}, {0x18093f20, 0x98060b4c}, {0x2adab636, 0xbb8b8bac}, {0x1819af20, 0x980e4c0a}, {0x18293f21, 0xba068cfd}, {0x1839af21, 0xba0ecdee}, {0x18493f22, 0xdc070ec3}, {0x1859af22, 0xdc0f4f97}, {0x30000000, 0x0}, {0x30000000, 0x0}, {0x30000000, 0x0}, {0x30000000, 0x0}, {0x30000000, 0x0}, {0x30000000, 0x0}},
    {{0x0, 0x0}, {0x2865401, 0x150406a}, {0x28d5203, 0x250c10c}, {0x2945005, 0x35141ae}, {0x2a424d31, 0x4d820218}, {0x178a231c, 0x310002a2}, {0x5b0e06, 0x4098352}, {0x179a3f1c, 0x31044416}, {0x620c08, 0x50a0497}, {0x17aa5b1c, 0x31048589}, {0x12a240a, 0x6228607}, {0x17ba771c, 0x3108c6d4}, {0x2714a0c, 0x74b0731}, {0x1f4380d, 0x83b47a5}, {0x17ca931c, 0x3109081a}, {0x339620e, 0x863887e}, {0x17daaf1c, 0x310d4960}, {0x17eacb1c, 0x310d8a11}, {0x17facb1e, 0x750dcab3}, {0x180a4620, 0x98060b56}, {0x181ab620, 0x980e4c1a}, {0x182a4621, 0xba068d0c}, {0x183ab621, 0xba0ecdfc}, {0x184a4622, 0xdc070ed0}, {0x185ab622, 0xdc0f4fa5}, {0x30000000, 0x0}, {0x30000000, 0x0}, {0x30000000, 0x0}, {0x30000000, 0x0}, {0x30000000, 0x0}, {0x30000000, 0x0}, {0x30000000, 0x0}},
    {{0x0, 0x0}, {0x2c65c01, 0x158406b}, {0x2cd5a03, 0x258c10d}, {0x2d45805, 0x35941af}, {0x2a434d32, 0x4e82021a}, {0x178b231d, 0x200002b9}, {0x2a5a7731, 0x77838365}, {0x179b3f1d, 0x2004442d}, {0x2a25408, 0x55204b1}, {0x17ab5b1d, 0x200485a0}, {0x3aa740a, 0x6728621}, {0x17bb771d, 0x2008c6e9}, {0x3f17a0c, 0x77b073f}, {0x374680d, 0x86b47b5}, {0x17cb931d, 0x2009082e}, {0x17a2c0e, 0x92b8895}, {0x17dbaf1d, 0x200d4974}, {0x17ebcb1d, 0x200d8a1b}, {0x17fbcb1f, 0x640dcabe}, {0x180b4d20, 0x98060b60}, {0x2adcc436, 0xc98bcbc4}, {0x181bbd20, 0x980e4c29}, {0x182b4d21, 0xba068d1c}, {0x183bbd21, 0xba0ece09}, {0x184b4d22, 0xdc070edd}, {0x185bbd22, 0xdc0f4fb2}, {0x30000000, 0x0}, {0x30000000, 0x0}, {0x30000000, 0x0}, {0x30000000, 0x0}, {0x30000000, 0x0}, {0x30000000, 0x0}},
    {{0x0, 0x0}, {0x3066401, 0x160406d}, {0x30d6203, 0x260c10f}, {0x3146005, 0x36141b1}, {0x2a442a33, 0x2c82421b}, {0x178c001e, 0x750002d1}, {0x39b7606, 0x4718377}, {0x179c1c1e, 0x75004444}, {0x1632e08, 0x52a04d1}, {0x17ac381e, 0x750485b7}, {0x16b2e0a, 0x62a8633}, {0x17bc541e, 0x7504c6fd}, {0xf21c0c, 0x71b074b}, {0xb5120d, 0x81347c2}, {0x17cc701e, 0x75090843}, {0x3b060e, 0x90388b1}, {0x17dc8c1e, 0x75094982}, {0x17eca81e, 0x750d8a25}, {0x17fcd21e, 0x750dcac8}, {0x180c5420, 0x98060b6b}, {0x181cc420, 0x980e4c38}, {0x182c5421, 0xba068d2b}, {0x183cc421, 0xba0ece16}, {0x184c5422, 0xdc070eeb}, {0x185cc422, 0xdc0f4fbf}, {0x30000000, 0x0}, {0x30000000, 0x0}, {0x30000000, 0x0}, {0x30000000, 0x0}, {0x30000000, 0x0}, {0x30000000, 0x0}, {0x30000000, 0x0}},
    {{0x0, 0x0}, {0x3466c01, 0x168406e}, {0x34d6a03, 0x268c110}, {0x3546805, 0x36941b2}, {0x2a452a34, 0x2d82421d}, {0x178d001f, 0x640002e8}, {0xdc1807, 0x419c386}, {0x179d1c1f, 0x6400445b}, {0x3236608, 0x56204e5}, {0x17ad381f, 0x640485cc}, {0x2eb5e0a, 0x65a8642}, {0x17bd541f, 0x6404c711}, {0x2a88c431, 0xc4868756}, {0x1f53a0d, 0x83b47ce}, {0x17cd701f, 0x64090857}, {0x2bb560e, 0x95388cb}, {0x17dd8c1f, 0x6409498c}, {0x17eda81f, 0x640d8a2f}, {0x17fdd21f, 0x640dcad2}, {0x180d5b20, 0x98060b75}, {0x181dcb20, 0x980e4c47}, {0x182d5b21, 0xba068d3a}, {0x183dcb21, 0xba0ece23}, {0x184d5b22, 0xdc070ef8}, {0x185dcb22, 0xdc0f4fcc}, {0x30000000, 0x0}, {0x30000000, 0x0}, {0x30000000, 0x0}, {0x30000000, 0x0}, {0x30000000, 0x0}, {0x30000000, 0x0}, {0x30000000, 0x0}},
    {{0x0, 0x0}, {0x3867401, 0x1704070}, {0x38d7203, 0x270c112}, {0x3947005, 0x37141b4}, {0x2a463133, 0x3382421e}, {0x178e071e, 0x750002ff}, {0x21c4007, 0x441c394}, {0x179e231e, 0x75004472}, {0xa41009, 0x51244f6}, {0x17ae3f1e, 0x750485e0}, {0x6c080b, 0x70ac651}, {0x17be5b1e, 0x7504c726}, {0x730e0c, 0x80b076e}, {0x760c0d, 0x80b47e8}, {0x17ce771e, 0x7509086b}, {0x13c200f, 0x923c8e4}, {0x17de931e, 0x75094996}, {0x17eeaf1e, 0x750d8a39}, {0x17fed91e, 0x750dcadc}, {0x180e6220, 0x98060b7f}, {0x181ed220, 0x980e4c56}, {0x182e6221, 0xba068d49}, {0x183ed221, 0xba0ece31}, {0x184e6222, 0xdc070f05}, {0x185ed222, 0xdc0f4fda}, {0x30000000, 0x0}, {0x30000000, 0x0}, {0x30000000, 0x0}, {0x30000000, 0x0}, {0x30000000, 0x0}, {0x30000000, 0x0}, {0x30000000, 0x0}},
    {{0x0, 0x0}, {0x3c67c01, 0x1784071}, {0x3cd7a03, 0x278c113}, {0x3d47805, 0x37941b5}, {0x2a473134, 0x34824220}, {0x178f071f, 0x64000316}, {0x3dc7807, 0x479c3a7}, {0x179f231f, 0x6400448a}, {0x2644809, 0x54a450b}, {0x17af3f1f, 0x640485f4}, {0x2a7c8c33, 0x8e85c662}, {0x17bf5b1f, 0x6404c73a}, {0x2b3560c, 0x8530785}, {0x17cf771f, 0x64090880}, {0x33b660e, 0x96388d0}, {0x3e040f, 0x903c92c}, {0x17df931f, 0x640949a1}, {0x17efaf1f, 0x640d8a43}, {0x17ffd91f, 0x640dcae6}, {0x180f6920, 0x98060b89}, {0x181fd920, 0x980e4c66}, {0x182f6921, 0xba068d58}, {0x183fd921, 0xba0ece3e}, {0x184f6922, 0xdc070f12}, {0x185fd922, 0xdc0f4fe7}, {0x30000000, 0x0}, {0x30000000, 0x0}, {0x30000000, 0x0}, {0x30000000, 0x0}, {0x30000000, 0x0}, {0x30000000, 0x0}, {0x30000000, 0x0}},
    {{0x0, 0x0}, {0x70601, 0x1004073}, {0xe0403, 0x200c115}, {0x150205, 0x30141b7}, {0x18600023, 0x31000228}, {0xd71e05, 0x419429e}, {0x18702a23, 0x31004330}, {0x19d3207, 0x431c3bd}, {0x18804623, 0x310484a4}, {0x650a09, 0x60a4522}, {0x18906223, 0x3104c60b}, {0x3ec780b, 0x77ac674}, {0x2af560b, 0x752c6e2}, {0x18a07e23, 0x31090751}, {0x135220d, 0x82347c7}, {0x18b09a23, 0x31094897}, {0x3bc700f, 0x973c8fe}, {0x18c0b623, 0x310d89ac}, {0x18d0d223, 0x310dca4f}, {0x18e00027, 0x98020af2}, {0x18f07027, 0x980a4b95}, {0x19000028, 0xba028c77}, {0x2af07037, 0x768d0cf4}, {0x19107028, 0xba0acd69}, {0x19200029, 0xdc030e4d}, {0x19307029, 0xdc0b4f22}, {0x30000000, 0x0}, {0x30000000, 0x0}, {0x30000000, 0x0}, {0x30000000, 0x0}, {0x30000000, 0x0}, {0x30000000, 0x0}},
    {{0x400800, 0x80000}, {0x470e01, 0x1084074}, {0x4e0c03, 0x208c116}, {0x550a05, 0x30941b8}, {0x18610024, 0x20000234}, {0x2574e05, 0x44942af}, {0x18712a24, 0x20004348}, {0x31d6207, 0x461c3ce}, {0x18814624, 0x200484bb}, {0x2254209, 0x6424536}, {0x28000a, 0x60285aa}, {0x18916224, 0x2004c620}, {0x1ad320b, 0x732c687}, {0x18a17e24, 0x20090765}, {0x3b5720d, 0x87347e1}, {0x18b19a24, 0x200948ab}, {0x13d220f, 0x923c90d}, {0x18c1b624, 0x200d89b6}, {0x18d1d224, 0x200dca59}, {0x18e10727, 0x98020afc}, {0x18f17727, 0x980a4b9f}, {0x19010728, 0xba028c86}, {0x2af17737, 0x7d8d0d03}, {0x19117728, 0xba0acd79}, {0x19210729, 0xdc030e5a}, {0x19317729, 0xdc0b4f2f}, {0x30000000, 0x0}, {0x30000000, 0x0}, {0x30000000, 0x0}, {0x30000000, 0x0}, {0x30000000, 0x0}, {0x30000000, 0x0}},
    {{0x801000, 0x100000}, {0x871601, 0x1104075}, {0x8e1403, 0x210c117}, {0x951205, 0x31141b9}, {0x18620723, 0x31000240}, {0x2a536932, 0x6a8302c2}, {0x18723123, 0x3100435f}, {0x9e1407, 0x511c3e0}, {0x18824d23, 0x310484d2}, {0x2e55a09, 0x65a453f}, {0x168280a, 0x62a85b9}, {0x18926923, 0x3104c634}, {0x3ad720b, 0x772c69b}, {0x18a28523, 0x3109077a}, {0x1f63c0d, 0x83b47f6}, {0x18b2a123, 0x310948bf}, {0x2bd520f, 0x953c91c}, {0x18c2bd23, 0x310d89c0}, {0x18d2d923, 0x310dca63}, {0x18e20e27, 0x98020b06}, {0x18f27e27, 0x980a4ba9}, {0x2ae20e37, 0x148c0c1f}, {0x19020e28, 0xba028c95}, {0x19127e28, 0xba0acd88}, {0x19220e29, 0xdc030e68}, {0x19327e29, 0xdc0b4f3c}, {0x30000000, 0x0}, {0x30000000, 0x0}, {0x30000000, 0x0}, {0x30000000, 0x0}, {0x30000000, 0x0}, {0x30000000, 0x0}},
    {{0xc01800, 0x180000}, {0xc71e01, 0x1184077}, {0xce1c03, 0x218c119}, {0xd51a05, 0x31941bb}, {0x18630724, 0x2000024b}, {0x1983006, 0x43182d5}, {0x18733124, 0x20004376}, {0x21e4407, 0x541c3f1}, {0x18834d24, 0x200484e9}, {0x2a6f7734, 0x7a84c54c}, {0x268480a, 0x64a85c3}, {0x18936924, 0x2004c648}, {0x1ee3c0b, 0x73ac6b1}, {0x18a38524, 0x2009078e}, {0x3f67c0d, 0x87b480b}, {0x18b3a124, 0x200948d4}, {0xfe1c0f, 0x91bc933}, {0x18c3bd24, 0x200d89cb}, {0x18d3d924, 0x200dca6d}, {0x18e31527, 0x98020b10}, {0x18f38527, 0x980a4bb3}, {0x2ae31537, 0x1b8c0c2e}, {0x19031528, 0xba028ca4}, {0x19138528, 0xba0acd97}, {0x19231529, 0xdc030e75}, {0x19338529, 0xdc0b4f49}, {0x30000000, 0x0}, {0x30000000, 0x0}, {0x30000000, 0x0}, {0x30000000, 0x0}, {0x30000000, 0x0}, {0x30000000, 0x0}},
    {{0x1002000, 0x200000}, {0x1072601, 0x1204078}, {0x10e2403, 0x220c11a}, {0x1152205, 0x32141bc}, {0x18640e23, 0x31000257}, {0x3186006, 0x46182e6}, {0x18740e25, 0x7500438d}, {0x3de7c07, 0x579c404}, {0x2a15208, 0x5520482}, {0x18842a25, 0x75008501}, {0x670e09, 0x60a457f}, {0x18944625, 0x7504c65d}, {0x2f060b, 0x702c6c9}, {0x18a46225, 0x750507a2}, {0x1b7360d, 0x833481e}, {0x18b47e25, 0x750948e8}, {0x2fe5c0f, 0x95bc948}, {0x18c49a25, 0x750989d5}, {0x18d4b625, 0x750dca78}, {0x2ac41c36, 0x218a4acc}, {0x18e41c27, 0x98020b1a}, {0x18f48c27, 0x980a4bc0}, {0x19041c28, 0xba028cb3}, {0x19148c28, 0xba0acda6}, {0x19241c29, 0xdc030e82}, {0x19348c29, 0xdc0b4f57}, {0x30000000, 0x0}, {0x30000000, 0x0}, {0x30000000, 0x0}, {0x30000000, 0x0}, {0x30000000, 0x0}, {0x30000000, 0x0}},
    {{0x1402800, 0x280000}, {0x1472e01, 0x128407a}, {0x14e2c03, 0x228c11c}, {0x1552a05, 0x32941be}, {0x18650e24, 0x20000262}, {0x991206, 0x41182f8}, {0x18750e26, 0x640043a4}, {0x15f2e07, 0x529c417}, {0x18852a26, 0x64008518}, {0x3e67c09, 0x67a4578}, {0x329620a, 0x66285f3}, {0x18954626, 0x6404c671}, {0x26f4e0b, 0x74ac6e0}, {0x18a56226, 0x640507b7}, {0x3776e0d, 0x86b4830}, {0x18b57e26, 0x640948fc}, {0x2aa10735, 0xb880953}, {0x18c59a26, 0x640989df}, {0x18d5b626, 0x640dca82}, {0x2ac52336, 0x288a4ad6}, {0x18e52327, 0x98020b25}, {0x18f59327, 0x980a4bd0}, {0x19052328, 0xba028cc2}, {0x19159328, 0xba0acdb5}, {0x19252329, 0xdc030e90}, {0x19359329, 0xdc0b4f64}, {0x30000000, 0x0}, {0x30000000, 0x0}, {0x30000000, 0x0}, {0x30000000, 0x0}, {0x30000000, 0x0}, {0x30000000, 0x0}},
    {{0x1803000, 0x300000}, {0x1873601, 0x130407b}, {0x18e3403, 0x230c11d}, {0x1953205, 0x33141bf}, {0x18661523, 0x3100026e}, {0x2194206, 0x4418309}, {0x18761525, 0x750043bc}, {0x2df5e07, 0x559c428}, {0x18863125, 0x7500852f}, {0x1a73609, 0x632458d}, {0x18964d25, 0x7504c685}, {0xaf160b, 0x712c6ce}, {0x1f13a0c, 0x73b072b}, {0x18a66925, 0x750507cb}, {0x78080e, 0x80b883a}, {0x2fa5c0e, 0x95b88a5}, {0x18b68525, 0x75094911}, {0x33f660f, 0x963c973}, {0x18c6a125, 0x750989e9}, {0x18d6bd25, 0x750dca8c}, {0x18e62a27, 0x98020b2f}, {0x18f69a27, 0x980a4bdf}, {0x19062a28, 0xba028cd2}, {0x19169a28, 0xba0acdc5}, {0x19262a29, 0xdc030e9d}, {0x19369a29, 0xdc0b4f71}, {0x30000000, 0x0}, {0x30000000, 0x0}, {0x30000000, 0x0}, {0x30000000, 0x0}, {0x30000000, 0x0}, {0x30000000, 0x0}},
    {{0x1c03800, 0x380000}, {0x1c73e01, 0x138407d}, {0x1ce3c03, 0x238c11f}, {0x1d53a05, 0x33941c1}, {0x18671524, 0x2000027a}, {0x3d97a06, 0x479831c}, {0x18771526, 0x640043d3}, {0x600808, 0x50a043a}, {0x2a698c32, 0x8d8484c1}, {0x18873126, 0x64008546}, {0x228400a, 0x64285c0}, {0x18974d26, 0x6404c69a}, {0x1f0380c, 0x73b0702}, {0xb3160c, 0x8130771}, {0x18a76926, 0x640507df}, {0x790a0e, 0x80b8863}, {0x18b78526, 0x64094925}, {0x18c7a126, 0x640989f3}, {0x18d7bd26, 0x640dca96}, {0x18e73127, 0x98020b39}, {0x2ad7a136, 0xa68b4b8d}, {0x18f7a127, 0x980a4bee}, {0x19073128, 0xba028ce1}, {0x1917a128, 0xba0acdd4}, {0x19273129, 0xdc030eaa}, {0x1937a129, 0xdc0b4f7f}, {0x30000000, 0x0}, {0x30000000, 0x0}, {0x30000000, 0x0}, {0x30000000, 0x0}, {0x30000000, 0x0}, {0x30000000, 0x0}},
    {{0x2004000, 0x400000}, {0x2074601, 0x140407e}, {0x20e4403, 0x240c120}, {0x2154205, 0x34141c2}, {0x18681c23, 0x31000285}, {0x1a0406, 0x4018320}, {0x18783823, 0x310443ea}, {0x1202008, 0x5220443}, {0x18885423, 0x3104855d}, {0xa8100a, 0x61285b0}, {0xab160a, 0x612862b}, {0x18987023, 0x3108c6ae}, {0x370680c, 0x76b0713}, {0x2734e0c, 0x84b0783}, {0x18a88c23, 0x310907f4}, {0x2a96bd33, 0xbf874873}, {0x18b8a823, 0x310d493a}, {0x18c8c423, 0x310d89fd}, {0x18d8c425, 0x750dcaa0}, {0x18e83827, 0x98060b43}, {0x2ad9af36, 0xb48b8ba1}, {0x18f8a827, 0x980e4bfd}, {0x19083828, 0xba068cf0}, {0x1918a828, 0xba0ecde3}, {0x19283829, 0xdc070eb7}, {0x1938a829, 0xdc0f4f8c}, {0x30000000, 0x0}, {0x30000000, 0x0}, {0x30000000, 0x0}, {0x30000000, 0x0}, {0x30000000, 0x0}, {0x30000000, 0x0}},
    {{0x2404800, 0x480000}, {0x2474e01, 0x148407f}, {0x24e4c03, 0x248c121}, {0x2554a05, 0x34941c3}, {0x18691c24, 0x20000291}, {0x9a1406, 0x4118326}, {0x18793824, 0x20044401}, {0x2e05808, 0x55a0457}, {0x2a35608, 0x55204df}, {0x18895424, 0x20048575}, {0x2a9520a, 0x65285ee}, {0x18997024, 0x2008c6c2}, {0xf11a0c, 0x71b0722}, {0x18a98c24, 0x20090808}, {0xf91a0e, 0x81b8868}, {0x18b9a824, 0x200d494e}, {0x2aac5435, 0x5888c9d7}, {0x18c9c424, 0x200d8a08}, {0x18d9c426, 0x640dcaab}, {0x18e93f27, 0x98060b4d}, {0x18f9af27, 0x980e4c0c}, {0x19093f28, 0xba068cff}, {0x2af8a837, 0xae8d8d6d}, {0x1919af28, 0xba0ecdf0}, {0x19293f29, 0xdc070ec5}, {0x1939af29, 0xdc0f4f99}, {0x30000000, 0x0}, {0x30000000, 0x0}, {0x30000000, 0x0}, {0x30000000, 0x0}, {0x30000000, 0x0}, {0x30000000, 0x0}},
    {{0x2805000, 0x500000}, {0x2875601, 0x1504081}, {0x28e5403, 0x250c123}, {0x2955205, 0x35141c5}, {0x2a485431, 0x5482822b}, {0x186a2323, 0x310002a5}, {0x9b1606, 0x4118355}, {0x187a3f23, 0x31044418}, {0xa21408, 0x512049a}, {0x188a5b23, 0x3104858c}, {0x16a2c0a, 0x62a860a}, {0x189a7723, 0x3108c6d7}, {0x2b1520c, 0x7530734}, {0x234400d, 0x84347a9}, {0x18aa9323, 0x3109081d}, {0x3b9720e, 0x8738884}, {0x18baaf23, 0x310d4962}, {0x18cacb23, 0x310d8a12}, {0x18dacb25, 0x750dcab5}, {0x18ea4627, 0x98060b58}, {0x18fab627, 0x980e4c1c}, {0x190a4628, 0xba068d0e}, {0x191ab628, 0xba0ecdfd}, {0x192a4629, 0xdc070ed2}, {0x193ab629, 0xdc0f4fa6}, {0x30000000, 0x0}, {0x30000000, 0x0}, {0x30000000, 0x0}, {0x30000000, 0x0}, {0x30000000, 0x0}, {0x30000000, 0x0}, {0x30000000, 0x0}},
    {{0x2c05800, 0x580000}, {0x2c75e01, 0x1584082}, {0x2ce5c03, 0x258c124}, {0x2d55a05, 0x35941c6}, {0x2a495432, 0x55828237}, {0x186b2324, 0x200002bc}, {0x21b4606, 0x4418366}, {0x187b3f24, 0x20044430}, {0x3226408, 0x56204b7}, {0x188b5b24, 0x200485a3}, {0x3ea7c0a, 0x67a8622}, {0x189b7724, 0x2008c6eb}, {0x2a87a134, 0xa4864742}, {0x3b4700d, 0x87347b8}, {0x18ab9324, 0x20090831}, {0x1ba340e, 0x9338898}, {0x18bbaf24, 0x200d4977}, {0x18cbcb24, 0x200d8a1c}, {0x18dbcb26, 0x640dcabf}, {0x18eb4d27, 0x98060b62}, {0x18fbbd27, 0x980e4c2b}, {0x190b4d28, 0xba068d1e}, {0x191bbd28, 0xba0ece0b}, {0x192b4d29, 0xdc070edf}, {0x193bbd29, 0xdc0f4fb4}, {0x30000000, 0x0}, {0x30000000, 0x0}, {0x30000000, 0x0}, {0x30000000, 0x0}, {0x30000000, 0x0}, {0x30000000, 0x0}, {0x30000000, 0x0}},
    {{0x3006000, 0x600000}, {0x3076601, 0x1604084}, {0x30e6403, 0x260c126}, {0x3156205, 0x36141c8}, {0x2a4a5b31, 0x5b828242}, {0x186c0025, 0x750002d3}, {0x3db7e06, 0x4798379}, {0x187c1c25, 0x75004447}, {0x1e33e08, 0x53a04d5}, {0x188c3825, 0x750485ba}, {0x1ab360a, 0x6328635}, {0x189c5425, 0x7504c700}, {0x132240c, 0x723074d}, {0xf51a0d, 0x81b47c5}, {0x18ac7025, 0x75090845}, {0xbb160e, 0x91388b6}, {0x18bc8c25, 0x75094983}, {0x18cca825, 0x750d8a26}, {0x18dcd225, 0x750dcac9}, {0x18ec5427, 0x98060b6c}, {0x2addcb36, 0xd08bcbd3}, {0x18fcc427, 0x980e4c3a}, {0x190c5428, 0xba068d2d}, {0x191cc428, 0xba0ece18}, {0x192c5429, 0xdc070eed}, {0x193cc429, 0xdc0f4fc1}, {0x30000000, 0x0}, {0x30000000, 0x0}, {0x30000000, 0x0}, {0x30000000, 0x0}, {0x30000000, 0x0}, {0x30000000, 0x0}},
    {{0x3406800, 0x680000}, {0x3476e01, 0x1684085}, {0x34e6c03, 0x268c127}, {0x3556a05, 0x36941c9}, {0x2a4b5b32, 0x5c82824e}, {0x186d0026, 0x640002eb}, {0x11c2007, 0x421c389}, {0x187d1c26, 0x6400445e}, {0x3a37608, 0x57204eb}, {0x188d3826, 0x640485ce}, {0x32b660a, 0x6628644}, {0x189d5426, 0x6404c714}, {0x2724c0c, 0x74b075a}, {0x235420d, 0x84347d1}, {0x18ad7026, 0x6409085a}, {0x2fb5e0e, 0x95b88cd}, {0x18bd8c26, 0x6409498e}, {0x18cda826, 0x640d8a30}, {0x18ddd226, 0x640dcad3}, {0x18ed5b27, 0x98060b76}, {0x2aded236, 0xd78bcbe3}, {0x18fdcb27, 0x980e4c49}, {0x190d5b28, 0xba068d3c}, {0x191dcb28, 0xba0ece25}, {0x192d5b29, 0xdc070efa}, {0x193dcb29, 0xdc0f4fce}, {0x30000000, 0x0}, {0x30000000, 0x0}, {0x30000000, 0x0}, {0x30000000, 0x0}, {0x30000000, 0x0}, {0x30000000, 0x0}},
    {{0x3807000, 0x700000}, {0x3877601, 0x1704087}, {0x38e7403, 0x270c129}, {0x3957205, 0x37141cb}, {0x2a4c3833, 0x3a82c25a}, {0x186e0725, 0x75000302}, {0x25c4807, 0x449c397}, {0x187e2325, 0x75004475}, {0xe41809, 0x51a44f9}, {0x188e3f25, 0x750485e3}, {0xac100b, 0x712c654}, {0x189e5b25, 0x7504c728}, {0xf31e0c, 0x81b0773}, {0x136240d, 0x82347f0}, {0x18ae7725, 0x7509086e}, {0x1bc300f, 0x933c8e9}, {0x18be9325, 0x75094998}, {0x18ceaf25, 0x750d8a3b}, {0x18ded925, 0x750dcadd}, {0x18ee6227, 0x98060b80}, {0x18fed227, 0x980e4c58}, {0x2aee6237, 0x688cccd5}, {0x190e6228, 0xba068d4b}, {0x191ed228, 0xba0ece33}, {0x192e6229, 0xdc070f07}, {0x193ed229, 0xdc0f4fdc}, {0x30000000, 0x0}, {0x30000000, 0x0}, {0x30000000, 0x0}, {0x30000000, 0x0}, {0x30000000, 0x0}, {0x30000000, 0x0}},
    {{0x3c07800, 0x780000}, {0x3c77e01, 0x1784088}, {0x3ce7c03, 0x278c12a}, {0x3d57a05, 0x37941cc}, {0x2a4d3834, 0x3b82c265}, {0x186f0726, 0x64000319}, {0x2a5d5434, 0x5783c3aa}, {0x187f2326, 0x6400448d}, {0x2a45009, 0x552450e}, {0x188f3f26, 0x640485f7}, {0x22c400b, 0x742c663}, {0x189f5b26, 0x6404c73d}, {0x333660c, 0x863078a}, {0x18af7726, 0x64090882}, {0x37b6e0e, 0x96b88d2}, {0xbe140f, 0x913c931}, {0x18bf9326, 0x640949a2}, {0x18cfaf26, 0x640d8a45}, {0x18dfd926, 0x640dcae8}, {0x18ef6927, 0x98060b8a}, {0x18ffd927, 0x980e4c67}, {0x2aef6937, 0x6f8ccce5}, {0x190f6928, 0xba068d5a}, {0x191fd928, 0xba0ece40}, {0x192f6929, 0xdc070f14}, {0x193fd929, 0xdc0f4fe9}, {0x30000000, 0x0}, {0x30000000, 0x0}, {0x30000000, 0x0}, {0x30000000, 0x0}, {0x30000000, 0x0}, {0x30000000, 0x0}},
    {{0x10200, 0x0}, {0x80002, 0x100808a}, {0xf0603, 0x200c12c}, {0x160405, 0x30141ce}, {0x1940002a, 0x3100022a}, {0x1172605, 0x42142a1}, {0x19502a2a, 0x31004335}, {0x1dd3a07, 0x439c3bf}, {0x1960462a, 0x310484a8}, {0xa51209, 0x6124525}, {0x1970622a, 0x3104c60f}, {0x2a7d8c34, 0x8f85c676}, {0x19807e2a, 0x31090755}, {0x1b4300d, 0x83347a4}, {0x1f73e0d, 0x83b481f}, {0x19909a2a, 0x3109489a}, {0x3fc780f, 0x97bc8ff}, {0x19a0b62a, 0x310d89ad}, {0x19b0d22a, 0x310dca50}, {0x2ac00036, 0x58a0aa3}, {0x19c0002e, 0x98020af3}, {0x19d0702e, 0x980a4b96}, {0x19e0002f, 0xba028c78}, {0x19f0702f, 0xba0acd6b}, {0x1a000030, 0xdc030e4f}, {0x1a107030, 0xdc0b4f24}, {0x30000000, 0x0}, {0x30000000, 0x0}, {0x30000000, 0x0}, {0x30000000, 0x0}, {0x30000000, 0x0}, {0x30000000, 0x0}},
    {{0x410a00, 0x80000}, {0x480802, 0x108808b}, {0x4f0e03, 0x208c12d}, {0x560c05, 0x30941cf}, {0x1941002b, 0x20000235}, {0x2975605, 0x45142b2}, {0x19512a2b, 0x2000434c}, {0x35d6a07, 0x469c3d1}, {0x1a03008, 0x5320448}, {0x1961462b, 0x200484bf}, {0x3a57209, 0x6724548}, {0x1971622b, 0x2004c623}, {0x1ed3a0b, 0x73ac688}, {0x19817e2b, 0x20090769}, {0x2a8faf34, 0xb286c7e5}, {0x19919a2b, 0x200948af}, {0x17d2a0f, 0x92bc910}, {0x19a1b62b, 0x200d89b7}, {0x19b1d22b, 0x200dca5a}, {0x2ac10736, 0xc8a0aad}, {0x19c1072e, 0x98020afd}, {0x19d1772e, 0x980a4ba0}, {0x19e1072f, 0xba028c88}, {0x19f1772f, 0xba0acd7b}, {0x1a010730, 0xdc030e5c}, {0x1a117730, 0xdc0b4f31}, {0x30000000, 0x0}, {0x30000000, 0x0}, {0x30000000, 0x0}, {0x30000000, 0x0}, {0x30000000, 0x0}, {0x30000000, 0x0}},
    {{0x811200, 0x100000}, {0x881002, 0x110808c}, {0x8f1603, 0x210c12e}, {0x961405, 0x31141d0}, {0x1942072a, 0x31000241}, {0x180006, 0x40182c4}, {0x1952312a, 0x31004363}, {0xde1c07, 0x519c3e3}, {0x19624d2a, 0x310484d7}, {0x3256209, 0x6624542}, {0x1a8300a, 0x63285bb}, {0x1972692a, 0x3104c638}, {0x2a7f9334, 0x9685c69f}, {0x1982852a, 0x3109077d}, {0x2a90d231, 0xd28707f9}, {0x1992a12a, 0x310948c3}, {0x33d620f, 0x963c921}, {0x19a2bd2a, 0x310d89c2}, {0x19b2d92a, 0x310dca65}, {0x2ac20e36, 0x138a0ab7}, {0x19c20e2e, 0x98020b07}, {0x19d27e2e, 0x980a4baa}, {0x19e20e2f, 0xba028c97}, {0x19f27e2f, 0xba0acd8a}, {0x1a020e30, 0xdc030e6a}, {0x1a127e30, 0xdc0b4f3e}, {0x30000000, 0x0}, {0x30000000, 0x0}, {0x30000000, 0x0}, {0x30000000, 0x0}, {0x30000000, 0x0}, {0x30000000, 0x0}},
    {{0xc11a00, 0x180000}, {0xc81802, 0x118808e}, {0xcf1e03, 0x218c130}, {0xd61c05, 0x31941d2}, {0x1943072b, 0x2000024d}, {0x1d83806, 0x43982d6}, {0x1953312b, 0x2000437a}, {0x25e4c07, 0x549c3f4}, {0x1212208, 0x5220471}, {0x19634d2b, 0x200484ee}, {0x3666c09, 0x66a4573}, {0x1973692b, 0x2004c64c}, {0x26e4c0b, 0x74ac6b7}, {0x1983852b, 0x20090792}, {0x2a91d232, 0xd387080d}, {0x1993a12b, 0x200948d8}, {0x17e2c0f, 0x92bc938}, {0x19a3bd2b, 0x200d89cc}, {0x19b3d92b, 0x200dca6f}, {0x2ac31536, 0x1a8a0ac1}, {0x19c3152e, 0x98020b12}, {0x19d3852e, 0x980a4bb4}, {0x19e3152f, 0xba028ca6}, {0x19f3852f, 0xba0acd99}, {0x1a031530, 0xdc030e77}, {0x1a138530, 0xdc0b4f4b}, {0x30000000, 0x0}, {0x30000000, 0x0}, {0x30000000, 0x0}, {0x30000000, 0x0}, {0x30000000, 0x0}, {0x30000000, 0x0}},
    {{0x1012200, 0x200000}, {0x1082002, 0x120808f}, {0x10f2603, 0x220c131}, {0x1162405, 0x32141d3}, {0x19440e2a, 0x31000258}, {0x3586806, 0x46982e9}, {0x19540e2c, 0x75004392}, {0x2a617e32, 0x7f840407}, {0x2e15a08, 0x55a0485}, {0x19642a2c, 0x75008505}, {0xe71e09, 0x61a4585}, {0x1974462c, 0x7504c660}, {0xef1e0b, 0x71ac6d0}, {0x1984622c, 0x750507a6}, {0x2a92d931, 0xd9870822}, {0x19947e2c, 0x750948ec}, {0x37e6c0f, 0x96bc94d}, {0x19a49a2c, 0x750989d6}, {0x2ab48c35, 0x90894a29}, {0x19b4b62c, 0x750dca79}, {0x19c41c2e, 0x98020b1c}, {0x19d48c2e, 0x980a4bc2}, {0x19e41c2f, 0xba028cb5}, {0x19f48c2f, 0xba0acda8}, {0x1a041c30, 0xdc030e84}, {0x1a148c30, 0xdc0b4f59}, {0x30000000, 0x0}, {0x30000000, 0x0}, {0x30000000, 0x0}, {0x30000000, 0x0}, {0x30000000, 0x0}, {0x30000000, 0x0}},
    {{0x1412a00, 0x280000}, {0x1482802, 0x1288091}, {0x14f2e03, 0x228c133}, {0x1562c05, 0x32941d5}, {0x19450e2b, 0x20000264}, {0xd91a06, 0x41982fb}, {0x19550e2d, 0x640043a9}, {0x19f3607, 0x531c41a}, {0x19652a2d, 0x6400851c}, {0x2a719a32, 0x9b85057b}, {0x3a9720a, 0x67285f8}, {0x1975462d, 0x6404c675}, {0x2ef5e0b, 0x75ac6e5}, {0x1985622d, 0x640507bb}, {0x3b7760d, 0x8734832}, {0x1fa3c0e, 0x93b8899}, {0x19957e2d, 0x64094900}, {0x1bf360f, 0x933c964}, {0x19a59a2d, 0x640989e0}, {0x19b5b62d, 0x640dca83}, {0x19c5232e, 0x98020b26}, {0x19d5932e, 0x980a4bd2}, {0x19e5232f, 0xba028cc4}, {0x19f5932f, 0xba0acdb7}, {0x1a052330, 0xdc030e91}, {0x1a159330, 0xdc0b4f66}, {0x30000000, 0x0}, {0x30000000, 0x0}, {0x30000000, 0x0}, {0x30000000, 0x0}, {0x30000000, 0x0}, {0x30000000, 0x0}},
    {{0x1813200, 0x300000}, {0x1883002, 0x1308092}, {0x18f3603, 0x230c134}, {0x1963405, 0x33141d6}, {0x1946152a, 0x3100026f}, {0x2594a06, 0x449830c}, {0x1956152c, 0x750043c0}, {0x31f6607, 0x561c42b}, {0x1966312c, 0x75008533}, {0x1e73e09, 0x63a458f}, {0x1aa340a, 0x632860d}, {0x19764d2c, 0x7504c689}, {0x70080c, 0x70b06f4}, {0x1986692c, 0x750507cf}, {0xb8100e, 0x813883c}, {0x1996852c, 0x75094915}, {0xbf160f, 0x913c959}, {0x19a6a12c, 0x750989ea}, {0x2ab69a35, 0x9e894a3d}, {0x19b6bd2c, 0x750dca8d}, {0x19c62a2e, 0x98020b30}, {0x19d69a2e, 0x980a4be1}, {0x19e62a2f, 0xba028cd4}, {0x19f69a2f, 0xba0acdc6}, {0x1a062a30, 0xdc030e9f}, {0x1a169a30, 0xdc0b4f73}, {0x30000000, 0x0}, {0x30000000, 0x0}, {0x30000000, 0x0}, {0x30000000, 0x0}, {0x30000000, 0x0}, {0x30000000, 0x0}},
    {{0x1c13a00, 0x380000}, {0x1c83802, 0x1388094}, {0x1cf3e03, 0x238c136}, {0x1d63c05, 0x33941d8}, {0x1947152b, 0x2000027b}, {0x2a574d34, 0x5083431f}, {0x1957152d, 0x640043d7}, {0xa01008, 0x512043d}, {0x1967312d, 0x6400854b}, {0x2e75e09, 0x65a459c}, {0x32a640a, 0x662861c}, {0x19774d2d, 0x6404c69e}, {0x2a849a33, 0x9c864705}, {0x1987692d, 0x640507e3}, {0x178280e, 0x82b8844}, {0x7b0e0e, 0x90b88b4}, {0x1997852d, 0x64094929}, {0x19a7a12d, 0x640989f5}, {0x19b7bd2d, 0x640dca97}, {0x2ac73136, 0x368a4aea}, {0x19c7312e, 0x98020b3a}, {0x19d7a12e, 0x980a4bf0}, {0x19e7312f, 0xba028ce3}, {0x19f7a12f, 0xba0acdd6}, {0x1a073130, 0xdc030eac}, {0x1a17a130, 0xdc0b4f80}, {0x30000000, 0x0}, {0x30000000, 0x0}, {0x30000000, 0x0}, {0x30000000, 0x0}, {0x30000000, 0x0}, {0x30000000, 0x0}},
    {{0x2014200, 0x400000}, {0x2084002, 0x1408095}, {0x20f4603, 0x240c137}, {0x2164405, 0x34141d9}, {0x19481c2a, 0x31000287}, {0x5a0c06, 0x4098323}, {0x1958382a, 0x310443ee}, {0x1602808, 0x52a0445}, {0x1a33608, 0x53204d4}, {0x1968542a, 0x31048562}, {0xa9120a, 0x61285da}, {0x1978702a, 0x3108c6b2}, {0x3b0700c, 0x7730715}, {0x19888c2a, 0x310907f8}, {0x338600e, 0x8638856}, {0x1998a82a, 0x310d493d}, {0x3bf760f, 0x973c978}, {0x19a8c42a, 0x310d89ff}, {0x19b8c42c, 0x750dcaa2}, {0x2ac83836, 0x3d8a8af4}, {0x19c8382e, 0x98060b44}, {0x19d8a82e, 0x980e4bff}, {0x19e8382f, 0xba068cf2}, {0x19f8a82f, 0xba0ecde5}, {0x1a083830, 0xdc070eb9}, {0x1a18a830, 0xdc0f4f8e}, {0x30000000, 0x0}, {0x30000000, 0x0}, {0x30000000, 0x0}, {0x30000000, 0x0}, {0x30000000, 0x0}, {0x30000000, 0x0}},
    {{0x2414a00, 0x480000}, {0x2484802, 0x1488096}, {0x24f4e03, 0x248c138}, {0x2564c05, 0x34941da}, {0x19491c2b, 0x20000292}, {0xda1c06, 0x4198329}, {0x1959382b, 0x20044406}, {0x3606808, 0x56a045d}, {0x3636e08, 0x56a04e8}, {0x1969542b, 0x20048579}, {0x3696a0a, 0x66a85f6}, {0x1979702b, 0x2008c6c6}, {0x131220c, 0x7230724}, {0x19898c2b, 0x2009080c}, {0x139220e, 0x823886a}, {0x1999a82b, 0x200d4952}, {0x2aa83835, 0x3c8889af}, {0x19a9c42b, 0x200d8a09}, {0x2ab9af35, 0xb3898a5c}, {0x19b9c42d, 0x640dcaac}, {0x19c93f2e, 0x98060b4f}, {0x19d9af2e, 0x980e4c0e}, {0x19e93f2f, 0xba068d01}, {0x19f9af2f, 0xba0ecdf2}, {0x1a093f30, 0xdc070ec7}, {0x1a19af30, 0xdc0f4f9b}, {0x30000000, 0x0}, {0x30000000, 0x0}, {0x30000000, 0x0}, {0x30000000, 0x0}, {0x30000000, 0x0}, {0x30000000, 0x0}},
    {{0x2815200, 0x500000}, {0x2885002, 0x1508098}, {0x28f5603, 0x250c13a}, {0x2965405, 0x35141dc}, {0x194a232a, 0x310002a9}, {0x2a587031, 0x70838336}, {0x195a3f2a, 0x3104441d}, {0x1a13208, 0x5320477}, {0x1242009, 0x52244fc}, {0x196a5b2a, 0x31048590}, {0x1ea3c0a, 0x63a860e}, {0x197a772a, 0x3108c6db}, {0x2f15a0c, 0x75b0736}, {0x274480d, 0x84b47ab}, {0x198a932a, 0x31090820}, {0x3f97a0e, 0x87b8885}, {0x199aaf2a, 0x310d4966}, {0x19aacb2a, 0x310d8a13}, {0x19bacb2c, 0x750dcab6}, {0x2aca4636, 0x4b8a8b09}, {0x19ca462e, 0x98060b59}, {0x19dab62e, 0x980e4c1d}, {0x19ea462f, 0xba068d10}, {0x19fab62f, 0xba0ecdff}, {0x1a0a4630, 0xdc070ed4}, {0x1a1ab630, 0xdc0f4fa8}, {0x30000000, 0x0}, {0x30000000, 0x0}, {0x30000000, 0x0}, {0x30000000, 0x0}, {0x30000000, 0x0}, {0x30000000, 0x0}},
    {{0x2c15a00, 0x580000}, {0x2c85802, 0x1588099}, {0x2cf5e03, 0x258c13b}, {0x2d65c05, 0x35941dd}, {0x194b232b, 0x200002c1}, {0x3da7c06, 0x479834a}, {0x195b3f2b, 0x20044434}, {0x3e17a08, 0x57a048f}, {0x2e45809, 0x55a4511}, {0x196b5b2b, 0x200485a7}, {0x2a79a832, 0xa9858625}, {0x197b772b, 0x2008c6ef}, {0x32040c, 0x7030743}, {0x3f4780d, 0x87b47b9}, {0x198b932b, 0x20090835}, {0x23a440e, 0x943889d}, {0x199baf2b, 0x200d497a}, {0x19abcb2b, 0x200d8a1d}, {0x19bbcb2d, 0x640dcac0}, {0x2acb4d36, 0x528a8b13}, {0x19cb4d2e, 0x98060b63}, {0x19dbbd2e, 0x980e4c2d}, {0x19eb4d2f, 0xba068d1f}, {0x19fbbd2f, 0xba0ece0d}, {0x1a0b4d30, 0xdc070ee1}, {0x1a1bbd30, 0xdc0f4fb6}, {0x30000000, 0x0}, {0x30000000, 0x0}, {0x30000000, 0x0}, {0x30000000, 0x0}, {0x30000000, 0x0}, {0x30000000, 0x0}},
    {{0x3016200, 0x600000}, {0x3086002, 0x160809b}, {0x30f6603, 0x260c13d}, {0x3166405, 0x36141df}, {0x194c002c, 0x750002d8}, {0x15b2e06, 0x429835d}, {0x195c1c2c, 0x7500444b}, {0x2a688c31, 0x8c8484aa}, {0xe51a09, 0x61a4528}, {0x196c382c, 0x750485be}, {0x1eb3e0a, 0x63a8637}, {0x3ed7a0b, 0x77ac69c}, {0x197c542c, 0x7504c703}, {0x133260c, 0x8230776}, {0x198c702c, 0x75090849}, {0x13b260e, 0x92388bc}, {0x199c8c2c, 0x75094985}, {0x19aca82c, 0x750d8a27}, {0x19bcd22c, 0x750dcaca}, {0x2acc5436, 0x598acb1d}, {0x19cc542e, 0x98060b6d}, {0x19dcc42e, 0x980e4c3c}, {0x19ec542f, 0xba068d2f}, {0x19fcc42f, 0xba0ece1a}, {0x1a0c5430, 0xdc070eee}, {0x1a1cc430, 0xdc0f4fc3}, {0x30000000, 0x0}, {0x30000000, 0x0}, {0x30000000, 0x0}, {0x30000000, 0x0}, {0x30000000, 0x0}, {0x30000000, 0x0}},
    {{0x3416a00, 0x680000}, {0x3486802, 0x168809c}, {0x34f6e03, 0x268c13e}, {0x3566c05, 0x36941e0}, {0x194d002d, 0x640002ef}, {0x2db5e06, 0x459836f}, {0x195d1c2d, 0x64004462}, {0x630e08, 0x50a04c5}, {0x2654a09, 0x64a4539}, {0x196d382d, 0x640485d2}, {0x36b6e0a, 0x66a8647}, {0x197d542d, 0x6404c718}, {0x2f25c0c, 0x75b075f}, {0x2f55a0d, 0x85b47d9}, {0x198d702d, 0x6409085d}, {0x3bb760e, 0x97388d5}, {0x199d8c2d, 0x6409498f}, {0x2aad5b35, 0x5f88c9e1}, {0x19ada82d, 0x640d8a32}, {0x19bdd22d, 0x640dcad4}, {0x19cd5b2e, 0x98060b77}, {0x19ddcb2e, 0x980e4c4b}, {0x19ed5b2f, 0xba068d3e}, {0x19fdcb2f, 0xba0ece27}, {0x1a0d5b30, 0xdc070efc}, {0x1a1dcb30, 0xdc0f4fd0}, {0x30000000, 0x0}, {0x30000000, 0x0}, {0x30000000, 0x0}, {0x30000000, 0x0}, {0x30000000, 0x0}, {0x30000000, 0x0}},
    {{0x3817200, 0x700000}, {0x3887002, 0x170809e}, {0x38f7603, 0x270c140}, {0x3967405, 0x37141e2}, {0x2a4e3f33, 0x4182c271}, {0x194e072c, 0x75000306}, {0x29c5007, 0x451c39a}, {0x195e232c, 0x7500447a}, {0x1642809, 0x52a44ff}, {0x196e3f2c, 0x750485e6}, {0xec180b, 0x71ac656}, {0x197e5b2c, 0x7504c72c}, {0x1732e0c, 0x82b0778}, {0x198e772c, 0x75090872}, {0x1bb360e, 0x93388c1}, {0x2fd5a0f, 0x95bc91f}, {0x199e932c, 0x75094999}, {0x19aeaf2c, 0x750d8a3c}, {0x2abed235, 0xd689ca8f}, {0x19bed92c, 0x750dcadf}, {0x19ce622e, 0x98060b82}, {0x19ded22e, 0x980e4c5a}, {0x19ee622f, 0xba068d4d}, {0x19fed22f, 0xba0ece34}, {0x1a0e6230, 0xdc070f09}, {0x1a1ed230, 0xdc0f4fdd}, {0x30000000, 0x0}, {0x30000000, 0x0}, {0x30000000, 0x0}, {0x30000000, 0x0}, {0x30000000, 0x0}, {0x30000000, 0x0}},
    {{0x3c17a00, 0x780000}, {0x3c87802, 0x178809f}, {0x3cf7e03, 0x278c141}, {0x3d67c05, 0x37941e3}, {0x2a4f3f34, 0x4282c27c}, {0x194f072d, 0x6400031d}, {0x1d0207, 0x401c3ac}, {0x195f232d, 0x64004491}, {0x3246009, 0x5624513}, {0x196f3f2d, 0x640485fb}, {0x26c480b, 0x74ac666}, {0x197f5b2d, 0x6404c740}, {0x3b3760c, 0x873078f}, {0x198f772d, 0x64090886}, {0x3fb7e0e, 0x97b88d6}, {0x13e240f, 0x923c936}, {0x199f932d, 0x640949a3}, {0x19afaf2d, 0x640d8a46}, {0x2abfd935, 0xdd89ca99}, {0x19bfd92d, 0x640dcae9}, {0x19cf692e, 0x98060b8c}, {0x19dfd92e, 0x980e4c69}, {0x19ef692f, 0xba068d5c}, {0x19ffd92f, 0xba0ece42}, {0x1a0f6930, 0xdc070f16}, {0x1a1fd930, 0xdc0f4feb}, {0x30000000, 0x0}, {0x30000000, 0x0}, {0x30000000, 0x0}, {0x30000000, 0x0}, {0x30000000, 0x0}, {0x30000000, 0x0}}
}};
static_assert(NJOB + NCONV == 32, "");

__device__ __forceinline__ unsigned read_back(const void* p) {
    unsigned v = 0;
    asm volatile("ld.relaxed.gpu.global.u32 %0, [%1];" : "=r"(v) : "l"(p) : "memory");
    return v;
}
__device__ __forceinline__ void publish(unsigned* flag, unsigned seen, unsigned zero) {
    asm volatile("{\n.reg .pred p;\n.reg .u32 t;\nredux.sync.or.b32 t, %1, 0xffffffff;\nand.b32 t, t, %2;\nadd.u32 t, t, 1;\n"
                 "elect.sync _|p, 0xffffffff;\n@p red.relaxed.gpu.global.add.u32 [%0], t;\n}" :: "l"(flag), "r"(seen), "r"(zero) : "memory");
}

__device__ __forceinline__ uint32_t zero_term(const unsigned (&sv)[4], float zxf) {
    int lo = 0, hi = 0;
#pragma unroll
    for (int h = 0; h < 4; h++) {
        const int l = (int)(short)(sv[h] & 0xFFFF);
        lo += l; hi += ((int)(sv[h] - (unsigned)l)) >> 16;
    }
    const float fl = __bfloat162float(__float2bfloat16_rn((float)lo)) * zxf, fh = __bfloat162float(__float2bfloat16_rn((float)hi)) * zxf;
    uint32_t z;
    asm("cvt.rn.bf16x2.f32 %0, %1, %2;" : "=r"(z) : "f"(fh), "f"(fl));
    return z;
}

__device__ __forceinline__ void load_x(Scratch* scr, uint32_t sb, int b, int lane) {
    const uint32_t bars = sb + SM_BAR;
    const int r = b & 15;
    const unsigned tgt = (*(volatile unsigned*)&scr->epoch[b] + 1) * 4;
    const unsigned* f = scr->flag + r * FS + (lane & 15);
    unsigned todo = 0xFFFF, v = ld_flag(f);
    asm volatile("barrier.cluster.wait.aligned;" ::: "memory");
#pragma unroll 1
    for (int it = 0; todo; it++) {
        unsigned m = __ballot_sync(~0u, (int)(v - tgt) >= 0) & todo;
        v = ld_flag(f);
        todo &= ~m;
        while (m) {
            const int sl = __ffs(m) - 1;
            m &= m - 1;
            if (elect_one()) {
                asm volatile("cp.async.bulk.shared::cluster.global.mbarrier::complete_tx::bytes [%0], [%1], %2, [%3];"
                             :: "r"(sb + SM_A + sl * 8192), "l"((const char*)scr->a8 + (r * 16 + sl) * 8192),
                                "r"(8192), "r"(bars + (B_FULL + sl) * 8) : "memory");
            }
        }
        if (it > (1 << 20)) __trap();
    }
}

__device__ __forceinline__ void store_out(const CUtensorMap* map, uint32_t sb, int b, int agent, int lane) {
    const uint32_t bars = sb + SM_BAR;
    const int r = b & 15, c = b >> 4;
    const uint32_t buf = sb + SM_OUT + agent * 4096, full = bars + (B_OFULL + agent) * 8;
    const int row = r * 128 + agent * 32;
#pragma unroll 1
    for (int t = 0; t < 7; t++) {
        asm volatile("{\n.reg .pred p;\n.reg .u32 c;\nmov.u32 c, 0;\n"
                     "WAIT_LOOP:\n"
                     "mbarrier.try_wait.parity.shared::cta.b64 p, [%4], %5;\n"
                     "@p bra WAIT_DONE;\n"
                     "add.u32 c, c, 1;\nsetp.lt.u32 p, c, 0x100000;\n"
                     "@p bra WAIT_LOOP;\n"
                     "trap;\n"
                     "WAIT_DONE:\n"
                     "fence.proxy.async.shared::cta;\n"
                     "elect.sync _|p, 0xffffffff;\n"
                     "@p cp.async.bulk.tensor.2d.global.shared::cta.tile.bulk_group [%0, {%1, %2}], [%3];\n"
                     "cp.async.bulk.commit_group;\n}"
                     :: "l"(map), "r"(c * TN + (((agent < 2 ? 0x6534120 : 0x6541230) >> (t * 4)) & 7) * 64), "r"(row), "r"(buf), "r"(full), "r"(t & 1) : "memory");
        asm volatile("cp.async.bulk.wait_group.read 0;" ::: "memory");
        if (t < 6 && elect_one()) mbar_arrive(bars + (B_OFREE + t * 4 + 4 + agent) * 8);
    }
}

template <int V> struct I { static constexpr int v = V; };
template <bool SIDE>
__device__ __forceinline__ void consume(Scratch* scr, const __nv_bfloat16* __restrict__ scale_w, const __nv_bfloat16* __restrict__ bias,
                                        const __nv_bfloat16* __restrict__ scale_x, uint32_t sb, int b, int warp, int lane) {
    constexpr int NR = NRING;
    const uint32_t bars = sb + SM_BAR;
    const int c = b >> 4;
    constexpr uint32_t SD = 0x400 >> 4;
    if ((sb & 0xFFFFFF) != 0x400) __trap();
    const int wg = warp >> 2;
    const unsigned short sxr = __ldg((const unsigned short*)scale_x);
    const uint32_t sx2 = (uint32_t)sxr * 0x10001u;
    const int c0 = (warp & 3) * 16 + (lane >> 2) * 2;
    uint32_t sw[4], bi[4];
#pragma unroll
    for (int i = 0; i < 4; i++) {
        const int col = c * TN + (i < 2 ? wg * 2 + i : i == 2 ? 4 + wg : 6) * 64 + c0;
        sw[i] = __ldg((const uint32_t*)(scale_w + col));
        bi[i] = __ldg((const uint32_t*)(bias + col));
    }
    const uint32_t st0 = sb + SM_OUT + (lane & 3) * 256 + (((c0 >> 3) ^ ((lane & 3) * 2)) << 4) + (c0 & 7) * 2;
    constexpr uint32_t DX0 = (SD + (SM_A >> 4)) | (1 << 16), DW0 = (SD + (SM_RING >> 4)) | (8 << 16);
    asm volatile("barrier.cluster.wait.aligned;" ::: "memory");
    int a0[64], a1[64];
    constexpr int MUL = SIDE ? 4 : 2, NONE = 64 * MUL, BIAS = NR + 64 - NG;
    const uint32_t go = mapa(bars + B_GO * 8, lane & (SIDE ? 1 : 15)) - (64 - NG) * MUL;
    const int key = SIDE ? (lane < 2 ? lane * 4 : 1) : (lane < 16 ? (lane >> 2) * 2 : 1);
    int pend = NONE;
    uint32_t bb = bars + (B_FULL + wg * 16) * 8;
#define RELEASE() { if ((pend & (NONE + 8 - MUL)) == key) mbar_arrive_cluster(go + (pend & ~7)); }
    struct Par { uint32_t a, b, c, d; };
    auto load_par = [&](int blk, uint32_t swv, uint32_t biv) {
        mbar_wait_cluster(bars + (B_PAR + blk) * 8);
        const uint32_t zc = lds32(sb + SM_PAR + (blk * 64 + c0) * 2);
        const float sxf = __uint_as_float(sx2 << 16);
        const float s0 = sxf * __uint_as_float(swv << 16), s1 = sxf * __uint_as_float(swv & 0xFFFF0000u);
        Par P = {__float_as_uint(s0), __float_as_uint(s1), __float_as_uint(fmaf(-__uint_as_float(zc << 16), s0, __uint_as_float(biv << 16))),
                 __float_as_uint(fmaf(-__uint_as_float(zc & 0xFFFF0000u), s1, __uint_as_float(biv & 0xFFFF0000u)))};
        asm volatile("" : "+r"(P.a), "+r"(P.b), "+r"(P.c), "+r"(P.d));
        return P;
    };
    auto drain = [&](int (&a)[64], auto Q, int t, const Par& P) {
#pragma unroll
        for (int q = Q.v; q < Q.v + 2; q++) {
#pragma unroll
            for (int j = 0; j < 8; j++) {
                const int o = q * 16 + (j >> 1) * 4 + (j & 1);
                asm("cvt.rn.f32.s32 %0, %0;\n\tcvt.rn.f32.s32 %1, %1;\n\tfma.rn.f32 %0, %0, %2, %4;\n\tfma.rn.f32 %1, %1, %3, %5;\n\t"
                    "cvt.rn.bf16x2.f32 %0, %1, %0;" : "+r"(a[o]), "+r"(a[o + 2]) : "r"(P.a), "r"(P.b), "r"(P.c), "r"(P.d));
            }
            mbar_wait(bars + (B_OFREE + t * 4 + q) * 8);
#pragma unroll
            for (int j = 0; j < 8; j++) sts32((st0 ^ ((j & 1) * 16)) + q * 4096 + (j >> 1) * 1024 + (j & 1) * 128, a[q * 16 + (j >> 1) * 4 + (j & 1)]);
            __syncwarp();
            if (lane == 0) mbar_arrive(bars + (B_OFULL + q) * 8);
        }
    };
    wg_fence();
    {
        uint32_t tbl = wg ? STEPS1 : STEPS0;
        uint32_t ba = bars + B_FULL * 8;
        int u = MUL * (wg * D_ + BIAS);
        uint32_t dw = DW0 + wg * D_ * 512;
        static_assert(D_ < NR, "");
        mbar_wait2(ba, bb);
#pragma unroll 1
        for (uint32_t dx = DX0;;) {
            mma_unit2(a0, a1, dw, dx, dx - DX0);
            dx += 512; ba += 8; bb += 8;
            const bool ready = mbar_test2(ba, bb);
            wg_wait<1>();
            RELEASE()
            pend = u;
            if (dx == DX0 + 16 * 512) break;
            u += MUL + (tbl & 1) * MUL;
            dw += 512 + (tbl & 1) * 512;
            if (dw >= DW0 + NR * 512) dw -= NR * 512;
            tbl >>= 1;
            if (!ready && !mbar_test2(ba, bb)) {
                wg_wait<0>();
                RELEASE()
                pend = NONE;
                mbar_wait2(ba, bb);
            }
        }
    }
    Par P0 = load_par(2 * wg, sw[0], bi[0]);
    const Par P1 = load_par(2 * wg + 1, sw[1], bi[1]);
    wg_wait<0>();
    RELEASE()
#pragma unroll 1
    for (int ph = 0; ph < 3; ph++) {
        if (ph + wg == 1) drain(a1, I<2>(), 3 - 2 * wg, P1);
        drain(a0, I<0>(), wg ? 4 * ph + 1 : 3 * ph, P0);
        const int u0 = 32 + ph * 16 + wg * 8;
        uint32_t dw = DW0 + (ph ? 48 % NR : wg ? 40 % NR : 32 % NR) * 512;
        bb = bars + (B_FULL + u0) * 8;
        const bool first = mbar_test(bb);
        drain(a0, I<2>(), ph ? 2 * ph + 2 + wg : 2 * wg, P0);
        if (ph + wg == 2) break;
#define RELEASE2() { if ((pend & (NONE + 8 - 2 * MUL)) == (key & ~MUL)) mbar_arrive_cluster(go + (pend & ~7)); }
        static_assert(NR % 2 == 0, "");
        pend = NONE;
        if (!first) mbar_wait(bb);
        wg_fence();
#pragma unroll 1
        for (int n = 0;; n += 2) {
            RELEASE2()
            const bool ready = mma_pair(a0, dw, DX0 + n * 1024, n, bb + n * 8 + 16);
            wg_wait<1>();
            pend = n ? MUL * (u0 + BIAS + n - 2) : NONE;
            if (n == 6) break;
            dw += 1024;
            if (dw == DW0 + NR * 512) dw = DW0;
            if (!ready) {
                RELEASE2()
                pend = NONE;
                mbar_wait(bb + n * 8 + 16);
            }
        }
        RELEASE2()
        pend = MUL * (u0 + BIAS + 6);
        if (ph == 0) drain(a1, I<0>(), 2 + 2 * wg, P1);
        P0 = load_par(4 + 2 * ph + wg, ph ? sw[3] : sw[2], ph ? bi[3] : bi[2]);
        wg_wait<0>();
        RELEASE2()
    }
    if (threadIdx.x == 128) asm volatile("red.relaxed.gpu.global.add.u32 [%0], 1;" :: "l"(scr->epoch + b) : "memory");
}

__global__ void __cluster_dims__(CS, 1, 1) __launch_bounds__(512, 1)
w8a8_kernel(const char* __restrict__ qx, const char* __restrict__ qw, Scratch* scr, const JobTable* __restrict__ jobs, const __nv_bfloat16* __restrict__ scale_w,
            const __nv_bfloat16* __restrict__ bias, const __nv_bfloat16* __restrict__ scale_x, const int* __restrict__ zero_x,
            const __grid_constant__ CUtensorMap map) {
    extern __shared__ __align__(1024) unsigned char smem_raw[];
    const uint32_t sb = (uint32_t)__cvta_generic_to_shared(smem_raw);
    const uint32_t bars = sb + SM_BAR;
    const int warp = __shfl_sync(~0u, threadIdx.x >> 5, 0), lane = threadIdx.x & 31;
    const int b = blockIdx.x, r = b & 15, c = b >> 4;
    const unsigned t0 = clk() + CFG_PF0;
    if (warp < CFG_NINIT) {
#pragma unroll 1
        for (int w = warp; w < 8; w += CFG_NINIT) {
            if (elect_one()) {
                const uint32_t cnt = w < B_GO / 16 ? 1 : 4 * CS + 1;
#pragma unroll
                for (int i = 0; i < 16; i++) mbar_init(bars + (w * 16 + i) * 8, cnt);
            }
            __syncwarp();
            const int i = w * 16 + lane;
            if (lane < 16 && i < B_OFREE + NOUT) mbar_expect_tx(bars + i * 8, i >= B_AFREE ? 0 : i >= B_PAR ? 128 : w == 1 ? 8192 : 16384);
            if (w == B_GO / 16 && 4 * lane + (r >> 2) < NRING)
                asm volatile("mbarrier.arrive.shared::cta.b64 _, [%0], %1;" :: "r"(bars + i * 8), "r"(4 * CS) : "memory");
        }
        if (warp == (B_SUM / 16) % CFG_NINIT) {
            if (elect_one()) {
#pragma unroll
                for (int k = 0; k < NOUT; k++) mbar_init(bars + (B_OFULL + k) * 8, 4);
                mbar_init(bars + B_SUM * 8, r < 8 ? 1 : 3);
                mbar_expect_tx(bars + B_SUM * 8, r < 8 ? 32 * 64 : 30 * 64);
            }
        }
        asm volatile("fence.mbarrier_init.release.cluster;" ::: "memory");
    } else if (warp == 7) {
        asm volatile("st.shared.v2.b32 [%0], {%1, %1};" :: "r"(sb + SM_SUM + lane * 8), "r"(0) : "memory");
        asm volatile("fence.release.sync_restrict::shared::cta.cluster;" ::: "memory");
    } else if (warp == 9) {
        asm volatile("griddepcontrol.launch_dependents;");
        if (elect_one()) asm volatile("prefetch.tensormap [%0];" :: "l"(&map) : "memory");
    } else if (warp >= 14) {
        const char* pf = qx + (r * 128 + ((threadIdx.x >> 1) & 31)) * (K_ * 4) + (lane & 1) * 128;
        if (c >= 5) asm volatile("prefetch.global.L2 [%0];" :: "l"(pf + (c - 5) * (32 * K_ * 4)) : "memory");
        asm volatile("prefetch.global.L2 [%0];" :: "l"(pf + ((c + 2) & 3) * (32 * K_ * 4) + ((c + 2) >> 2) * 256) : "memory");
    }
    asm volatile("barrier.cluster.arrive.relaxed.aligned;" ::: "memory");

    if (warp >= 8) {
        asm volatile("setmaxnreg.dec.sync.aligned.u32 88;");
        int agent = -1;
        if (warp >= 16 - NCONV) {
            const int cw = warp - (16 - NCONV);
            const unsigned zero = blockIdx.y;
            const char* const gx = qx + (lane >> 4) * (K_ * 4) + (lane & 15) * 16;
            const char* const gw = qw + lane * 8;
            const int wrB = ((lane >> 3) * 32 + (lane & 7)) * 16;
            uint2 tab;
            asm volatile("ld.global.nc.v2.u32 {%0, %1}, [%2];" : "=r"(tab.x), "=r"(tab.y) : "l"(&jobs->e[b][lane]));
            bool synced = false;
#pragma unroll 1
            for (int p = cw || c >= 5 ? cw : NCONV;; p = p < CFG_PZ ? p + NCONV : p < CFG_PZ + 3 ? 31 : p + 3) {
                uint2 j;
                if (p < 4) {
                    const int g = 7 * p + c - 5;
                    j.x = ((r * 128 + (g & 3) * 32) * 16 + (g >> 2)) | (r * 64 + g) << 16;
                    j.y = max((p - 1) * (CFG_P0 / 4) + b * (CFG_P0 * 4 / NCTA) / 16, 0) | (r * FS + (g >> 2)) << 14 | p << 24;
                } else { j.x = __shfl_sync(~0u, tab.x, p); j.y = __shfl_sync(~0u, tab.y, p); }
                if (j.x >= 3u << 28) break;
                const int kind = j.x >> 28, sig = (j.y >> 14) & 0x3FF;
                char* tile = (char*)scr + ((j.x >> 16) & 0xFFF) * 2048;
                const char* g = (kind ? gw : gx) + (j.x & 0xFFFF) * 256;
                for (int rem; (rem = (int)(j.y & 0x3FFF) * 4 - (int)(clk() - t0)) > 0;) if (rem > CFG_SLEEP) __nanosleep(CFG_SLEEP / 4);
                if (kind == 0) {
                    uint4 v[16];
#pragma unroll
                    for (int i = 0; i < 16; i++)
                        asm volatile("ld.global.nc.L1::no_allocate.v4.b32 {%0,%1,%2,%3}, [%4];"
                                     : "=r"(v[i].x), "=r"(v[i].y), "=r"(v[i].z), "=r"(v[i].w) : "l"(g + i * (2 * K_ * 4)));
#pragma unroll
                    for (int i = 0; i < 16; i++)
                        asm volatile("st.global.b32 [%0], %1;" :: "l"(tile + ((lane * 4) ^ ((i & 3) * 16)) + i * 128),
                                     "r"(pack4(v[i].x, v[i].y, v[i].z, v[i].w)) : "memory");
                    asm volatile("fence.proxy.async.global;" ::: "memory");
                    __syncwarp();
                    publish(scr->flag + sig, read_back(tile + lane * 64), zero);
                } else {
                    uint2 v[32];
                    unsigned o[16];
#pragma unroll
                    for (int k = 0; k < 32; k++)
                        asm volatile("ld.global.nc.L1::no_allocate.v2.b32 {%0,%1}, [%2];" : "=r"(v[k].x), "=r"(v[k].y) : "l"(g + k * (N_ * 4)));
                    if (!synced) asm volatile("barrier.cluster.wait.aligned;" ::: "memory");
                    synced = true;
#pragma unroll
                    for (int i = 0; i < 8; i++) {
                        o[i] = pack4(v[4 * i].x, v[4 * i + 1].x, v[4 * i + 2].x, v[4 * i + 3].x);
                        o[8 + i] = pack4(v[4 * i].y, v[4 * i + 1].y, v[4 * i + 2].y, v[4 * i + 3].y);
                        if ((i & 3) == 3) {
                            stg128(tile + wrB + (i >> 2) * 128, make_uint4(o[i - 3], o[i - 2], o[i - 1], o[i]));
                            stg128(tile + wrB + (i >> 2) * 128 + 256, make_uint4(o[i + 5], o[i + 6], o[i + 7], o[i + 8]));
                        }
                    }
                    asm volatile("{\n.reg .pred p;\nsetp.eq.u32 p, %1, 0;\nfence.proxy.async.global;\nbar.warp.sync 0xffffffff;\n"
                                 "@p mbarrier.arrive.shared::cta.b64 _, [%0];\n}" :: "r"(bars + (B_GO + (sig & 15)) * 8), "r"(lane | (kind & 2)) : "memory");
                    int cs[4];
#pragma unroll
                    for (int i = 0; i < 4; i++)
                        cs[i] = __dp4a((int)o[4 * i], 0x01010101, __dp4a((int)o[4 * i + 1], 0x01010101,
                                __dp4a((int)o[4 * i + 2], 0x01010101, __dp4a((int)o[4 * i + 3], 0x01010101, 0))));
                    const unsigned csv = cs[0] + cs[1] + (cs[2] + cs[3]) * 65536;
                    if (kind == 1) {
                        const int own = (j.y >> (24 + (lane >> 4) * 4)) & 15;
                        const uint32_t so = SM_SUM + (sig & 48) * 4 + (lane & 15) * 4;
                        if (own != r) {
                            const uint32_t ro = mapa(sb, own);
                            asm volatile("red.async.relaxed.cluster.shared::cluster.mbarrier::complete_tx::bytes.add.u32 [%0], %1, [%2];"
                                         :: "r"(ro + so), "r"(csv), "r"(ro + SM_BAR + B_SUM * 8) : "memory");
                        } else asm volatile("red.relaxed.cluster.shared::cta.add.u32 [%0], %1;" :: "r"(sb + so), "r"(csv) : "memory");
                        __syncwarp();
                        if (own == r && (lane & 15) == 0) mbar_arrive(bars + B_SUM * 8);
                    } else {
                        unsigned* csp = scr->cs + (j.y >> 24) * 32 + lane;
                        asm volatile("st.global.u32 [%0], %1;" :: "l"(csp), "r"(csv) : "memory");
                        publish(scr->flag + sig, read_back(tile + lane * 64) | read_back(csp), zero);
                    }
                }
                __syncwarp();
            }
            if (!synced) asm volatile("barrier.cluster.wait.aligned;" ::: "memory");
            agent = (cw + 6 * NCONV - CFG_PZ) % NCONV + 1;
            if (agent > 3) agent = -1;
        } else if (warp == 9) {
            asm volatile("barrier.cluster.wait.aligned;" ::: "memory");
        } else {
            load_x(scr, sb, b, lane);
            agent = 0;
        }
        const char* src = (const char*)scr->b8 + (c * 224 + r) * 2048;
        const int zxi = __ldg(zero_x);
#pragma unroll 1
        for (int i = 0, slot = r >> 2, end = 8;; end = NG / 4) {
#pragma unroll 1
            for (; warp == 9 && i < end; i++) {
                asm volatile("{\n.reg .pred p;\nWAIT_LOOP:\nmbarrier.try_wait.parity.shared::cta.b64 p, [%4], 0;\n@!p bra WAIT_LOOP;\n"
                             "elect.sync _|p, 0xffffffff;\n"
                             "@p cp.async.bulk.shared::cluster.global.mbarrier::complete_tx::bytes.multicast::cluster [%0], [%1], 2048, [%2], %3;\n}"
                             :: "r"(sb + SM_RING + slot * 8192 + (r & 3) * 2048), "l"(src + i * 32768),
                                "r"(bars + (B_FULL + bar_of(4 * i + (r >> 2))) * 8), "h"((uint16_t)0xFFFF), "r"(bars + (B_GO + i) * 8) : "memory");
                slot += slot >= NRING - 4 ? 4 - NRING : 4;
            }
            if (end != 8) break;
            if (warp == (r < 8 ? 9 : r < 10 ? 8 : r < 14 ? 16 - NCONV + (CFG_PZ + 3) % NCONV : 0)) {
                const float zxf = __bfloat162float(__float2bfloat16_rn((float)zxi));
                const int grp = sum_group(r);
                mbar_wait_cluster(bars + B_SUM * 8);
                unsigned sv[4];
#pragma unroll
                for (int h = 0; h < 4; h++) sv[h] = lds32(sb + SM_SUM + h * 64 + (lane & 15) * 4);
                const uint32_t z = zero_term(sv, zxf);
#pragma unroll 2
                for (int k = 0; k < 8; k++) {
                    const uint32_t rb = mapa(sb, k * 2 + (lane >> 4));
                    st_async32(rb + SM_PAR + grp * 64 + (lane & 15) * 4, z, rb + SM_BAR + (B_PAR + (grp >> 1)) * 8);
                }
            }
        }
        __syncwarp();
        if (agent >= 0) store_out(&map, sb, b, agent, lane);
    } else {
        asm volatile("setmaxnreg.inc.sync.aligned.u32 168;");
        consume<false>(scr, scale_w, bias, scale_x, sb, b, warp, lane);
    }
}

__global__ void __cluster_dims__(2, 1, 1) __launch_bounds__(512, 1)
w8a8_side(Scratch* scr, const __nv_bfloat16* __restrict__ scale_w, const __nv_bfloat16* __restrict__ bias,
          const __nv_bfloat16* __restrict__ scale_x, const int* __restrict__ zero_x, const __grid_constant__ CUtensorMap map) {
    extern __shared__ __align__(1024) unsigned char smem_raw[];
    const uint32_t sb = (uint32_t)__cvta_generic_to_shared(smem_raw);
    const uint32_t bars = sb + SM_BAR;
    const int warp = __shfl_sync(~0u, threadIdx.x >> 5, 0), lane = threadIdx.x & 31;
    const int b = NCTA + blockIdx.x, rank = b & 1;
    constexpr int NR = NRING;
    if (warp < B_OFULL / 16) {
        if (elect_one()) {
            const uint32_t cnt = warp < B_GO / 16 ? 1 : 9;
#pragma unroll
            for (int i = 0; i < 16; i++) mbar_init(bars + (warp * 16 + i) * 8, cnt);
        }
        __syncwarp();
        const int i = warp * 16 + lane;
        if (lane < 16 && i < B_PAR) mbar_expect_tx(bars + i * 8, warp == 1 ? 8192 : 16384);
        if (lane < 16 && i >= B_OFREE && i < B_OFREE + NOUT) mbar_arrive(bars + i * 8);
        if (warp == B_GO / 16 && 2 * lane + rank < NR)
            asm volatile("mbarrier.arrive.shared::cta.b64 _, [%0], %1;" :: "r"(bars + i * 8), "r"(8) : "memory");
        asm volatile("fence.mbarrier_init.release.cluster;" ::: "memory");
    } else if (warp == B_OFULL / 16) {
        if (elect_one()) {
#pragma unroll
            for (int i = 0; i < NOUT; i++) mbar_init(bars + (B_OFULL + i) * 8, 4);
            asm volatile("fence.mbarrier_init.release.cluster;" ::: "memory");
        }
        __syncwarp();
    } else if (warp == 13 && elect_one()) asm volatile("prefetch.tensormap [%0];" :: "l"(&map) : "memory");
    asm volatile("barrier.cluster.arrive.relaxed.aligned;" ::: "memory");

    if (warp >= 8) {
        asm volatile("setmaxnreg.dec.sync.aligned.u32 88;");
        int agent = -1;
        if (warp == 8) {
            load_x(scr, sb, b, lane);
            agent = 0;
        } else if (warp == 11) {
            const unsigned tgt = (*(volatile unsigned*)&scr->epoch[b] + 1) * 4;
            const unsigned* f = scr->flag + CS * FS + lane;
            unsigned todo0 = ~0u, todo1 = 0xFFFFFF, v0 = ld_flag(f), v1 = ld_flag(f + 32);
            bool par = lane >= 3;
            asm volatile("barrier.cluster.wait.aligned;" ::: "memory");
#pragma unroll 1
            for (int it = 0; todo0 | todo1; it++) {
                const unsigned m0 = __ballot_sync(~0u, (int)(v0 - tgt) >= 0) & todo0, m1 = __ballot_sync(~0u, (int)(v1 - tgt) >= 0) & todo1;
                v0 = ld_flag(f); v1 = ld_flag(f + 32);
                todo0 &= ~m0; todo1 &= ~m1;
                if ((lane & 1) == rank) {
                    if (m0 >> lane & 1) mbar_arrive(bars + (B_GO + (lane >> 1)) * 8);
                    if (m1 >> lane & 1) mbar_arrive(bars + (B_GO + 16 + (lane >> 1)) * 8);
                }
                if (!par && !(lane ? todo1 << (32 - lane * 16) : todo0)) { par = true; mbar_arrive(bars + (B_AFREE + lane) * 8); }
                if (it > (1 << 20)) __trap();
            }
        } else if (warp == 9) {
            asm volatile("barrier.cluster.wait.aligned;" ::: "memory");
            const char* src = (const char*)scr->b8 + (7 * NG + rank) * 8192;
#pragma unroll 1
            for (int i = 0, slot = rank; i < NG / 2; i++) {
                asm volatile("{\n.reg .pred p;\nWAIT_LOOP:\nmbarrier.try_wait.parity.shared::cta.b64 p, [%4], 0;\n@!p bra WAIT_LOOP;\n"
                             "elect.sync _|p, 0xffffffff;\n"
                             "@p cp.async.bulk.shared::cluster.global.mbarrier::complete_tx::bytes.multicast::cluster [%0], [%1], 8192, [%2], %3;\n}"
                             :: "r"(sb + SM_RING + slot * 8192), "l"(src + i * 16384),
                                "r"(bars + (B_FULL + bar_of(2 * i + rank)) * 8), "h"((uint16_t)3), "r"(bars + (B_GO + i) * 8) : "memory");
                slot += slot >= NR - 2 ? 2 - NR : 2;
            }
        } else if (warp == 12 || warp == 15) {
            const float zxf = __bfloat162float(__float2bfloat16_rn((float)__ldg(zero_x)));
            asm volatile("barrier.cluster.wait.aligned;" ::: "memory");
#pragma unroll 1
            for (int blk = warp & 2; blk < 7; blk += 4) {
                const int w = min(blk * 32 + lane * 2, TN / 2 - 2);
                mbar_wait(bars + (B_AFREE + max(blk / 2 - 1, 0)) * 8);
                uint2 v[32];
                unsigned s0[4], s1[4];
#pragma unroll
                for (int k = 0; k < 32; k++) v[k] = __ldcg((const uint2*)(scr->cs + k * (TN / 2) + w));
#pragma unroll
                for (int h = 0; h < 4; h++) {
                    s0[h] = s1[h] = 0;
#pragma unroll
                    for (int k = 0; k < 8; k++) { s0[h] += v[8 * h + k].x; s1[h] += v[8 * h + k].y; }
                }
                sts32(sb + SM_PAR + w * 4, zero_term(s0, zxf));
                sts32(sb + SM_PAR + w * 4 + 4, zero_term(s1, zxf));
                __syncwarp();
                if (lane < 2) mbar_arrive(bars + (B_PAR + blk + lane) * 8);
            }
        } else {
            asm volatile("barrier.cluster.wait.aligned;" ::: "memory");
            agent = warp == 10 ? 1 : warp - 11;
        }
        if (agent >= 0) store_out(&map, sb, b, agent, lane);
    } else {
        asm volatile("setmaxnreg.inc.sync.aligned.u32 168;");
        consume<true>(scr, scale_w, bias, scale_x, sb, b, warp, lane);
    }
}

}

typedef CUresult (*EncodeFn)(CUtensorMap*, CUtensorMapDataType, cuuint32_t, void*, const cuuint64_t*, const cuuint64_t*,
                             const cuuint32_t*, const cuuint32_t*, CUtensorMapInterleave, CUtensorMapSwizzle,
                             CUtensorMapL2promotion, CUtensorMapFloatOOBfill);

namespace w8 {

constexpr int M_ = 2048, K_ = 1024, N_ = 3584;
constexpr int WA = 160, WB = 64;
constexpr int TN = 2 * WA + 2 * WB;
static_assert(TN == 448, "");
constexpr int X1 = 13;
constexpr int NSLOT = 7, SLOT = WA * 64;
constexpr int NSTG = 3, PFD = 700, NCONV = 5;
constexpr int NU = 48;
constexpr int UX = 32 + NSLOT;
constexpr int NJOB = 22;
constexpr int NCTA = 128;

constexpr int nA = 64, nWA = WA / 4, nWB = WB / 4;
constexpr int SEG1 = X1 * (nA + 2 * nWA);
constexpr int SEG2 = SEG1 + (16 - X1) * (nA + nWA);
constexpr int SEG3 = SEG2 + (16 - X1) * nWA;
constexpr int SEG4 = SEG3 + 16 * nWB;
constexpr int SEG5 = SEG4 + 16 * nWB;
static_assert(SEG5 == NJOB * NCTA, "");

constexpr int SM_A = 0;
constexpr int SM_RING = 131072;
constexpr int SM_STG = SM_RING + NSLOT * SLOT;
constexpr int SM_PAR = SM_STG + NSTG * 8192;
constexpr int SM_BAR = SM_PAR + 3 * TN * 2;
constexpr int B_FULLB = 0, B_FULLA = 48, B_GO = 64, B_PAR = 88, B_PSTEP = 92, B_AFREE = 100, B_NINIT = 102, B_FULLS = 102, B_END = 108;
constexpr int SM_TOTAL = SM_BAR + B_END * 8;
static_assert(SM_TOTAL <= 232448, "");

__device__ uint4 g_a8[M_ * K_ / 16];
__device__ uint4 g_b8[N_ * K_ / 16];
__device__ uint4 g_cs[16 * N_ * 2 / 16];
__device__ unsigned g_flag[16 * 16 + 8 * 64];
__device__ unsigned g_epoch[NCTA];
__device__ unsigned g_sink;
constexpr int SM_ALLOC = SM_TOTAL;

__device__ __forceinline__ void mbar_init(uint32_t bar, uint32_t cnt) {
    asm volatile("mbarrier.init.shared::cta.b64 [%0], %1;" :: "r"(bar), "r"(cnt) : "memory");
}
__device__ __forceinline__ void mbar_expect_tx(uint32_t bar, uint32_t bytes) {
    asm volatile("mbarrier.arrive.expect_tx.shared::cta.b64 _, [%0], %1;" :: "r"(bar), "r"(bytes) : "memory");
}
__device__ __forceinline__ void mbar_arrive(uint32_t bar) {
    asm volatile("mbarrier.arrive.shared::cta.b64 _, [%0];" :: "r"(bar) : "memory");
}
__device__ __forceinline__ void mbar_arrive_cluster(uint32_t bar) {
    asm volatile("mbarrier.arrive.shared::cluster.b64 _, [%0];" :: "r"(bar) : "memory");
}
__device__ __forceinline__ void mbar_wait(uint32_t bar, uint32_t parity = 0) {
    asm volatile("{\n.reg .pred p;\n.reg .u32 c;\n"
                 "mbarrier.try_wait.parity.shared::cta.b64 p, [%0], %1;\n"
                 "@p bra WAIT_DONE;\n"
                 "mov.u32 c, 0;\n"
                 "WAIT_LOOP:\n"
                 "mbarrier.try_wait.parity.shared::cta.b64 p, [%0], %1;\n"
                 "@p bra WAIT_DONE;\n"
                 "add.u32 c, c, 1;\nsetp.lt.u32 p, c, 0x100000;\n"
                 "@p bra WAIT_LOOP;\n"
                 "trap;\n"
                 "WAIT_DONE:\n}" :: "r"(bar), "r"(parity) : "memory");
}
__device__ __forceinline__ void mbar_wait2(uint32_t bar0, uint32_t bar1) {
    asm volatile("{\n.reg .pred p, q;\n.reg .u32 c;\nmov.u32 c, 0;\n"
                 "WAIT_LOOP:\n"
                 "mbarrier.try_wait.parity.shared::cta.b64 p, [%0], 0;\n"
                 "mbarrier.try_wait.parity.shared::cta.b64 q, [%1], 0;\n"
                 "and.pred p, p, q;\n"
                 "@p bra WAIT_DONE;\n"
                 "add.u32 c, c, 1;\nsetp.lt.u32 p, c, 0x100000;\n"
                 "@p bra WAIT_LOOP;\n"
                 "trap;\n"
                 "WAIT_DONE:\n}" :: "r"(bar0), "r"(bar1) : "memory");
}
__device__ __forceinline__ bool mbar_test(uint32_t bar) {
    uint32_t ok;
    asm volatile("{\n.reg .pred p;\nmbarrier.test_wait.parity.shared::cta.b64 p, [%1], 0;\nselp.u32 %0, 1, 0, p;\n}" : "=r"(ok) : "r"(bar) : "memory");
    return ok;
}
__device__ __forceinline__ bool mbar_test2(uint32_t bar0, uint32_t bar1) {
    uint32_t ok;
    asm volatile("{\n.reg .pred p, q;\nmbarrier.test_wait.parity.shared::cta.b64 p, [%1], 0;\n"
                 "mbarrier.test_wait.parity.shared::cta.b64 q, [%2], 0;\nand.pred p, p, q;\nselp.u32 %0, 1, 0, p;\n}"
                 : "=r"(ok) : "r"(bar0), "r"(bar1) : "memory");
    return ok;
}
__device__ __forceinline__ bool elect_one() {
    uint32_t ok;
    asm volatile("{\n.reg .pred p;\nelect.sync _|p, 0xffffffff;\nselp.u32 %0, 1, 0, p;\n}" : "=r"(ok));
    return ok;
}
__device__ __forceinline__ unsigned ld_acquire(const unsigned* p) {
    unsigned v;
    asm volatile("ld.acquire.gpu.global.u32 %0, [%1];" : "=r"(v) : "l"(p) : "memory");
    return v;
}
__device__ __forceinline__ unsigned ld_flag(const unsigned* p) {
    unsigned v;
    asm volatile("ld.relaxed.gpu.global.u32 %0, [%1];" : "=r"(v) : "l"(p) : "memory");
    return v;
}
__device__ __forceinline__ uint4 lds128(uint32_t a) {
    uint4 v;
    asm volatile("ld.shared.v4.b32 {%0,%1,%2,%3}, [%4];" : "=r"(v.x), "=r"(v.y), "=r"(v.z), "=r"(v.w) : "r"(a) : "memory");
    return v;
}
__device__ __forceinline__ void sts128(uint32_t a, uint4 v) {
    asm volatile("st.shared.v4.b32 [%0], {%1,%2,%3,%4};" :: "r"(a), "r"(v.x), "r"(v.y), "r"(v.z), "r"(v.w) : "memory");
}
__device__ __forceinline__ uint32_t lds32(uint32_t a) {
    uint32_t v;
    asm volatile("ld.shared.b32 %0, [%1];" : "=r"(v) : "r"(a) : "memory");
    return v;
}
__device__ __forceinline__ void sts32(uint32_t a, uint32_t v) {
    asm volatile("st.shared.b32 [%0], %1;" :: "r"(a), "r"(v) : "memory");
}
__device__ __forceinline__ void stg128(void* p, uint4 v) {
    asm volatile("st.global.v4.b32 [%0], {%1,%2,%3,%4};" :: "l"(p), "r"(v.x), "r"(v.y), "r"(v.z), "r"(v.w) : "memory");
}
__device__ __forceinline__ unsigned pack4(unsigned a, unsigned b, unsigned c, unsigned d) {
    unsigned lo, r;
    asm("cvt.pack.sat.s8.s32.b32 %0, %1, %2, 0;" : "=r"(lo) : "r"(d), "r"(c));
    asm("cvt.pack.sat.s8.s32.b32 %0, %1, %2, %3;" : "=r"(r) : "r"(b), "r"(a), "r"(lo));
    return r;
}
__device__ __forceinline__ void cpasync16(uint32_t dst, const void* src) {
    asm volatile("cp.async.cg.shared.global [%0], [%1], 16;" :: "r"(dst), "l"(src) : "memory");
}
__device__ __forceinline__ unsigned pf_l2(const void* p) {
    unsigned v;
    asm volatile("ld.global.cg.L2::128B.u32 %0, [%1];" : "=r"(v) : "l"(p) : "memory");
    return v;
}

constexpr uint32_t DESC_A_HI = 0x80000000u | (512 >> 4);
constexpr uint32_t DESC_B_HI = 128 >> 4;
template <int NR> __device__ __forceinline__ void wgmma_n160(int (&d)[NR], uint32_t alo, uint32_t blo, int scale_d) {
    asm volatile("{\n.reg .pred p;\n.reg .b64 da, db;\nsetp.ne.b32 p, %82, 0;\n"
        "mov.b64 da, {%80, %83};\nmov.b64 db, {%81, %84};\n"
        "wgmma.mma_async.sync.aligned.m64n160k32.s32.s8.s8 "
        "{%0, %1, %2, %3, %4, %5, %6, %7, %8, %9, %10, %11, %12, %13, %14, %15, "
        "%16, %17, %18, %19, %20, %21, %22, %23, %24, %25, %26, %27, %28, %29, %30, %31, "
        "%32, %33, %34, %35, %36, %37, %38, %39, %40, %41, %42, %43, %44, %45, %46, %47, "
        "%48, %49, %50, %51, %52, %53, %54, %55, %56, %57, %58, %59, %60, %61, %62, %63, "
        "%64, %65, %66, %67, %68, %69, %70, %71, %72, %73, %74, %75, %76, %77, %78, %79}, "
        "da, db, p;\n}\n"
        : "+r"(d[0]), "+r"(d[1]), "+r"(d[2]), "+r"(d[3]), "+r"(d[4]), "+r"(d[5]), "+r"(d[6]), "+r"(d[7]),
          "+r"(d[8]), "+r"(d[9]), "+r"(d[10]), "+r"(d[11]), "+r"(d[12]), "+r"(d[13]), "+r"(d[14]), "+r"(d[15]),
          "+r"(d[16]), "+r"(d[17]), "+r"(d[18]), "+r"(d[19]), "+r"(d[20]), "+r"(d[21]), "+r"(d[22]), "+r"(d[23]),
          "+r"(d[24]), "+r"(d[25]), "+r"(d[26]), "+r"(d[27]), "+r"(d[28]), "+r"(d[29]), "+r"(d[30]), "+r"(d[31]),
          "+r"(d[32]), "+r"(d[33]), "+r"(d[34]), "+r"(d[35]), "+r"(d[36]), "+r"(d[37]), "+r"(d[38]), "+r"(d[39]),
          "+r"(d[40]), "+r"(d[41]), "+r"(d[42]), "+r"(d[43]), "+r"(d[44]), "+r"(d[45]), "+r"(d[46]), "+r"(d[47]),
          "+r"(d[48]), "+r"(d[49]), "+r"(d[50]), "+r"(d[51]), "+r"(d[52]), "+r"(d[53]), "+r"(d[54]), "+r"(d[55]),
          "+r"(d[56]), "+r"(d[57]), "+r"(d[58]), "+r"(d[59]), "+r"(d[60]), "+r"(d[61]), "+r"(d[62]), "+r"(d[63]),
          "+r"(d[64]), "+r"(d[65]), "+r"(d[66]), "+r"(d[67]), "+r"(d[68]), "+r"(d[69]), "+r"(d[70]), "+r"(d[71]),
          "+r"(d[72]), "+r"(d[73]), "+r"(d[74]), "+r"(d[75]), "+r"(d[76]), "+r"(d[77]), "+r"(d[78]), "+r"(d[79])
        : "r"(alo), "r"(blo), "r"(scale_d), "r"(DESC_A_HI), "r"(DESC_B_HI));
}
template <int NR> __device__ __forceinline__ void wgmma_t128(int (&d)[NR], uint32_t alo, uint32_t blo, int scale_d) {
    asm volatile("{\n.reg .pred p;\n.reg .b64 da, db;\nsetp.ne.b32 p, %66, 0;\n"
        "mov.b64 da, {%64, %67};\nmov.b64 db, {%65, %68};\n"
        "wgmma.mma_async.sync.aligned.m64n128k32.s32.s8.s8 "
        "{%0, %1, %2, %3, %4, %5, %6, %7, %8, %9, %10, %11, %12, %13, %14, %15, "
        "%16, %17, %18, %19, %20, %21, %22, %23, %24, %25, %26, %27, %28, %29, %30, %31, "
        "%32, %33, %34, %35, %36, %37, %38, %39, %40, %41, %42, %43, %44, %45, %46, %47, "
        "%48, %49, %50, %51, %52, %53, %54, %55, %56, %57, %58, %59, %60, %61, %62, %63}, "
        "da, db, p;\n}\n"
        : "+r"(d[0]), "+r"(d[1]), "+r"(d[2]), "+r"(d[3]), "+r"(d[4]), "+r"(d[5]), "+r"(d[6]), "+r"(d[7]),
          "+r"(d[8]), "+r"(d[9]), "+r"(d[10]), "+r"(d[11]), "+r"(d[12]), "+r"(d[13]), "+r"(d[14]), "+r"(d[15]),
          "+r"(d[16]), "+r"(d[17]), "+r"(d[18]), "+r"(d[19]), "+r"(d[20]), "+r"(d[21]), "+r"(d[22]), "+r"(d[23]),
          "+r"(d[24]), "+r"(d[25]), "+r"(d[26]), "+r"(d[27]), "+r"(d[28]), "+r"(d[29]), "+r"(d[30]), "+r"(d[31]),
          "+r"(d[32]), "+r"(d[33]), "+r"(d[34]), "+r"(d[35]), "+r"(d[36]), "+r"(d[37]), "+r"(d[38]), "+r"(d[39]),
          "+r"(d[40]), "+r"(d[41]), "+r"(d[42]), "+r"(d[43]), "+r"(d[44]), "+r"(d[45]), "+r"(d[46]), "+r"(d[47]),
          "+r"(d[48]), "+r"(d[49]), "+r"(d[50]), "+r"(d[51]), "+r"(d[52]), "+r"(d[53]), "+r"(d[54]), "+r"(d[55]),
          "+r"(d[56]), "+r"(d[57]), "+r"(d[58]), "+r"(d[59]), "+r"(d[60]), "+r"(d[61]), "+r"(d[62]), "+r"(d[63])
        : "r"(alo), "r"(blo), "r"(scale_d), "r"(DESC_B_HI), "r"(DESC_A_HI));
}

__device__ __forceinline__ void wg_fence() { asm volatile("wgmma.fence.sync.aligned;" ::: "memory"); }
__device__ __forceinline__ void wg_commit() { asm volatile("wgmma.commit_group.sync.aligned;" ::: "memory"); }
template <int N> __device__ __forceinline__ void wg_wait() { asm volatile("wgmma.wait_group.sync.aligned %0;" :: "n"(N) : "memory"); }

struct Job { int src; int dst; };
__host__ __device__ constexpr int unit_of(int piece, int slab) {
    return piece < 2 ? (slab < X1 ? 2 * slab + piece : (piece ? 16 : X1) + slab) : 32 + (piece - 2) * 8 + (slab >> 1);
}
__device__ __forceinline__ Job decode_job(int g) {
    int slab, idx, piece;
    if (g < SEG2) {
        int r;
        if (g < SEG1) { slab = g / (nA + 2 * nWA); r = g - slab * (nA + 2 * nWA); }
        else { g -= SEG1; slab = g / (nA + nWA); r = g - slab * (nA + nWA); slab += X1; }
        piece = r < nA ? -1 : (r < nA + nWA ? 0 : 1);
        idx = r < nA ? r : r - nA - piece * nWA;
    } else if (g < SEG3) {
        g -= SEG2; slab = g / nWA; idx = g - slab * nWA; slab += X1; piece = 1;
    } else {
        g -= SEG3; piece = 2 + (g >> 8); slab = (g >> 4) & 15; idx = g & 15;
        static_assert(nWB == 16, "");
    }
    Job j;
    if (piece < 0) {
        const int flag = (idx >> 2) * 16 + slab;
        j.src = idx * 32 + (slab << 12);
        j.dst = (flag * 512 + (idx & 3) * 128) | (flag << 18);
    } else {
        const bool wide = piece < 2;
        const int w = wide ? WA : WB;
        const int nb = wide ? idx / (WA / 32) : idx / (WB / 32);
        const int J = idx - nb * (w / 32);
        const int cb = nb * TN + (wide ? piece * WA : 2 * WA - 2 * WB + piece * WB);
        j.src = cb + J * 32 + (slab << 12) + (wide ? 1 << 16 : 2 << 16);
        j.dst = (cb * (K_ / 16) + slab * w * 4 + J * 32) | ((256 + nb * 64 + unit_of(piece, slab)) << 18);
    }
    return j;
}
struct Coord { const CUtensorMap* m; int x, y, z; };
__device__ __forceinline__ Coord job_coord(const CUtensorMap* maps, int src) {
    const bool w = src >> 16;
    const int c0 = src & 0xFFF, slab = (src >> 12) & 15;
    return {maps + (w ? 1 : 0), w ? c0 : 0, w ? slab * 64 : slab * 2, w ? 0 : c0};
}
__device__ __forceinline__ void raw_load(const Coord& c, uint32_t dst, uint32_t bar) {
    mbar_expect_tx(bar, 8192);
    asm volatile("cp.async.bulk.tensor.3d.shared::cluster.global.tile.mbarrier::complete_tx::bytes [%0], [%1, {%2, %3, %4}], [%5];"
                 :: "r"(dst), "l"(c.m), "r"(c.x), "r"(c.y), "r"(c.z), "r"(bar) : "memory");
}
__device__ __forceinline__ void raw_prefetch(const Coord& c) {
    asm volatile("cp.async.bulk.prefetch.tensor.3d.L2.global.tile [%0, {%1, %2, %3}];"
                 :: "l"(c.m), "r"(c.x), "r"(c.y), "r"(c.z) : "memory");
}
__host__ __device__ constexpr unsigned unit_mask(int piece, int s0, int s1) {
    unsigned m = 0;
    for (int s = s0; s < s1; s++) m |= 1u << (unit_of(piece, s) & 31);
    return m;
}
__host__ __device__ constexpr int slot_of(int u) {
    return u < UX ? (u % NSLOT) * (SLOT / 2048) : u < UX + NSTG ? NSLOT * (SLOT / 2048) + (u - UX) * 4 : ((u - NSTG) % NSLOT) * (SLOT / 2048);
}
__host__ __device__ constexpr uint64_t slot_table(int piece) {
    uint64_t t = 0;
    if (piece < 2) for (int s = 0; s < 16; s++) t |= (uint64_t)(unit_of(piece, s) % NSLOT) << (4 * s);
    else for (int s = 0; s < 8; s++) t |= (uint64_t)slot_of(unit_of(piece, 2 * s)) << (8 * s);
    return t;
}
struct Maps { CUtensorMap m[3]; };

__device__ __forceinline__ uint32_t bf2_op_epi(int a, int b, uint32_t zc, uint32_t sx, uint32_t sw, uint32_t bi) {
    uint32_t v;
    float fa = __int2float_rn(a), fb = __int2float_rn(b);
    asm("cvt.rn.bf16x2.f32 %0, %1, %2;" : "=r"(v) : "f"(fb), "f"(fa));
    asm("sub.rn.bf16x2 %0, %0, %1;" : "+r"(v) : "r"(zc));
    asm("mul.rn.bf16x2 %0, %0, %1;" : "+r"(v) : "r"(sx));
    asm("mul.rn.bf16x2 %0, %0, %1;" : "+r"(v) : "r"(sw));
    asm("add.rn.bf16x2 %0, %0, %1;" : "+r"(v) : "r"(bi));
    return v;
}

struct Par { uint4 zc, sw, bi; };
__device__ __forceinline__ Par ld_par(uint32_t p) { return {lds128(p), lds128(p + TN * 2), lds128(p + TN * 4)}; }
__device__ __forceinline__ void epi_row(const int (&a)[WA / 2], int o, const Par& p, uint32_t sx2, char* out) {
    uint4 r;
    r.x = bf2_op_epi(a[o + 0], a[o + 4], p.zc.x, sx2, p.sw.x, p.bi.x);
    r.y = bf2_op_epi(a[o + 8], a[o + 12], p.zc.y, sx2, p.sw.y, p.bi.y);
    r.z = bf2_op_epi(a[o + 1], a[o + 5], p.zc.z, sx2, p.sw.z, p.bi.z);
    r.w = bf2_op_epi(a[o + 9], a[o + 13], p.zc.w, sx2, p.sw.w, p.bi.w);
    stg128(out, r);
}
template <int J, int JN>
__device__ __forceinline__ void epilogue(const int (&a)[WA / 2], Par& p, uint32_t par, uint32_t sx2, char* out) {
    epi_row(a, J * 16, p, sx2, out + J * 64);
    Par n = p;
    if (JN != J) n = ld_par(par + JN * 64);
    epi_row(a, J * 16 + 2, p, sx2, out + 8 * (N_ * 2) + J * 64);
    p = n;
}

__global__ void __cluster_dims__(2, 1, 1) __launch_bounds__(512, 1)
w8a8_kernel(const __grid_constant__ Maps maps, const char* __restrict__ qx, const char* __restrict__ qw, const __nv_bfloat16* __restrict__ scale_x, const int* __restrict__ zero_x,
            const __nv_bfloat16* __restrict__ scale_w, const __nv_bfloat16* __restrict__ bias,
            __nv_bfloat16* __restrict__ out) {
    extern __shared__ __align__(1024) unsigned char smem_raw[];
    const uint32_t sb = (uint32_t)__cvta_generic_to_shared(smem_raw);
    const uint32_t bars = sb + SM_BAR;
    const int warp = __shfl_sync(~0u, threadIdx.x >> 5, 0), lane = threadIdx.x & 31;
    const int b = blockIdx.x, rank = b & 1, nb = (b >> 1) & 7, mb = (b >> 4) * 2 + rank;

    if (warp >= 8) {
        asm volatile("setmaxnreg.dec.sync.aligned.u32 56;");
        if (warp >= 16 - NCONV) {
            const int cw = warp - (16 - NCONV);
            unsigned t0;
            asm volatile("mov.u32 %0, %clock;" : "=r"(t0));
            t0 += 100;
            asm volatile("barrier.cluster.arrive.relaxed.aligned;" ::: "memory");
            const Job mj = decode_job(min(lane, NJOB - 1) * NCTA + b);
            static_assert(NCONV == NSTG + 2 && NJOB == 22, "");
            const uint32_t s = sb + (cw < NSTG ? SM_STG + cw * 8192 : SM_A + (14 - NSTG + cw) * 8192);
            const uint32_t sbar = bars + (B_FULLS + cw) * 8;
            {
                const Coord c = job_coord(maps.m, __shfl_sync(~0u, mj.src, cw));
                if (elect_one()) {
                    mbar_init(sbar, 1);
                    asm volatile("fence.mbarrier_init.release.cluster;" ::: "memory");
                    unsigned t;
                    do { asm volatile("mov.u32 %0, %clock;" : "=r"(t)); } while ((int)(t - t0) < cw * PFD + (cw ? b * 88 : b * 0) / 16);
                    raw_load(c, s, sbar);
                }
                __syncwarp();
            }
            asm volatile("barrier.cluster.wait.aligned;" ::: "memory");
            t0 += b * 88 / 16;
            const int c4 = lane & 3, ln = (lane >> 2) * 2 + (c4 >> 1);
            const uint32_t rdA = ln * 128 + ((((c4 & 1) << 2) ^ (ln & 7)) << 4);
            const uint32_t rdB = (lane >> 3) * 2048 + (lane & 7) * 16;
            const int wrA = (lane >> 2) * 4 + (c4 ^ ((lane >> 3) & 3));
            uint32_t par = 0;
#pragma unroll 1
            for (int j = cw, jn; j < NJOB; j = jn, par ^= 1) {
                jn = j < 13 ? j + NCONV : (j < 15 ? 31 : j + NSTG);
                const int src = __shfl_sync(~0u, mj.src, j), dst = __shfl_sync(~0u, mj.dst, j);
                const int nsrc = __shfl_sync(~0u, mj.src, jn);
                const int kind = src >> 16;
                uint4 o[4];
                uint4* d;
                int dstep;
                mbar_wait(sbar, par);
                if (kind == 0) {
                    const uint32_t a0 = s + rdA;
                    d = g_a8 + (dst & 0x3FFFF) + wrA;
                    dstep = 32;
#pragma unroll
                    for (int i = 0; i < 4; i++) {
                        uint4 v0 = lds128(a0 + i * 2048), v1 = lds128((a0 ^ 16) + i * 2048);
                        uint4 v2 = lds128((a0 ^ 32) + i * 2048), v3 = lds128((a0 ^ 48) + i * 2048);
                        o[i].x = pack4(v0.x, v0.y, v0.z, v0.w); o[i].y = pack4(v1.x, v1.y, v1.z, v1.w);
                        o[i].z = pack4(v2.x, v2.y, v2.z, v2.w); o[i].w = pack4(v3.x, v3.y, v3.z, v3.w);
                    }
                } else {
                    const uint32_t a0 = s + rdB;
                    d = g_b8 + (dst & 0x3FFFF) + (lane >> 3) * (kind == 1 ? WA : WB) + (lane & 7);
                    dstep = 8;
#define CV_B(m, f)                                                                                    \
                    {                                                                                 \
                        uint4 v0 = lds128(a0 + m * 512), v1 = lds128(a0 + m * 512 + 128);             \
                        uint4 v2 = lds128(a0 + m * 512 + 256), v3 = lds128(a0 + m * 512 + 384);       \
                        o[0].f = pack4(v0.x, v1.x, v2.x, v3.x); o[1].f = pack4(v0.y, v1.y, v2.y, v3.y); \
                        o[2].f = pack4(v0.z, v1.z, v2.z, v3.z); o[3].f = pack4(v0.w, v1.w, v2.w, v3.w); \
                    }
                    CV_B(0, x) CV_B(1, y) CV_B(2, z) CV_B(3, w)
                }
#pragma unroll
                for (int i = 0; i < 4; i++) stg128(d + i * dstep, o[i]);
                unsigned tn;
                asm volatile("mov.u32 %0, %clock;" : "=r"(tn));
                const bool late = jn < NJOB && (int)(tn - t0) < jn * PFD;
                if (!late && elect_one()) {
                    if (jn < NJOB) { raw_load(job_coord(maps.m, nsrc), s, sbar); }
                    else if (jn == 31) mbar_arrive(bars + (B_AFREE - NSTG + cw) * 8);
                    else if (0 != 1) {
                        uint32_t ra;
                        asm("mapa.shared::cluster.u32 %0, %1, %2;" : "=r"(ra) : "r"(bars + (B_GO + ((UX + cw) >> 1)) * 8), "r"((UX + cw) & 1));
                        mbar_arrive_cluster(ra);
                    }
                }
                const int* csp = (const int*)d;
                unsigned csv = o[0].x;
                if (kind != 0) {
                    int cs[4];
#pragma unroll
                    for (int i = 0; i < 4; i++)
                        cs[i] = __dp4a((int)o[i].x, 0x01010101, __dp4a((int)o[i].y, 0x01010101,
                                __dp4a((int)o[i].z, 0x01010101, __dp4a((int)o[i].w, 0x01010101, 0))));
                    const int p01 = cs[0] + cs[1] * 65536, p23 = cs[2] + cs[3] * 65536;
                    const bool odd = lane & 8;
                    int v = (odd ? p23 : p01) + __shfl_xor_sync(~0u, odd ? p01 : p23, 8);
                    v += __shfl_xor_sync(~0u, v, 16);
                    int* p = (int*)g_cs + ((src >> 12) & 15) * (N_ / 2) + ((src & 0xFFF) >> 1) + (lane & 15);
                    if (lane < 16) *p = v;
                    csp = p; csv = v;
                }
#pragma unroll 1
                for (int it = 0; it < 1000; it++) {
                    bool ok = true;
                    if ((lane & 3) == 0) {
                        unsigned rb[5];
#pragma unroll
                        for (int i = 0; i < 4; i++)
                            asm volatile("ld.relaxed.gpu.global.u32 %0, [%1];" : "=r"(rb[i]) : "l"(d + i * dstep) : "memory");
                        asm volatile("ld.relaxed.gpu.global.u32 %0, [%1];" : "=r"(rb[4]) : "l"(csp) : "memory");
                        ok = rb[0] == o[0].x && rb[1] == o[1].x && rb[2] == o[2].x && rb[3] == o[3].x && rb[4] == csv;
                    }
                    if (__all_sync(~0u, ok)) break;
                }
                if (elect_one()) asm volatile("red.relaxed.gpu.global.add.u32 [%0], 1;" :: "l"(g_flag + ((unsigned)dst >> 18)) : "memory");
                __syncwarp();
                if (late && elect_one()) {
                    do { asm volatile("mov.u32 %0, %clock;" : "=r"(tn)); } while ((int)(tn - t0) < jn * PFD);
                    raw_load(job_coord(maps.m, nsrc), s, sbar);
                }
                __syncwarp();
            }
        } else if (warp == 8) {
            asm volatile("barrier.cluster.arrive.relaxed.aligned;" ::: "memory");
            const unsigned ep = *(volatile unsigned*)&g_epoch[b] + 1;
            const unsigned* f1 = g_flag + 256 + nb * 64 + lane;
            const unsigned* f2 = lane < 16 ? f1 + 32 : g_flag + mb * 16 + lane - 16;
            const unsigned t1 = ep * (WA / 32), t2 = ep * 4;
            static_assert(WB / 16 == 4, "");
            const unsigned n1 = lane == 0 ? unit_mask(0, 0, 8) : lane == 1 ? unit_mask(1, 0, 8) : lane == 2 ? unit_mask(0, 8, 16)
                              : lane == 3 ? unit_mask(1, 8, 16) : 0u;
            const unsigned n2 = lane < 4 ? 0u : 0xFFFFu;
            bool d1 = false, d2 = false, d3 = lane >= 5, fr = lane < 30;
            asm volatile("barrier.cluster.wait.aligned;" ::: "memory");
            for (int it = 0; 0 != 1; it++) {
                unsigned v1 = t1, v2 = t2;
                if (!d1) v1 = ld_flag(f1);
                if (!d2) v2 = ld_flag(f2);
                if (!fr) fr = mbar_test(bars + (B_AFREE - 30 + lane) * 8);
                if (!d2 && fr && (int)(v2 - t2) >= 0) {
                    d2 = true;
                    if (lane >= 16) {
                        asm volatile("fence.proxy.async.global;" ::: "memory");
                        asm volatile("cp.async.bulk.shared::cluster.global.mbarrier::complete_tx::bytes [%0], [%1], %2, [%3];"
                                     :: "r"(sb + SM_A + (lane - 16) * 8192), "l"((const char*)g_a8 + (mb * 16 + lane - 16) * 8192),
                                        "r"(8192), "r"(bars + (B_FULLA + lane - 16) * 8) : "memory");
                    } else if ((lane & 1) == rank) mbar_arrive(bars + (B_GO + 16 + (lane >> 1)) * 8);
                }
                if (!d1 && (int)(v1 - t1) >= 0) {
                    d1 = true;
                    if ((lane & 1) == rank) mbar_arrive(bars + (B_GO + (lane >> 1)) * 8);
                }
                const unsigned m1 = __ballot_sync(~0u, d1), m2 = __ballot_sync(~0u, d2);
                if (!d3 && (m1 & n1) == n1 && (m2 & n2) == n2) { d3 = true; mbar_arrive(bars + (B_PSTEP + lane) * 8); }
                if ((m1 & m2) == ~0u) break;
                if (it > (1 << 22)) __trap();
            }
        } else if (warp == 9) {
            asm volatile("barrier.cluster.arrive.relaxed.aligned;" ::: "memory");
            const int u = 2 * lane + rank;
            int so, fb;
            if (u < 2 * X1) { so = (u & 1) * (WA * K_) + (u >> 1) * (WA * 64); fb = (u & 1) * 24 + (u >> 1); }
            else if (u < X1 + 16) { so = (u - X1) * (WA * 64); fb = u - X1; }
            else if (u < 32) { so = WA * K_ + (u - 16) * (WA * 64); fb = 24 + u - 16; }
            else { so = 2 * WA * K_ + (u - 32) * (WB * 128); fb = u < 40 ? u - 16 : u; }
            const char* srcB = (const char*)g_b8 + nb * TN * K_ + so;
            const uint32_t dstB = sb + SM_RING + slot_of(u) * 2048;
            asm volatile("barrier.cluster.wait.aligned;" ::: "memory");
#pragma unroll 1
            for (int i = 0; i < NU / 2 && 0 != 1; i++) {
                mbar_wait(bars + (B_GO + i) * 8);
                if (lane == i) {
                    asm volatile("fence.proxy.async.global;" ::: "memory");
                    asm volatile("cp.async.bulk.shared::cluster.global.mbarrier::complete_tx::bytes.multicast::cluster [%0], [%1], %2, [%3], %4;"
                                 :: "r"(dstB), "l"(srcB), "r"(u < 32 ? WA * 64 : WB * 128), "r"(bars + (B_FULLB + fb) * 8), "h"((uint16_t)3) : "memory");
                }
                __syncwarp();
            }
        } else if (warp == 10) {
            unsigned pv, pv2;
            {
                static_assert(X1 > 0 && nA == 64 && nWA == 40, "");
                const int i = b - (b < 104 ? 64 : 104), q = i / 5;
                const char* p = b < 64 ? qx + (b * 32 + (lane >> 1)) * (K_ * 4) + (lane & 1) * 128
                                       : qw + lane * (N_ * 4) + (q * TN + (b < 104 ? 0 : WA) + (i - q * 5) * 32) * 4;
                pv = pf_l2(p);
                pv2 = pf_l2(p + (b < 64 ? 16 * K_ * 4 : 32 * N_ * 4));
                if (lane < 3) asm volatile("prefetch.tensormap [%0];" :: "l"(maps.m + lane) : "memory");
            }
            asm volatile("barrier.cluster.arrive.relaxed.aligned;" ::: "memory");
            if ((pv ^ pv2) == 0x40000000u) g_sink = pv;
            const float zxf = __bfloat162float(__float2bfloat16_rn((float)__ldg(zero_x)));
#pragma unroll 1
            for (int i = lane; i < TN / 4; i += 32) {
                const bool hi = i >= TN / 8;
                sts128(sb + SM_PAR + TN * 2 + i * 16, __ldg((const uint4*)((hi ? bias : scale_w) + nb * TN) + (hi ? i - TN / 8 : i)));
            }
            asm volatile("barrier.cluster.wait.aligned;" ::: "memory");
            int c[8], cs[8];
#pragma unroll
            for (int i = 0; i < 8; i++) { c[i] = 0; cs[i] = 0; }
#pragma unroll 1
            for (int st = 0; st < 5 && 0 != 1; st++) {
                const bool wide = st < 4;
                const int half = wide ? (st >> 1) : (lane >> 4);
                const int col = wide ? (st & 1) * WA + min(lane, WA / 8 - 1) * 8 : 2 * WA + (lane & 15) * 8;
                const uint4* src = g_cs + (half * 8 * N_ + nb * TN + col) / 8;
                mbar_wait(bars + (B_PSTEP + st) * 8);
                uint4 v[8];
#pragma unroll
                for (int i = 0; i < 8; i++) v[i] = __ldcg(src + i * (N_ / 8));
#pragma unroll
                for (int h = 0; h < 8; h += 4) {
                    const unsigned sv[4] = {v[h].x + v[h + 1].x + v[h + 2].x + v[h + 3].x, v[h].y + v[h + 1].y + v[h + 2].y + v[h + 3].y,
                                            v[h].z + v[h + 1].z + v[h + 2].z + v[h + 3].z, v[h].w + v[h + 1].w + v[h + 2].w + v[h + 3].w};
#pragma unroll
                    for (int i = 0; i < 4; i++) {
                        const int lo = (int)(short)(sv[i] & 0xFFFF);
                        c[2 * i] += lo; c[2 * i + 1] += ((int)(sv[i] - (unsigned)lo)) >> 16;
                    }
                }
                if (st >= 2) {
                    uint32_t z[4];
#pragma unroll
                    for (int i = 0; i < 8; i++) {
                        const int o = __shfl_xor_sync(~0u, c[i], 16);
                        if (!wide) c[i] += o;
                    }
#pragma unroll
                    for (int i = 0; i < 4; i++) {
                        const float lo = __bfloat162float(__float2bfloat16_rn((float)c[2 * i])) * zxf;
                        const float hi = __bfloat162float(__float2bfloat16_rn((float)c[2 * i + 1])) * zxf;
                        asm("cvt.rn.bf16x2.f32 %0, %1, %2;" : "=r"(z[i]) : "f"(hi), "f"(lo));
                    }
                    const uint32_t za = sb + SM_PAR + ((col & ~31) + (col & 8) * 2 + ((col >> 3) & 2)) * 2;
#pragma unroll
                    for (int i = 0; i < 4; i++) sts32(za + i * 8, z[i]);
                    __syncwarp();
                    if (lane == 0) { mbar_arrive(bars + (B_PAR + st - 2) * 8); }
#pragma unroll
                    for (int i = 0; i < 8; i++) c[i] = 0;
                }
#pragma unroll
                for (int i = 0; i < 8; i++) { const int t = c[i]; c[i] = cs[i]; cs[i] = t; }
            }
        } else {
            asm volatile("barrier.cluster.arrive.relaxed.aligned;" ::: "memory");
            asm volatile("barrier.cluster.wait.aligned;" ::: "memory");
        }
    } else {
        asm volatile("setmaxnreg.inc.sync.aligned.u32 200;");
        {
            constexpr int PER = (B_NINIT + 7) / 8;
            if (elect_one()) {
#pragma unroll 1
                for (int i = warp * PER; i < min(warp * PER + PER, B_NINIT); i++)
                    {
                    const int u = 2 * (i - B_GO) + rank;
                    mbar_init(bars + i * 8, (i < B_GO || i >= B_PAR || u < NSLOT) ? 1 : (u >= UX && u < UX + NSTG) ? 3 : 9);
                }
            }
            __syncwarp();
            const int i = warp * PER + lane;
            if (lane < PER && i < B_GO) mbar_expect_tx(bars + i * 8, (i < 16 || (i >= 24 && i < 40)) ? WA * 64 : 8192);
            static_assert(WB * 128 == 8192, "");
            asm volatile("fence.mbarrier_init.release.cluster;" ::: "memory");
        }
        asm volatile("barrier.cluster.arrive.relaxed.aligned;" ::: "memory");
        const int wg = warp >> 2;
        const uint32_t sd = (sb & 0x3FFFF) >> 4;
        const unsigned short sxr = __ldg((const unsigned short*)scale_x);
        const uint32_t sx2 = (uint32_t)sxr * 0x10001u;
        char* orow = (char*)out + (size_t)(mb * 128 + (warp & 3) * 16 + (lane >> 2)) * (N_ * 2) + (nb * TN + (lane & 3) * 8 + wg * WA) * 2;
        const uint32_t par = sb + SM_PAR + (lane & 3) * 16 + wg * WA * 2;
        uint32_t reladdr;
        int rell;
        {
            const int u = lane < 16 ? (lane < X1 ? 2 * lane + wg : (wg ? 16 : X1) + lane) : 16 + wg * 8 + lane;
            const int v = u + (u < 32 ? NSLOT : NSLOT + NSTG);
            rell = (lane < 24 && v < NU) ? lane : 99;
            asm("mapa.shared::cluster.u32 %0, %1, %2;" : "=r"(reladdr) : "r"(bars + (B_GO + (v >> 1)) * 8), "r"(v & 1));
        }
        asm volatile("barrier.cluster.wait.aligned;" ::: "memory");
        int a0[WA / 2], a1[WA / 2];
        uint32_t barB = bars + (B_FULLB + wg * 24) * 8;
        bool ready = false;
#define HAND_BACK(done) if (rell <= (done)) { mbar_arrive_cluster(reladdr); rell = 99; }
        if (0 != 1) {
            wg_fence();
            {
                uint64_t tbl = wg ? slot_table(1) : slot_table(0);
                uint32_t da = (sd + (SM_A >> 4)) | (1 << 16);
#pragma unroll 1
                for (int s = 0; s < 16; s++) {
                    const uint32_t db = ((sd + (SM_RING >> 4)) | (WA << 16)) + ((uint32_t)tbl & 15) * (SLOT >> 4);
                    const bool starved = !ready && !mbar_test2(bars + (B_FULLA + s) * 8, barB);
                    if (starved) {
                        wg_wait<0>();
                        HAND_BACK(s - 1)
                        mbar_wait2(bars + (B_FULLA + s) * 8, barB);
                    }
                    wgmma_n160(a0, da, db, s);
                    wgmma_n160(a1, da + 256, db, s);
                    wgmma_n160(a0, da + 2, db + 2 * WA, 1);
                    wgmma_n160(a1, da + 258, db + 2 * WA, 1);
                    wg_commit();
                    HAND_BACK(s - 2)
                    tbl >>= 4; da += 512; barB += 8;
                    ready = mbar_test2(bars + (B_FULLA + min(s + 1, 15)) * 8, barB);
                    wg_wait<1>();
                }
            }
            HAND_BACK(14)
            wg_wait<0>();
            HAND_BACK(15)
            mbar_wait(bars + (B_PAR + wg) * 8);
            Par P = ld_par(par);
            char* const orow1 = orow + 64 * (N_ * 2);
            epilogue<0, 1>(a0, P, par, sx2, orow); epilogue<1, 2>(a0, P, par, sx2, orow);
            epilogue<2, 3>(a0, P, par, sx2, orow); epilogue<3, 0>(a0, P, par, sx2, orow);
            int t[64];
            wg_fence();
            {
                uint64_t tbl = wg ? slot_table(3) : slot_table(2);
                uint32_t da = (sd + (SM_A >> 4)) | (1 << 16);
#pragma unroll
                for (int i = 16; i < 24; i++) {
                    const uint32_t db = ((sd + (SM_RING >> 4)) | (WB << 16)) + ((uint32_t)tbl & 255) * 128;
                    const bool starved = !ready && !mbar_test(barB);
                    if (starved) {
                        wg_wait<0>();
                        HAND_BACK(i - 1)
                        mbar_wait(barB);
                    }
#pragma unroll
                    for (int k = 0; k < 4; k++) wgmma_t128(t, db + k * 2 * WB, da + (k >> 1) * 512 + (k & 1) * 2, k ? 1 : i - 16);
                    wg_commit();
                    HAND_BACK(i - 2)
                    tbl >>= 8; da += 1024; barB += 8;
                    ready = mbar_test(barB);
                    switch (i) {
                        case 16: epilogue<0, 0>(a1, P, par, sx2, orow1); break;
                        case 17: epilogue<1, 1>(a1, P, par, sx2, orow1); break;
                        case 18: epilogue<2, 2>(a1, P, par, sx2, orow1); break;
                        case 19: epilogue<3, 3>(a1, P, par, sx2, orow1); break;
                        case 20: epilogue<4, 4>(a1, P, par, sx2, orow1); break;
                        case 21: epilogue<4, 4>(a0, P, par, sx2, orow); break;
                        default: break;
                    }
                    if (i < 20) P = ld_par(par + (i - 15) * 64);
                    wg_wait<1>();
                }
            }
            HAND_BACK(22)
            mbar_wait(bars + (B_PAR + 2) * 8);
            const int w = warp & 3, q = lane >> 2, c0 = (w >> 1) * 32 + q * 4 + (w & 1) * 2;
            const uint32_t pp = sb + SM_PAR + (2 * WA + wg * WB + c0) * 2;
            const uint32_t zc = lds32(pp), sw = lds32(pp + TN * 2), bi = lds32(pp + TN * 4);
            const int r0 = (lane & 3) * 2;
            const uint32_t st0 = r0 * 128 + (((c0 >> 3) ^ r0) << 4) + (c0 & 7) * 2, st1 = (st0 ^ 16) + 128;
            wg_wait<0>();
            asm volatile("bar.sync %0, 128;" :: "r"(3 + wg) : "memory");
#pragma unroll
            for (int h = 0; h < 2; h++) {
                const uint32_t buf = sb + SM_RING + (wg ? slot_of(UX + 1 + h) : slot_of(UX - 1 + h)) * 2048;
#pragma unroll
                for (int j = 0; j < 8; j++) {
                    const int o = h * 32 + j * 4;
                    sts32(buf + st0 + j * 1024, bf2_op_epi(t[o], t[o + 2], zc, sx2, sw, bi));
                    sts32(buf + st1 + j * 1024, bf2_op_epi(t[o + 1], t[o + 3], zc, sx2, sw, bi));
                }
                asm volatile("fence.proxy.async.shared::cta;" ::: "memory");
                asm volatile("bar.sync %0, 128;" :: "r"(3 + wg) : "memory");
                if (w == 0 && elect_one())
                    asm volatile("cp.async.bulk.tensor.2d.global.shared::cta.tile.bulk_group [%0, {%1, %2}], [%3];"
                                 :: "l"(maps.m + 2), "r"(nb * TN + 2 * WA + wg * WB), "r"(mb * 128 + h * 64), "r"(buf) : "memory");
            }
            if (w == 0) {
                asm volatile("cp.async.bulk.commit_group;" ::: "memory");
                asm volatile("cp.async.bulk.wait_group.read 0;" ::: "memory");
            }
        }
        if (threadIdx.x == 128) asm volatile("red.relaxed.gpu.global.add.u32 [%0], 1;" :: "l"(g_epoch + b) : "memory");
    }
}

static void launch(EncodeFn encode, void* const* d_in, void* d_out) {
    Maps maps;
    CUtensorMap &mx = maps.m[0], &mw = maps.m[1];
    {
        const cuuint64_t dim[3] = {32, K_ / 32, M_}, str[2] = {128, K_ * 4};
        const cuuint32_t box[3] = {32, 2, 32}, es[3] = {1, 1, 1};
        encode(&mx, CU_TENSOR_MAP_DATA_TYPE_INT32, 3, d_in[0], dim, str, box, es, CU_TENSOR_MAP_INTERLEAVE_NONE,
               CU_TENSOR_MAP_SWIZZLE_128B, CU_TENSOR_MAP_L2_PROMOTION_NONE, CU_TENSOR_MAP_FLOAT_OOB_FILL_NONE);
    }
    {
        const cuuint64_t dim[3] = {N_, K_, 1}, str[2] = {N_ * 4, (cuuint64_t)N_ * K_ * 4};
        const cuuint32_t box[3] = {32, 64, 1}, es[3] = {1, 1, 1};
        encode(&mw, CU_TENSOR_MAP_DATA_TYPE_INT32, 3, d_in[1], dim, str, box, es, CU_TENSOR_MAP_INTERLEAVE_NONE,
               CU_TENSOR_MAP_SWIZZLE_NONE, CU_TENSOR_MAP_L2_PROMOTION_NONE, CU_TENSOR_MAP_FLOAT_OOB_FILL_NONE);
    }
    {
        const cuuint64_t dim[2] = {N_, M_}, str[1] = {N_ * 2};
        const cuuint32_t box[2] = {WB, 64}, es[2] = {1, 1};
        encode(&maps.m[2], CU_TENSOR_MAP_DATA_TYPE_BFLOAT16, 2, d_out, dim, str, box, es, CU_TENSOR_MAP_INTERLEAVE_NONE,
               CU_TENSOR_MAP_SWIZZLE_128B, CU_TENSOR_MAP_L2_PROMOTION_NONE, CU_TENSOR_MAP_FLOAT_OOB_FILL_NONE);
    }
    w8a8_kernel<<<NCTA, 512, SM_ALLOC>>>(maps, (const char*)d_in[0], (const char*)d_in[1], (const __nv_bfloat16*)d_in[2], (const int*)d_in[3],
                                         (const __nv_bfloat16*)d_in[4], (const __nv_bfloat16*)d_in[5],
                                         (__nv_bfloat16*)d_out);
}

}

extern "C" void kernel_launch(void* const* d_in, const int* in_sizes, int n_in, void* d_out, int out_size) {
    using namespace ra;
    static EncodeFn encode = nullptr;
    static Scratch* scr = nullptr;
    static const JobTable* jobs = nullptr;
    static bool fits = false;
    if (!encode) {
        void* fn = nullptr;
        cudaDriverEntryPointQueryResult qr;
        cudaGetDriverEntryPoint("cuTensorMapEncodeTiled", &fn, cudaEnableDefault, &qr);
        encode = (EncodeFn)fn;
        cudaGetSymbolAddress((void**)&scr, g_scratch);
        cudaGetSymbolAddress((void**)&jobs, g_jobs);
        cudaFuncSetAttribute(w8a8_kernel, cudaFuncAttributeMaxDynamicSharedMemorySize, SM_ALLOC);
        cudaFuncSetAttribute(w8a8_kernel, cudaFuncAttributeNonPortableClusterSizeAllowed, 1);
        cudaFuncSetAttribute(w8a8_side, cudaFuncAttributeMaxDynamicSharedMemorySize, SM_ALLOC);
        cudaFuncSetAttribute(w8::w8a8_kernel, cudaFuncAttributeMaxDynamicSharedMemorySize, w8::SM_ALLOC);
        cudaLaunchConfig_t oc = {};
        oc.gridDim = dim3(NCTA); oc.blockDim = dim3(512); oc.dynamicSmemBytes = SM_ALLOC;
        cudaLaunchAttribute oa[1];
        oa[0].id = cudaLaunchAttributeClusterDimension; oa[0].val.clusterDim.x = CS; oa[0].val.clusterDim.y = 1; oa[0].val.clusterDim.z = 1;
        oc.attrs = oa; oc.numAttrs = 1;
        int nc = 0;
        fits = cudaOccupancyMaxActiveClusters(&nc, w8a8_kernel, &oc) == cudaSuccess && nc >= NCTA / CS;
        cudaGetLastError();
    }
    if (!fits) { w8::launch(encode, d_in, d_out); return; }
    CUtensorMap map;
    {
        const cuuint64_t dim[2] = {N_, M_}, str[1] = {N_ * 2};
        const cuuint32_t box[2] = {64, 32}, es[2] = {1, 1};
        encode(&map, CU_TENSOR_MAP_DATA_TYPE_BFLOAT16, 2, d_out, dim, str, box, es, CU_TENSOR_MAP_INTERLEAVE_NONE,
               CU_TENSOR_MAP_SWIZZLE_128B, CU_TENSOR_MAP_L2_PROMOTION_NONE, CU_TENSOR_MAP_FLOAT_OOB_FILL_NONE);
    }
    w8a8_kernel<<<NCTA, 512, SM_ALLOC, cudaStreamPerThread>>>((const char*)d_in[0], (const char*)d_in[1], scr, jobs, (const __nv_bfloat16*)d_in[4],
                                                             (const __nv_bfloat16*)d_in[5], (const __nv_bfloat16*)d_in[2], (const int*)d_in[3], map);
    cudaLaunchConfig_t cfg = {};
    cfg.gridDim = dim3(16); cfg.blockDim = dim3(512); cfg.dynamicSmemBytes = SM_ALLOC; cfg.stream = cudaStreamPerThread;
    cudaLaunchAttribute at[1];
    at[0].id = cudaLaunchAttributeProgrammaticStreamSerialization; at[0].val.programmaticStreamSerializationAllowed = 1;
    cfg.attrs = at; cfg.numAttrs = 1;
    cudaLaunchKernelEx(&cfg, w8a8_side, scr, (const __nv_bfloat16*)d_in[4], (const __nv_bfloat16*)d_in[5], (const __nv_bfloat16*)d_in[2],
                       (const int*)d_in[3], map);
}
```

```cpp
#include <cuda_runtime.h>
#include <cuda.h>
#include <cuda_bf16.h>
#include <stdint.h>

namespace ra {

constexpr int CFG_D = 3;
constexpr int CFG_P0 = 650;
constexpr int CFG_PF0 = 0;
constexpr int CFG_SLEEP = 200;
constexpr int CFG_NINIT = 2;
constexpr int CFG_NR = 10;
constexpr int CFG_PZ = 16;
constexpr int CFG_NOC = 12;
constexpr int CFG_YN = 10;
constexpr int CFG_YP = 1100;
constexpr int CFG_Y0 = 0;

constexpr int M_ = 2048, K_ = 1024, N_ = 3584;
constexpr int CS = 16, NCTA = 112, TN = 448;
constexpr int NRING = CFG_NR, NCONV = 6, NJOB = 26, NG = 56, NOUT = 4, D_ = CFG_D;

constexpr int SM_A = 0;
constexpr int SM_RING = 131072;
constexpr int SM_OUT = SM_RING + NRING * 8192;
constexpr int SM_PAR = SM_OUT + NOUT * 4096;
constexpr int SM_SUM = SM_PAR + 1024;
constexpr int SM_BAR = SM_SUM + 256;
constexpr int B_FULL = 0, B_PAR = 64, B_AFREE = 72, B_OFREE = 76, B_SUM = 108, B_GO = 112, B_OFULL = 144, B_END = 148;
constexpr int SM_TOTAL = SM_BAR + B_END * 8;

constexpr int FS = 32;
struct __align__(2048) Scratch {
    uint4 a8[M_ * K_ / 16];
    uint4 b8[N_ * K_ / 16];
    unsigned cs[32 * TN / 2];
    unsigned flag[CS * FS + 64];
    unsigned epoch[128];
};
__device__ Scratch g_scratch;
constexpr int SM_ALLOC = SM_TOTAL;
static_assert(SM_ALLOC <= 232448, "");

__device__ __forceinline__ void mbar_init(uint32_t bar, uint32_t cnt) {
    asm volatile("mbarrier.init.shared::cta.b64 [%0], %1;" :: "r"(bar), "r"(cnt) : "memory");
}
__device__ __forceinline__ void mbar_expect_tx(uint32_t bar, uint32_t bytes) {
    asm volatile("mbarrier.arrive.expect_tx.shared::cta.b64 _, [%0], %1;" :: "r"(bar), "r"(bytes) : "memory");
}
__device__ __forceinline__ void mbar_arrive(uint32_t bar) {
    asm volatile("mbarrier.arrive.shared::cta.b64 _, [%0];" :: "r"(bar) : "memory");
}
__device__ __forceinline__ void mbar_arrive_cluster(uint32_t bar) {
    asm volatile("mbarrier.arrive.shared::cluster.b64 _, [%0];" :: "r"(bar) : "memory");
}
__device__ __forceinline__ void mbar_wait(uint32_t bar) {
    asm volatile("{\n.reg .pred p;\nWAIT_LOOP:\nmbarrier.try_wait.parity.shared::cta.b64 p, [%0], 0;\n@!p bra WAIT_LOOP;\n}" :: "r"(bar) : "memory");
}
__device__ __forceinline__ void mbar_wait_cluster(uint32_t bar) {
    asm volatile("{\n.reg .pred p;\nWAIT_LOOP:\nmbarrier.try_wait.parity.relaxed.cluster.shared::cta.b64 p, [%0], 0;\n@!p bra WAIT_LOOP;\n"
                 "fence.acquire.sync_restrict::shared::cluster.cluster;\n}" :: "r"(bar) : "memory");
}
__device__ __forceinline__ void mbar_wait2(uint32_t bar0, uint32_t bar1) { mbar_wait(bar0); mbar_wait(bar1); }
__device__ __forceinline__ bool mbar_test(uint32_t bar) {
    uint32_t ok;
    asm volatile("{\n.reg .pred p;\nmbarrier.test_wait.parity.shared::cta.b64 p, [%1], 0;\nselp.u32 %0, 1, 0, p;\n}" : "=r"(ok) : "r"(bar) : "memory");
    return ok;
}
__device__ __forceinline__ bool mbar_test2(uint32_t bar0, uint32_t bar1) {
    uint32_t ok;
    asm volatile("{\n.reg .pred p, q;\nmbarrier.test_wait.parity.shared::cta.b64 p, [%1], 0;\n"
                 "mbarrier.test_wait.parity.shared::cta.b64 q, [%2], 0;\nand.pred p, p, q;\nselp.u32 %0, 1, 0, p;\n}"
                 : "=r"(ok) : "r"(bar0), "r"(bar1) : "memory");
    return ok;
}
__device__ __forceinline__ bool elect_one() {
    uint32_t ok;
    asm volatile("{\n.reg .pred p;\nelect.sync _|p, 0xffffffff;\nselp.u32 %0, 1, 0, p;\n}" : "=r"(ok));
    return ok;
}
__device__ __forceinline__ uint32_t mapa(uint32_t a, uint32_t cta) {
    uint32_t r;
    asm("mapa.shared::cluster.u32 %0, %1, %2;" : "=r"(r) : "r"(a), "r"(cta));
    return r;
}
__device__ __forceinline__ void st_async32(uint32_t a, uint32_t v, uint32_t bar) {
    asm volatile("st.async.shared::cluster.mbarrier::complete_tx::bytes.b32 [%0], %1, [%2];" :: "r"(a), "r"(v), "r"(bar) : "memory");
}
__device__ __forceinline__ unsigned ld_flag(const unsigned* p) {
    unsigned v;
    asm volatile("ld.relaxed.gpu.global.u32 %0, [%1];" : "=r"(v) : "l"(p) : "memory");
    return v;
}
__device__ __forceinline__ unsigned clk() { unsigned t; asm volatile("mov.u32 %0, %clock;" : "=r"(t)); return t; }
__device__ __forceinline__ uint32_t lds32(uint32_t a) {
    uint32_t v;
    asm volatile("ld.shared.b32 %0, [%1];" : "=r"(v) : "r"(a) : "memory");
    return v;
}
__device__ __forceinline__ void sts32(uint32_t a, uint32_t v) {
    asm volatile("st.shared.b32 [%0], %1;" :: "r"(a), "r"(v) : "memory");
}
__device__ __forceinline__ void stg128(void* p, uint4 v) {
    asm volatile("st.global.v4.b32 [%0], {%1,%2,%3,%4};" :: "l"(p), "r"(v.x), "r"(v.y), "r"(v.z), "r"(v.w) : "memory");
}
__device__ __forceinline__ unsigned pack4(unsigned a, unsigned b, unsigned c, unsigned d) {
    unsigned lo, r;
    asm("cvt.pack.sat.s8.s32.b32 %0, %1, %2, 0;" : "=r"(lo) : "r"(d), "r"(c));
    asm("cvt.pack.sat.s8.s32.b32 %0, %1, %2, %3;" : "=r"(r) : "r"(b), "r"(a), "r"(lo));
    return r;
}
constexpr uint32_t DESC_A_HI = 256 >> 4;
constexpr uint32_t DESC_B_HI = 0x80000000u | (512 >> 4);
__device__ __forceinline__ void mma_unit2(int (&d)[64], int (&e)[64], uint32_t alo, uint32_t blo, int scale_d) {
    asm volatile("{\n.reg .pred p;\n.reg .b64 da, db;\nsetp.ne.b32 p, %130, 0;\n"
        "mov.b64 da, {%128, %131};\nmov.b64 db, {%129, %132};\n"
        "wgmma.mma_async.sync.aligned.m64n128k32.s32.s8.s8 "
        "{%0, %1, %2, %3, %4, %5, %6, %7, %8, %9, %10, %11, %12, %13, %14, %15, "
        "%16, %17, %18, %19, %20, %21, %22, %23, %24, %25, %26, %27, %28, %29, %30, %31, "
        "%32, %33, %34, %35, %36, %37, %38, %39, %40, %41, %42, %43, %44, %45, %46, %47, "
        "%48, %49, %50, %51, %52, %53, %54, %55, %56, %57, %58, %59, %60, %61, %62, %63}, "
        "da, db, p;\n"
        "add.s64 da, da, 128;\n"
        "wgmma.mma_async.sync.aligned.m64n128k32.s32.s8.s8 "
        "{%64, %65, %66, %67, %68, %69, %70, %71, %72, %73, %74, %75, %76, %77, %78, %79, "
        "%80, %81, %82, %83, %84, %85, %86, %87, %88, %89, %90, %91, %92, %93, %94, %95, "
        "%96, %97, %98, %99, %100, %101, %102, %103, %104, %105, %106, %107, %108, %109, %110, %111, "
        "%112, %113, %114, %115, %116, %117, %118, %119, %120, %121, %122, %123, %124, %125, %126, %127}, "
        "da, db, p;\n"
        "add.s64 da, da, 128;\nadd.s64 db, db, 2;\n"
        "wgmma.mma_async.sync.aligned.m64n128k32.s32.s8.s8 "
        "{%0, %1, %2, %3, %4, %5, %6, %7, %8, %9, %10, %11, %12, %13, %14, %15, "
        "%16, %17, %18, %19, %20, %21, %22, %23, %24, %25, %26, %27, %28, %29, %30, %31, "
        "%32, %33, %34, %35, %36, %37, %38, %39, %40, %41, %42, %43, %44, %45, %46, %47, "
        "%48, %49, %50, %51, %52, %53, %54, %55, %56, %57, %58, %59, %60, %61, %62, %63}, "
        "da, db, 1;\n"
        "add.s64 da, da, 128;\n"
        "wgmma.mma_async.sync.aligned.m64n128k32.s32.s8.s8 "
        "{%64, %65, %66, %67, %68, %69, %70, %71, %72, %73, %74, %75, %76, %77, %78, %79, "
        "%80, %81, %82, %83, %84, %85, %86, %87, %88, %89, %90, %91, %92, %93, %94, %95, "
        "%96, %97, %98, %99, %100, %101, %102, %103, %104, %105, %106, %107, %108, %109, %110, %111, "
        "%112, %113, %114, %115, %116, %117, %118, %119, %120, %121, %122, %123, %124, %125, %126, %127}, "
        "da, db, 1;\n"
        "wgmma.commit_group.sync.aligned;\n}\n"
        : "+r"(d[0]), "+r"(d[1]), "+r"(d[2]), "+r"(d[3]), "+r"(d[4]), "+r"(d[5]), "+r"(d[6]), "+r"(d[7]),
          "+r"(d[8]), "+r"(d[9]), "+r"(d[10]), "+r"(d[11]), "+r"(d[12]), "+r"(d[13]), "+r"(d[14]), "+r"(d[15]),
          "+r"(d[16]), "+r"(d[17]), "+r"(d[18]), "+r"(d[19]), "+r"(d[20]), "+r"(d[21]), "+r"(d[22]), "+r"(d[23]),
          "+r"(d[24]), "+r"(d[25]), "+r"(d[26]), "+r"(d[27]), "+r"(d[28]), "+r"(d[29]), "+r"(d[30]), "+r"(d[31]),
          "+r"(d[32]), "+r"(d[33]), "+r"(d[34]), "+r"(d[35]), "+r"(d[36]), "+r"(d[37]), "+r"(d[38]), "+r"(d[39]),
          "+r"(d[40]), "+r"(d[41]), "+r"(d[42]), "+r"(d[43]), "+r"(d[44]), "+r"(d[45]), "+r"(d[46]), "+r"(d[47]),
          "+r"(d[48]), "+r"(d[49]), "+r"(d[50]), "+r"(d[51]), "+r"(d[52]), "+r"(d[53]), "+r"(d[54]), "+r"(d[55]),
          "+r"(d[56]), "+r"(d[57]), "+r"(d[58]), "+r"(d[59]), "+r"(d[60]), "+r"(d[61]), "+r"(d[62]), "+r"(d[63]),
          "+r"(e[0]), "+r"(e[1]), "+r"(e[2]), "+r"(e[3]), "+r"(e[4]), "+r"(e[5]), "+r"(e[6]), "+r"(e[7]),
          "+r"(e[8]), "+r"(e[9]), "+r"(e[10]), "+r"(e[11]), "+r"(e[12]), "+r"(e[13]), "+r"(e[14]), "+r"(e[15]),
          "+r"(e[16]), "+r"(e[17]), "+r"(e[18]), "+r"(e[19]), "+r"(e[20]), "+r"(e[21]), "+r"(e[22]), "+r"(e[23]),
          "+r"(e[24]), "+r"(e[25]), "+r"(e[26]), "+r"(e[27]), "+r"(e[28]), "+r"(e[29]), "+r"(e[30]), "+r"(e[31]),
          "+r"(e[32]), "+r"(e[33]), "+r"(e[34]), "+r"(e[35]), "+r"(e[36]), "+r"(e[37]), "+r"(e[38]), "+r"(e[39]),
          "+r"(e[40]), "+r"(e[41]), "+r"(e[42]), "+r"(e[43]), "+r"(e[44]), "+r"(e[45]), "+r"(e[46]), "+r"(e[47]),
          "+r"(e[48]), "+r"(e[49]), "+r"(e[50]), "+r"(e[51]), "+r"(e[52]), "+r"(e[53]), "+r"(e[54]), "+r"(e[55]),
          "+r"(e[56]), "+r"(e[57]), "+r"(e[58]), "+r"(e[59]), "+r"(e[60]), "+r"(e[61]), "+r"(e[62]), "+r"(e[63])
        : "r"(alo), "r"(blo), "r"(scale_d), "n"(DESC_A_HI), "n"(DESC_B_HI) : "memory");
}
__device__ __forceinline__ bool mma_pair(int (&d)[64], uint32_t alo, uint32_t blo, int scale_d, uint32_t bar) {
    uint32_t ok;
    asm volatile("{\n.reg .pred p, q;\n.reg .b64 da, db;\nsetp.ne.b32 p, %67, 0;\n"
        "mov.b64 da, {%65, %68};\nmov.b64 db, {%66, %69};\n"
        "wgmma.mma_async.sync.aligned.m64n128k32.s32.s8.s8 "
        "{%0, %1, %2, %3, %4, %5, %6, %7, %8, %9, %10, %11, %12, %13, %14, %15, "
        "%16, %17, %18, %19, %20, %21, %22, %23, %24, %25, %26, %27, %28, %29, %30, %31, "
        "%32, %33, %34, %35, %36, %37, %38, %39, %40, %41, %42, %43, %44, %45, %46, %47, "
        "%48, %49, %50, %51, %52, %53, %54, %55, %56, %57, %58, %59, %60, %61, %62, %63}, "
        "da, db, p;\n"
        "add.s64 da, da, 128;\nadd.s64 db, db, 2;\n"
        "wgmma.mma_async.sync.aligned.m64n128k32.s32.s8.s8 "
        "{%0, %1, %2, %3, %4, %5, %6, %7, %8, %9, %10, %11, %12, %13, %14, %15, "
        "%16, %17, %18, %19, %20, %21, %22, %23, %24, %25, %26, %27, %28, %29, %30, %31, "
        "%32, %33, %34, %35, %36, %37, %38, %39, %40, %41, %42, %43, %44, %45, %46, %47, "
        "%48, %49, %50, %51, %52, %53, %54, %55, %56, %57, %58, %59, %60, %61, %62, %63}, "
        "da, db, 1;\n"
        "add.s64 da, da, 128;\nadd.s64 db, db, 510;\n"
        "wgmma.mma_async.sync.aligned.m64n128k32.s32.s8.s8 "
        "{%0, %1, %2, %3, %4, %5, %6, %7, %8, %9, %10, %11, %12, %13, %14, %15, "
        "%16, %17, %18, %19, %20, %21, %22, %23, %24, %25, %26, %27, %28, %29, %30, %31, "
        "%32, %33, %34, %35, %36, %37, %38, %39, %40, %41, %42, %43, %44, %45, %46, %47, "
        "%48, %49, %50, %51, %52, %53, %54, %55, %56, %57, %58, %59, %60, %61, %62, %63}, "
        "da, db, 1;\n"
        "add.s64 da, da, 128;\nadd.s64 db, db, 2;\n"
        "wgmma.mma_async.sync.aligned.m64n128k32.s32.s8.s8 "
        "{%0, %1, %2, %3, %4, %5, %6, %7, %8, %9, %10, %11, %12, %13, %14, %15, "
        "%16, %17, %18, %19, %20, %21, %22, %23, %24, %25, %26, %27, %28, %29, %30, %31, "
        "%32, %33, %34, %35, %36, %37, %38, %39, %40, %41, %42, %43, %44, %45, %46, %47, "
        "%48, %49, %50, %51, %52, %53, %54, %55, %56, %57, %58, %59, %60, %61, %62, %63}, "
        "da, db, 1;\n"
        "add.s64 da, da, 128;\nadd.s64 db, db, 510;\n"
        "wgmma.mma_async.sync.aligned.m64n128k32.s32.s8.s8 "
        "{%0, %1, %2, %3, %4, %5, %6, %7, %8, %9, %10, %11, %12, %13, %14, %15, "
        "%16, %17, %18, %19, %20, %21, %22, %23, %24, %25, %26, %27, %28, %29, %30, %31, "
        "%32, %33, %34, %35, %36, %37, %38, %39, %40, %41, %42, %43, %44, %45, %46, %47, "
        "%48, %49, %50, %51, %52, %53, %54, %55, %56, %57, %58, %59, %60, %61, %62, %63}, "
        "da, db, 1;\n"
        "add.s64 da, da, 128;\nadd.s64 db, db, 2;\n"
        "mbarrier.test_wait.parity.shared::cta.b64 q, [%70], 0;\n"
        "wgmma.mma_async.sync.aligned.m64n128k32.s32.s8.s8 "
        "{%0, %1, %2, %3, %4, %5, %6, %7, %8, %9, %10, %11, %12, %13, %14, %15, "
        "%16, %17, %18, %19, %20, %21, %22, %23, %24, %25, %26, %27, %28, %29, %30, %31, "
        "%32, %33, %34, %35, %36, %37, %38, %39, %40, %41, %42, %43, %44, %45, %46, %47, "
        "%48, %49, %50, %51, %52, %53, %54, %55, %56, %57, %58, %59, %60, %61, %62, %63}, "
        "da, db, 1;\n"
        "add.s64 da, da, 128;\nadd.s64 db, db, 510;\n"
        "wgmma.mma_async.sync.aligned.m64n128k32.s32.s8.s8 "
        "{%0, %1, %2, %3, %4, %5, %6, %7, %8, %9, %10, %11, %12, %13, %14, %15, "
        "%16, %17, %18, %19, %20, %21, %22, %23, %24, %25, %26, %27, %28, %29, %30, %31, "
        "%32, %33, %34, %35, %36, %37, %38, %39, %40, %41, %42, %43, %44, %45, %46, %47, "
        "%48, %49, %50, %51, %52, %53, %54, %55, %56, %57, %58, %59, %60, %61, %62, %63}, "
        "da, db, 1;\n"
        "add.s64 da, da, 128;\nadd.s64 db, db, 2;\n"
        "wgmma.mma_async.sync.aligned.m64n128k32.s32.s8.s8 "
        "{%0, %1, %2, %3, %4, %5, %6, %7, %8, %9, %10, %11, %12, %13, %14, %15, "
        "%16, %17, %18, %19, %20, %21, %22, %23, %24, %25, %26, %27, %28, %29, %30, %31, "
        "%32, %33, %34, %35, %36, %37, %38, %39, %40, %41, %42, %43, %44, %45, %46, %47, "
        "%48, %49, %50, %51, %52, %53, %54, %55, %56, %57, %58, %59, %60, %61, %62, %63}, "
        "da, db, 1;\n"
        "wgmma.commit_group.sync.aligned;\nselp.u32 %64, 1, 0, q;\n}\n"
        : "+r"(d[0]), "+r"(d[1]), "+r"(d[2]), "+r"(d[3]), "+r"(d[4]), "+r"(d[5]), "+r"(d[6]), "+r"(d[7]),
          "+r"(d[8]), "+r"(d[9]), "+r"(d[10]), "+r"(d[11]), "+r"(d[12]), "+r"(d[13]), "+r"(d[14]), "+r"(d[15]),
          "+r"(d[16]), "+r"(d[17]), "+r"(d[18]), "+r"(d[19]), "+r"(d[20]), "+r"(d[21]), "+r"(d[22]), "+r"(d[23]),
          "+r"(d[24]), "+r"(d[25]), "+r"(d[26]), "+r"(d[27]), "+r"(d[28]), "+r"(d[29]), "+r"(d[30]), "+r"(d[31]),
          "+r"(d[32]), "+r"(d[33]), "+r"(d[34]), "+r"(d[35]), "+r"(d[36]), "+r"(d[37]), "+r"(d[38]), "+r"(d[39]),
          "+r"(d[40]), "+r"(d[41]), "+r"(d[42]), "+r"(d[43]), "+r"(d[44]), "+r"(d[45]), "+r"(d[46]), "+r"(d[47]),
          "+r"(d[48]), "+r"(d[49]), "+r"(d[50]), "+r"(d[51]), "+r"(d[52]), "+r"(d[53]), "+r"(d[54]), "+r"(d[55]),
          "+r"(d[56]), "+r"(d[57]), "+r"(d[58]), "+r"(d[59]), "+r"(d[60]), "+r"(d[61]), "+r"(d[62]), "+r"(d[63]), "=r"(ok)
        : "r"(alo), "r"(blo), "r"(scale_d), "n"(DESC_A_HI), "n"(DESC_B_HI), "r"(bar) : "memory");
    return ok;
}

__device__ __forceinline__ void wg_fence() { asm volatile("wgmma.fence.sync.aligned;" ::: "memory"); }
template <int N> __device__ __forceinline__ void wg_wait() { asm volatile("wgmma.wait_group.sync.aligned %0;" :: "n"(N) : "memory"); }

__host__ __device__ constexpr int unit_of(int wg, int s) { return wg ? (s < 16 - D_ ? D_ + 2 * s : s + 16) : (s < D_ ? s : 2 * s - D_ + 1); }

__host__ __device__ constexpr int bar_of(int u) { return u >= 32 ? u & ~1 : u < D_ || u >= 32 - D_ ? u : ((u - D_) & 1) ? D_ + ((u - D_) >> 1) : 16 + ((u - D_) >> 1); }
constexpr uint32_t step_table(int wg) {
    uint32_t t = 0;
    for (int s = 0; s < 15; s++) t |= (uint32_t)(unit_of(wg, s + 1) - unit_of(wg, s) - 1) << s;
    return t;
}
constexpr uint32_t STEPS0 = step_table(0), STEPS1 = step_table(1);
__host__ __device__ constexpr int sum_owner(int g) { return g < 8 ? (g & 4) | (g & 1) << 1 | (~g >> 1 & 1) : g; }
__device__ __forceinline__ int sum_group(int r) { return r < 8 ? (r & 4) | (~r & 1) << 1 | (r >> 1 & 1) : r; }
__device__ __forceinline__ int col_of(int c, int blk) { return (c < 7 ? blk * 7 + c : 49 + blk) * 64; }

struct JobTable { uint2 e[NCTA][NJOB + NCONV]; };
__device__ const JobTable g_jobs = {{
    {{0x0, 0x0}, {0x20400, 0x1000000}, {0x90202, 0x20080a2}, {0x100004, 0x3010144}, {0x14000000, 0x31000221}, {0x971605, 0x411429b}, {0x14102a00, 0x31004322}, {0x5d0a07, 0x409c3af}, {0x14204600, 0x31048495}, {0x250209, 0x602451f}, {0x14306200, 0x3104c5ff}, {0x2ec580b, 0x75ac66b}, {0x14407e00, 0x31090744}, {0x1732e0c, 0x82b0778}, {0x14509a00, 0x3109488a}, {0xfb1e0e, 0x91b88b9}, {0x1460b600, 0x310d89a6}, {0x1470d200, 0x310dca49}, {0x1480001c, 0x98020aeb}, {0x1490701c, 0x980a4b8e}, {0x14a00023, 0xba028c6d}, {0x14b07023, 0xba0acd60}, {0x14c0002a, 0xdc030e44}, {0x14d0702a, 0xdc0b4f18}, {0x30000000, 0x0}, {0x30000000, 0x0}, {0x30000000, 0x0}, {0x30000000, 0x0}, {0x30000000, 0x0}, {0x30000000, 0x0}, {0x30000000, 0x0}, {0x30000000, 0x0}},
    {{0x0, 0x0}, {0x420c00, 0x1080001}, {0x490a02, 0x20880a3}, {0x500804, 0x3090145}, {0x14010007, 0x2000022d}, {0x1d73e05, 0x43942a8}, {0x14112a07, 0x20004339}, {0x11d2207, 0x421c3b7}, {0x14214607, 0x200484ac}, {0xa51209, 0x6124525}, {0x14316207, 0x2004c613}, {0xad120b, 0x712c67c}, {0x14417e07, 0x20090759}, {0x2b3560c, 0x8530785}, {0x14519a07, 0x2009489e}, {0x1fb3e0e, 0x93b88c2}, {0x1461b607, 0x200d89b0}, {0x1471d207, 0x200dca53}, {0x1481071c, 0x98020af6}, {0x1491771c, 0x980a4b98}, {0x14a10723, 0xba028c7c}, {0x14b17723, 0xba0acd6f}, {0x14c1072a, 0xdc030e51}, {0x14d1772a, 0xdc0b4f25}, {0x30000000, 0x0}, {0x30000000, 0x0}, {0x30000000, 0x0}, {0x30000000, 0x0}, {0x30000000, 0x0}, {0x30000000, 0x0}, {0x30000000, 0x0}, {0x30000000, 0x0}},
    {{0x0, 0x0}, {0x821400, 0x1100002}, {0x891202, 0x21080a4}, {0x901004, 0x3110146}, {0x14020700, 0x31000238}, {0x3176605, 0x46142b8}, {0x14123100, 0x31004350}, {0x1dd3a07, 0x439c3bf}, {0x14224d00, 0x310484c4}, {0x1252209, 0x622452b}, {0x14326900, 0x3104c627}, {0x22d420b, 0x742c68c}, {0x14428500, 0x3109076d}, {0x3736e0c, 0x86b078d}, {0x1452a100, 0x310948b3}, {0x2bb560e, 0x95388cb}, {0x1462bd00, 0x310d89ba}, {0x1472d900, 0x310dca5d}, {0x14820e1c, 0x98020b00}, {0x14927e1c, 0x980a4ba3}, {0x14a20e23, 0xba028c8b}, {0x14b27e23, 0xba0acd7e}, {0x14c20e2a, 0xdc030e5e}, {0x14d27e2a, 0xdc0b4f33}, {0x30000000, 0x0}, {0x30000000, 0x0}, {0x30000000, 0x0}, {0x30000000, 0x0}, {0x30000000, 0x0}, {0x30000000, 0x0}, {0x30000000, 0x0}, {0x30000000, 0x0}},
    {{0x0, 0x0}, {0xc21c00, 0x1180004}, {0xc91a02, 0x21880a6}, {0xd01804, 0x3190148}, {0x14030707, 0x20000244}, {0x580806, 0x40982c6}, {0x14133107, 0x20004367}, {0x31d6207, 0x461c3ce}, {0x14234d07, 0x200484db}, {0x1e53a09, 0x63a4532}, {0x14336907, 0x2004c63c}, {0x36d6a0b, 0x76ac698}, {0x2f0580c, 0x75b070e}, {0x14438507, 0x20090781}, {0x2b7560d, 0x8534828}, {0x1453a107, 0x200948c7}, {0x1463bd07, 0x200d89c4}, {0x1473d907, 0x200dca67}, {0x1483151c, 0x98020b0a}, {0x1493851c, 0x980a4bad}, {0x14a31523, 0xba028c9b}, {0x14b38523, 0xba0acd8e}, {0x14c3152a, 0xdc030e6b}, {0x14d3852a, 0xdc0b4f40}, {0x30000000, 0x0}, {0x30000000, 0x0}, {0x30000000, 0x0}, {0x30000000, 0x0}, {0x30000000, 0x0}, {0x30000000, 0x0}, {0x30000000, 0x0}, {0x30000000, 0x0}},
    {{0x0, 0x0}, {0x1022400, 0x1200005}, {0x1092202, 0x22080a7}, {0x1102004, 0x3210149}, {0x14040e00, 0x3100024f}, {0x1983006, 0x43182d5}, {0x14140e0e, 0x7500437f}, {0x5e0c07, 0x509c3dd}, {0x14242a0e, 0x750084f2}, {0x2654a09, 0x64a4539}, {0x1434460e, 0x7504c650}, {0xee1c0b, 0x71ac6a8}, {0xb0100c, 0x71306f7}, {0x1444620e, 0x75050796}, {0x1b7360d, 0x833481e}, {0x14547e0e, 0x750948db}, {0x14649a0e, 0x750989ce}, {0x1474b60e, 0x750dca71}, {0x14841c1c, 0x98020b14}, {0x14948c1c, 0x980a4bb7}, {0x14a41c23, 0xba028caa}, {0x14b48c23, 0xba0acd9d}, {0x14c41c2a, 0xdc030e79}, {0x14d48c2a, 0xdc0b4f4d}, {0x30000000, 0x0}, {0x30000000, 0x0}, {0x30000000, 0x0}, {0x30000000, 0x0}, {0x30000000, 0x0}, {0x30000000, 0x0}, {0x30000000, 0x0}, {0x30000000, 0x0}},
    {{0x0, 0x0}, {0x1422c00, 0x1280007}, {0x1492a02, 0x22880a9}, {0x1502804, 0x329014b}, {0x14050e07, 0x2000025b}, {0x2d85806, 0x45982e3}, {0x14150e15, 0x64004396}, {0x19e3407, 0x531c3ec}, {0x14252a15, 0x64008509}, {0x2e55a09, 0x65a453f}, {0x14354615, 0x6404c664}, {0x22e440b, 0x742c6b4}, {0x30000c, 0x70306f2}, {0x14456215, 0x640507aa}, {0x3776e0d, 0x86b4830}, {0x14557e15, 0x640948f0}, {0x14659a15, 0x640989d9}, {0x1475b615, 0x640dca7b}, {0x1485231c, 0x98020b1e}, {0x1495931c, 0x980a4bc6}, {0x14a52323, 0xba028cb9}, {0x14b59323, 0xba0acdac}, {0x14c5232a, 0xdc030e86}, {0x14d5932a, 0xdc0b4f5b}, {0x30000000, 0x0}, {0x30000000, 0x0}, {0x30000000, 0x0}, {0x30000000, 0x0}, {0x30000000, 0x0}, {0x30000000, 0x0}, {0x30000000, 0x0}, {0x30000000, 0x0}},
    {{0x0, 0x0}, {0x1823400, 0x1300008}, {0x1893202, 0x23080aa}, {0x1903004, 0x331014c}, {0x14061500, 0x31000267}, {0x190206, 0x40182f2}, {0x1416150e, 0x750043ad}, {0x25e4c07, 0x549c3f4}, {0x1e13a08, 0x53a0478}, {0x1426310e, 0x75008521}, {0x14364d0e, 0x7504c679}, {0x36e6c0b, 0x76ac6c1}, {0x1b0300c, 0x7330701}, {0x1446690e, 0x750507be}, {0x237460d, 0x8434823}, {0x1456850e, 0x75094904}, {0x1466a10e, 0x750989e3}, {0x1476bd0e, 0x750dca86}, {0x14862a1c, 0x98020b28}, {0x14969a1c, 0x980a4bd5}, {0x14a62a23, 0xba028cc8}, {0x2af07037, 0x768d0cf4}, {0x14b69a23, 0xba0acdbb}, {0x14c62a2a, 0xdc030e93}, {0x14d69a2a, 0xdc0b4f68}, {0x30000000, 0x0}, {0x30000000, 0x0}, {0x30000000, 0x0}, {0x30000000, 0x0}, {0x30000000, 0x0}, {0x30000000, 0x0}, {0x30000000, 0x0}},
    {{0x0, 0x0}, {0x1c23c00, 0x138000a}, {0x1c93a02, 0x23880ac}, {0x1d03804, 0x339014e}, {0x14071507, 0x20000272}, {0x1592a06, 0x4298300}, {0x1dc3807, 0x439c390}, {0x14171515, 0x640043c4}, {0x1212208, 0x5220471}, {0x14273115, 0x64008538}, {0x14374d15, 0x6404c68d}, {0x12f260b, 0x722c6d3}, {0x232440c, 0x7430757}, {0x14476915, 0x640507d3}, {0x1f73e0d, 0x83b481f}, {0x14578515, 0x64094918}, {0x1467a115, 0x640989ed}, {0x1477bd15, 0x640dca90}, {0x1487311c, 0x98020b33}, {0x1497a11c, 0x980a4be5}, {0x14a73123, 0xba028cd7}, {0x2af59337, 0x998d4d40}, {0x14b7a123, 0xba0acdca}, {0x14c7312a, 0xdc030ea1}, {0x14d7a12a, 0xdc0b4f75}, {0x30000000, 0x0}, {0x30000000, 0x0}, {0x30000000, 0x0}, {0x30000000, 0x0}, {0x30000000, 0x0}, {0x30000000, 0x0}, {0x30000000, 0x0}},
    {{0x0, 0x0}, {0x2024400, 0x140000b}, {0x2094202, 0x24080ad}, {0x2104004, 0x341014f}, {0x2a271532, 0x168041f1}, {0x14081c00, 0x3100027e}, {0x3db7e06, 0x4798379}, {0x14183800, 0x310443dc}, {0x1a13208, 0x5320477}, {0x14285400, 0x3104854f}, {0x1692a0a, 0x62a85e1}, {0x14387000, 0x3108c6a1}, {0x2b1520c, 0x7530734}, {0x14488c00, 0x310907e7}, {0x2f75e0d, 0x85b482b}, {0x1458a800, 0x310d492d}, {0x3f060f, 0x903c954}, {0x1468c400, 0x310d89f7}, {0x1478c40e, 0x750dca9a}, {0x1488381c, 0x98060b3d}, {0x1498a81c, 0x980e4bf4}, {0x14a83823, 0xba068ce7}, {0x14b8a823, 0xba0ecdd9}, {0x14c8382a, 0xdc070eae}, {0x14d8a82a, 0xdc0f4f82}, {0x30000000, 0x0}, {0x30000000, 0x0}, {0x30000000, 0x0}, {0x30000000, 0x0}, {0x30000000, 0x0}, {0x30000000, 0x0}, {0x30000000, 0x0}},
    {{0x0, 0x0}, {0x2424c00, 0x148000c}, {0x2494a02, 0x24880ae}, {0x2504804, 0x3490150}, {0x2a200031, 0x8001e7}, {0x14091c07, 0x2000028a}, {0x1db3e06, 0x4398362}, {0x14193807, 0x200443f3}, {0x2614a08, 0x54a0480}, {0x14295407, 0x20048566}, {0xe91a0a, 0x61a85dc}, {0x14397007, 0x2008c6b6}, {0xf11a0c, 0x71b0722}, {0x14498c07, 0x200907fb}, {0x3b7760d, 0x8734832}, {0x1459a807, 0x200d4941}, {0x7f0e0f, 0x90bc957}, {0x1469c407, 0x200d8a01}, {0x1479c415, 0x640dcaa4}, {0x14893f1c, 0x98060b47}, {0x1499af1c, 0x980e4c03}, {0x14a93f23, 0xba068cf6}, {0x14b9af23, 0xba0ecde7}, {0x14c93f2a, 0xdc070ebb}, {0x14d9af2a, 0xdc0f4f90}, {0x30000000, 0x0}, {0x30000000, 0x0}, {0x30000000, 0x0}, {0x30000000, 0x0}, {0x30000000, 0x0}, {0x30000000, 0x0}, {0x30000000, 0x0}},
    {{0x0, 0x0}, {0x2825400, 0x150000e}, {0x2895202, 0x25080b0}, {0x2905004, 0x3510152}, {0x2a210032, 0x18001e8}, {0x140a2300, 0x31000297}, {0x31a6406, 0x4618343}, {0x141a3f00, 0x3104440a}, {0x2a15208, 0x5520482}, {0x142a5b00, 0x3104857d}, {0x1e93a0a, 0x63a85e5}, {0x143a7700, 0x3108c6ca}, {0x270480c, 0x74b0708}, {0x144a9300, 0x31090810}, {0x78080e, 0x80b883a}, {0x145aaf00, 0x310d4956}, {0x13f260f, 0x923c95e}, {0x146acb00, 0x310d8a0b}, {0x147acb0e, 0x750dcaae}, {0x148a461c, 0x98060b51}, {0x149ab61c, 0x980e4c12}, {0x14aa4623, 0xba068d05}, {0x14bab623, 0xba0ecdf4}, {0x14ca462a, 0xdc070ec8}, {0x14dab62a, 0xdc0f4f9d}, {0x30000000, 0x0}, {0x30000000, 0x0}, {0x30000000, 0x0}, {0x30000000, 0x0}, {0x30000000, 0x0}, {0x30000000, 0x0}, {0x30000000, 0x0}},
    {{0x0, 0x0}, {0x2c25c00, 0x158000f}, {0x2c95a02, 0x25880b1}, {0x2d05804, 0x3590153}, {0x2a220731, 0x78001ea}, {0x140b2307, 0x200002ae}, {0x1da3c06, 0x4398333}, {0x141b3f07, 0x20044421}, {0x3216208, 0x5620488}, {0x142b5b07, 0x20048595}, {0x2a9520a, 0x65285ee}, {0x143b7707, 0x2008c6de}, {0x1f0380c, 0x73b0702}, {0x144b9307, 0x20090824}, {0x138200e, 0x8238841}, {0x27b4e0e, 0x94b88c8}, {0x145baf07, 0x200d496a}, {0x146bcb07, 0x200d8a16}, {0x147bcb15, 0x640dcab9}, {0x148b4d1c, 0x98060b5b}, {0x149bbd1c, 0x980e4c21}, {0x14ab4d23, 0xba068d14}, {0x14bbbd23, 0xba0ece01}, {0x14cb4d2a, 0xdc070ed6}, {0x14dbbd2a, 0xdc0f4faa}, {0x30000000, 0x0}, {0x30000000, 0x0}, {0x30000000, 0x0}, {0x30000000, 0x0}, {0x30000000, 0x0}, {0x30000000, 0x0}, {0x30000000, 0x0}},
    {{0x0, 0x0}, {0x3026400, 0x1600011}, {0x3096202, 0x26080b3}, {0x3106004, 0x3610155}, {0x2a230732, 0x88001eb}, {0x140c000e, 0x750002c5}, {0xda1c06, 0x4198329}, {0x141c1c0e, 0x75004438}, {0x3a17208, 0x572048e}, {0x142c380e, 0x750485ac}, {0x3696a0a, 0x66a85f6}, {0x143c540e, 0x7504c6f3}, {0x130200c, 0x72306fc}, {0x34000d, 0x8034794}, {0x144c700e, 0x75090839}, {0x17b2e0e, 0x92b88be}, {0x145c8c0e, 0x7509497d}, {0x146ca80e, 0x750d8a20}, {0x147cd20e, 0x750dcac3}, {0x148c541c, 0x98060b66}, {0x149cc41c, 0x980e4c30}, {0x14ac5423, 0xba068d23}, {0x14bcc423, 0xba0ece0f}, {0x14cc542a, 0xdc070ee3}, {0x14dcc42a, 0xdc0f4fb8}, {0x30000000, 0x0}, {0x30000000, 0x0}, {0x30000000, 0x0}, {0x30000000, 0x0}, {0x30000000, 0x0}, {0x30000000, 0x0}, {0x30000000, 0x0}},
    {{0x0, 0x0}, {0x3426c00, 0x1680012}, {0x3496a02, 0x26880b4}, {0x3506804, 0x3690156}, {0x2a240e31, 0xe8041ed}, {0x140d0015, 0x640002dc}, {0x1a0406, 0x4018320}, {0x141d1c15, 0x64004450}, {0x620c08, 0x50a0497}, {0x142d3815, 0x640485c1}, {0x2a040a, 0x60285fd}, {0x2c000b, 0x702c64f}, {0x143d5415, 0x6404c707}, {0x3b3760c, 0x873078f}, {0x144d7015, 0x6409084d}, {0x33b660e, 0x96388d0}, {0x145d8c15, 0x64094987}, {0x146da815, 0x640d8a2a}, {0x147dd215, 0x640dcacd}, {0x148d5b1c, 0x98060b70}, {0x149dcb1c, 0x980e4c40}, {0x14ad5b23, 0xba068d32}, {0x14bdcb23, 0xba0ece1c}, {0x14cd5b2a, 0xdc070ef0}, {0x14ddcb2a, 0xdc0f4fc5}, {0x30000000, 0x0}, {0x30000000, 0x0}, {0x30000000, 0x0}, {0x30000000, 0x0}, {0x30000000, 0x0}, {0x30000000, 0x0}, {0x30000000, 0x0}},
    {{0x0, 0x0}, {0x3827400, 0x1700014}, {0x3897202, 0x27080b6}, {0x3907004, 0x3710158}, {0x2a250e32, 0xf8041ee}, {0x140e070e, 0x750002f3}, {0x3997206, 0x471831b}, {0x141e230e, 0x75004467}, {0xe21c08, 0x51a049d}, {0x1652a09, 0x62a452e}, {0x142e3f0e, 0x750485d6}, {0xac100b, 0x712c654}, {0x143e5b0e, 0x7504c71c}, {0xf4180d, 0x81b479c}, {0x144e770e, 0x75090861}, {0x13b260e, 0x92388bc}, {0x145e930e, 0x75094991}, {0x146eaf0e, 0x750d8a34}, {0x147ed90e, 0x750dcad7}, {0x148e621c, 0x98060b7a}, {0x149ed21c, 0x980e4c4f}, {0x14ae6223, 0xba068d42}, {0x14bed223, 0xba0ece29}, {0x14ce622a, 0xdc070efe}, {0x14ded22a, 0xdc0f4fd2}, {0x30000000, 0x0}, {0x30000000, 0x0}, {0x30000000, 0x0}, {0x30000000, 0x0}, {0x30000000, 0x0}, {0x30000000, 0x0}, {0x30000000, 0x0}},
    {{0x0, 0x0}, {0x3c27c00, 0x1780015}, {0x3c97a02, 0x27880b7}, {0x3d07804, 0x3790159}, {0x2a261531, 0x158041f0}, {0x140f0715, 0x6400030b}, {0x3196206, 0x4618315}, {0x21d4207, 0x441c3c3}, {0x141f2315, 0x6400447e}, {0xe51a09, 0x61a4528}, {0x142f3f15, 0x640485ea}, {0x22c400b, 0x742c663}, {0x143f5b15, 0x6404c730}, {0x2734e0c, 0x84b0783}, {0x144f7715, 0x64090876}, {0x1bb360e, 0x93388c1}, {0x145f9315, 0x6409499b}, {0x146faf15, 0x640d8a3e}, {0x147fd915, 0x640dcae1}, {0x148f691c, 0x98060b84}, {0x149fd91c, 0x980e4c5e}, {0x14af6923, 0xba068d51}, {0x14bfd923, 0xba0ece36}, {0x14cf692a, 0xdc070f0b}, {0x14dfd92a, 0xdc0f4fdf}, {0x30000000, 0x0}, {0x30000000, 0x0}, {0x30000000, 0x0}, {0x30000000, 0x0}, {0x30000000, 0x0}, {0x30000000, 0x0}, {0x30000000, 0x0}},
    {{0x0, 0x0}, {0x30600, 0x1000017}, {0xa0402, 0x20080b9}, {0x110204, 0x301015b}, {0x14e00001, 0x31000222}, {0xd71e05, 0x419429e}, {0x14f02a01, 0x31004325}, {0x2dd5a07, 0x459c3cc}, {0x15004601, 0x31048498}, {0x1a53209, 0x6324531}, {0x15106201, 0x3104c601}, {0x32c600b, 0x762c66d}, {0x15207e01, 0x31090747}, {0x3f37e0c, 0x87b0791}, {0x15309a01, 0x3109488c}, {0x23b460e, 0x94388c6}, {0x1540b601, 0x310d89a7}, {0x1550d201, 0x310dca4a}, {0x1560001d, 0x98020aed}, {0x1570701d, 0x980a4b90}, {0x15800024, 0xba028c6f}, {0x15907024, 0xba0acd62}, {0x15a0002b, 0xdc030e46}, {0x15b0702b, 0xdc0b4f1a}, {0x30000000, 0x0}, {0x30000000, 0x0}, {0x30000000, 0x0}, {0x30000000, 0x0}, {0x30000000, 0x0}, {0x30000000, 0x0}, {0x30000000, 0x0}, {0x30000000, 0x0}},
    {{0x0, 0x0}, {0x430e00, 0x1080018}, {0x4a0c02, 0x20880ba}, {0x510a04, 0x309015c}, {0x14e10008, 0x2000022e}, {0x2174605, 0x44142ac}, {0x14f12a08, 0x2000433c}, {0x3dd7a07, 0x479c3d6}, {0x15014608, 0x200484af}, {0x2254209, 0x6424536}, {0x15116208, 0x2004c615}, {0xed1a0b, 0x71ac67f}, {0x15217e08, 0x2009075b}, {0xb4100d, 0x8134799}, {0x15319a08, 0x200948a1}, {0x37b6e0e, 0x96b88d2}, {0x1541b608, 0x200d89b1}, {0x1551d208, 0x200dca54}, {0x1561071d, 0x98020af7}, {0x1571771d, 0x980a4b9a}, {0x15810724, 0xba028c7e}, {0x15917724, 0xba0acd71}, {0x15a1072b, 0xdc030e53}, {0x15b1772b, 0xdc0b4f27}, {0x30000000, 0x0}, {0x30000000, 0x0}, {0x30000000, 0x0}, {0x30000000, 0x0}, {0x30000000, 0x0}, {0x30000000, 0x0}, {0x30000000, 0x0}, {0x30000000, 0x0}},
    {{0x0, 0x0}, {0x831600, 0x1100019}, {0x8a1402, 0x21080bb}, {0x911204, 0x311015d}, {0x14e20701, 0x3100023a}, {0x3576e05, 0x46942bb}, {0x14f23101, 0x31004353}, {0x11e2407, 0x521c3e6}, {0x15024d01, 0x310484c7}, {0x2a55209, 0x652453c}, {0x15126901, 0x3104c62a}, {0x26d4a0b, 0x74ac68e}, {0x15228501, 0x3109076f}, {0x1b4300d, 0x83347a4}, {0x1532a101, 0x310948b5}, {0x3c000f, 0x903c8da}, {0x1542bd01, 0x310d89bb}, {0x1552d901, 0x310dca5e}, {0x15620e1d, 0x98020b01}, {0x15727e1d, 0x980a4ba4}, {0x15820e24, 0xba028c8d}, {0x15927e24, 0xba0acd80}, {0x15a20e2b, 0xdc030e60}, {0x15b27e2b, 0xdc0b4f35}, {0x30000000, 0x0}, {0x30000000, 0x0}, {0x30000000, 0x0}, {0x30000000, 0x0}, {0x30000000, 0x0}, {0x30000000, 0x0}, {0x30000000, 0x0}, {0x30000000, 0x0}},
    {{0x0, 0x0}, {0xc31e00, 0x118001b}, {0xca1c02, 0x21880bd}, {0xd11a04, 0x319015f}, {0x14e30708, 0x20000245}, {0x981006, 0x41182c9}, {0x14f33108, 0x2000436a}, {0x21e4407, 0x541c3f1}, {0x15034d08, 0x200484de}, {0x3256209, 0x6624542}, {0x15136908, 0x2004c63e}, {0x3ad720b, 0x772c69b}, {0x15238508, 0x20090784}, {0x2b4500d, 0x85347ae}, {0x1533a108, 0x200948ca}, {0xfc180f, 0x91bc8e2}, {0x1543bd08, 0x200d89c5}, {0x1553d908, 0x200dca68}, {0x1563151d, 0x98020b0b}, {0x1573851d, 0x980a4bae}, {0x15831524, 0xba028c9d}, {0x15938524, 0xba0acd8f}, {0x15a3152b, 0xdc030e6d}, {0x15b3852b, 0xdc0b4f42}, {0x30000000, 0x0}, {0x30000000, 0x0}, {0x30000000, 0x0}, {0x30000000, 0x0}, {0x30000000, 0x0}, {0x30000000, 0x0}, {0x30000000, 0x0}, {0x30000000, 0x0}},
    {{0x0, 0x0}, {0x1032600, 0x120001c}, {0x10a2402, 0x22080be}, {0x1112204, 0x3210160}, {0x14e40e01, 0x31000251}, {0x1d83806, 0x43982d6}, {0x14f40e0f, 0x75004382}, {0x2de5c07, 0x559c3fa}, {0x15042a0f, 0x750084f5}, {0x260409, 0x602454e}, {0x1514460f, 0x7504c652}, {0x12e240b, 0x722c6aa}, {0x1524620f, 0x75050798}, {0x3b4700d, 0x87347b8}, {0x2f8580e, 0x85b8853}, {0x15347e0f, 0x750948de}, {0x15449a0f, 0x750989d0}, {0x1554b60f, 0x750dca73}, {0x15641c1d, 0x98020b15}, {0x15748c1d, 0x980a4bb9}, {0x15841c24, 0xba028cac}, {0x15948c24, 0xba0acd9f}, {0x15a41c2b, 0xdc030e7b}, {0x15b48c2b, 0xdc0b4f4f}, {0x30000000, 0x0}, {0x30000000, 0x0}, {0x30000000, 0x0}, {0x30000000, 0x0}, {0x30000000, 0x0}, {0x30000000, 0x0}, {0x30000000, 0x0}, {0x30000000, 0x0}},
    {{0x0, 0x0}, {0x1432e00, 0x128001e}, {0x14a2c02, 0x22880c0}, {0x1512a04, 0x3290162}, {0x14e50e08, 0x2000025d}, {0x3186006, 0x46182e6}, {0x14f50e16, 0x64004399}, {0x35e6c07, 0x569c400}, {0x15052a16, 0x6400850c}, {0xe61c09, 0x61a4556}, {0x15154616, 0x6404c667}, {0x26e4c0b, 0x74ac6b7}, {0x15256216, 0x640507ad}, {0xb5120d, 0x81347c2}, {0xf8180e, 0x81b883f}, {0x15357e16, 0x640948f2}, {0x15459a16, 0x640989da}, {0x1555b616, 0x640dca7d}, {0x1565231d, 0x98020b20}, {0x1575931d, 0x980a4bc8}, {0x15852324, 0xba028cbb}, {0x15959324, 0xba0acdae}, {0x15a5232b, 0xdc030e88}, {0x15b5932b, 0xdc0b4f5c}, {0x30000000, 0x0}, {0x30000000, 0x0}, {0x30000000, 0x0}, {0x30000000, 0x0}, {0x30000000, 0x0}, {0x30000000, 0x0}, {0x30000000, 0x0}, {0x30000000, 0x0}},
    {{0x0, 0x0}, {0x1833600, 0x130001f}, {0x18a3402, 0x23080c1}, {0x1913204, 0x3310163}, {0x14e61501, 0x31000268}, {0x590a06, 0x40982f5}, {0x14f6150f, 0x750043b0}, {0x3de7c07, 0x579c404}, {0x1506310f, 0x75008523}, {0x1662c09, 0x62a455c}, {0x15164d0f, 0x7504c67b}, {0x3ae740b, 0x772c6c4}, {0x3f0780c, 0x77b0716}, {0x1526690f, 0x750507c1}, {0x1b8300e, 0x8338847}, {0x1536850f, 0x75094907}, {0x1546a10f, 0x750989e4}, {0x1556bd0f, 0x750dca87}, {0x15662a1d, 0x98020b2a}, {0x15769a1d, 0x980a4bd7}, {0x15862a24, 0xba028cca}, {0x15969a24, 0xba0acdbd}, {0x15a62a2b, 0xdc030e95}, {0x15b69a2b, 0xdc0b4f6a}, {0x30000000, 0x0}, {0x30000000, 0x0}, {0x30000000, 0x0}, {0x30000000, 0x0}, {0x30000000, 0x0}, {0x30000000, 0x0}, {0x30000000, 0x0}, {0x30000000, 0x0}},
    {{0x0, 0x0}, {0x1c33e00, 0x1380021}, {0x1ca3c02, 0x23880c3}, {0x1d13a04, 0x3390165}, {0x14e71508, 0x20000274}, {0x1993206, 0x4318303}, {0x14f71516, 0x640043c7}, {0x5f0e07, 0x509c40b}, {0x3e17a08, 0x57a048f}, {0x15073116, 0x6400853b}, {0x15174d16, 0x6404c690}, {0x16f2e0b, 0x72ac6d6}, {0xb1120c, 0x713071f}, {0x15276916, 0x640507d5}, {0x38000e, 0x8038837}, {0x15378516, 0x6409491b}, {0x1547a116, 0x640989ee}, {0x1557bd16, 0x640dca91}, {0x1567311d, 0x98020b34}, {0x1577a11d, 0x980a4be6}, {0x15873124, 0xba028cd9}, {0x2af48c37, 0x928d4d31}, {0x1597a124, 0xba0acdcc}, {0x15a7312b, 0xdc030ea3}, {0x15b7a12b, 0xdc0b4f77}, {0x30000000, 0x0}, {0x30000000, 0x0}, {0x30000000, 0x0}, {0x30000000, 0x0}, {0x30000000, 0x0}, {0x30000000, 0x0}, {0x30000000, 0x0}},
    {{0x0, 0x0}, {0x2034600, 0x1400022}, {0x20a4402, 0x24080c4}, {0x2114204, 0x3410166}, {0x2a281c31, 0x1c8081f3}, {0x14e81c01, 0x3100027f}, {0xdc1807, 0x419c386}, {0x14f83801, 0x310443de}, {0x2e15a08, 0x55a0485}, {0x15085401, 0x31048552}, {0x1a9320a, 0x63285e4}, {0x15187001, 0x3108c6a4}, {0x3b1720c, 0x773073e}, {0x15288c01, 0x310907ea}, {0x3f77e0d, 0x87b4833}, {0x1538a801, 0x310d492f}, {0xbf160f, 0x913c959}, {0x1548c401, 0x310d89f8}, {0x1558c40f, 0x750dca9b}, {0x1568381d, 0x98060b3e}, {0x1578a81d, 0x980e4bf6}, {0x15883824, 0xba068ce8}, {0x1598a824, 0xba0ecddb}, {0x15a8382b, 0xdc070eb0}, {0x15b8a82b, 0xdc0f4f84}, {0x30000000, 0x0}, {0x30000000, 0x0}, {0x30000000, 0x0}, {0x30000000, 0x0}, {0x30000000, 0x0}, {0x30000000, 0x0}, {0x30000000, 0x0}},
    {{0x0, 0x0}, {0x2434e00, 0x1480023}, {0x24a4c02, 0x24880c5}, {0x2514a04, 0x3490167}, {0x2a291c32, 0x1d8081f4}, {0x14e91c08, 0x2000028b}, {0x31b6606, 0x4618372}, {0x14f93808, 0x200443f6}, {0x3616a08, 0x56a048b}, {0x15095408, 0x20048569}, {0x2694a0a, 0x64a85eb}, {0x15197008, 0x2008c6b8}, {0x2714a0c, 0x74b0731}, {0x15298c08, 0x200907fe}, {0xb8100e, 0x813883c}, {0x1539a808, 0x200d4944}, {0x1bf360f, 0x933c964}, {0x1549c408, 0x200d8a03}, {0x1559c416, 0x640dcaa5}, {0x15693f1d, 0x98060b48}, {0x1579af1d, 0x980e4c05}, {0x15893f24, 0xba068cf8}, {0x1599af24, 0xba0ecde9}, {0x15a93f2b, 0xdc070ebd}, {0x15b9af2b, 0xdc0f4f92}, {0x30000000, 0x0}, {0x30000000, 0x0}, {0x30000000, 0x0}, {0x30000000, 0x0}, {0x30000000, 0x0}, {0x30000000, 0x0}, {0x30000000, 0x0}},
    {{0x0, 0x0}, {0x2835600, 0x1500025}, {0x28a5402, 0x25080c7}, {0x2915204, 0x3510169}, {0x2a2a2331, 0x238081f6}, {0x14ea2301, 0x31000299}, {0x5b0e06, 0x4098352}, {0x14fa3f01, 0x3104440d}, {0x220408, 0x5020494}, {0x150a5b01, 0x31048580}, {0x329620a, 0x66285f3}, {0x151a7701, 0x3108c6cd}, {0x3b0700c, 0x7730715}, {0x152a9301, 0x31090812}, {0x178280e, 0x82b8844}, {0x153aaf01, 0x310d4958}, {0x23f460f, 0x943c969}, {0x154acb01, 0x310d8a0d}, {0x155acb0f, 0x750dcab0}, {0x156a461d, 0x98060b52}, {0x157ab61d, 0x980e4c14}, {0x158a4624, 0xba068d07}, {0x159ab624, 0xba0ecdf6}, {0x15aa462b, 0xdc070eca}, {0x15bab62b, 0xdc0f4f9f}, {0x30000000, 0x0}, {0x30000000, 0x0}, {0x30000000, 0x0}, {0x30000000, 0x0}, {0x30000000, 0x0}, {0x30000000, 0x0}, {0x30000000, 0x0}},
    {{0x0, 0x0}, {0x2c35e00, 0x1580026}, {0x2ca5c02, 0x25880c8}, {0x2d15a04, 0x359016a}, {0x2a2b2332, 0x248081f7}, {0x14eb2308, 0x200002b1}, {0x39a7406, 0x4718349}, {0x14fb3f08, 0x20044424}, {0xa21408, 0x512049a}, {0x150b5b08, 0x20048598}, {0x3e97a0a, 0x67a85f9}, {0x151b7708, 0x2008c6e1}, {0x370680c, 0x76b0713}, {0x152b9308, 0x20090827}, {0x278480e, 0x84b884e}, {0x3fe7c0f, 0x97bc950}, {0x153baf08, 0x200d496c}, {0x154bcb08, 0x200d8a17}, {0x155bcb16, 0x640dcaba}, {0x156b4d1d, 0x98060b5d}, {0x157bbd1d, 0x980e4c23}, {0x158b4d24, 0xba068d16}, {0x159bbd24, 0xba0ece03}, {0x15ab4d2b, 0xdc070ed8}, {0x15bbbd2b, 0xdc0f4fac}, {0x30000000, 0x0}, {0x30000000, 0x0}, {0x30000000, 0x0}, {0x30000000, 0x0}, {0x30000000, 0x0}, {0x30000000, 0x0}, {0x30000000, 0x0}},
    {{0x0, 0x0}, {0x3036600, 0x1600028}, {0x30a6402, 0x26080ca}, {0x3116204, 0x361016c}, {0x2a2c0033, 0x280c1f8}, {0x14ec000f, 0x750002c8}, {0x25a4c06, 0x449833b}, {0x14fc1c0f, 0x7500443b}, {0x1622c08, 0x52a04a2}, {0x150c380f, 0x750485af}, {0xea1c0a, 0x61a8605}, {0x151c540f, 0x7504c6f5}, {0x2b0500c, 0x753070b}, {0x152c700f, 0x7509083b}, {0x338600e, 0x8638856}, {0x13c200f, 0x923c8e4}, {0x153c8c0f, 0x7509497e}, {0x154ca80f, 0x750d8a21}, {0x155cd20f, 0x750dcac4}, {0x156c541d, 0x98060b67}, {0x157cc41d, 0x980e4c32}, {0x158c5424, 0xba068d25}, {0x159cc424, 0xba0ece10}, {0x15ac542b, 0xdc070ee5}, {0x15bcc42b, 0xdc0f4fb9}, {0x30000000, 0x0}, {0x30000000, 0x0}, {0x30000000, 0x0}, {0x30000000, 0x0}, {0x30000000, 0x0}, {0x30000000, 0x0}, {0x30000000, 0x0}},
    {{0x0, 0x0}, {0x3436e00, 0x1680029}, {0x34a6c02, 0x26880cb}, {0x3516a04, 0x369016d}, {0x2a2d0034, 0x380c1fa}, {0x14ed0016, 0x640002df}, {0x15a2c06, 0x429832f}, {0x14fd1c16, 0x64004453}, {0x1e23c08, 0x53a04a7}, {0x150d3816, 0x640485c4}, {0x16a2c0a, 0x62a860a}, {0x16c280b, 0x72ac65b}, {0x151d5416, 0x6404c70a}, {0x74080d, 0x80b4797}, {0x152d7016, 0x6409084f}, {0x3fb7e0e, 0x97b88d6}, {0x153d8c16, 0x64094988}, {0x154da816, 0x640d8a2b}, {0x155dd216, 0x640dcace}, {0x156d5b1d, 0x98060b71}, {0x157dcb1d, 0x980e4c41}, {0x158d5b24, 0xba068d34}, {0x159dcb24, 0xba0ece1e}, {0x15ad5b2b, 0xdc070ef2}, {0x15bdcb2b, 0xdc0f4fc7}, {0x30000000, 0x0}, {0x30000000, 0x0}, {0x30000000, 0x0}, {0x30000000, 0x0}, {0x30000000, 0x0}, {0x30000000, 0x0}, {0x30000000, 0x0}},
    {{0x0, 0x0}, {0x3837600, 0x170002b}, {0x38a7402, 0x27080cd}, {0x3917204, 0x371016f}, {0x2a2e0733, 0x980c1fb}, {0x14ee070f, 0x750002f6}, {0x9a1406, 0x4118326}, {0x14fe230f, 0x7500446a}, {0x2a25408, 0x55204b1}, {0x3656a09, 0x66a4545}, {0x150e3f0f, 0x750485d8}, {0xec180b, 0x71ac656}, {0x151e5b0f, 0x7504c71e}, {0x134200d, 0x823479f}, {0x152e770f, 0x75090864}, {0x2fb5e0e, 0x95b88cd}, {0x153e930f, 0x75094993}, {0x154eaf0f, 0x750d8a35}, {0x155ed90f, 0x750dcad8}, {0x156e621d, 0x98060b7b}, {0x157ed21d, 0x980e4c51}, {0x158e6224, 0xba068d44}, {0x159ed224, 0xba0ece2b}, {0x15ae622b, 0xdc070eff}, {0x15bed22b, 0xdc0f4fd4}, {0x30000000, 0x0}, {0x30000000, 0x0}, {0x30000000, 0x0}, {0x30000000, 0x0}, {0x30000000, 0x0}, {0x30000000, 0x0}, {0x30000000, 0x0}},
    {{0x0, 0x0}, {0x3c37e00, 0x178002c}, {0x3ca7c02, 0x27880ce}, {0x3d17a04, 0x3790170}, {0x2a2f0734, 0xa80c1fd}, {0x14ef0716, 0x6400030e}, {0x3d97a06, 0x479831c}, {0x14ff2316, 0x64004481}, {0x3626c08, 0x56a04ba}, {0x3a57209, 0x6724548}, {0x150f3f16, 0x640485ed}, {0x26c480b, 0x74ac666}, {0x151f5b16, 0x6404c732}, {0x2f4580d, 0x85b47b0}, {0x152f7716, 0x64090878}, {0x3bb760e, 0x97388d5}, {0x153f9316, 0x6409499d}, {0x154faf16, 0x640d8a40}, {0x155fd916, 0x640dcae2}, {0x156f691d, 0x98060b85}, {0x157fd91d, 0x980e4c60}, {0x158f6924, 0xba068d53}, {0x159fd924, 0xba0ece38}, {0x15af692b, 0xdc070f0d}, {0x15bfd92b, 0xdc0f4fe1}, {0x30000000, 0x0}, {0x30000000, 0x0}, {0x30000000, 0x0}, {0x30000000, 0x0}, {0x30000000, 0x0}, {0x30000000, 0x0}, {0x30000000, 0x0}},
    {{0x0, 0x0}, {0x40001, 0x100402e}, {0xb0602, 0x20080d0}, {0x120404, 0x3010172}, {0x15c00002, 0x31000224}, {0x1172605, 0x42142a1}, {0x15d02a02, 0x31004328}, {0x15e04602, 0x3104849b}, {0x230608, 0x50204c2}, {0x660c09, 0x60a4550}, {0x15f06202, 0x3104c604}, {0x36c680b, 0x76ac670}, {0x16007e02, 0x31090749}, {0x1752a0d, 0x82b47ca}, {0x16109a02, 0x3109488f}, {0xbc100f, 0x913c8df}, {0x1620b602, 0x310d89a8}, {0x1630d202, 0x310dca4b}, {0x1640001e, 0x98020aee}, {0x1650701e, 0x980a4b91}, {0x16600025, 0xba028c71}, {0x16707025, 0xba0acd64}, {0x1680002c, 0xdc030e47}, {0x1690702c, 0xdc0b4f1c}, {0x30000000, 0x0}, {0x30000000, 0x0}, {0x30000000, 0x0}, {0x30000000, 0x0}, {0x30000000, 0x0}, {0x30000000, 0x0}, {0x30000000, 0x0}, {0x30000000, 0x0}},
    {{0x0, 0x0}, {0x440801, 0x108402f}, {0x4b0e02, 0x20880d1}, {0x520c04, 0x3090173}, {0x15c10009, 0x20000230}, {0x2574e05, 0x44942af}, {0x15d12a09, 0x2000433f}, {0x29e5407, 0x551c3f7}, {0x15e14609, 0x200484b2}, {0x3e57a09, 0x67a4549}, {0x15f16209, 0x2004c618}, {0x12d220b, 0x722c682}, {0x16017e09, 0x2009075e}, {0x234400d, 0x84347a9}, {0x16119a09, 0x200948a3}, {0x7c080f, 0x90bc8dd}, {0x1621b609, 0x200d89b2}, {0x1631d209, 0x200dca55}, {0x1641071e, 0x98020af8}, {0x1651771e, 0x980a4b9b}, {0x16610725, 0xba028c80}, {0x16717725, 0xba0acd73}, {0x1681072c, 0xdc030e55}, {0x1691772c, 0xdc0b4f29}, {0x30000000, 0x0}, {0x30000000, 0x0}, {0x30000000, 0x0}, {0x30000000, 0x0}, {0x30000000, 0x0}, {0x30000000, 0x0}, {0x30000000, 0x0}, {0x30000000, 0x0}},
    {{0x0, 0x0}, {0x841001, 0x1104030}, {0x8b1602, 0x21080d2}, {0x921404, 0x3110174}, {0x15c20702, 0x3100023b}, {0x3977605, 0x47142be}, {0x15d23102, 0x31004356}, {0x31e6407, 0x561c3fd}, {0x15e24d02, 0x310484ca}, {0xa61409, 0x6124553}, {0x15f26902, 0x3104c62c}, {0x2ad520b, 0x752c691}, {0x16028502, 0x31090772}, {0x334600d, 0x86347b3}, {0x1612a102, 0x310948b8}, {0x17c280f, 0x92bc8e7}, {0x1622bd02, 0x310d89bd}, {0x1632d902, 0x310dca5f}, {0x16420e1e, 0x98020b02}, {0x16527e1e, 0x980a4ba5}, {0x16620e25, 0xba028c8f}, {0x16727e25, 0xba0acd82}, {0x16820e2c, 0xdc030e62}, {0x16927e2c, 0xdc0b4f37}, {0x30000000, 0x0}, {0x30000000, 0x0}, {0x30000000, 0x0}, {0x30000000, 0x0}, {0x30000000, 0x0}, {0x30000000, 0x0}, {0x30000000, 0x0}, {0x30000000, 0x0}},
    {{0x0, 0x0}, {0xc41801, 0x1184032}, {0xcb1e02, 0x21880d4}, {0xd21c04, 0x3190176}, {0x15c30709, 0x20000247}, {0xd81806, 0x41982cc}, {0x15d33109, 0x2000436d}, {0x39e7407, 0x571c403}, {0x15e34d09, 0x200484e1}, {0x1262409, 0x6224559}, {0x15f36909, 0x2004c641}, {0x2e040b, 0x702c6a0}, {0x16038509, 0x20090786}, {0x3f4780d, 0x87b47b9}, {0x1613a109, 0x200948cc}, {0x27c480f, 0x94bc8f1}, {0x1623bd09, 0x200d89c7}, {0x1633d909, 0x200dca6a}, {0x1643151e, 0x98020b0c}, {0x1653851e, 0x980a4baf}, {0x16631525, 0xba028c9e}, {0x16738525, 0xba0acd91}, {0x1683152c, 0xdc030e6f}, {0x1693852c, 0xdc0b4f44}, {0x30000000, 0x0}, {0x30000000, 0x0}, {0x30000000, 0x0}, {0x30000000, 0x0}, {0x30000000, 0x0}, {0x30000000, 0x0}, {0x30000000, 0x0}, {0x30000000, 0x0}},
    {{0x0, 0x0}, {0x1042001, 0x1204033}, {0x10b2602, 0x22080d5}, {0x1122404, 0x3210177}, {0x15c40e02, 0x31000252}, {0x2184006, 0x44182db}, {0x15d40e10, 0x75004385}, {0x1f0607, 0x501c409}, {0x15e42a10, 0x750084f8}, {0x1e63c09, 0x63a4560}, {0x15f44610, 0x7504c655}, {0x16e2c0b, 0x72ac6ad}, {0x16046210, 0x7505079b}, {0xf51a0d, 0x81b47c5}, {0x16147e10, 0x750948e0}, {0x33c600f, 0x963c8f9}, {0x16249a10, 0x750989d1}, {0x1634b610, 0x750dca74}, {0x16441c1e, 0x98020b17}, {0x16548c1e, 0x980a4bbb}, {0x16641c25, 0xba028cae}, {0x16748c25, 0xba0acda0}, {0x16841c2c, 0xdc030e7d}, {0x16948c2c, 0xdc0b4f51}, {0x30000000, 0x0}, {0x30000000, 0x0}, {0x30000000, 0x0}, {0x30000000, 0x0}, {0x30000000, 0x0}, {0x30000000, 0x0}, {0x30000000, 0x0}, {0x30000000, 0x0}},
    {{0x0, 0x0}, {0x1442801, 0x1284035}, {0x14b2e02, 0x22880d7}, {0x1522c04, 0x3290179}, {0x15c50e09, 0x2000025e}, {0x3586806, 0x46982e9}, {0x15d50e17, 0x6400439c}, {0xdf1e07, 0x519c411}, {0x15e52a17, 0x6400850f}, {0x2a65409, 0x652456b}, {0x15f54617, 0x6404c669}, {0x2ae540b, 0x752c6ba}, {0x16056217, 0x640507af}, {0x235420d, 0x84347d1}, {0xf91a0e, 0x81b8868}, {0x16157e17, 0x640948f5}, {0x16259a17, 0x640989db}, {0x1635b617, 0x640dca7e}, {0x1645231e, 0x98020b21}, {0x1655931e, 0x980a4bca}, {0x16652325, 0xba028cbd}, {0x16759325, 0xba0acdb0}, {0x1685232c, 0xdc030e8a}, {0x1695932c, 0xdc0b4f5e}, {0x30000000, 0x0}, {0x30000000, 0x0}, {0x30000000, 0x0}, {0x30000000, 0x0}, {0x30000000, 0x0}, {0x30000000, 0x0}, {0x30000000, 0x0}, {0x30000000, 0x0}},
    {{0x0, 0x0}, {0x1843001, 0x1304036}, {0x18b3602, 0x23080d8}, {0x1923404, 0x331017a}, {0x15c61502, 0x3100026a}, {0x991206, 0x41182f8}, {0x15d61510, 0x750043b3}, {0x19f3607, 0x531c41a}, {0x15e63110, 0x75008526}, {0x3666c09, 0x66a4573}, {0x15f64d10, 0x7504c67e}, {0x3ee7c0b, 0x77ac6c5}, {0x16066910, 0x750507c3}, {0x3756a0d, 0x86b47de}, {0x3f8780e, 0x87b885c}, {0x16168510, 0x75094909}, {0x1626a110, 0x750989e5}, {0x1636bd10, 0x750dca88}, {0x16462a1e, 0x98020b2b}, {0x16569a1e, 0x980a4bd9}, {0x16662a25, 0xba028ccc}, {0x16769a25, 0xba0acdbf}, {0x16862a2c, 0xdc030e97}, {0x16969a2c, 0xdc0b4f6c}, {0x30000000, 0x0}, {0x30000000, 0x0}, {0x30000000, 0x0}, {0x30000000, 0x0}, {0x30000000, 0x0}, {0x30000000, 0x0}, {0x30000000, 0x0}, {0x30000000, 0x0}},
    {{0x0, 0x0}, {0x1c43801, 0x1384038}, {0x1cb3e02, 0x23880da}, {0x1d23c04, 0x339017c}, {0x15c71509, 0x20000275}, {0x1d93a06, 0x4398305}, {0x15d71517, 0x640043ca}, {0x21f4607, 0x541c420}, {0x15e73117, 0x6400853e}, {0x3e67c09, 0x67a4578}, {0x15f74d17, 0x6404c692}, {0x1af360b, 0x732c6d8}, {0x1f4380d, 0x83b47a5}, {0x16076917, 0x640507d8}, {0x39020e, 0x8038860}, {0x16178517, 0x6409491e}, {0x1627a117, 0x640989ef}, {0x1637bd17, 0x640dca92}, {0x1647311e, 0x98020b35}, {0x1657a11e, 0x980a4be8}, {0x16673125, 0xba028cdb}, {0x2af27e37, 0x848d0d12}, {0x1677a125, 0xba0acdce}, {0x1687312c, 0xdc030ea4}, {0x1697a12c, 0xdc0b4f79}, {0x30000000, 0x0}, {0x30000000, 0x0}, {0x30000000, 0x0}, {0x30000000, 0x0}, {0x30000000, 0x0}, {0x30000000, 0x0}, {0x30000000, 0x0}},
    {{0x0, 0x0}, {0x2044001, 0x1404039}, {0x20b4602, 0x24080db}, {0x2124404, 0x341017d}, {0x2a302a31, 0x2a8101fe}, {0x15c81c02, 0x31000281}, {0x15d83802, 0x310443e1}, {0x29f5607, 0x551c426}, {0x2224408, 0x54204ab}, {0x15e85402, 0x31048555}, {0x2e95a0a, 0x65a85f1}, {0x15f87002, 0x3108c6a6}, {0x1b1320c, 0x733072a}, {0x16088c02, 0x310907ec}, {0x238400e, 0x843884c}, {0x1618a802, 0x310d4932}, {0x17f2e0f, 0x92bc961}, {0x1628c402, 0x310d89fa}, {0x1638c410, 0x750dca9d}, {0x1648381e, 0x98060b3f}, {0x1658a81e, 0x980e4bf7}, {0x16683825, 0xba068cea}, {0x1678a825, 0xba0ecddd}, {0x1688382c, 0xdc070eb2}, {0x1698a82c, 0xdc0f4f86}, {0x30000000, 0x0}, {0x30000000, 0x0}, {0x30000000, 0x0}, {0x30000000, 0x0}, {0x30000000, 0x0}, {0x30000000, 0x0}, {0x30000000, 0x0}},
    {{0x0, 0x0}, {0x2444801, 0x148403a}, {0x24b4e02, 0x24880dc}, {0x2524c04, 0x349017e}, {0x2a312a32, 0x2b810200}, {0x15c91c09, 0x2000028c}, {0x9c1007, 0x411c383}, {0x15d93809, 0x200443f9}, {0x1222408, 0x522049f}, {0x15e95409, 0x2004856c}, {0x3a9720a, 0x67285f8}, {0x15f97009, 0x2008c6bb}, {0xb2140c, 0x7130748}, {0x16098c09, 0x20090801}, {0x1f8380e, 0x83b8848}, {0x1619a809, 0x200d4946}, {0x1ff3e0f, 0x93bc965}, {0x1629c409, 0x200d8a04}, {0x1639c417, 0x640dcaa7}, {0x16493f1e, 0x98060b4a}, {0x1659af1e, 0x980e4c07}, {0x16693f25, 0xba068cfa}, {0x1679af25, 0xba0ecdea}, {0x16893f2c, 0xdc070ebf}, {0x1699af2c, 0xdc0f4f93}, {0x30000000, 0x0}, {0x30000000, 0x0}, {0x30000000, 0x0}, {0x30000000, 0x0}, {0x30000000, 0x0}, {0x30000000, 0x0}, {0x30000000, 0x0}},
    {{0x0, 0x0}, {0x2845001, 0x150403c}, {0x28b5602, 0x25080de}, {0x2925404, 0x3510180}, {0x2a323131, 0x31810201}, {0x15ca2302, 0x3100029c}, {0x2db5e06, 0x459836f}, {0x15da3f02, 0x31044410}, {0x1a23408, 0x53204a5}, {0x15ea5b02, 0x31048583}, {0x6a0c0a, 0x60a8600}, {0x15fa7702, 0x3108c6cf}, {0x331620c, 0x7630739}, {0x160a9302, 0x31090815}, {0x2b8500e, 0x8538851}, {0x161aaf02, 0x310d495b}, {0x2bf560f, 0x953c96e}, {0x162acb02, 0x310d8a0e}, {0x163acb10, 0x750dcab1}, {0x164a461e, 0x98060b54}, {0x165ab61e, 0x980e4c16}, {0x166a4625, 0xba068d09}, {0x167ab625, 0xba0ecdf8}, {0x168a462c, 0xdc070ecc}, {0x169ab62c, 0xdc0f4fa1}, {0x30000000, 0x0}, {0x30000000, 0x0}, {0x30000000, 0x0}, {0x30000000, 0x0}, {0x30000000, 0x0}, {0x30000000, 0x0}, {0x30000000, 0x0}},
    {{0x0, 0x0}, {0x2c45801, 0x158403d}, {0x2cb5e02, 0x25880df}, {0x2d25c04, 0x3590181}, {0x2a333132, 0x32810203}, {0x15cb2309, 0x200002b4}, {0x11b2606, 0x421835a}, {0x15db3f09, 0x20044427}, {0x2624c08, 0x54a04ae}, {0x15eb5b09, 0x2004859a}, {0x12a240a, 0x6228607}, {0x15fb7709, 0x2008c6e4}, {0x131220c, 0x7230724}, {0x160b9309, 0x20090829}, {0x3b8700e, 0x873885b}, {0x161baf09, 0x200d496f}, {0x37f6e0f, 0x96bc975}, {0x162bcb09, 0x200d8a18}, {0x163bcb17, 0x640dcabb}, {0x164b4d1e, 0x98060b5e}, {0x165bbd1e, 0x980e4c25}, {0x166b4d25, 0xba068d18}, {0x167bbd25, 0xba0ece05}, {0x168b4d2c, 0xdc070eda}, {0x169bbd2c, 0xdc0f4fae}, {0x30000000, 0x0}, {0x30000000, 0x0}, {0x30000000, 0x0}, {0x30000000, 0x0}, {0x30000000, 0x0}, {0x30000000, 0x0}, {0x30000000, 0x0}},
    {{0x0, 0x0}, {0x3046001, 0x160403f}, {0x30b6602, 0x26080e1}, {0x3126404, 0x3610183}, {0x2a340e33, 0x10814204}, {0x15cc0010, 0x750002cb}, {0x3da7c06, 0x479834a}, {0x15dc1c10, 0x7500443e}, {0x3226408, 0x56204b7}, {0x15ec3810, 0x750485b2}, {0x22a440a, 0x6428612}, {0x15fc5410, 0x7504c6f8}, {0x710a0c, 0x70b071d}, {0x160c7010, 0x7509083e}, {0xb9120e, 0x8138865}, {0x37e6c0f, 0x96bc94d}, {0x161c8c10, 0x75094980}, {0x162ca810, 0x750d8a22}, {0x163cd210, 0x750dcac5}, {0x164c541e, 0x98060b68}, {0x165cc41e, 0x980e4c34}, {0x166c5425, 0xba068d27}, {0x167cc425, 0xba0ece12}, {0x168c542c, 0xdc070ee7}, {0x169cc42c, 0xdc0f4fbb}, {0x30000000, 0x0}, {0x30000000, 0x0}, {0x30000000, 0x0}, {0x30000000, 0x0}, {0x30000000, 0x0}, {0x30000000, 0x0}, {0x30000000, 0x0}},
    {{0x0, 0x0}, {0x3446801, 0x1684040}, {0x34b6e02, 0x26880e2}, {0x3526c04, 0x3690184}, {0x2a350e34, 0x11814205}, {0x15cd0017, 0x640002e2}, {0x2da5c06, 0x4598340}, {0x15dd1c17, 0x64004455}, {0x3e27c08, 0x57a04be}, {0x15ed3817, 0x640485c7}, {0x2aa540a, 0x6528617}, {0x1ed3a0b, 0x73ac688}, {0x15fd5417, 0x6404c70c}, {0x160d7017, 0x64090852}, {0x1792a0e, 0x82b886d}, {0x37c680f, 0x96bc8fb}, {0x161d8c17, 0x6409498a}, {0x162da817, 0x640d8a2d}, {0x163dd217, 0x640dcacf}, {0x164d5b1e, 0x98060b72}, {0x165dcb1e, 0x980e4c43}, {0x166d5b25, 0xba068d36}, {0x167dcb25, 0xba0ece20}, {0x168d5b2c, 0xdc070ef4}, {0x169dcb2c, 0xdc0f4fc9}, {0x30000000, 0x0}, {0x30000000, 0x0}, {0x30000000, 0x0}, {0x30000000, 0x0}, {0x30000000, 0x0}, {0x30000000, 0x0}, {0x30000000, 0x0}},
    {{0x0, 0x0}, {0x3847001, 0x1704042}, {0x38b7602, 0x27080e4}, {0x3927404, 0x3710186}, {0x2a361533, 0x17814207}, {0x15ce0710, 0x750002f9}, {0x19a3406, 0x4318332}, {0x15de2310, 0x7500446d}, {0xa31608, 0x51204c8}, {0x15ee3f10, 0x750485db}, {0x3aa740a, 0x6728621}, {0x1ec380b, 0x73ac65f}, {0x15fe5b10, 0x7504c721}, {0x274480d, 0x84b47ab}, {0x160e7710, 0x75090866}, {0x2fc580f, 0x95bc8f6}, {0x161e9310, 0x75094994}, {0x162eaf10, 0x750d8a37}, {0x163ed910, 0x750dcada}, {0x164e621e, 0x98060b7c}, {0x165ed21e, 0x980e4c53}, {0x166e6225, 0xba068d45}, {0x167ed225, 0xba0ece2d}, {0x168e622c, 0xdc070f01}, {0x169ed22c, 0xdc0f4fd6}, {0x30000000, 0x0}, {0x30000000, 0x0}, {0x30000000, 0x0}, {0x30000000, 0x0}, {0x30000000, 0x0}, {0x30000000, 0x0}, {0x30000000, 0x0}},
    {{0x0, 0x0}, {0x3c47801, 0x1784043}, {0x3cb7e02, 0x27880e5}, {0x3d27c04, 0x3790187}, {0x2a371534, 0x18814208}, {0x2995206, 0x451830f}, {0x15cf0717, 0x64000310}, {0x15df2317, 0x64004484}, {0x1232608, 0x52204ce}, {0x2e65c09, 0x65a456d}, {0x15ef3f17, 0x640485ef}, {0x1ef3e0b, 0x73ac6d9}, {0x15ff5b17, 0x6404c735}, {0x374680d, 0x86b47b5}, {0x160f7717, 0x6409087b}, {0x1fc380f, 0x93bc8eb}, {0x161f9317, 0x6409499e}, {0x162faf17, 0x640d8a41}, {0x163fd917, 0x640dcae4}, {0x164f691e, 0x98060b87}, {0x165fd91e, 0x980e4c62}, {0x166f6925, 0xba068d55}, {0x167fd925, 0xba0ece3a}, {0x168f692c, 0xdc070f0f}, {0x169fd92c, 0xdc0f4fe3}, {0x30000000, 0x0}, {0x30000000, 0x0}, {0x30000000, 0x0}, {0x30000000, 0x0}, {0x30000000, 0x0}, {0x30000000, 0x0}, {0x30000000, 0x0}},
    {{0x0, 0x0}, {0x50201, 0x1004045}, {0xc0003, 0x200c0e7}, {0x130604, 0x3010189}, {0x16a00003, 0x31000225}, {0x1572e05, 0x42942a4}, {0x16b02a03, 0x3100432b}, {0x16c04603, 0x3104849e}, {0x1e33e08, 0x53a04d5}, {0x2664c09, 0x64a4568}, {0x16d06203, 0x3104c606}, {0x3ec780b, 0x77ac674}, {0x16e07e03, 0x3109074c}, {0x1f53a0d, 0x83b47ce}, {0x16f09a03, 0x31094892}, {0x23c400f, 0x943c8ee}, {0x1700b603, 0x310d89a9}, {0x1710d203, 0x310dca4c}, {0x1720001f, 0x98020aef}, {0x1730701f, 0x980a4b92}, {0x17400026, 0xba028c73}, {0x17507026, 0xba0acd66}, {0x1760002d, 0xdc030e49}, {0x1770702d, 0xdc0b4f1e}, {0x30000000, 0x0}, {0x30000000, 0x0}, {0x30000000, 0x0}, {0x30000000, 0x0}, {0x30000000, 0x0}, {0x30000000, 0x0}, {0x30000000, 0x0}, {0x30000000, 0x0}},
    {{0x0, 0x0}, {0x450a01, 0x1084046}, {0x4c0803, 0x208c0e8}, {0x530e04, 0x309018a}, {0x16a1000a, 0x20000231}, {0x2975605, 0x45142b2}, {0x16b12a0a, 0x20004342}, {0x11f2607, 0x521c414}, {0x16c1460a, 0x200484b5}, {0x1a63409, 0x632455f}, {0x16d1620a, 0x2004c61b}, {0x16d2a0b, 0x72ac684}, {0x16e17e0a, 0x20090760}, {0x35020d, 0x80347bd}, {0x16f19a0a, 0x200948a6}, {0x1bc300f, 0x933c8e9}, {0x1701b60a, 0x200d89b4}, {0x1711d20a, 0x200dca57}, {0x1721071f, 0x98020af9}, {0x1731771f, 0x980a4b9c}, {0x17410726, 0xba028c82}, {0x17517726, 0xba0acd75}, {0x1761072d, 0xdc030e57}, {0x1771772d, 0xdc0b4f2b}, {0x30000000, 0x0}, {0x30000000, 0x0}, {0x30000000, 0x0}, {0x30000000, 0x0}, {0x30000000, 0x0}, {0x30000000, 0x0}, {0x30000000, 0x0}, {0x30000000, 0x0}},
    {{0x0, 0x0}, {0x851201, 0x1104047}, {0x8c1003, 0x210c0e9}, {0x931604, 0x311018b}, {0x16a20703, 0x3100023d}, {0x3d77e05, 0x47942bf}, {0x16b23103, 0x31004359}, {0x9f1607, 0x511c40e}, {0x16c24d03, 0x310484cc}, {0x2264409, 0x6424565}, {0x16d26903, 0x3104c62f}, {0x2ed5a0b, 0x75ac693}, {0x16e28503, 0x31090775}, {0x750a0d, 0x80b47c0}, {0x16f2a103, 0x310948ba}, {0x2bc500f, 0x953c8f4}, {0x1702bd03, 0x310d89be}, {0x1712d903, 0x310dca61}, {0x17220e1f, 0x98020b04}, {0x17327e1f, 0x980a4ba6}, {0x17420e26, 0xba028c91}, {0x17527e26, 0xba0acd84}, {0x17620e2d, 0xdc030e64}, {0x17727e2d, 0xdc0b4f38}, {0x30000000, 0x0}, {0x30000000, 0x0}, {0x30000000, 0x0}, {0x30000000, 0x0}, {0x30000000, 0x0}, {0x30000000, 0x0}, {0x30000000, 0x0}, {0x30000000, 0x0}},
    {{0x0, 0x0}, {0xc51a01, 0x1184049}, {0xcc1803, 0x218c0eb}, {0xd31e04, 0x319018d}, {0x16a3070a, 0x20000248}, {0x1182006, 0x42182cf}, {0x16b3310a, 0x20004370}, {0x15f2e07, 0x529c417}, {0x16c34d0a, 0x200484e4}, {0x3266409, 0x6624570}, {0x16d3690a, 0x2004c643}, {0x6e0c0b, 0x70ac6a3}, {0x16e3850a, 0x20090789}, {0x1b5320d, 0x83347cc}, {0x16f3a10a, 0x200948cf}, {0x3bc700f, 0x973c8fe}, {0x1703bd0a, 0x200d89c8}, {0x1713d90a, 0x200dca6b}, {0x1723151f, 0x98020b0e}, {0x1733851f, 0x980a4bb1}, {0x17431526, 0xba028ca0}, {0x17538526, 0xba0acd93}, {0x1763152d, 0xdc030e71}, {0x1773852d, 0xdc0b4f46}, {0x30000000, 0x0}, {0x30000000, 0x0}, {0x30000000, 0x0}, {0x30000000, 0x0}, {0x30000000, 0x0}, {0x30000000, 0x0}, {0x30000000, 0x0}, {0x30000000, 0x0}},
    {{0x0, 0x0}, {0x1052201, 0x120404a}, {0x10c2003, 0x220c0ec}, {0x1132604, 0x321018e}, {0x16a40e03, 0x31000254}, {0x2584806, 0x44982de}, {0x16b40e11, 0x75004387}, {0x1df3e07, 0x539c41b}, {0x16c42a11, 0x750084fb}, {0x3a67409, 0x6724576}, {0x16d44611, 0x7504c658}, {0x1ae340b, 0x732c6af}, {0x16e46211, 0x7505079d}, {0x2b5520d, 0x85347d7}, {0x16f47e11, 0x750948e3}, {0xbd120f, 0x913c908}, {0x17049a11, 0x750989d2}, {0x1714b611, 0x750dca75}, {0x17241c1f, 0x98020b18}, {0x17348c1f, 0x980a4bbd}, {0x17441c26, 0xba028cb0}, {0x17548c26, 0xba0acda2}, {0x17641c2d, 0xdc030e7e}, {0x17748c2d, 0xdc0b4f53}, {0x30000000, 0x0}, {0x30000000, 0x0}, {0x30000000, 0x0}, {0x30000000, 0x0}, {0x30000000, 0x0}, {0x30000000, 0x0}, {0x30000000, 0x0}, {0x30000000, 0x0}},
    {{0x0, 0x0}, {0x1452a01, 0x128404c}, {0x14c2803, 0x228c0ee}, {0x1532e04, 0x3290190}, {0x16a50e0a, 0x2000025f}, {0x3987006, 0x47182ec}, {0x16b50e18, 0x6400439f}, {0x25f4e07, 0x549c423}, {0x16c52a18, 0x64008512}, {0x670e09, 0x60a457f}, {0x16d54618, 0x6404c66c}, {0x2ee5c0b, 0x75ac6bc}, {0x16e56218, 0x640507b2}, {0x3b5720d, 0x87347e1}, {0x16f57e18, 0x640948f7}, {0x17d2a0f, 0x92bc910}, {0x17059a18, 0x640989dc}, {0x1715b618, 0x640dca7f}, {0x1725231f, 0x98020b22}, {0x1735931f, 0x980a4bcc}, {0x17452326, 0xba028cbf}, {0x17559326, 0xba0acdb2}, {0x1765232d, 0xdc030e8c}, {0x1775932d, 0xdc0b4f60}, {0x30000000, 0x0}, {0x30000000, 0x0}, {0x30000000, 0x0}, {0x30000000, 0x0}, {0x30000000, 0x0}, {0x30000000, 0x0}, {0x30000000, 0x0}, {0x30000000, 0x0}},
    {{0x0, 0x0}, {0x1853201, 0x130404d}, {0x18c3003, 0x230c0ef}, {0x1933604, 0x3310191}, {0x16a61503, 0x3100026b}, {0xd91a06, 0x41982fb}, {0x16b61511, 0x750043b6}, {0x31f6607, 0x561c42b}, {0x16c63111, 0x75008529}, {0x1272609, 0x6224588}, {0x16d64d11, 0x7504c680}, {0x2f060b, 0x702c6c9}, {0x16e66911, 0x750507c6}, {0x760c0d, 0x80b47e8}, {0x16f68511, 0x7509490c}, {0x23d420f, 0x943c917}, {0x1706a111, 0x750989e7}, {0x1716bd11, 0x750dca89}, {0x17262a1f, 0x98020b2c}, {0x17369a1f, 0x980a4bdb}, {0x17462a26, 0xba028cce}, {0x17569a26, 0xba0acdc1}, {0x17662a2d, 0xdc030e99}, {0x17769a2d, 0xdc0b4f6e}, {0x30000000, 0x0}, {0x30000000, 0x0}, {0x30000000, 0x0}, {0x30000000, 0x0}, {0x30000000, 0x0}, {0x30000000, 0x0}, {0x30000000, 0x0}, {0x30000000, 0x0}},
    {{0x0, 0x0}, {0x1c53a01, 0x138404f}, {0x1cc3803, 0x238c0f1}, {0x1d33e04, 0x3390193}, {0x16a7150a, 0x20000277}, {0x2194206, 0x4418309}, {0x16b71518, 0x640043cd}, {0x3df7e07, 0x579c433}, {0x16c73118, 0x64008540}, {0x1e73e09, 0x63a458f}, {0x16d74d18, 0x6404c695}, {0x22f460b, 0x742c6dd}, {0x16e76918, 0x640507da}, {0x1762c0d, 0x82b47f3}, {0x1f93a0e, 0x83b8871}, {0x16f78518, 0x64094920}, {0x1707a118, 0x640989f1}, {0x1717bd18, 0x640dca94}, {0x1727311f, 0x98020b36}, {0x1737a11f, 0x980a4bea}, {0x17473126, 0xba028cdd}, {0x2af17737, 0x7d8d0d03}, {0x1757a126, 0xba0acdd0}, {0x1767312d, 0xdc030ea6}, {0x1777a12d, 0xdc0b4f7b}, {0x30000000, 0x0}, {0x30000000, 0x0}, {0x30000000, 0x0}, {0x30000000, 0x0}, {0x30000000, 0x0}, {0x30000000, 0x0}, {0x30000000, 0x0}},
    {{0x0, 0x0}, {0x2054201, 0x1404050}, {0x20c4003, 0x240c0f2}, {0x2134604, 0x3410194}, {0x2a383831, 0x3881820a}, {0x16a81c03, 0x31000282}, {0x16b83803, 0x310443e4}, {0x600808, 0x50a043a}, {0x16c85403, 0x31048558}, {0x2674e09, 0x64a4596}, {0x1ea3c0a, 0x63a860e}, {0x16d87003, 0x3108c6a9}, {0x2724c0c, 0x74b075a}, {0x16e88c03, 0x310907ef}, {0x2794a0e, 0x84b8877}, {0x16f8a803, 0x310d4934}, {0x2ff5e0f, 0x95bc970}, {0x1708c403, 0x310d89fb}, {0x1718c411, 0x750dca9e}, {0x1728381f, 0x98060b41}, {0x1738a81f, 0x980e4bf9}, {0x17483826, 0xba068cec}, {0x1758a826, 0xba0ecddf}, {0x1768382d, 0xdc070eb4}, {0x1778a82d, 0xdc0f4f88}, {0x30000000, 0x0}, {0x30000000, 0x0}, {0x30000000, 0x0}, {0x30000000, 0x0}, {0x30000000, 0x0}, {0x30000000, 0x0}, {0x30000000, 0x0}},
    {{0x0, 0x0}, {0x2454a01, 0x1484051}, {0x24c4803, 0x248c0f3}, {0x2534e04, 0x3490195}, {0x2a393832, 0x3981820b}, {0x16a91c0a, 0x2000028e}, {0x19c3007, 0x431c38f}, {0x16b9380a, 0x200443fb}, {0x2e25c08, 0x55a04b4}, {0x16c9540a, 0x2004856f}, {0xaa140a, 0x6128602}, {0x16d9700a, 0x2008c6bd}, {0x1722c0c, 0x72b0750}, {0x16e98c0a, 0x20090803}, {0x378680e, 0x86b8858}, {0x16f9a80a, 0x200d4949}, {0x27f4e0f, 0x94bc96b}, {0x1709c40a, 0x200d8a05}, {0x1719c418, 0x640dcaa8}, {0x17293f1f, 0x98060b4b}, {0x1739af1f, 0x980e4c09}, {0x17493f26, 0xba068cfb}, {0x1759af26, 0xba0ecdec}, {0x17693f2d, 0xdc070ec1}, {0x1779af2d, 0xdc0f4f95}, {0x30000000, 0x0}, {0x30000000, 0x0}, {0x30000000, 0x0}, {0x30000000, 0x0}, {0x30000000, 0x0}, {0x30000000, 0x0}, {0x30000000, 0x0}},
    {{0x0, 0x0}, {0x2855201, 0x1504053}, {0x28c5003, 0x250c0f5}, {0x2935604, 0x3510197}, {0x2a3a3f31, 0x3f81820d}, {0x16aa2303, 0x3100029f}, {0x5c0807, 0x409c380}, {0x16ba3f03, 0x31044413}, {0x3a27408, 0x57204bc}, {0x16ca5b03, 0x31048586}, {0x1aa340a, 0x632860d}, {0x16da7703, 0x3108c6d2}, {0xf21c0c, 0x71b074b}, {0x16ea9303, 0x31090817}, {0x790a0e, 0x80b8863}, {0x16faaf03, 0x310d495d}, {0x33f660f, 0x963c973}, {0x170acb03, 0x310d8a0f}, {0x171acb11, 0x750dcab2}, {0x172a461f, 0x98060b55}, {0x173ab61f, 0x980e4c18}, {0x174a4626, 0xba068d0b}, {0x175ab626, 0xba0ecdfa}, {0x176a462d, 0xdc070ece}, {0x177ab62d, 0xdc0f4fa3}, {0x30000000, 0x0}, {0x30000000, 0x0}, {0x30000000, 0x0}, {0x30000000, 0x0}, {0x30000000, 0x0}, {0x30000000, 0x0}, {0x30000000, 0x0}},
    {{0x0, 0x0}, {0x2c55a01, 0x1584054}, {0x2cc5803, 0x258c0f6}, {0x2d35e04, 0x3590198}, {0x2a3b3f32, 0x4081820e}, {0x16ab230a, 0x200002b6}, {0x25b4e06, 0x4498369}, {0x16bb3f0a, 0x2004442a}, {0x630e08, 0x50a04c5}, {0x16cb5b0a, 0x2004859d}, {0x26a4c0a, 0x64a8614}, {0x16db770a, 0x2008c6e6}, {0x3716a0c, 0x76b073b}, {0x16eb930a, 0x2009082c}, {0x139220e, 0x823886a}, {0x16fbaf0a, 0x200d4972}, {0x170bcb0a, 0x200d8a19}, {0x171bcb18, 0x640dcabc}, {0x172b4d1f, 0x98060b5f}, {0x173bbd1f, 0x980e4c27}, {0x174b4d26, 0xba068d1a}, {0x175bbd26, 0xba0ece07}, {0x176b4d2d, 0xdc070edb}, {0x177bbd2d, 0xdc0f4fb0}, {0x30000000, 0x0}, {0x30000000, 0x0}, {0x30000000, 0x0}, {0x30000000, 0x0}, {0x30000000, 0x0}, {0x30000000, 0x0}, {0x30000000, 0x0}, {0x30000000, 0x0}},
    {{0x0, 0x0}, {0x3056201, 0x1604056}, {0x30c6003, 0x260c0f8}, {0x3136604, 0x361019a}, {0x2a3c1c33, 0x1e81c210}, {0x16ac0011, 0x750002ce}, {0x15b2e06, 0x429835d}, {0x16bc1c11, 0x75004441}, {0xe31e08, 0x51a04cb}, {0x16cc3811, 0x750485b5}, {0x32a640a, 0x662861c}, {0x16dc5411, 0x7504c6fa}, {0x231420c, 0x743072f}, {0x16ec7011, 0x75090840}, {0x239420e, 0x8438874}, {0x16fc8c11, 0x75094981}, {0x170ca811, 0x750d8a24}, {0x171cd211, 0x750dcac6}, {0x172c541f, 0x98060b69}, {0x173cc41f, 0x980e4c36}, {0x174c5426, 0xba068d29}, {0x175cc426, 0xba0ece14}, {0x176c542d, 0xdc070ee9}, {0x177cc42d, 0xdc0f4fbd}, {0x30000000, 0x0}, {0x30000000, 0x0}, {0x30000000, 0x0}, {0x30000000, 0x0}, {0x30000000, 0x0}, {0x30000000, 0x0}, {0x30000000, 0x0}, {0x30000000, 0x0}},
    {{0x0, 0x0}, {0x3456a01, 0x1684057}, {0x34c6803, 0x268c0f9}, {0x3536e04, 0x369019b}, {0x2a3d1c34, 0x1f81c211}, {0x16ad0018, 0x640002e5}, {0x1b0606, 0x401834f}, {0x16bd1c18, 0x64004458}, {0x1a33608, 0x53204d4}, {0x16cd3818, 0x640485c9}, {0x6b0e0a, 0x60a8629}, {0x16dd5418, 0x6404c70f}, {0x1712a0c, 0x72b0727}, {0x16ed7018, 0x64090855}, {0x2f95a0e, 0x85b887c}, {0x16fd8c18, 0x6409498b}, {0x170da818, 0x640d8a2e}, {0x171dd218, 0x640dcad1}, {0x172d5b1f, 0x98060b74}, {0x173dcb1f, 0x980e4c45}, {0x174d5b26, 0xba068d38}, {0x175dcb26, 0xba0ece21}, {0x176d5b2d, 0xdc070ef6}, {0x177dcb2d, 0xdc0f4fca}, {0x30000000, 0x0}, {0x30000000, 0x0}, {0x30000000, 0x0}, {0x30000000, 0x0}, {0x30000000, 0x0}, {0x30000000, 0x0}, {0x30000000, 0x0}, {0x30000000, 0x0}},
    {{0x0, 0x0}, {0x3857201, 0x1704059}, {0x38c7003, 0x270c0fb}, {0x3937604, 0x371019d}, {0x2a3e2333, 0x2581c213}, {0x16ae0711, 0x750002fc}, {0x35a6c06, 0x4698346}, {0x16be2311, 0x75004470}, {0x2634e08, 0x54a04dc}, {0x16ce3f11, 0x750485dd}, {0xeb1e0a, 0x61a862e}, {0x2ac500b, 0x752c668}, {0x16de5b11, 0x7504c723}, {0x16ee7711, 0x75090869}, {0x3f97a0e, 0x87b8885}, {0x1fd3a0f, 0x93bc913}, {0x16fe9311, 0x75094995}, {0x170eaf11, 0x750d8a38}, {0x171ed911, 0x750dcadb}, {0x172e621f, 0x98060b7e}, {0x173ed21f, 0x980e4c54}, {0x174e6226, 0xba068d47}, {0x2afdcb37, 0xd18dcdb9}, {0x175ed226, 0xba0ece2f}, {0x176e622d, 0xdc070f03}, {0x177ed22d, 0xdc0f4fd8}, {0x30000000, 0x0}, {0x30000000, 0x0}, {0x30000000, 0x0}, {0x30000000, 0x0}, {0x30000000, 0x0}, {0x30000000, 0x0}},
    {{0x0, 0x0}, {0x3c57a01, 0x178405a}, {0x3cc7803, 0x278c0fc}, {0x3d37e04, 0x379019e}, {0x2a3f2334, 0x2681c214}, {0x170605, 0x4014295}, {0x16af0718, 0x64000313}, {0x16bf2318, 0x64004487}, {0x2e35e08, 0x55a04e2}, {0x16cf3f18, 0x640485f2}, {0x16b2e0a, 0x62a8633}, {0x3ac700b, 0x772c672}, {0x16df5b18, 0x6404c738}, {0x135220d, 0x82347c7}, {0x16ef7718, 0x6409087d}, {0x13d220f, 0x923c90d}, {0x16ff9318, 0x6409499f}, {0x170faf18, 0x640d8a42}, {0x171fd918, 0x640dcae5}, {0x172f691f, 0x98060b88}, {0x173fd91f, 0x980e4c64}, {0x174f6926, 0xba068d56}, {0x175fd926, 0xba0ece3c}, {0x176f692d, 0xdc070f11}, {0x177fd92d, 0xdc0f4fe5}, {0x30000000, 0x0}, {0x30000000, 0x0}, {0x30000000, 0x0}, {0x30000000, 0x0}, {0x30000000, 0x0}, {0x30000000, 0x0}, {0x30000000, 0x0}},
    {{0x0, 0x0}, {0x60401, 0x100405c}, {0xd0203, 0x200c0fe}, {0x140005, 0x30141a0}, {0x17800004, 0x31000227}, {0x1973605, 0x43142a7}, {0x17902a04, 0x3100432d}, {0x17a04604, 0x310484a1}, {0x3636e08, 0x56a04e8}, {0x1672e09, 0x62a458a}, {0x17b06204, 0x3104c609}, {0x2d020b, 0x702c677}, {0x17c07e04, 0x3109074e}, {0x2754a0d, 0x84b47d4}, {0x17d09a04, 0x31094894}, {0x3d020f, 0x903c903}, {0x17e0b604, 0x310d89ab}, {0x17f0d204, 0x310dca4e}, {0x18000020, 0x98020af0}, {0x18107020, 0x980a4b93}, {0x18200027, 0xba028c75}, {0x18307027, 0xba0acd68}, {0x1840002e, 0xdc030e4b}, {0x1850702e, 0xdc0b4f20}, {0x30000000, 0x0}, {0x30000000, 0x0}, {0x30000000, 0x0}, {0x30000000, 0x0}, {0x30000000, 0x0}, {0x30000000, 0x0}, {0x30000000, 0x0}, {0x30000000, 0x0}},
    {{0x0, 0x0}, {0x460c01, 0x108405d}, {0x4d0a03, 0x208c0ff}, {0x540805, 0x30941a1}, {0x1781000b, 0x20000232}, {0x2d75e05, 0x45942b5}, {0x17912a0b, 0x20004345}, {0x17a1460b, 0x200484b8}, {0x240009, 0x50244f1}, {0xe71e09, 0x61a4585}, {0x17b1620b, 0x2004c61d}, {0x1ad320b, 0x732c687}, {0x17c17e0b, 0x20090763}, {0x36040d, 0x80347e6}, {0x17d19a0b, 0x200948a8}, {0x7d0a0f, 0x90bc905}, {0x17e1b60b, 0x200d89b5}, {0x17f1d20b, 0x200dca58}, {0x18010720, 0x98020afb}, {0x18117720, 0x980a4b9e}, {0x18210727, 0xba028c84}, {0x18317727, 0xba0acd77}, {0x1841072e, 0xdc030e59}, {0x1851772e, 0xdc0b4f2d}, {0x30000000, 0x0}, {0x30000000, 0x0}, {0x30000000, 0x0}, {0x30000000, 0x0}, {0x30000000, 0x0}, {0x30000000, 0x0}, {0x30000000, 0x0}, {0x30000000, 0x0}},
    {{0x0, 0x0}, {0x861401, 0x110405e}, {0x8d1203, 0x210c100}, {0x941005, 0x31141a2}, {0x17820704, 0x3100023e}, {0x180006, 0x40182c4}, {0x17923104, 0x3100435c}, {0x35f6e07, 0x569c42e}, {0x17a24d04, 0x310484cf}, {0x270609, 0x602457c}, {0x17b26904, 0x3104c631}, {0x32d620b, 0x762c696}, {0x17c28504, 0x31090777}, {0x2f55a0d, 0x85b47d9}, {0x17d2a104, 0x310948bd}, {0x3fc780f, 0x97bc8ff}, {0x17e2bd04, 0x310d89bf}, {0x17f2d904, 0x310dca62}, {0x18020e20, 0x98020b05}, {0x18127e20, 0x980a4ba8}, {0x18220e27, 0xba028c93}, {0x18327e27, 0xba0acd86}, {0x18420e2e, 0xdc030e66}, {0x18527e2e, 0xdc0b4f3a}, {0x30000000, 0x0}, {0x30000000, 0x0}, {0x30000000, 0x0}, {0x30000000, 0x0}, {0x30000000, 0x0}, {0x30000000, 0x0}, {0x30000000, 0x0}, {0x30000000, 0x0}},
    {{0x0, 0x0}, {0xc61c01, 0x1184060}, {0xcd1a03, 0x218c102}, {0xd41805, 0x31941a4}, {0x1783070b, 0x2000024a}, {0x1582806, 0x42982d2}, {0x1793310b, 0x20004373}, {0x2df5e07, 0x559c428}, {0x17a34d0b, 0x200484e7}, {0xa71609, 0x6124582}, {0x17b3690b, 0x2004c646}, {0xae140b, 0x712c6a5}, {0x17c3850b, 0x2009078b}, {0x335620d, 0x86347dc}, {0x17d3a10b, 0x200948d1}, {0xfd1a0f, 0x91bc90a}, {0x17e3bd0b, 0x200d89c9}, {0x17f3d90b, 0x200dca6c}, {0x18031520, 0x98020b0f}, {0x18138520, 0x980a4bb2}, {0x18231527, 0xba028ca2}, {0x18338527, 0xba0acd95}, {0x1843152e, 0xdc030e73}, {0x1853852e, 0xdc0b4f48}, {0x30000000, 0x0}, {0x30000000, 0x0}, {0x30000000, 0x0}, {0x30000000, 0x0}, {0x30000000, 0x0}, {0x30000000, 0x0}, {0x30000000, 0x0}, {0x30000000, 0x0}},
    {{0x0, 0x0}, {0x1062401, 0x1204061}, {0x10d2203, 0x220c103}, {0x1142005, 0x32141a5}, {0x17840e04, 0x31000255}, {0x2985006, 0x45182e1}, {0x17940e12, 0x7500438a}, {0x39f7607, 0x571c431}, {0x17a42a12, 0x750084fe}, {0x1a73609, 0x632458d}, {0x17b44612, 0x7504c65a}, {0x1ee3c0b, 0x73ac6b1}, {0x17c46212, 0x750507a0}, {0x3f57a0d, 0x87b47e2}, {0x17d47e12, 0x750948e6}, {0x1bd320f, 0x933c912}, {0x17e49a12, 0x750989d3}, {0x17f4b612, 0x750dca76}, {0x18041c20, 0x98020b19}, {0x18148c20, 0x980a4bbf}, {0x18241c27, 0xba028cb1}, {0x18348c27, 0xba0acda4}, {0x18441c2e, 0xdc030e80}, {0x18548c2e, 0xdc0b4f55}, {0x30000000, 0x0}, {0x30000000, 0x0}, {0x30000000, 0x0}, {0x30000000, 0x0}, {0x30000000, 0x0}, {0x30000000, 0x0}, {0x30000000, 0x0}, {0x30000000, 0x0}},
    {{0x0, 0x0}, {0x1462c01, 0x1284063}, {0x14d2a03, 0x228c105}, {0x1542805, 0x32941a7}, {0x17850e0b, 0x20000261}, {0x3d87806, 0x47982ee}, {0x17950e19, 0x640043a2}, {0x200008, 0x5020437}, {0x17a52a19, 0x64008515}, {0x2274609, 0x6424593}, {0x17b54619, 0x6404c66e}, {0x32e640b, 0x762c6bf}, {0x17c56219, 0x640507b4}, {0xb6140d, 0x81347eb}, {0x17d57e19, 0x640948fa}, {0x2fd5a0f, 0x95bc91f}, {0x17e59a19, 0x640989de}, {0x17f5b619, 0x640dca81}, {0x18052320, 0x98020b23}, {0x18159320, 0x980a4bce}, {0x18252327, 0xba028cc1}, {0x18359327, 0xba0acdb3}, {0x1845232e, 0xdc030e8e}, {0x1855932e, 0xdc0b4f62}, {0x30000000, 0x0}, {0x30000000, 0x0}, {0x30000000, 0x0}, {0x30000000, 0x0}, {0x30000000, 0x0}, {0x30000000, 0x0}, {0x30000000, 0x0}, {0x30000000, 0x0}},
    {{0x0, 0x0}, {0x1863401, 0x1304064}, {0x18d3203, 0x230c106}, {0x1943005, 0x33141a8}, {0x17861504, 0x3100026c}, {0x1192206, 0x42182fe}, {0x17961512, 0x750043b9}, {0xa01008, 0x512043d}, {0x17a63112, 0x7500852c}, {0x2e75e09, 0x65a459c}, {0x17b64d12, 0x7504c683}, {0xaf160b, 0x712c6ce}, {0x17c66912, 0x750507c9}, {0x1b6340d, 0x83347f5}, {0x17d68512, 0x7509490e}, {0x3fd7a0f, 0x97bc928}, {0x17e6a112, 0x750989e8}, {0x17f6bd12, 0x750dca8b}, {0x18062a20, 0x98020b2e}, {0x18169a20, 0x980a4bdd}, {0x18262a27, 0xba028cd0}, {0x18369a27, 0xba0acdc3}, {0x18462a2e, 0xdc030e9b}, {0x18569a2e, 0xdc0b4f6f}, {0x30000000, 0x0}, {0x30000000, 0x0}, {0x30000000, 0x0}, {0x30000000, 0x0}, {0x30000000, 0x0}, {0x30000000, 0x0}, {0x30000000, 0x0}, {0x30000000, 0x0}},
    {{0x0, 0x0}, {0x1c63c01, 0x1384066}, {0x1cd3a03, 0x238c108}, {0x1d43805, 0x33941aa}, {0x1787150b, 0x20000278}, {0x2594a06, 0x449830c}, {0x17971519, 0x640043d0}, {0xe01808, 0x51a0440}, {0x17a73119, 0x64008543}, {0x3a77609, 0x67245a5}, {0x17b74d19, 0x6404c697}, {0x2af560b, 0x752c6e2}, {0x17c76919, 0x640507dd}, {0x236440d, 0x84347fa}, {0x17d78519, 0x64094923}, {0x7e0c0f, 0x90bc92e}, {0x17e7a119, 0x640989f2}, {0x17f7bd19, 0x640dca95}, {0x18073120, 0x98020b38}, {0x1817a120, 0x980a4bec}, {0x18273127, 0xba028cdf}, {0x1837a127, 0xba0acdd2}, {0x1847312e, 0xdc030ea8}, {0x1857a12e, 0xdc0b4f7d}, {0x30000000, 0x0}, {0x30000000, 0x0}, {0x30000000, 0x0}, {0x30000000, 0x0}, {0x30000000, 0x0}, {0x30000000, 0x0}, {0x30000000, 0x0}, {0x30000000, 0x0}},
    {{0x0, 0x0}, {0x2064401, 0x1404067}, {0x20d4203, 0x240c109}, {0x2144005, 0x34141ab}, {0x2a404631, 0x46820215}, {0x17881c04, 0x31000284}, {0x17983804, 0x310443e7}, {0x1202008, 0x5220443}, {0x17a85404, 0x3104855b}, {0x28000a, 0x60285aa}, {0x36a6c0a, 0x66a861e}, {0x17b87004, 0x3108c6ac}, {0x17c88c04, 0x310907f1}, {0x336640d, 0x8634804}, {0x339620e, 0x863887e}, {0x17d8a804, 0x310d4937}, {0x3bf760f, 0x973c978}, {0x17e8c404, 0x310d89fc}, {0x17f8c412, 0x750dca9f}, {0x18083820, 0x98060b42}, {0x1818a820, 0x980e4bfb}, {0x18283827, 0xba068cee}, {0x1838a827, 0xba0ecde1}, {0x1848382e, 0xdc070eb5}, {0x1858a82e, 0xdc0f4f8a}, {0x30000000, 0x0}, {0x30000000, 0x0}, {0x30000000, 0x0}, {0x30000000, 0x0}, {0x30000000, 0x0}, {0x30000000, 0x0}, {0x30000000, 0x0}},
    {{0x0, 0x0}, {0x2464c01, 0x1484068}, {0x24d4a03, 0x248c10a}, {0x2544805, 0x34941ac}, {0x2a414632, 0x47820217}, {0x17891c0b, 0x2000028f}, {0x1799380b, 0x200443fe}, {0x1602808, 0x52a0445}, {0x17a9540b, 0x20048572}, {0xe8180a, 0x61a85b3}, {0x2b060a, 0x6028626}, {0x17b9700b, 0x2008c6c0}, {0x132240c, 0x723074d}, {0x17c98c0b, 0x20090806}, {0x7a0c0e, 0x90b888b}, {0x17d9a80b, 0x200d494b}, {0x17e9c40b, 0x200d8a06}, {0x17f9c419, 0x640dcaa9}, {0x18093f20, 0x98060b4c}, {0x1819af20, 0x980e4c0a}, {0x18293f27, 0xba068cfd}, {0x2af7a137, 0xa78d4d5e}, {0x1839af27, 0xba0ecdee}, {0x18493f2e, 0xdc070ec3}, {0x1859af2e, 0xdc0f4f97}, {0x30000000, 0x0}, {0x30000000, 0x0}, {0x30000000, 0x0}, {0x30000000, 0x0}, {0x30000000, 0x0}, {0x30000000, 0x0}, {0x30000000, 0x0}},
    {{0x0, 0x0}, {0x2865401, 0x150406a}, {0x28d5203, 0x250c10c}, {0x2945005, 0x35141ae}, {0x2a424d31, 0x4d820218}, {0x178a2304, 0x310002a2}, {0x11c2007, 0x421c389}, {0x179a3f04, 0x31044416}, {0x1632e08, 0x52a04d1}, {0x17aa5b04, 0x31048589}, {0x2ea5c0a, 0x65a8619}, {0x17ba7704, 0x3108c6d4}, {0x1b2340c, 0x7330752}, {0x17ca9304, 0x3109081a}, {0x1b9320e, 0x833886f}, {0x17daaf04, 0x310d4960}, {0x17eacb04, 0x310d8a11}, {0x17facb12, 0x750dcab3}, {0x180a4620, 0x98060b56}, {0x181ab620, 0x980e4c1a}, {0x182a4627, 0xba068d0c}, {0x183ab627, 0xba0ecdfc}, {0x184a462e, 0xdc070ed0}, {0x185ab62e, 0xdc0f4fa5}, {0x30000000, 0x0}, {0x30000000, 0x0}, {0x30000000, 0x0}, {0x30000000, 0x0}, {0x30000000, 0x0}, {0x30000000, 0x0}, {0x30000000, 0x0}, {0x30000000, 0x0}},
    {{0x0, 0x0}, {0x2c65c01, 0x158406b}, {0x2cd5a03, 0x258c10d}, {0x2d45805, 0x35941af}, {0x2a434d32, 0x4e82021a}, {0x178b230b, 0x200002b9}, {0x35b6e06, 0x4698375}, {0x179b3f0b, 0x2004442d}, {0x2234608, 0x54204d9}, {0x17ab5b0b, 0x200485a0}, {0x3ea7c0a, 0x67a8622}, {0x17bb770b, 0x2008c6e9}, {0x720c0c, 0x70b0746}, {0x17cb930b, 0x2009082e}, {0x2b9520e, 0x8538879}, {0x17dbaf0b, 0x200d4974}, {0x17ebcb0b, 0x200d8a1b}, {0x17fbcb19, 0x640dcabe}, {0x180b4d20, 0x98060b60}, {0x181bbd20, 0x980e4c29}, {0x182b4d27, 0xba068d1c}, {0x2afab637, 0xbc8d8d8c}, {0x183bbd27, 0xba0ece09}, {0x184b4d2e, 0xdc070edd}, {0x185bbd2e, 0xdc0f4fb2}, {0x30000000, 0x0}, {0x30000000, 0x0}, {0x30000000, 0x0}, {0x30000000, 0x0}, {0x30000000, 0x0}, {0x30000000, 0x0}, {0x30000000, 0x0}},
    {{0x0, 0x0}, {0x3066401, 0x160406d}, {0x30d6203, 0x260c10f}, {0x3146005, 0x36141b1}, {0x2a442a33, 0x2c82421b}, {0x178c0012, 0x750002d1}, {0x29b5606, 0x451836c}, {0x179c1c12, 0x75004444}, {0x2a35608, 0x55204df}, {0x17ac3812, 0x750485b7}, {0xab160a, 0x612862b}, {0x17bc5412, 0x7504c6fd}, {0x3f17a0c, 0x77b073f}, {0x17cc7012, 0x75090843}, {0x3796a0e, 0x86b8881}, {0x17dc8c12, 0x75094982}, {0x17eca812, 0x750d8a25}, {0x17fcd212, 0x750dcac8}, {0x180c5420, 0x98060b6b}, {0x181cc420, 0x980e4c38}, {0x182c5427, 0xba068d2b}, {0x183cc427, 0xba0ece16}, {0x184c542e, 0xdc070eeb}, {0x185cc42e, 0xdc0f4fbf}, {0x30000000, 0x0}, {0x30000000, 0x0}, {0x30000000, 0x0}, {0x30000000, 0x0}, {0x30000000, 0x0}, {0x30000000, 0x0}, {0x30000000, 0x0}, {0x30000000, 0x0}},
    {{0x0, 0x0}, {0x3466c01, 0x168406e}, {0x34d6a03, 0x268c110}, {0x3546805, 0x36941b2}, {0x2a452a34, 0x2d82421d}, {0x178d0019, 0x640002e8}, {0x21b4606, 0x4418366}, {0x179d1c19, 0x6400445b}, {0x3236608, 0x56204e5}, {0x17ad3819, 0x640485cc}, {0x12b260a, 0x6228630}, {0x17bd5419, 0x6404c711}, {0x32040c, 0x7030743}, {0x17cd7019, 0x64090857}, {0x3a040e, 0x9038889}, {0x17dd8c19, 0x6409498c}, {0x17eda819, 0x640d8a2f}, {0x17fdd219, 0x640dcad2}, {0x180d5b20, 0x98060b75}, {0x181dcb20, 0x980e4c47}, {0x182d5b27, 0xba068d3a}, {0x183dcb27, 0xba0ece23}, {0x184d5b2e, 0xdc070ef8}, {0x185dcb2e, 0xdc0f4fcc}, {0x30000000, 0x0}, {0x30000000, 0x0}, {0x30000000, 0x0}, {0x30000000, 0x0}, {0x30000000, 0x0}, {0x30000000, 0x0}, {0x30000000, 0x0}, {0x30000000, 0x0}},
    {{0x0, 0x0}, {0x3867401, 0x1704070}, {0x38d7203, 0x270c112}, {0x3947005, 0x37141b4}, {0x2a463133, 0x3382421e}, {0x178e0712, 0x750002ff}, {0xdb1e06, 0x4198358}, {0x179e2312, 0x75004472}, {0x3e37e08, 0x57a04ec}, {0x17ae3f12, 0x750485e0}, {0x1ab360a, 0x6328635}, {0x3ed7a0b, 0x77ac69c}, {0x17be5b12, 0x7504c726}, {0x17ce7712, 0x7509086b}, {0xfa1c0e, 0x91b8890}, {0x3ff7e0f, 0x97bc979}, {0x17de9312, 0x75094996}, {0x17eeaf12, 0x750d8a39}, {0x17fed912, 0x750dcadc}, {0x180e6220, 0x98060b7f}, {0x181ed220, 0x980e4c56}, {0x182e6227, 0xba068d49}, {0x183ed227, 0xba0ece31}, {0x184e622e, 0xdc070f05}, {0x185ed22e, 0xdc0f4fda}, {0x30000000, 0x0}, {0x30000000, 0x0}, {0x30000000, 0x0}, {0x30000000, 0x0}, {0x30000000, 0x0}, {0x30000000, 0x0}, {0x30000000, 0x0}},
    {{0x0, 0x0}, {0x3c67c01, 0x1784071}, {0x3cd7a03, 0x278c113}, {0x3d47805, 0x37941b5}, {0x2a473134, 0x34824220}, {0x570e05, 0x4094298}, {0x178f0719, 0x64000316}, {0x179f2319, 0x6400448a}, {0xa41009, 0x51244f6}, {0x17af3f19, 0x640485f4}, {0x22b460a, 0x642863a}, {0x6d0a0b, 0x70ac67a}, {0x17bf5b19, 0x6404c73a}, {0x17cf7719, 0x64090880}, {0x1fa3c0e, 0x93b8899}, {0x33e640f, 0x963c94a}, {0x17df9319, 0x640949a1}, {0x17efaf19, 0x640d8a43}, {0x17ffd919, 0x640dcae6}, {0x180f6920, 0x98060b89}, {0x181fd920, 0x980e4c66}, {0x182f6927, 0xba068d58}, {0x183fd927, 0xba0ece3e}, {0x184f692e, 0xdc070f12}, {0x185fd92e, 0xdc0f4fe7}, {0x30000000, 0x0}, {0x30000000, 0x0}, {0x30000000, 0x0}, {0x30000000, 0x0}, {0x30000000, 0x0}, {0x30000000, 0x0}, {0x30000000, 0x0}},
    {{0x0, 0x0}, {0x70601, 0x1004073}, {0xe0403, 0x200c115}, {0x150205, 0x30141b7}, {0x18600005, 0x31000228}, {0x18702a05, 0x31004330}, {0x9d1207, 0x411c3b1}, {0x18804605, 0x310484a4}, {0x1242009, 0x52244fc}, {0x128200a, 0x62285b6}, {0x18906205, 0x3104c60b}, {0x18a07e05, 0x31090751}, {0x1b3360c, 0x833077b}, {0x18b09a05, 0x31094897}, {0x2fa5c0e, 0x95b88a5}, {0x3bd720f, 0x973c926}, {0x18c0b605, 0x310d89ac}, {0x18d0d205, 0x310dca4f}, {0x18e00021, 0x98020af2}, {0x18f07021, 0x980a4b95}, {0x19000028, 0xba028c77}, {0x19107028, 0xba0acd69}, {0x1920002f, 0xdc030e4d}, {0x1930702f, 0xdc0b4f22}, {0x30000000, 0x0}, {0x30000000, 0x0}, {0x30000000, 0x0}, {0x30000000, 0x0}, {0x30000000, 0x0}, {0x30000000, 0x0}, {0x30000000, 0x0}, {0x30000000, 0x0}},
    {{0x400800, 0x80000}, {0x470e01, 0x1084074}, {0x4e0c03, 0x208c116}, {0x550a05, 0x30941b8}, {0x1861000c, 0x20000234}, {0x18712a0c, 0x20004348}, {0x15d2a07, 0x429c3ba}, {0x1881460c, 0x200484bb}, {0x1a43009, 0x5324502}, {0x68080a, 0x60a85ad}, {0x1891620c, 0x2004c620}, {0x18a17e0c, 0x20090765}, {0x2f35e0c, 0x85b0788}, {0xf61c0d, 0x81b47ed}, {0x18b19a0c, 0x200948ab}, {0x33d620f, 0x963c921}, {0x18c1b60c, 0x200d89b6}, {0x18d1d20c, 0x200dca59}, {0x18e10721, 0x98020afc}, {0x18f17721, 0x980a4b9f}, {0x19010728, 0xba028c86}, {0x19117728, 0xba0acd79}, {0x1921072f, 0xdc030e5a}, {0x1931772f, 0xdc0b4f2f}, {0x30000000, 0x0}, {0x30000000, 0x0}, {0x30000000, 0x0}, {0x30000000, 0x0}, {0x30000000, 0x0}, {0x30000000, 0x0}, {0x30000000, 0x0}, {0x30000000, 0x0}},
    {{0x801000, 0x100000}, {0x871601, 0x1104075}, {0x8e1403, 0x210c117}, {0x951205, 0x31141b9}, {0x18620705, 0x31000240}, {0x18723105, 0x3100435f}, {0x25d4a07, 0x449c3c6}, {0x18824d05, 0x310484d2}, {0x2644809, 0x54a450b}, {0x3676e09, 0x66a45a2}, {0x18926905, 0x3104c634}, {0x36f6e0b, 0x76ac6ea}, {0x18a28505, 0x3109077a}, {0x2764c0d, 0x84b47fd}, {0x18b2a105, 0x310948bf}, {0x2bd520f, 0x953c91c}, {0x18c2bd05, 0x310d89c0}, {0x18d2d905, 0x310dca63}, {0x18e20e21, 0x98020b06}, {0x18f27e21, 0x980a4ba9}, {0x19020e28, 0xba028c95}, {0x19127e28, 0xba0acd88}, {0x19220e2f, 0xdc030e68}, {0x19327e2f, 0xdc0b4f3c}, {0x30000000, 0x0}, {0x30000000, 0x0}, {0x30000000, 0x0}, {0x30000000, 0x0}, {0x30000000, 0x0}, {0x30000000, 0x0}, {0x30000000, 0x0}, {0x30000000, 0x0}},
    {{0xc01800, 0x180000}, {0xc71e01, 0x1184077}, {0xce1c03, 0x218c119}, {0xd51a05, 0x31941bb}, {0x1863070c, 0x2000024b}, {0x1873310c, 0x20004376}, {0x35d6a07, 0x469c3d1}, {0x1a03008, 0x5320448}, {0x18834d0c, 0x200484e9}, {0x2a75609, 0x6524599}, {0x1893690c, 0x2004c648}, {0x6f0e0b, 0x70ac6cb}, {0x18a3850c, 0x2009078e}, {0x136240d, 0x82347f0}, {0x18b3a10c, 0x200948d4}, {0x27d4a0f, 0x94bc91a}, {0x18c3bd0c, 0x200d89cb}, {0x18d3d90c, 0x200dca6d}, {0x18e31521, 0x98020b10}, {0x18f38521, 0x980a4bb3}, {0x19031528, 0xba028ca4}, {0x19138528, 0xba0acd97}, {0x1923152f, 0xdc030e75}, {0x1933852f, 0xdc0b4f49}, {0x30000000, 0x0}, {0x30000000, 0x0}, {0x30000000, 0x0}, {0x30000000, 0x0}, {0x30000000, 0x0}, {0x30000000, 0x0}, {0x30000000, 0x0}, {0x30000000, 0x0}},
    {{0x1002000, 0x200000}, {0x1072601, 0x1204078}, {0x10e2403, 0x220c11a}, {0x1152205, 0x32141bc}, {0x18640e05, 0x31000257}, {0x18740e13, 0x7500438d}, {0x1e0407, 0x501c3da}, {0x1e03808, 0x53a044a}, {0x18842a13, 0x75008501}, {0x3276609, 0x662459f}, {0x18944613, 0x7504c65d}, {0x26f4e0b, 0x74ac6e0}, {0x18a46213, 0x750507a2}, {0x1f63c0d, 0x83b47f6}, {0x18b47e13, 0x750948e8}, {0x37d6a0f, 0x96bc924}, {0x18c49a13, 0x750989d5}, {0x18d4b613, 0x750dca78}, {0x18e41c21, 0x98020b1a}, {0x18f48c21, 0x980a4bc0}, {0x19041c28, 0xba028cb3}, {0x19148c28, 0xba0acda6}, {0x19241c2f, 0xdc030e82}, {0x19348c2f, 0xdc0b4f57}, {0x30000000, 0x0}, {0x30000000, 0x0}, {0x30000000, 0x0}, {0x30000000, 0x0}, {0x30000000, 0x0}, {0x30000000, 0x0}, {0x30000000, 0x0}, {0x30000000, 0x0}},
    {{0x1402800, 0x280000}, {0x1472e01, 0x128407a}, {0x14e2c03, 0x228c11c}, {0x1552a05, 0x32941be}, {0x18650e0c, 0x20000262}, {0x18750e1a, 0x640043a4}, {0xde1c07, 0x519c3e3}, {0x2604808, 0x54a0451}, {0x18852a1a, 0x64008518}, {0x3e77e09, 0x67a45a6}, {0x1895461a, 0x6404c671}, {0x3af760b, 0x772c6ec}, {0x18a5621a, 0x640507b7}, {0x2b6540d, 0x85347ff}, {0x18b57e1a, 0x640948fc}, {0x3e040f, 0x903c92c}, {0x18c59a1a, 0x640989df}, {0x18d5b61a, 0x640dca82}, {0x18e52321, 0x98020b25}, {0x18f59321, 0x980a4bd0}, {0x19052328, 0xba028cc2}, {0x19159328, 0xba0acdb5}, {0x1925232f, 0xdc030e90}, {0x1935932f, 0xdc0b4f64}, {0x30000000, 0x0}, {0x30000000, 0x0}, {0x30000000, 0x0}, {0x30000000, 0x0}, {0x30000000, 0x0}, {0x30000000, 0x0}, {0x30000000, 0x0}, {0x30000000, 0x0}},
    {{0x1803000, 0x300000}, {0x1873601, 0x130407b}, {0x18e3403, 0x230c11d}, {0x1953205, 0x33141bf}, {0x18661505, 0x3100026e}, {0x18761513, 0x750043bc}, {0x1de3c07, 0x539c3ed}, {0x2a05008, 0x5520454}, {0x18863113, 0x7500852f}, {0xa8100a, 0x61285b0}, {0x18964d13, 0x7504c685}, {0xf0180c, 0x71b06f9}, {0x18a66913, 0x750507cb}, {0x3766c0d, 0x86b4807}, {0x18b68513, 0x75094911}, {0xfe1c0f, 0x91bc933}, {0x18c6a113, 0x750989e9}, {0x18d6bd13, 0x750dca8c}, {0x18e62a21, 0x98020b2f}, {0x18f69a21, 0x980a4bdf}, {0x19062a28, 0xba028cd2}, {0x19169a28, 0xba0acdc5}, {0x19262a2f, 0xdc030e9d}, {0x19369a2f, 0xdc0b4f71}, {0x30000000, 0x0}, {0x30000000, 0x0}, {0x30000000, 0x0}, {0x30000000, 0x0}, {0x30000000, 0x0}, {0x30000000, 0x0}, {0x30000000, 0x0}, {0x30000000, 0x0}},
    {{0x1c03800, 0x380000}, {0x1c73e01, 0x138407d}, {0x1ce3c03, 0x238c11f}, {0x1d53a05, 0x33941c1}, {0x1867150c, 0x2000027a}, {0x1c0007, 0x401c37d}, {0x1877151a, 0x640043d3}, {0x2204008, 0x542044e}, {0x1887311a, 0x64008546}, {0x168280a, 0x62a85b9}, {0x18974d1a, 0x6404c69a}, {0x2f15a0c, 0x75b0736}, {0x18a7691a, 0x640507df}, {0x3b6740d, 0x8734809}, {0x18b7851a, 0x64094925}, {0x23e440f, 0x943c940}, {0x18c7a11a, 0x640989f3}, {0x18d7bd1a, 0x640dca96}, {0x18e73121, 0x98020b39}, {0x18f7a121, 0x980a4bee}, {0x19073128, 0xba028ce1}, {0x1917a128, 0xba0acdd4}, {0x1927312f, 0xdc030eaa}, {0x1937a12f, 0xdc0b4f7f}, {0x30000000, 0x0}, {0x30000000, 0x0}, {0x30000000, 0x0}, {0x30000000, 0x0}, {0x30000000, 0x0}, {0x30000000, 0x0}, {0x30000000, 0x0}, {0x30000000, 0x0}},
    {{0x2004000, 0x400000}, {0x2074601, 0x140407e}, {0x20e4403, 0x240c120}, {0x2154205, 0x34141c2}, {0x18681c05, 0x31000285}, {0x19b3606, 0x4318360}, {0x18783805, 0x310443ea}, {0x2e05808, 0x55a0457}, {0x18885405, 0x3104855d}, {0x228400a, 0x64285c0}, {0x18987005, 0x3108c6ae}, {0x31020c, 0x703071a}, {0x18a88c05, 0x310907f4}, {0x770e0d, 0x80b4811}, {0x3fa7c0e, 0x97b88ae}, {0x18b8a805, 0x310d493a}, {0x18c8c405, 0x310d89fd}, {0x18d8c413, 0x750dcaa0}, {0x18e83821, 0x98060b43}, {0x18f8a821, 0x980e4bfd}, {0x19083828, 0xba068cf0}, {0x2af38537, 0x8b8d0d21}, {0x1918a828, 0xba0ecde3}, {0x1928382f, 0xdc070eb7}, {0x1938a82f, 0xdc0f4f8c}, {0x30000000, 0x0}, {0x30000000, 0x0}, {0x30000000, 0x0}, {0x30000000, 0x0}, {0x30000000, 0x0}, {0x30000000, 0x0}, {0x30000000, 0x0}},
    {{0x2404800, 0x480000}, {0x2474e01, 0x148407f}, {0x24e4c03, 0x248c121}, {0x2554a05, 0x34941c3}, {0x18691c0c, 0x20000291}, {0x29a5406, 0x451833d}, {0x1879380c, 0x20044401}, {0x3606808, 0x56a045d}, {0x1889540c, 0x20048575}, {0x2e8580a, 0x65a85c8}, {0x1899700c, 0x2008c6c2}, {0x230400c, 0x7430706}, {0x174280d, 0x82b47a1}, {0x18a98c0c, 0x20090808}, {0x13a240e, 0x9238893}, {0x18b9a80c, 0x200d494e}, {0x18c9c40c, 0x200d8a08}, {0x18d9c41a, 0x640dcaab}, {0x18e93f21, 0x98060b4d}, {0x18f9af21, 0x980e4c0c}, {0x19093f28, 0xba068cff}, {0x2af69a37, 0xa08d4d4f}, {0x1919af28, 0xba0ecdf0}, {0x19293f2f, 0xdc070ec5}, {0x1939af2f, 0xdc0f4f99}, {0x30000000, 0x0}, {0x30000000, 0x0}, {0x30000000, 0x0}, {0x30000000, 0x0}, {0x30000000, 0x0}, {0x30000000, 0x0}, {0x30000000, 0x0}},
    {{0x2805000, 0x500000}, {0x2875601, 0x1504081}, {0x28e5403, 0x250c123}, {0x2955205, 0x35141c5}, {0x2a485431, 0x5482822b}, {0x186a2305, 0x310002a5}, {0x187a3f05, 0x31044418}, {0x210208, 0x5020465}, {0x188a5b05, 0x3104858c}, {0x3a8700a, 0x67285cf}, {0x26b4e0a, 0x64a863d}, {0x189a7705, 0x3108c6d7}, {0x3726c0c, 0x76b0764}, {0x18aa9305, 0x3109081d}, {0x27a4c0e, 0x94b88a0}, {0x18baaf05, 0x310d4962}, {0x18cacb05, 0x310d8a12}, {0x18dacb13, 0x750dcab5}, {0x18ea4621, 0x98060b58}, {0x18fab621, 0x980e4c1c}, {0x190a4628, 0xba068d0e}, {0x2af9af37, 0xb58d8d7c}, {0x191ab628, 0xba0ecdfd}, {0x192a462f, 0xdc070ed2}, {0x193ab62f, 0xdc0f4fa6}, {0x30000000, 0x0}, {0x30000000, 0x0}, {0x30000000, 0x0}, {0x30000000, 0x0}, {0x30000000, 0x0}, {0x30000000, 0x0}, {0x30000000, 0x0}},
    {{0x2c05800, 0x580000}, {0x2c75e01, 0x1584082}, {0x2ce5c03, 0x258c124}, {0x2d55a05, 0x35941c6}, {0x2a495432, 0x55828237}, {0x186b230c, 0x200002bc}, {0x31c6007, 0x461c3a0}, {0x187b3f0c, 0x20044430}, {0x3a37608, 0x57204eb}, {0x188b5b0c, 0x200485a3}, {0x1eb3e0a, 0x63a8637}, {0x189b770c, 0x2008c6eb}, {0x2f25c0c, 0x75b075f}, {0x18ab930c, 0x20090831}, {0x3b9720e, 0x8738884}, {0x18bbaf0c, 0x200d4977}, {0x18cbcb0c, 0x200d8a1c}, {0x18dbcb1a, 0x640dcabf}, {0x18eb4d21, 0x98060b62}, {0x18fbbd21, 0x980e4c2b}, {0x190b4d28, 0xba068d1e}, {0x191bbd28, 0xba0ece0b}, {0x192b4d2f, 0xdc070edf}, {0x193bbd2f, 0xdc0f4fb4}, {0x30000000, 0x0}, {0x30000000, 0x0}, {0x30000000, 0x0}, {0x30000000, 0x0}, {0x30000000, 0x0}, {0x30000000, 0x0}, {0x30000000, 0x0}, {0x30000000, 0x0}},
    {{0x3006000, 0x600000}, {0x3076601, 0x1604084}, {0x30e6403, 0x260c126}, {0x3156205, 0x36141c8}, {0x2a4a5b31, 0x5b828242}, {0x186c0013, 0x750002d3}, {0x21c4007, 0x441c394}, {0x187c1c13, 0x75004447}, {0x640809, 0x50a44f4}, {0x188c3813, 0x750485ba}, {0x2ab560a, 0x652863f}, {0x189c5413, 0x7504c700}, {0x2b2540c, 0x753075c}, {0x18ac7013, 0x75090845}, {0xba140e, 0x913888e}, {0x18bc8c13, 0x75094983}, {0x18cca813, 0x750d8a26}, {0x18dcd213, 0x750dcac9}, {0x18ec5421, 0x98060b6c}, {0x18fcc421, 0x980e4c3a}, {0x190c5428, 0xba068d2d}, {0x191cc428, 0xba0ece18}, {0x192c542f, 0xdc070eed}, {0x193cc42f, 0xdc0f4fc1}, {0x30000000, 0x0}, {0x30000000, 0x0}, {0x30000000, 0x0}, {0x30000000, 0x0}, {0x30000000, 0x0}, {0x30000000, 0x0}, {0x30000000, 0x0}, {0x30000000, 0x0}},
    {{0x3406800, 0x680000}, {0x3476e01, 0x1684085}, {0x34e6c03, 0x268c127}, {0x3556a05, 0x36941c9}, {0x2a4b5b32, 0x5c82824e}, {0x186d001a, 0x640002eb}, {0x25c4807, 0x449c397}, {0x187d1c1a, 0x6400445e}, {0xe41809, 0x51a44f9}, {0x188d381a, 0x640485ce}, {0x2eb5e0a, 0x65a8642}, {0x189d541a, 0x6404c714}, {0x332640c, 0x7630761}, {0x18ad701a, 0x6409085a}, {0x17a2c0e, 0x92b8895}, {0x18bd8c1a, 0x6409498e}, {0x18cda81a, 0x640d8a30}, {0x18ddd21a, 0x640dcad3}, {0x18ed5b21, 0x98060b76}, {0x18fdcb21, 0x980e4c49}, {0x190d5b28, 0xba068d3c}, {0x191dcb28, 0xba0ece25}, {0x192d5b2f, 0xdc070efa}, {0x193dcb2f, 0xdc0f4fce}, {0x30000000, 0x0}, {0x30000000, 0x0}, {0x30000000, 0x0}, {0x30000000, 0x0}, {0x30000000, 0x0}, {0x30000000, 0x0}, {0x30000000, 0x0}, {0x30000000, 0x0}},
    {{0x3807000, 0x700000}, {0x3877601, 0x1704087}, {0x38e7403, 0x270c129}, {0x3957205, 0x37141cb}, {0x2a4c3833, 0x3a82c25a}, {0x186e0713, 0x75000302}, {0x29c5007, 0x451c39a}, {0x187e2313, 0x75004475}, {0x1642809, 0x52a44ff}, {0x188e3f13, 0x750485e3}, {0x32b660a, 0x6628644}, {0x189e5b13, 0x7504c728}, {0x3b2740c, 0x7730767}, {0x18ae7713, 0x7509086e}, {0x23a440e, 0x943889d}, {0x18be9313, 0x75094998}, {0x18ceaf13, 0x750d8a3b}, {0x18ded913, 0x750dcadd}, {0x18ee6221, 0x98060b80}, {0x18fed221, 0x980e4c58}, {0x190e6228, 0xba068d4b}, {0x191ed228, 0xba0ece33}, {0x192e622f, 0xdc070f07}, {0x193ed22f, 0xdc0f4fdc}, {0x30000000, 0x0}, {0x30000000, 0x0}, {0x30000000, 0x0}, {0x30000000, 0x0}, {0x30000000, 0x0}, {0x30000000, 0x0}, {0x30000000, 0x0}, {0x30000000, 0x0}},
    {{0x3c07800, 0x780000}, {0x3c77e01, 0x1784088}, {0x3ce7c03, 0x278c12a}, {0x3d57a05, 0x37941cc}, {0x2a4d3834, 0x3b82c265}, {0x186f071a, 0x64000319}, {0x3dc7807, 0x479c3a7}, {0x187f231a, 0x6400448d}, {0x2244009, 0x5424508}, {0x188f3f1a, 0x640485f7}, {0x3ab760a, 0x672864a}, {0x189f5b1a, 0x6404c73d}, {0xb3160c, 0x8130771}, {0x18af771a, 0x64090882}, {0x37a6c0e, 0x96b88aa}, {0x18bf931a, 0x640949a2}, {0x18cfaf1a, 0x640d8a45}, {0x18dfd91a, 0x640dcae8}, {0x18ef6921, 0x98060b8a}, {0x18ffd921, 0x980e4c67}, {0x190f6928, 0xba068d5a}, {0x191fd928, 0xba0ece40}, {0x192f692f, 0xdc070f14}, {0x193fd92f, 0xdc0f4fe9}, {0x30000000, 0x0}, {0x30000000, 0x0}, {0x30000000, 0x0}, {0x30000000, 0x0}, {0x30000000, 0x0}, {0x30000000, 0x0}, {0x30000000, 0x0}, {0x30000000, 0x0}},
    {{0x10200, 0x0}, {0x80002, 0x100808a}, {0xf0603, 0x200c12c}, {0x160405, 0x30141ce}, {0x19400006, 0x3100022a}, {0x19502a06, 0x31004335}, {0xdd1a07, 0x419c3b4}, {0x19604606, 0x310484a8}, {0x2e45809, 0x55a4511}, {0x690a0a, 0x60a85d7}, {0x19706206, 0x3104c60f}, {0x19807e06, 0x31090755}, {0x233460c, 0x8430780}, {0x19909a06, 0x3109489a}, {0x3b060e, 0x90388b1}, {0x27e4c0f, 0x94bc942}, {0x19a0b606, 0x310d89ad}, {0x19b0d206, 0x310dca50}, {0x19c00022, 0x98020af3}, {0x19d07022, 0x980a4b96}, {0x19e00029, 0xba028c78}, {0x19f07029, 0xba0acd6b}, {0x2affd937, 0xdf8dcdd7}, {0x1a000030, 0xdc030e4f}, {0x1a107030, 0xdc0b4f24}, {0x30000000, 0x0}, {0x30000000, 0x0}, {0x30000000, 0x0}, {0x30000000, 0x0}, {0x30000000, 0x0}, {0x30000000, 0x0}, {0x30000000, 0x0}},
    {{0x410a00, 0x80000}, {0x480802, 0x108808b}, {0x4f0e03, 0x208c12d}, {0x560c05, 0x30941cf}, {0x1941000d, 0x20000235}, {0x19512a0d, 0x2000434c}, {0x19d3207, 0x431c3bd}, {0x1961460d, 0x200484bf}, {0x3646809, 0x56a4516}, {0x3e8780a, 0x67a85d1}, {0x1971620d, 0x2004c623}, {0x19817e0d, 0x20090769}, {0x333660c, 0x863078a}, {0x1772e0d, 0x82b481b}, {0x19919a0d, 0x200948af}, {0x1fe3c0f, 0x93bc93c}, {0x19a1b60d, 0x200d89b7}, {0x19b1d20d, 0x200dca5a}, {0x19c10722, 0x98020afd}, {0x19d17722, 0x980a4ba0}, {0x19e10729, 0xba028c88}, {0x19f17729, 0xba0acd7b}, {0x1a010730, 0xdc030e5c}, {0x1a117730, 0xdc0b4f31}, {0x30000000, 0x0}, {0x30000000, 0x0}, {0x30000000, 0x0}, {0x30000000, 0x0}, {0x30000000, 0x0}, {0x30000000, 0x0}, {0x30000000, 0x0}, {0x30000000, 0x0}},
    {{0x811200, 0x100000}, {0x881002, 0x110808c}, {0x8f1603, 0x210c12e}, {0x961405, 0x31141d0}, {0x19420706, 0x31000241}, {0x19523106, 0x31004363}, {0x29d5207, 0x451c3c9}, {0x19624d06, 0x310484d7}, {0x3e47809, 0x57a451b}, {0x328600a, 0x66285ca}, {0x19726906, 0x3104c638}, {0x32f660b, 0x762c6e7}, {0x19828506, 0x3109077d}, {0x2f65c0d, 0x85b4802}, {0x1992a106, 0x310948c3}, {0x17e2c0f, 0x92bc938}, {0x19a2bd06, 0x310d89c2}, {0x19b2d906, 0x310dca65}, {0x19c20e22, 0x98020b07}, {0x19d27e22, 0x980a4baa}, {0x19e20e29, 0xba028c97}, {0x19f27e29, 0xba0acd8a}, {0x1a020e30, 0xdc030e6a}, {0x1a127e30, 0xdc0b4f3e}, {0x30000000, 0x0}, {0x30000000, 0x0}, {0x30000000, 0x0}, {0x30000000, 0x0}, {0x30000000, 0x0}, {0x30000000, 0x0}, {0x30000000, 0x0}, {0x30000000, 0x0}},
    {{0xc11a00, 0x180000}, {0xc81802, 0x118808e}, {0xcf1e03, 0x218c130}, {0xd61c05, 0x31941d2}, {0x1943070d, 0x2000024d}, {0x1953310d, 0x2000437a}, {0x39d7207, 0x471c3d4}, {0x19634d0d, 0x200484ee}, {0x650a09, 0x60a4522}, {0x268480a, 0x64a85c3}, {0x1973690d, 0x2004c64c}, {0xef1e0b, 0x71ac6d0}, {0x1983850d, 0x20090792}, {0x137260d, 0x8234819}, {0x1993a10d, 0x200948d8}, {0x13e240f, 0x923c936}, {0x19a3bd0d, 0x200d89cc}, {0x19b3d90d, 0x200dca6f}, {0x19c31522, 0x98020b12}, {0x19d38522, 0x980a4bb4}, {0x19e31529, 0xba028ca6}, {0x19f38529, 0xba0acd99}, {0x1a031530, 0xdc030e77}, {0x1a138530, 0xdc0b4f4b}, {0x30000000, 0x0}, {0x30000000, 0x0}, {0x30000000, 0x0}, {0x30000000, 0x0}, {0x30000000, 0x0}, {0x30000000, 0x0}, {0x30000000, 0x0}, {0x30000000, 0x0}},
    {{0x1012200, 0x200000}, {0x1082002, 0x120808f}, {0x10f2603, 0x220c131}, {0x1162405, 0x32141d3}, {0x19440e06, 0x31000258}, {0x19540e14, 0x75004392}, {0x9e1407, 0x511c3e0}, {0x3a07008, 0x5720460}, {0x19642a14, 0x75008505}, {0x1a8300a, 0x63285bb}, {0x19744614, 0x7504c660}, {0x2ef5e0b, 0x75ac6e5}, {0x19846214, 0x750507a6}, {0x3f67c0d, 0x87b480b}, {0x19947e14, 0x750948ec}, {0xbe140f, 0x913c931}, {0x19a49a14, 0x750989d6}, {0x19b4b614, 0x750dca79}, {0x19c41c22, 0x98020b1c}, {0x19d48c22, 0x980a4bc2}, {0x19e41c29, 0xba028cb5}, {0x19f48c29, 0xba0acda8}, {0x1a041c30, 0xdc030e84}, {0x1a148c30, 0xdc0b4f59}, {0x30000000, 0x0}, {0x30000000, 0x0}, {0x30000000, 0x0}, {0x30000000, 0x0}, {0x30000000, 0x0}, {0x30000000, 0x0}, {0x30000000, 0x0}, {0x30000000, 0x0}},
    {{0x1412a00, 0x280000}, {0x1482802, 0x1288091}, {0x14f2e03, 0x228c133}, {0x1562c05, 0x32941d5}, {0x19450e0d, 0x20000264}, {0x19550e1b, 0x640043a9}, {0x15e2c07, 0x529c3e9}, {0x610a08, 0x50a0468}, {0x19652a1b, 0x6400851c}, {0x1e8380a, 0x63a85bc}, {0x1975461b, 0x6404c675}, {0x3ef7e0b, 0x77ac6ee}, {0x1985621b, 0x640507bb}, {0xb7160d, 0x8134814}, {0x19957e1b, 0x64094900}, {0x1be340f, 0x933c93b}, {0x19a59a1b, 0x640989e0}, {0x19b5b61b, 0x640dca83}, {0x19c52322, 0x98020b26}, {0x19d59322, 0x980a4bd2}, {0x19e52329, 0xba028cc4}, {0x19f59329, 0xba0acdb7}, {0x1a052330, 0xdc030e91}, {0x1a159330, 0xdc0b4f66}, {0x30000000, 0x0}, {0x30000000, 0x0}, {0x30000000, 0x0}, {0x30000000, 0x0}, {0x30000000, 0x0}, {0x30000000, 0x0}, {0x30000000, 0x0}, {0x30000000, 0x0}},
    {{0x1813200, 0x300000}, {0x1883002, 0x1308092}, {0x18f3603, 0x230c134}, {0x1963405, 0x33141d6}, {0x19461506, 0x3100026f}, {0x15c2807, 0x429c38c}, {0x19561514, 0x750043c0}, {0x3206008, 0x562045a}, {0x19663114, 0x75008533}, {0x2a8500a, 0x65285c5}, {0x19764d14, 0x7504c689}, {0x1f23c0c, 0x73b0754}, {0x19866914, 0x750507cf}, {0x37060d, 0x803480f}, {0x19968514, 0x75094915}, {0x2be540f, 0x953c945}, {0x19a6a114, 0x750989ea}, {0x19b6bd14, 0x750dca8d}, {0x19c62a22, 0x98020b30}, {0x19d69a22, 0x980a4be1}, {0x19e62a29, 0xba028cd4}, {0x19f69a29, 0xba0acdc6}, {0x1a062a30, 0xdc030e9f}, {0x1a169a30, 0xdc0b4f73}, {0x30000000, 0x0}, {0x30000000, 0x0}, {0x30000000, 0x0}, {0x30000000, 0x0}, {0x30000000, 0x0}, {0x30000000, 0x0}, {0x30000000, 0x0}, {0x30000000, 0x0}},
    {{0x1c13a00, 0x380000}, {0x1c83802, 0x1388094}, {0x1cf3e03, 0x238c136}, {0x1d63c05, 0x33941d8}, {0x1947150d, 0x2000027b}, {0x39b7606, 0x4718377}, {0x1957151b, 0x640043d7}, {0x3e07808, 0x57a0461}, {0x1967311b, 0x6400854b}, {0x368680a, 0x66a85cd}, {0x19774d1b, 0x6404c69e}, {0x1f13a0c, 0x73b072b}, {0x1987691b, 0x640507e3}, {0xf71e0d, 0x81b4816}, {0x1997851b, 0x64094929}, {0x2fe5c0f, 0x95bc948}, {0x19a7a11b, 0x640989f5}, {0x19b7bd1b, 0x640dca97}, {0x19c73122, 0x98020b3a}, {0x19d7a122, 0x980a4bf0}, {0x19e73129, 0xba028ce3}, {0x19f7a129, 0xba0acdd6}, {0x1a073130, 0xdc030eac}, {0x1a17a130, 0xdc0b4f80}, {0x30000000, 0x0}, {0x30000000, 0x0}, {0x30000000, 0x0}, {0x30000000, 0x0}, {0x30000000, 0x0}, {0x30000000, 0x0}, {0x30000000, 0x0}, {0x30000000, 0x0}},
    {{0x2014200, 0x400000}, {0x2084002, 0x1408095}, {0x20f4603, 0x240c137}, {0x2164405, 0x34141d9}, {0x19481c06, 0x31000287}, {0x9b1606, 0x4118355}, {0x19583806, 0x310443ee}, {0xa11208, 0x512046b}, {0x19685406, 0x31048562}, {0x29020a, 0x60285d5}, {0x19787006, 0x3108c6b2}, {0x330600c, 0x7630710}, {0x19888c06, 0x310907f8}, {0x2774e0d, 0x84b4825}, {0x1998a806, 0x310d493d}, {0x3be740f, 0x973c94f}, {0x19a8c406, 0x310d89ff}, {0x19b8c414, 0x750dcaa2}, {0x19c83822, 0x98060b44}, {0x19d8a822, 0x980e4bff}, {0x19e83829, 0xba068cf2}, {0x19f8a829, 0xba0ecde5}, {0x1a083830, 0xdc070eb9}, {0x1a18a830, 0xdc0f4f8e}, {0x30000000, 0x0}, {0x30000000, 0x0}, {0x30000000, 0x0}, {0x30000000, 0x0}, {0x30000000, 0x0}, {0x30000000, 0x0}, {0x30000000, 0x0}, {0x30000000, 0x0}},
    {{0x2414a00, 0x480000}, {0x2484802, 0x1488096}, {0x24f4e03, 0x248c138}, {0x2564c05, 0x34941da}, {0x19491c0d, 0x20000292}, {0x21a4406, 0x4418338}, {0x1959380d, 0x20044406}, {0xe11a08, 0x51a046e}, {0x1969540d, 0x20048579}, {0xa9120a, 0x61285da}, {0x1979700d, 0x2008c6c6}, {0x170280c, 0x72b06fe}, {0x19898c0d, 0x2009080c}, {0x337660d, 0x863482d}, {0x1999a80d, 0x200d4952}, {0xff1e0f, 0x91bc95c}, {0x19a9c40d, 0x200d8a09}, {0x19b9c41b, 0x640dcaac}, {0x19c93f22, 0x98060b4f}, {0x19d9af22, 0x980e4c0e}, {0x19e93f29, 0xba068d01}, {0x19f9af29, 0xba0ecdf2}, {0x1a093f30, 0xdc070ec7}, {0x1a19af30, 0xdc0f4f9b}, {0x30000000, 0x0}, {0x30000000, 0x0}, {0x30000000, 0x0}, {0x30000000, 0x0}, {0x30000000, 0x0}, {0x30000000, 0x0}, {0x30000000, 0x0}, {0x30000000, 0x0}},
    {{0x2815200, 0x500000}, {0x2885002, 0x1508098}, {0x28f5603, 0x250c13a}, {0x2965405, 0x35141dc}, {0x194a2306, 0x310002a9}, {0x11a2406, 0x421832c}, {0x195a3f06, 0x3104441d}, {0x1612a08, 0x52a0474}, {0x196a5b06, 0x31048590}, {0x129220a, 0x62285df}, {0x197a7706, 0x3108c6db}, {0x70080c, 0x70b06f4}, {0x1f33e0c, 0x83b077c}, {0x198a9306, 0x31090820}, {0x2ba540e, 0x95388a2}, {0x199aaf06, 0x310d4966}, {0x19aacb06, 0x310d8a13}, {0x19bacb14, 0x750dcab6}, {0x19ca4622, 0x98060b59}, {0x19dab622, 0x980e4c1d}, {0x19ea4629, 0xba068d10}, {0x2af8a837, 0xae8d8d6d}, {0x19fab629, 0xba0ecdff}, {0x1a0a4630, 0xdc070ed4}, {0x1a1ab630, 0xdc0f4fa8}, {0x30000000, 0x0}, {0x30000000, 0x0}, {0x30000000, 0x0}, {0x30000000, 0x0}, {0x30000000, 0x0}, {0x30000000, 0x0}, {0x30000000, 0x0}},
    {{0x2c15a00, 0x580000}, {0x2c85802, 0x1588099}, {0x2cf5e03, 0x258c13b}, {0x2d65c05, 0x35941dd}, {0x194b230d, 0x200002c1}, {0x5a0c06, 0x4098323}, {0x195b3f0d, 0x20044434}, {0x2214208, 0x542047d}, {0x196b5b0d, 0x200485a7}, {0x229420a, 0x64285e9}, {0x1ac300b, 0x732c65e}, {0x197b770d, 0x2008c6ef}, {0xf31e0c, 0x81b0773}, {0x198b930d, 0x20090835}, {0xbb160e, 0x91388b6}, {0x199baf0d, 0x200d497a}, {0x19abcb0d, 0x200d8a1d}, {0x19bbcb1b, 0x640dcac0}, {0x19cb4d22, 0x98060b63}, {0x19dbbd22, 0x980e4c2d}, {0x19eb4d29, 0xba068d1f}, {0x19fbbd29, 0xba0ece0d}, {0x1a0b4d30, 0xdc070ee1}, {0x1a1bbd30, 0xdc0f4fb6}, {0x30000000, 0x0}, {0x30000000, 0x0}, {0x30000000, 0x0}, {0x30000000, 0x0}, {0x30000000, 0x0}, {0x30000000, 0x0}, {0x30000000, 0x0}, {0x30000000, 0x0}},
    {{0x3016200, 0x600000}, {0x3086002, 0x160809b}, {0x30f6603, 0x260c13d}, {0x3166405, 0x36141df}, {0x194c0014, 0x750002d8}, {0x3596a06, 0x4698318}, {0x39c7007, 0x471c3a6}, {0x195c1c14, 0x7500444b}, {0x1e43809, 0x53a4504}, {0x196c3814, 0x750485be}, {0x36b6e0a, 0x66a8647}, {0x197c5414, 0x7504c703}, {0x3f27c0c, 0x77b0768}, {0x198c7014, 0x75090849}, {0x1ba340e, 0x9338898}, {0x199c8c14, 0x75094985}, {0x19aca814, 0x750d8a27}, {0x19bcd214, 0x750dcaca}, {0x19cc5422, 0x98060b6d}, {0x19dcc422, 0x980e4c3c}, {0x19ec5429, 0xba068d2f}, {0x2afbbd37, 0xc38d8d9b}, {0x19fcc429, 0xba0ece1a}, {0x1a0c5430, 0xdc070eee}, {0x1a1cc430, 0xdc0f4fc3}, {0x30000000, 0x0}, {0x30000000, 0x0}, {0x30000000, 0x0}, {0x30000000, 0x0}, {0x30000000, 0x0}, {0x30000000, 0x0}, {0x30000000, 0x0}},
    {{0x3416a00, 0x680000}, {0x3486802, 0x168809c}, {0x34f6e03, 0x268c13e}, {0x3566c05, 0x36941e0}, {0x194d001b, 0x640002ef}, {0x2d95a06, 0x4598312}, {0x35c6807, 0x469c3a3}, {0x195d1c1b, 0x64004462}, {0x2a45009, 0x552450e}, {0x196d381b, 0x640485d2}, {0x6c080b, 0x70ac651}, {0x197d541b, 0x6404c718}, {0x33060c, 0x803076c}, {0x198d701b, 0x6409085d}, {0x33a640e, 0x96388a7}, {0x199d8c1b, 0x6409498f}, {0x19ada81b, 0x640d8a32}, {0x19bdd21b, 0x640dcad4}, {0x19cd5b22, 0x98060b77}, {0x19ddcb22, 0x980e4c4b}, {0x19ed5b29, 0xba068d3e}, {0x2afcc437, 0xca8dcdaa}, {0x19fdcb29, 0xba0ece27}, {0x1a0d5b30, 0xdc070efc}, {0x1a1dcb30, 0xdc0f4fd0}, {0x30000000, 0x0}, {0x30000000, 0x0}, {0x30000000, 0x0}, {0x30000000, 0x0}, {0x30000000, 0x0}, {0x30000000, 0x0}, {0x30000000, 0x0}},
    {{0x3817200, 0x700000}, {0x3887002, 0x170809e}, {0x38f7603, 0x270c140}, {0x3967405, 0x37141e2}, {0x2a4e3f33, 0x4182c271}, {0x194e0714, 0x75000306}, {0x2dc5807, 0x459c39d}, {0x195e2314, 0x7500447a}, {0x3246009, 0x5624513}, {0x196e3f14, 0x750485e6}, {0x3eb7e0a, 0x67a864b}, {0x197e5b14, 0x7504c72c}, {0x730e0c, 0x80b076e}, {0x198e7714, 0x75090872}, {0x3ba740e, 0x97388ac}, {0x199e9314, 0x75094999}, {0x19aeaf14, 0x750d8a3c}, {0x19bed914, 0x750dcadf}, {0x19ce6222, 0x98060b82}, {0x19ded222, 0x980e4c5a}, {0x19ee6229, 0xba068d4d}, {0x19fed229, 0xba0ece34}, {0x1a0e6230, 0xdc070f09}, {0x1a1ed230, 0xdc0f4fdd}, {0x30000000, 0x0}, {0x30000000, 0x0}, {0x30000000, 0x0}, {0x30000000, 0x0}, {0x30000000, 0x0}, {0x30000000, 0x0}, {0x30000000, 0x0}, {0x30000000, 0x0}},
    {{0x3c17a00, 0x780000}, {0x3c87802, 0x178809f}, {0x3cf7e03, 0x278c141}, {0x3d67c05, 0x37941e3}, {0x2a4f3f34, 0x4282c27c}, {0x194f071b, 0x6400031d}, {0x1d0207, 0x401c3ac}, {0x195f231b, 0x64004491}, {0x3a47009, 0x5724519}, {0x196f3f1b, 0x640485fb}, {0x12c200b, 0x722c659}, {0x197f5b1b, 0x6404c740}, {0x133260c, 0x8230776}, {0x198f771b, 0x64090886}, {0x7b0e0e, 0x90b88b4}, {0x199f931b, 0x640949a3}, {0x19afaf1b, 0x640d8a46}, {0x19bfd91b, 0x640dcae9}, {0x19cf6922, 0x98060b8c}, {0x19dfd922, 0x980e4c69}, {0x19ef6929, 0xba068d5c}, {0x2afed237, 0xd88dcdc8}, {0x19ffd929, 0xba0ece42}, {0x1a0f6930, 0xdc070f16}, {0x1a1fd930, 0xdc0f4feb}, {0x30000000, 0x0}, {0x30000000, 0x0}, {0x30000000, 0x0}, {0x30000000, 0x0}, {0x30000000, 0x0}, {0x30000000, 0x0}, {0x30000000, 0x0}}
}};
static_assert(NJOB + NCONV == 32, "");

__device__ __forceinline__ unsigned read_back(const void* p) {
    unsigned v = 0;
    asm volatile("ld.relaxed.gpu.global.u32 %0, [%1];" : "=r"(v) : "l"(p) : "memory");
    return v;
}
__device__ __forceinline__ void publish(unsigned* flag, unsigned seen, unsigned zero) {
    asm volatile("{\n.reg .pred p;\n.reg .u32 t;\nredux.sync.or.b32 t, %1, 0xffffffff;\nand.b32 t, t, %2;\nadd.u32 t, t, 1;\n"
                 "elect.sync _|p, 0xffffffff;\n@p red.relaxed.gpu.global.add.u32 [%0], t;\n}" :: "l"(flag), "r"(seen), "r"(zero) : "memory");
}

__device__ __forceinline__ void load_w(uint2 (&v)[32], const char* g) {
#pragma unroll
    for (int k = 0; k < 32; k++)
        asm volatile("ld.global.nc.L1::no_allocate.v2.b32 {%0,%1}, [%2];" : "=r"(v[k].x), "=r"(v[k].y) : "l"(g + k * (N_ * 4)));
}
__device__ __forceinline__ void store_w(const uint2 (&v)[32], unsigned (&o)[16], char* d) {
#pragma unroll
    for (int i = 0; i < 8; i++) {
        o[i] = pack4(v[4 * i].x, v[4 * i + 1].x, v[4 * i + 2].x, v[4 * i + 3].x);
        o[8 + i] = pack4(v[4 * i].y, v[4 * i + 1].y, v[4 * i + 2].y, v[4 * i + 3].y);
        if ((i & 3) == 3) {
            stg128(d + (i >> 2) * 128, make_uint4(o[i - 3], o[i - 2], o[i - 1], o[i]));
            stg128(d + (i >> 2) * 128 + 256, make_uint4(o[i + 5], o[i + 6], o[i + 7], o[i + 8]));
        }
    }
}
__device__ __forceinline__ unsigned col_sums(const unsigned (&o)[16]) {
    int cs[4];
#pragma unroll
    for (int i = 0; i < 4; i++)
        cs[i] = __dp4a((int)o[4 * i], 0x01010101, __dp4a((int)o[4 * i + 1], 0x01010101,
                __dp4a((int)o[4 * i + 2], 0x01010101, __dp4a((int)o[4 * i + 3], 0x01010101, 0))));
    return cs[0] + cs[1] + (cs[2] + cs[3]) * 65536;
}
__device__ __forceinline__ void wait_until(int due, unsigned t0) {
    for (int rem; (rem = due - (int)(clk() - t0)) > 0;) if (rem > CFG_SLEEP) __nanosleep(CFG_SLEEP / 4);
}

__device__ __forceinline__ uint32_t zero_term(const unsigned (&sv)[4], float zxf) {
    int lo = 0, hi = 0;
#pragma unroll
    for (int h = 0; h < 4; h++) {
        const int l = (int)(short)(sv[h] & 0xFFFF);
        lo += l; hi += ((int)(sv[h] - (unsigned)l)) >> 16;
    }
    const float fl = __bfloat162float(__float2bfloat16_rn((float)lo)) * zxf, fh = __bfloat162float(__float2bfloat16_rn((float)hi)) * zxf;
    uint32_t z;
    asm("cvt.rn.bf16x2.f32 %0, %1, %2;" : "=r"(z) : "f"(fh), "f"(fl));
    return z;
}

__device__ __forceinline__ void load_x(Scratch* scr, uint32_t sb, int b, int lane) {
    const uint32_t bars = sb + SM_BAR;
    const int r = b & 15;
    const unsigned tgt = (*(volatile unsigned*)&scr->epoch[b] + 1) * 4;
    const unsigned* f = scr->flag + r * FS + (lane & 15);
    unsigned todo = 0xFFFF, v = ld_flag(f);
    asm volatile("barrier.cluster.wait.aligned;" ::: "memory");
#pragma unroll 1
    for (int it = 0; todo; it++) {
        unsigned m = __ballot_sync(~0u, (int)(v - tgt) >= 0) & todo;
        v = ld_flag(f);
        todo &= ~m;
        while (m) {
            const int sl = __ffs(m) - 1;
            m &= m - 1;
            if (elect_one()) {
                asm volatile("cp.async.bulk.shared::cluster.global.mbarrier::complete_tx::bytes [%0], [%1], %2, [%3];"
                             :: "r"(sb + SM_A + sl * 8192), "l"((const char*)scr->a8 + (r * 16 + sl) * 8192),
                                "r"(8192), "r"(bars + (B_FULL + sl) * 8) : "memory");
            }
        }
        if (it > (1 << 20)) __trap();
    }
}

__device__ __forceinline__ void store_out(const CUtensorMap* map, uint32_t sb, int b, int agent, int lane) {
    const uint32_t bars = sb + SM_BAR;
    const int r = b & 15, c = b >> 4;
    const uint32_t buf = sb + SM_OUT + agent * 4096, full = bars + (B_OFULL + agent) * 8;
    const int row = r * 128 + agent * 32;
#pragma unroll 1
    for (int t = 0; t < 7; t++) {
        asm volatile("{\n.reg .pred p;\n.reg .u32 c;\nmov.u32 c, 0;\n"
                     "WAIT_LOOP:\n"
                     "mbarrier.try_wait.parity.shared::cta.b64 p, [%4], %5;\n"
                     "@p bra WAIT_DONE;\n"
                     "add.u32 c, c, 1;\nsetp.lt.u32 p, c, 0x100000;\n"
                     "@p bra WAIT_LOOP;\n"
                     "trap;\n"
                     "WAIT_DONE:\n"
                     "fence.proxy.async.shared::cta;\n"
                     "elect.sync _|p, 0xffffffff;\n"
                     "@p cp.async.bulk.tensor.2d.global.shared::cta.tile.bulk_group [%0, {%1, %2}], [%3];\n"
                     "cp.async.bulk.commit_group;\n}"
                     :: "l"(map), "r"(col_of(c, ((agent < 2 ? 0x6534120 : 0x6541230) >> (t * 4)) & 7)), "r"(row), "r"(buf), "r"(full), "r"(t & 1) : "memory");
        asm volatile("cp.async.bulk.wait_group.read 0;" ::: "memory");
        if (t < 6 && elect_one()) mbar_arrive(bars + (B_OFREE + t * 4 + 4 + agent) * 8);
    }
}

template <int V> struct I { static constexpr int v = V; };
template <bool SIDE>
__device__ __forceinline__ void consume(Scratch* scr, const __nv_bfloat16* __restrict__ scale_w, const __nv_bfloat16* __restrict__ bias,
                                        const __nv_bfloat16* __restrict__ scale_x, uint32_t sb, int b, int warp, int lane) {
    constexpr int NR = NRING;
    const uint32_t bars = sb + SM_BAR;
    const int c = b >> 4;
    constexpr uint32_t SD = 0x400 >> 4;
    if ((sb & 0xFFFFFF) != 0x400) __trap();
    const int wg = warp >> 2;
    const unsigned short sxr = __ldg((const unsigned short*)scale_x);
    const uint32_t sx2 = (uint32_t)sxr * 0x10001u;
    const int c0 = (warp & 3) * 16 + (lane >> 2) * 2;
    uint32_t sw[4], bi[4];
#pragma unroll
    for (int i = 0; i < 4; i++) {
        const int col = col_of(c, i < 2 ? wg * 2 + i : i == 2 ? 4 + wg : 6) + c0;
        sw[i] = __ldg((const uint32_t*)(scale_w + col));
        bi[i] = __ldg((const uint32_t*)(bias + col));
    }
    const uint32_t st0 = sb + SM_OUT + (lane & 3) * 256 + (((c0 >> 3) ^ ((lane & 3) * 2)) << 4) + (c0 & 7) * 2;
    constexpr uint32_t DX0 = (SD + (SM_A >> 4)) | (1 << 16), DW0 = (SD + (SM_RING >> 4)) | (8 << 16);
    asm volatile("barrier.cluster.wait.aligned;" ::: "memory");
    int a0[64], a1[64];
    constexpr int MUL = SIDE ? 4 : 2, NONE = 64 * MUL, BIAS = NR + 64 - NG;
    const uint32_t go = mapa(bars + B_GO * 8, lane & (SIDE ? 1 : 15)) - (64 - NG) * MUL;
    const int key = SIDE ? (lane < 2 ? lane * 4 : 1) : (lane < 16 ? (lane >> 2) * 2 : 1);
    int pend = NONE;
    uint32_t bb = bars + (B_FULL + wg * 16) * 8;
#define RELEASE() { if ((pend & (NONE + 8 - MUL)) == key) mbar_arrive_cluster(go + (pend & ~7)); }
    struct Par { uint32_t a, b, c, d; };
    auto load_par = [&](int blk, uint32_t swv, uint32_t biv) {
        mbar_wait_cluster(bars + (B_PAR + blk) * 8);
        const uint32_t zc = lds32(sb + SM_PAR + (blk * 64 + c0) * 2);
        const float sxf = __uint_as_float(sx2 << 16);
        const float s0 = sxf * __uint_as_float(swv << 16), s1 = sxf * __uint_as_float(swv & 0xFFFF0000u);
        Par P = {__float_as_uint(s0), __float_as_uint(s1), __float_as_uint(fmaf(-__uint_as_float(zc << 16), s0, __uint_as_float(biv << 16))),
                 __float_as_uint(fmaf(-__uint_as_float(zc & 0xFFFF0000u), s1, __uint_as_float(biv & 0xFFFF0000u)))};
        asm volatile("" : "+r"(P.a), "+r"(P.b), "+r"(P.c), "+r"(P.d));
        return P;
    };
    auto drain = [&](int (&a)[64], auto Q, int t, const Par& P) {
#pragma unroll
        for (int q = Q.v; q < Q.v + 2; q++) {
#pragma unroll
            for (int j = 0; j < 8; j++) {
                const int o = q * 16 + (j >> 1) * 4 + (j & 1);
                asm("cvt.rn.f32.s32 %0, %0;\n\tcvt.rn.f32.s32 %1, %1;\n\tfma.rn.f32 %0, %0, %2, %4;\n\tfma.rn.f32 %1, %1, %3, %5;\n\t"
                    "cvt.rn.bf16x2.f32 %0, %1, %0;" : "+r"(a[o]), "+r"(a[o + 2]) : "r"(P.a), "r"(P.b), "r"(P.c), "r"(P.d));
            }
            mbar_wait(bars + (B_OFREE + t * 4 + q) * 8);
#pragma unroll
            for (int j = 0; j < 8; j++) sts32((st0 ^ ((j & 1) * 16)) + q * 4096 + (j >> 1) * 1024 + (j & 1) * 128, a[q * 16 + (j >> 1) * 4 + (j & 1)]);
            __syncwarp();
            if (lane == 0) mbar_arrive(bars + (B_OFULL + q) * 8);
        }
    };
    wg_fence();
    {
        uint32_t tbl = wg ? STEPS1 : STEPS0;
        uint32_t ba = bars + B_FULL * 8;
        int u = MUL * (wg * D_ + BIAS);
        uint32_t dw = DW0 + wg * D_ * 512;
        static_assert(D_ < NR, "");
        mbar_wait2(ba, bb);
#pragma unroll 1
        for (uint32_t dx = DX0;;) {
            mma_unit2(a0, a1, dw, dx, dx - DX0);
            dx += 512; ba += 8; bb += 8;
            const bool ready = mbar_test2(ba, bb);
            wg_wait<1>();
            RELEASE()
            pend = u;
            if (dx == DX0 + 16 * 512) break;
            u += MUL + (tbl & 1) * MUL;
            dw += 512 + (tbl & 1) * 512;
            if (dw >= DW0 + NR * 512) dw -= NR * 512;
            tbl >>= 1;
            if (!ready && !mbar_test2(ba, bb)) {
                wg_wait<0>();
                RELEASE()
                pend = NONE;
                mbar_wait2(ba, bb);
            }
        }
    }
    Par P0 = load_par(2 * wg, sw[0], bi[0]);
    const Par P1 = load_par(2 * wg + 1, sw[1], bi[1]);
    wg_wait<0>();
    RELEASE()
#pragma unroll 1
    for (int ph = 0; ph < 3; ph++) {
        if (ph + wg == 1) drain(a1, I<2>(), 3 - 2 * wg, P1);
        drain(a0, I<0>(), wg ? 4 * ph + 1 : 3 * ph, P0);
        const int u0 = 32 + ph * 16 + wg * 8;
        uint32_t dw = DW0 + (ph ? 48 % NR : wg ? 40 % NR : 32 % NR) * 512;
        bb = bars + (B_FULL + u0) * 8;
        const bool first = mbar_test(bb);
        drain(a0, I<2>(), ph ? 2 * ph + 2 + wg : 2 * wg, P0);
        if (ph + wg == 2) break;
#define RELEASE2() { if ((pend & (NONE + 8 - 2 * MUL)) == (key & ~MUL)) mbar_arrive_cluster(go + (pend & ~7)); }
        static_assert(NR % 2 == 0, "");
        pend = NONE;
        if (!first) mbar_wait(bb);
        wg_fence();
#pragma unroll 1
        for (int n = 0;; n += 2) {
            RELEASE2()
            const bool ready = mma_pair(a0, dw, DX0 + n * 1024, n, bb + n * 8 + 16);
            wg_wait<1>();
            pend = n ? MUL * (u0 + BIAS + n - 2) : NONE;
            if (n == 6) break;
            dw += 1024;
            if (dw == DW0 + NR * 512) dw = DW0;
            if (!ready) {
                RELEASE2()
                pend = NONE;
                mbar_wait(bb + n * 8 + 16);
            }
        }
        RELEASE2()
        pend = MUL * (u0 + BIAS + 6);
        if (ph == 0) drain(a1, I<0>(), 2 + 2 * wg, P1);
        P0 = load_par(4 + 2 * ph + wg, ph ? sw[3] : sw[2], ph ? bi[3] : bi[2]);
        wg_wait<0>();
        RELEASE2()
    }
    if (threadIdx.x == 128) asm volatile("red.relaxed.gpu.global.add.u32 [%0], 1;" :: "l"(scr->epoch + b) : "memory");
}

__global__ void __cluster_dims__(CS, 1, 1) __launch_bounds__(512, 1)
w8a8_kernel(const char* __restrict__ qx, const char* __restrict__ qw, Scratch* scr, const JobTable* __restrict__ jobs, const __nv_bfloat16* __restrict__ scale_w,
            const __nv_bfloat16* __restrict__ bias, const __nv_bfloat16* __restrict__ scale_x, const int* __restrict__ zero_x,
            const __grid_constant__ CUtensorMap map) {
    extern __shared__ __align__(1024) unsigned char smem_raw[];
    const uint32_t sb = (uint32_t)__cvta_generic_to_shared(smem_raw);
    const uint32_t bars = sb + SM_BAR;
    const int warp = __shfl_sync(~0u, threadIdx.x >> 5, 0), lane = threadIdx.x & 31;
    const int b = blockIdx.x, r = b & 15, c = b >> 4;
    const unsigned t0 = clk() + CFG_PF0;
    if (warp < CFG_NINIT) {
#pragma unroll 1
        for (int w = warp; w < 8; w += CFG_NINIT) {
            if (elect_one()) {
                const uint32_t cnt = w < B_GO / 16 ? 1 : 4 * CS + 1;
#pragma unroll
                for (int i = 0; i < 16; i++) mbar_init(bars + (w * 16 + i) * 8, cnt);
            }
            __syncwarp();
            const int i = w * 16 + lane;
            if (lane < 16 && i < B_OFREE + NOUT) mbar_expect_tx(bars + i * 8, i >= B_AFREE ? 0 : i >= B_PAR ? 128 : w == 1 ? 8192 : 16384);
            if (w == B_GO / 16 && 4 * lane + (r >> 2) < NRING)
                asm volatile("mbarrier.arrive.shared::cta.b64 _, [%0], %1;" :: "r"(bars + i * 8), "r"(4 * CS) : "memory");
        }
        if (warp == (B_SUM / 16) % CFG_NINIT) {
            if (elect_one()) {
#pragma unroll
                for (int k = 0; k < NOUT; k++) mbar_init(bars + (B_OFULL + k) * 8, 4);
                mbar_init(bars + B_SUM * 8, r < 8 ? 1 : 3);
                mbar_expect_tx(bars + B_SUM * 8, r < 8 ? 32 * 64 : 30 * 64);
            }
        }
        asm volatile("fence.mbarrier_init.release.cluster;" ::: "memory");
    } else if (warp == 7) {
        asm volatile("st.shared.v2.b32 [%0], {%1, %1};" :: "r"(sb + SM_SUM + lane * 8), "r"(0) : "memory");
        asm volatile("fence.release.sync_restrict::shared::cta.cluster;" ::: "memory");
    } else if (warp == 9) {
        asm volatile("griddepcontrol.launch_dependents;");
        if (elect_one()) asm volatile("prefetch.tensormap [%0];" :: "l"(&map) : "memory");
    } else if (warp >= 14) {
        const char* pf = qx + (r * 128 + ((threadIdx.x >> 1) & 31)) * (K_ * 4) + (lane & 1) * 128;
        if (c >= 5) asm volatile("prefetch.global.L2 [%0];" :: "l"(pf + (c - 5) * (32 * K_ * 4)) : "memory");
        asm volatile("prefetch.global.L2 [%0];" :: "l"(pf + ((c + 2) & 3) * (32 * K_ * 4) + ((c + 2) >> 2) * 256) : "memory");
    }
    asm volatile("barrier.cluster.arrive.relaxed.aligned;" ::: "memory");

    if (warp >= 8) {
        asm volatile("setmaxnreg.dec.sync.aligned.u32 88;");
        int agent = -1;
        if (warp >= 16 - NCONV) {
            const int cw = warp - (16 - NCONV);
            const unsigned zero = blockIdx.y;
            const char* const gx = qx + (lane >> 4) * (K_ * 4) + (lane & 15) * 16;
            const char* const gw = qw + lane * 8;
            const int wrB = ((lane >> 3) * 32 + (lane & 7)) * 16;
            uint2 tab;
            asm volatile("ld.global.nc.v2.u32 {%0, %1}, [%2];" : "=r"(tab.x), "=r"(tab.y) : "l"(&jobs->e[b][lane]));
            bool synced = false;
#pragma unroll 1
            for (int p = cw || c >= 5 ? cw : NCONV;; p = p < CFG_PZ ? p + NCONV : p < CFG_PZ + 3 ? 31 : p + 3) {
                uint2 j;
                if (p < 4) {
                    const int g = 7 * p + c - 5;
                    j.x = ((r * 128 + (g & 3) * 32) * 16 + (g >> 2)) | (r * 64 + g) << 16;
                    j.y = max((p - 1) * (CFG_P0 / 4) + b * (CFG_P0 * 4 / NCTA) / 16, 0) | (r * FS + (g >> 2)) << 14 | p << 24;
                } else { j.x = __shfl_sync(~0u, tab.x, p); j.y = __shfl_sync(~0u, tab.y, p); }
                if (j.x >= 3u << 28) break;
                const int kind = j.x >> 28, sig = (j.y >> 14) & 0x3FF;
                char* tile = (char*)scr + ((j.x >> 16) & 0xFFF) * 2048;
                const char* g = (kind ? gw : gx) + (j.x & 0xFFFF) * 256;
                wait_until((j.y & 0x3FFF) * 4, t0);
                if (kind == 0) {
                    uint4 v[16];
#pragma unroll
                    for (int i = 0; i < 16; i++)
                        asm volatile("ld.global.nc.L1::no_allocate.v4.b32 {%0,%1,%2,%3}, [%4];"
                                     : "=r"(v[i].x), "=r"(v[i].y), "=r"(v[i].z), "=r"(v[i].w) : "l"(g + i * (2 * K_ * 4)));
#pragma unroll
                    for (int i = 0; i < 16; i++)
                        asm volatile("st.global.b32 [%0], %1;" :: "l"(tile + ((lane * 4) ^ ((i & 3) * 16)) + i * 128),
                                     "r"(pack4(v[i].x, v[i].y, v[i].z, v[i].w)) : "memory");
                    asm volatile("fence.proxy.async.global;" ::: "memory");
                    __syncwarp();
                    publish(scr->flag + sig, read_back(tile + lane * 64), zero);
                } else {
                    uint2 v[32];
                    unsigned o[16];
                    load_w(v, g);
                    if (!synced) asm volatile("barrier.cluster.wait.aligned;" ::: "memory");
                    synced = true;
                    store_w(v, o, tile + wrB);
                    asm volatile("{\n.reg .pred p;\nsetp.eq.u32 p, %1, 0;\nfence.proxy.async.global;\nbar.warp.sync 0xffffffff;\n"
                                 "@p mbarrier.arrive.shared::cta.b64 _, [%0];\n}" :: "r"(bars + (B_GO + (sig & 15)) * 8), "r"(lane | (kind & 2)) : "memory");
                    const unsigned csv = col_sums(o);
                    if (kind == 1) {
                        const int own = (j.y >> (24 + (lane >> 4) * 4)) & 15;
                        const uint32_t so = SM_SUM + (sig & 48) * 4 + (lane & 15) * 4;
                        if (own != r) {
                            const uint32_t ro = mapa(sb, own);
                            asm volatile("red.async.relaxed.cluster.shared::cluster.mbarrier::complete_tx::bytes.add.u32 [%0], %1, [%2];"
                                         :: "r"(ro + so), "r"(csv), "r"(ro + SM_BAR + B_SUM * 8) : "memory");
                        } else asm volatile("red.relaxed.cluster.shared::cta.add.u32 [%0], %1;" :: "r"(sb + so), "r"(csv) : "memory");
                        __syncwarp();
                        if (own == r && (lane & 15) == 0) mbar_arrive(bars + B_SUM * 8);
                    } else {
                        unsigned* csp = scr->cs + (j.y >> 24) * 32 + lane;
                        asm volatile("st.global.u32 [%0], %1;" :: "l"(csp), "r"(csv) : "memory");
                        publish(scr->flag + sig, read_back(tile + lane * 64) | read_back(csp), zero);
                    }
                }
                __syncwarp();
            }
            if (!synced) asm volatile("barrier.cluster.wait.aligned;" ::: "memory");
            agent = (cw + 6 * NCONV - CFG_PZ) % NCONV + 1;
            if (agent > 3) agent = -1;
        } else if (warp == 9) {
            asm volatile("barrier.cluster.wait.aligned;" ::: "memory");
        } else {
            load_x(scr, sb, b, lane);
            agent = 0;
        }
        const char* src = (const char*)scr->b8 + (c * 224 + r) * 2048;
        const int zxi = __ldg(zero_x);
#pragma unroll 1
        for (int i = 0, slot = r >> 2, end = 8;; end = NG / 4) {
#pragma unroll 1
            for (; warp == 9 && i < end; i++) {
                asm volatile("{\n.reg .pred p;\nWAIT_LOOP:\nmbarrier.try_wait.parity.shared::cta.b64 p, [%4], 0;\n@!p bra WAIT_LOOP;\n"
                             "elect.sync _|p, 0xffffffff;\n"
                             "@p cp.async.bulk.shared::cluster.global.mbarrier::complete_tx::bytes.multicast::cluster [%0], [%1], 2048, [%2], %3;\n}"
                             :: "r"(sb + SM_RING + slot * 8192 + (r & 3) * 2048), "l"(src + i * 32768),
                                "r"(bars + (B_FULL + bar_of(4 * i + (r >> 2))) * 8), "h"((uint16_t)0xFFFF), "r"(bars + (B_GO + i) * 8) : "memory");
                slot += slot >= NRING - 4 ? 4 - NRING : 4;
            }
            if (end != 8) break;
            if (warp == (r < 8 ? 9 : r < 10 ? 8 : r < 14 ? 16 - NCONV + (CFG_PZ + 3) % NCONV : 0)) {
                const float zxf = __bfloat162float(__float2bfloat16_rn((float)zxi));
                const int grp = sum_group(r);
                mbar_wait_cluster(bars + B_SUM * 8);
                unsigned sv[4];
#pragma unroll
                for (int h = 0; h < 4; h++) sv[h] = lds32(sb + SM_SUM + h * 64 + (lane & 15) * 4);
                const uint32_t z = zero_term(sv, zxf);
#pragma unroll 2
                for (int k = 0; k < 8; k++) {
                    const uint32_t rb = mapa(sb, k * 2 + (lane >> 4));
                    st_async32(rb + SM_PAR + grp * 64 + (lane & 15) * 4, z, rb + SM_BAR + (B_PAR + (grp >> 1)) * 8);
                }
            }
        }
        __syncwarp();
        if (agent >= 0) store_out(&map, sb, b, agent, lane);
    } else {
        asm volatile("setmaxnreg.inc.sync.aligned.u32 168;");
        consume<false>(scr, scale_w, bias, scale_x, sb, b, warp, lane);
    }
}

__global__ void __cluster_dims__(2, 1, 1) __launch_bounds__(512, 1)
w8a8_side(const char* __restrict__ qw, Scratch* scr, const __nv_bfloat16* __restrict__ scale_w, const __nv_bfloat16* __restrict__ bias,
          const __nv_bfloat16* __restrict__ scale_x, const int* __restrict__ zero_x, const __grid_constant__ CUtensorMap map) {
    extern __shared__ __align__(1024) unsigned char smem_raw[];
    const uint32_t sb = (uint32_t)__cvta_generic_to_shared(smem_raw);
    const uint32_t bars = sb + SM_BAR;
    const int warp = __shfl_sync(~0u, threadIdx.x >> 5, 0), lane = threadIdx.x & 31;
    const int b = NCTA + blockIdx.x, rank = b & 1;
    constexpr int NR = NRING;
    const unsigned t0 = clk();
    if (warp < 3) {
#pragma unroll 1
        for (int w = warp; w < B_OFULL / 16; w += 3) {
            if (elect_one()) {
                const uint32_t cnt = w < B_GO / 16 ? 1 : 9;
#pragma unroll
                for (int i = 0; i < 16; i++) mbar_init(bars + (w * 16 + i) * 8, cnt);
            }
            __syncwarp();
            const int i = w * 16 + lane;
            if (lane < 16 && i < B_PAR) mbar_expect_tx(bars + i * 8, w == 1 ? 8192 : 16384);
            if (lane < 16 && i >= B_OFREE && i < B_OFREE + NOUT) mbar_arrive(bars + i * 8);
            if (w == B_GO / 16 && 2 * lane + rank < NR)
                asm volatile("mbarrier.arrive.shared::cta.b64 _, [%0], %1;" :: "r"(bars + i * 8), "r"(8) : "memory");
        }
        asm volatile("fence.mbarrier_init.release.cluster;" ::: "memory");
    } else if (warp == 3) {
        if (elect_one()) {
#pragma unroll
            for (int i = 0; i < NOUT; i++) mbar_init(bars + (B_OFULL + i) * 8, 4);
            asm volatile("fence.mbarrier_init.release.cluster;" ::: "memory");
        }
        __syncwarp();
    } else if (warp == 11 && elect_one()) asm volatile("prefetch.tensormap [%0];" :: "l"(&map) : "memory");
    asm volatile("barrier.cluster.arrive.relaxed.aligned;" ::: "memory");

    if (warp >= 8) {
        asm volatile("setmaxnreg.dec.sync.aligned.u32 88;");
        int agent = -1;
        if (warp == 10 || warp >= 12) {
#pragma unroll 1
            for (int i = CFG_NOC / 4 + ((0x143002 >> (4 * (warp - 10))) & 7); i < CFG_NOC / 4 + CFG_YN; i += 5) {
                const int G = i * 16 + blockIdx.x, u = G >> 2, f = bar_of(u);
                const int blk = u < 32 ? (f >> 4) * 2 + (G & 1) : u >> 3, step = u < 32 ? (f & 15) * 2 + (G >> 1 & 1) : G & 31;
                char* const tile = (char*)scr->b8 + (7 * 224 + G) * 2048;
                unsigned* const csp = scr->cs + (step * 7 + blk) * 32 + lane;
                uint2 v[32];
                unsigned o[16];
                wait_until((G - CFG_NOC * 4) * (CFG_YP / 16) + CFG_Y0, t0);
                load_w(v, qw + step * (32 * N_ * 4) + (49 + blk) * 256 + lane * 8);
                store_w(v, o, tile + ((lane >> 3) * 32 + (lane & 7)) * 16);
                asm volatile("st.global.u32 [%0], %1;" :: "l"(csp), "r"(col_sums(o)) : "memory");
                asm volatile("fence.proxy.async.global;" ::: "memory");
                __syncwarp();
                publish(scr->flag + CS * FS + u, read_back(tile + lane * 64) | read_back(csp), blockIdx.y);
            }
        }
        if (warp == 8) {
            load_x(scr, sb, b, lane);
            agent = 0;
        } else if (warp == 11) {
            const unsigned tgt = (*(volatile unsigned*)&scr->epoch[b] + 1) * 4;
            const unsigned* f = scr->flag + CS * FS + lane;
            unsigned todo0 = ~0u, todo1 = 0xFFFFFF, v0 = ld_flag(f), v1 = ld_flag(f + 32);
            bool par = lane >= 3;
            asm volatile("barrier.cluster.wait.aligned;" ::: "memory");
#pragma unroll 1
            for (int it = 0; todo0 | todo1; it++) {
                const unsigned m0 = __ballot_sync(~0u, (int)(v0 - tgt) >= 0) & todo0, m1 = __ballot_sync(~0u, (int)(v1 - tgt) >= 0) & todo1;
                v0 = ld_flag(f); v1 = ld_flag(f + 32);
                todo0 &= ~m0; todo1 &= ~m1;
                if ((lane & 1) == rank) {
                    if (m0 >> lane & 1) mbar_arrive(bars + (B_GO + (lane >> 1)) * 8);
                    if (m1 >> lane & 1) mbar_arrive(bars + (B_GO + 16 + (lane >> 1)) * 8);
                }
                if (!par && !(lane ? todo1 << (32 - lane * 16) : todo0)) { par = true; mbar_arrive(bars + (B_AFREE + lane) * 8); }
                if (it > (1 << 20)) __trap();
            }
        } else if (warp == 9) {
            asm volatile("barrier.cluster.wait.aligned;" ::: "memory");
            const char* src = (const char*)scr->b8 + (7 * NG + rank) * 8192;
#pragma unroll 1
            for (int i = 0, slot = rank; i < NG / 2; i++) {
                asm volatile("{\n.reg .pred p;\nWAIT_LOOP:\nmbarrier.try_wait.parity.shared::cta.b64 p, [%4], 0;\n@!p bra WAIT_LOOP;\n"
                             "elect.sync _|p, 0xffffffff;\n"
                             "@p cp.async.bulk.shared::cluster.global.mbarrier::complete_tx::bytes.multicast::cluster [%0], [%1], 8192, [%2], %3;\n}"
                             :: "r"(sb + SM_RING + slot * 8192), "l"(src + i * 16384),
                                "r"(bars + (B_FULL + bar_of(2 * i + rank)) * 8), "h"((uint16_t)3), "r"(bars + (B_GO + i) * 8) : "memory");
                slot += slot >= NR - 2 ? 2 - NR : 2;
            }
        } else if (warp == 12 || warp == 15) {
            const float zxf = __bfloat162float(__float2bfloat16_rn((float)__ldg(zero_x)));
            asm volatile("barrier.cluster.wait.aligned;" ::: "memory");
#pragma unroll 1
            for (int blk = warp & 2; blk < 7; blk += 4) {
                const int w = min(blk * 32 + lane * 2, TN / 2 - 2);
                mbar_wait(bars + (B_AFREE + max(blk / 2 - 1, 0)) * 8);
                uint2 v[32];
                unsigned s0[4], s1[4];
#pragma unroll
                for (int k = 0; k < 32; k++) v[k] = __ldcg((const uint2*)(scr->cs + k * (TN / 2) + w));
#pragma unroll
                for (int h = 0; h < 4; h++) {
                    s0[h] = s1[h] = 0;
#pragma unroll
                    for (int k = 0; k < 8; k++) { s0[h] += v[8 * h + k].x; s1[h] += v[8 * h + k].y; }
                }
                sts32(sb + SM_PAR + w * 4, zero_term(s0, zxf));
                sts32(sb + SM_PAR + w * 4 + 4, zero_term(s1, zxf));
                __syncwarp();
                if (lane < 2) mbar_arrive(bars + (B_PAR + blk + lane) * 8);
            }
        } else {
            asm volatile("barrier.cluster.wait.aligned;" ::: "memory");
            agent = warp == 10 ? 1 : warp - 11;
        }
        if (agent >= 0) store_out(&map, sb, b, agent, lane);
    } else {
        asm volatile("setmaxnreg.inc.sync.aligned.u32 168;");
        consume<true>(scr, scale_w, bias, scale_x, sb, b, warp, lane);
    }
}

}

typedef CUresult (*EncodeFn)(CUtensorMap*, CUtensorMapDataType, cuuint32_t, void*, const cuuint64_t*, const cuuint64_t*,
                             const cuuint32_t*, const cuuint32_t*, CUtensorMapInterleave, CUtensorMapSwizzle,
                             CUtensorMapL2promotion, CUtensorMapFloatOOBfill);

namespace w8 {

constexpr int M_ = 2048, K_ = 1024, N_ = 3584;
constexpr int WA = 160, WB = 64;
constexpr int TN = 2 * WA + 2 * WB;
static_assert(TN == 448, "");
constexpr int X1 = 13;
constexpr int NSLOT = 7, SLOT = WA * 64;
constexpr int NSTG = 3, PFD = 700, NCONV = 5;
constexpr int NU = 48;
constexpr int UX = 32 + NSLOT;
constexpr int NJOB = 22;
constexpr int NCTA = 128;

constexpr int nA = 64, nWA = WA / 4, nWB = WB / 4;
constexpr int SEG1 = X1 * (nA + 2 * nWA);
constexpr int SEG2 = SEG1 + (16 - X1) * (nA + nWA);
constexpr int SEG3 = SEG2 + (16 - X1) * nWA;
constexpr int SEG4 = SEG3 + 16 * nWB;
constexpr int SEG5 = SEG4 + 16 * nWB;
static_assert(SEG5 == NJOB * NCTA, "");

constexpr int SM_A = 0;
constexpr int SM_RING = 131072;
constexpr int SM_STG = SM_RING + NSLOT * SLOT;
constexpr int SM_PAR = SM_STG + NSTG * 8192;
constexpr int SM_BAR = SM_PAR + 3 * TN * 2;
constexpr int B_FULLB = 0, B_FULLA = 48, B_GO = 64, B_PAR = 88, B_PSTEP = 92, B_AFREE = 100, B_NINIT = 102, B_FULLS = 102, B_END = 108;
constexpr int SM_TOTAL = SM_BAR + B_END * 8;
static_assert(SM_TOTAL <= 232448, "");

__device__ uint4 g_a8[M_ * K_ / 16];
__device__ uint4 g_b8[N_ * K_ / 16];
__device__ uint4 g_cs[16 * N_ * 2 / 16];
__device__ unsigned g_flag[16 * 16 + 8 * 64];
__device__ unsigned g_epoch[NCTA];
__device__ unsigned g_sink;
constexpr int SM_ALLOC = SM_TOTAL;

__device__ __forceinline__ void mbar_init(uint32_t bar, uint32_t cnt) {
    asm volatile("mbarrier.init.shared::cta.b64 [%0], %1;" :: "r"(bar), "r"(cnt) : "memory");
}
__device__ __forceinline__ void mbar_expect_tx(uint32_t bar, uint32_t bytes) {
    asm volatile("mbarrier.arrive.expect_tx.shared::cta.b64 _, [%0], %1;" :: "r"(bar), "r"(bytes) : "memory");
}
__device__ __forceinline__ void mbar_arrive(uint32_t bar) {
    asm volatile("mbarrier.arrive.shared::cta.b64 _, [%0];" :: "r"(bar) : "memory");
}
__device__ __forceinline__ void mbar_arrive_cluster(uint32_t bar) {
    asm volatile("mbarrier.arrive.shared::cluster.b64 _, [%0];" :: "r"(bar) : "memory");
}
__device__ __forceinline__ void mbar_wait(uint32_t bar, uint32_t parity = 0) {
    asm volatile("{\n.reg .pred p;\n.reg .u32 c;\n"
                 "mbarrier.try_wait.parity.shared::cta.b64 p, [%0], %1;\n"
                 "@p bra WAIT_DONE;\n"
                 "mov.u32 c, 0;\n"
                 "WAIT_LOOP:\n"
                 "mbarrier.try_wait.parity.shared::cta.b64 p, [%0], %1;\n"
                 "@p bra WAIT_DONE;\n"
                 "add.u32 c, c, 1;\nsetp.lt.u32 p, c, 0x100000;\n"
                 "@p bra WAIT_LOOP;\n"
                 "trap;\n"
                 "WAIT_DONE:\n}" :: "r"(bar), "r"(parity) : "memory");
}
__device__ __forceinline__ void mbar_wait2(uint32_t bar0, uint32_t bar1) {
    asm volatile("{\n.reg .pred p, q;\n.reg .u32 c;\nmov.u32 c, 0;\n"
                 "WAIT_LOOP:\n"
                 "mbarrier.try_wait.parity.shared::cta.b64 p, [%0], 0;\n"
                 "mbarrier.try_wait.parity.shared::cta.b64 q, [%1], 0;\n"
                 "and.pred p, p, q;\n"
                 "@p bra WAIT_DONE;\n"
                 "add.u32 c, c, 1;\nsetp.lt.u32 p, c, 0x100000;\n"
                 "@p bra WAIT_LOOP;\n"
                 "trap;\n"
                 "WAIT_DONE:\n}" :: "r"(bar0), "r"(bar1) : "memory");
}
__device__ __forceinline__ bool mbar_test(uint32_t bar) {
    uint32_t ok;
    asm volatile("{\n.reg .pred p;\nmbarrier.test_wait.parity.shared::cta.b64 p, [%1], 0;\nselp.u32 %0, 1, 0, p;\n}" : "=r"(ok) : "r"(bar) : "memory");
    return ok;
}
__device__ __forceinline__ bool mbar_test2(uint32_t bar0, uint32_t bar1) {
    uint32_t ok;
    asm volatile("{\n.reg .pred p, q;\nmbarrier.test_wait.parity.shared::cta.b64 p, [%1], 0;\n"
                 "mbarrier.test_wait.parity.shared::cta.b64 q, [%2], 0;\nand.pred p, p, q;\nselp.u32 %0, 1, 0, p;\n}"
                 : "=r"(ok) : "r"(bar0), "r"(bar1) : "memory");
    return ok;
}
__device__ __forceinline__ bool elect_one() {
    uint32_t ok;
    asm volatile("{\n.reg .pred p;\nelect.sync _|p, 0xffffffff;\nselp.u32 %0, 1, 0, p;\n}" : "=r"(ok));
    return ok;
}
__device__ __forceinline__ unsigned ld_acquire(const unsigned* p) {
    unsigned v;
    asm volatile("ld.acquire.gpu.global.u32 %0, [%1];" : "=r"(v) : "l"(p) : "memory");
    return v;
}
__device__ __forceinline__ unsigned ld_flag(const unsigned* p) {
    unsigned v;
    asm volatile("ld.relaxed.gpu.global.u32 %0, [%1];" : "=r"(v) : "l"(p) : "memory");
    return v;
}
__device__ __forceinline__ uint4 lds128(uint32_t a) {
    uint4 v;
    asm volatile("ld.shared.v4.b32 {%0,%1,%2,%3}, [%4];" : "=r"(v.x), "=r"(v.y), "=r"(v.z), "=r"(v.w) : "r"(a) : "memory");
    return v;
}
__device__ __forceinline__ void sts128(uint32_t a, uint4 v) {
    asm volatile("st.shared.v4.b32 [%0], {%1,%2,%3,%4};" :: "r"(a), "r"(v.x), "r"(v.y), "r"(v.z), "r"(v.w) : "memory");
}
__device__ __forceinline__ uint32_t lds32(uint32_t a) {
    uint32_t v;
    asm volatile("ld.shared.b32 %0, [%1];" : "=r"(v) : "r"(a) : "memory");
    return v;
}
__device__ __forceinline__ void sts32(uint32_t a, uint32_t v) {
    asm volatile("st.shared.b32 [%0], %1;" :: "r"(a), "r"(v) : "memory");
}
__device__ __forceinline__ void stg128(void* p, uint4 v) {
    asm volatile("st.global.v4.b32 [%0], {%1,%2,%3,%4};" :: "l"(p), "r"(v.x), "r"(v.y), "r"(v.z), "r"(v.w) : "memory");
}
__device__ __forceinline__ unsigned pack4(unsigned a, unsigned b, unsigned c, unsigned d) {
    unsigned lo, r;
    asm("cvt.pack.sat.s8.s32.b32 %0, %1, %2, 0;" : "=r"(lo) : "r"(d), "r"(c));
    asm("cvt.pack.sat.s8.s32.b32 %0, %1, %2, %3;" : "=r"(r) : "r"(b), "r"(a), "r"(lo));
    return r;
}
__device__ __forceinline__ void cpasync16(uint32_t dst, const void* src) {
    asm volatile("cp.async.cg.shared.global [%0], [%1], 16;" :: "r"(dst), "l"(src) : "memory");
}
__device__ __forceinline__ unsigned pf_l2(const void* p) {
    unsigned v;
    asm volatile("ld.global.cg.L2::128B.u32 %0, [%1];" : "=r"(v) : "l"(p) : "memory");
    return v;
}

constexpr uint32_t DESC_A_HI = 0x80000000u | (512 >> 4);
constexpr uint32_t DESC_B_HI = 128 >> 4;
template <int NR> __device__ __forceinline__ void wgmma_n160(int (&d)[NR], uint32_t alo, uint32_t blo, int scale_d) {
    asm volatile("{\n.reg .pred p;\n.reg .b64 da, db;\nsetp.ne.b32 p, %82, 0;\n"
        "mov.b64 da, {%80, %83};\nmov.b64 db, {%81, %84};\n"
        "wgmma.mma_async.sync.aligned.m64n160k32.s32.s8.s8 "
        "{%0, %1, %2, %3, %4, %5, %6, %7, %8, %9, %10, %11, %12, %13, %14, %15, "
        "%16, %17, %18, %19, %20, %21, %22, %23, %24, %25, %26, %27, %28, %29, %30, %31, "
        "%32, %33, %34, %35, %36, %37, %38, %39, %40, %41, %42, %43, %44, %45, %46, %47, "
        "%48, %49, %50, %51, %52, %53, %54, %55, %56, %57, %58, %59, %60, %61, %62, %63, "
        "%64, %65, %66, %67, %68, %69, %70, %71, %72, %73, %74, %75, %76, %77, %78, %79}, "
        "da, db, p;\n}\n"
        : "+r"(d[0]), "+r"(d[1]), "+r"(d[2]), "+r"(d[3]), "+r"(d[4]), "+r"(d[5]), "+r"(d[6]), "+r"(d[7]),
          "+r"(d[8]), "+r"(d[9]), "+r"(d[10]), "+r"(d[11]), "+r"(d[12]), "+r"(d[13]), "+r"(d[14]), "+r"(d[15]),
          "+r"(d[16]), "+r"(d[17]), "+r"(d[18]), "+r"(d[19]), "+r"(d[20]), "+r"(d[21]), "+r"(d[22]), "+r"(d[23]),
          "+r"(d[24]), "+r"(d[25]), "+r"(d[26]), "+r"(d[27]), "+r"(d[28]), "+r"(d[29]), "+r"(d[30]), "+r"(d[31]),
          "+r"(d[32]), "+r"(d[33]), "+r"(d[34]), "+r"(d[35]), "+r"(d[36]), "+r"(d[37]), "+r"(d[38]), "+r"(d[39]),
          "+r"(d[40]), "+r"(d[41]), "+r"(d[42]), "+r"(d[43]), "+r"(d[44]), "+r"(d[45]), "+r"(d[46]), "+r"(d[47]),
          "+r"(d[48]), "+r"(d[49]), "+r"(d[50]), "+r"(d[51]), "+r"(d[52]), "+r"(d[53]), "+r"(d[54]), "+r"(d[55]),
          "+r"(d[56]), "+r"(d[57]), "+r"(d[58]), "+r"(d[59]), "+r"(d[60]), "+r"(d[61]), "+r"(d[62]), "+r"(d[63]),
          "+r"(d[64]), "+r"(d[65]), "+r"(d[66]), "+r"(d[67]), "+r"(d[68]), "+r"(d[69]), "+r"(d[70]), "+r"(d[71]),
          "+r"(d[72]), "+r"(d[73]), "+r"(d[74]), "+r"(d[75]), "+r"(d[76]), "+r"(d[77]), "+r"(d[78]), "+r"(d[79])
        : "r"(alo), "r"(blo), "r"(scale_d), "r"(DESC_A_HI), "r"(DESC_B_HI));
}
template <int NR> __device__ __forceinline__ void wgmma_t128(int (&d)[NR], uint32_t alo, uint32_t blo, int scale_d) {
    asm volatile("{\n.reg .pred p;\n.reg .b64 da, db;\nsetp.ne.b32 p, %66, 0;\n"
        "mov.b64 da, {%64, %67};\nmov.b64 db, {%65, %68};\n"
        "wgmma.mma_async.sync.aligned.m64n128k32.s32.s8.s8 "
        "{%0, %1, %2, %3, %4, %5, %6, %7, %8, %9, %10, %11, %12, %13, %14, %15, "
        "%16, %17, %18, %19, %20, %21, %22, %23, %24, %25, %26, %27, %28, %29, %30, %31, "
        "%32, %33, %34, %35, %36, %37, %38, %39, %40, %41, %42, %43, %44, %45, %46, %47, "
        "%48, %49, %50, %51, %52, %53, %54, %55, %56, %57, %58, %59, %60, %61, %62, %63}, "
        "da, db, p;\n}\n"
        : "+r"(d[0]), "+r"(d[1]), "+r"(d[2]), "+r"(d[3]), "+r"(d[4]), "+r"(d[5]), "+r"(d[6]), "+r"(d[7]),
          "+r"(d[8]), "+r"(d[9]), "+r"(d[10]), "+r"(d[11]), "+r"(d[12]), "+r"(d[13]), "+r"(d[14]), "+r"(d[15]),
          "+r"(d[16]), "+r"(d[17]), "+r"(d[18]), "+r"(d[19]), "+r"(d[20]), "+r"(d[21]), "+r"(d[22]), "+r"(d[23]),
          "+r"(d[24]), "+r"(d[25]), "+r"(d[26]), "+r"(d[27]), "+r"(d[28]), "+r"(d[29]), "+r"(d[30]), "+r"(d[31]),
          "+r"(d[32]), "+r"(d[33]), "+r"(d[34]), "+r"(d[35]), "+r"(d[36]), "+r"(d[37]), "+r"(d[38]), "+r"(d[39]),
          "+r"(d[40]), "+r"(d[41]), "+r"(d[42]), "+r"(d[43]), "+r"(d[44]), "+r"(d[45]), "+r"(d[46]), "+r"(d[47]),
          "+r"(d[48]), "+r"(d[49]), "+r"(d[50]), "+r"(d[51]), "+r"(d[52]), "+r"(d[53]), "+r"(d[54]), "+r"(d[55]),
          "+r"(d[56]), "+r"(d[57]), "+r"(d[58]), "+r"(d[59]), "+r"(d[60]), "+r"(d[61]), "+r"(d[62]), "+r"(d[63])
        : "r"(alo), "r"(blo), "r"(scale_d), "r"(DESC_B_HI), "r"(DESC_A_HI));
}

__device__ __forceinline__ void wg_fence() { asm volatile("wgmma.fence.sync.aligned;" ::: "memory"); }
__device__ __forceinline__ void wg_commit() { asm volatile("wgmma.commit_group.sync.aligned;" ::: "memory"); }
template <int N> __device__ __forceinline__ void wg_wait() { asm volatile("wgmma.wait_group.sync.aligned %0;" :: "n"(N) : "memory"); }

struct Job { int src; int dst; };
__host__ __device__ constexpr int unit_of(int piece, int slab) {
    return piece < 2 ? (slab < X1 ? 2 * slab + piece : (piece ? 16 : X1) + slab) : 32 + (piece - 2) * 8 + (slab >> 1);
}
__device__ __forceinline__ Job decode_job(int g) {
    int slab, idx, piece;
    if (g < SEG2) {
        int r;
        if (g < SEG1) { slab = g / (nA + 2 * nWA); r = g - slab * (nA + 2 * nWA); }
        else { g -= SEG1; slab = g / (nA + nWA); r = g - slab * (nA + nWA); slab += X1; }
        piece = r < nA ? -1 : (r < nA + nWA ? 0 : 1);
        idx = r < nA ? r : r - nA - piece * nWA;
    } else if (g < SEG3) {
        g -= SEG2; slab = g / nWA; idx = g - slab * nWA; slab += X1; piece = 1;
    } else {
        g -= SEG3; piece = 2 + (g >> 8); slab = (g >> 4) & 15; idx = g & 15;
        static_assert(nWB == 16, "");
    }
    Job j;
    if (piece < 0) {
        const int flag = (idx >> 2) * 16 + slab;
        j.src = idx * 32 + (slab << 12);
        j.dst = (flag * 512 + (idx & 3) * 128) | (flag << 18);
    } else {
        const bool wide = piece < 2;
        const int w = wide ? WA : WB;
        const int nb = wide ? idx / (WA / 32) : idx / (WB / 32);
        const int J = idx - nb * (w / 32);
        const int cb = nb * TN + (wide ? piece * WA : 2 * WA - 2 * WB + piece * WB);
        j.src = cb + J * 32 + (slab << 12) + (wide ? 1 << 16 : 2 << 16);
        j.dst = (cb * (K_ / 16) + slab * w * 4 + J * 32) | ((256 + nb * 64 + unit_of(piece, slab)) << 18);
    }
    return j;
}
struct Coord { const CUtensorMap* m; int x, y, z; };
__device__ __forceinline__ Coord job_coord(const CUtensorMap* maps, int src) {
    const bool w = src >> 16;
    const int c0 = src & 0xFFF, slab = (src >> 12) & 15;
    return {maps + (w ? 1 : 0), w ? c0 : 0, w ? slab * 64 : slab * 2, w ? 0 : c0};
}
__device__ __forceinline__ void raw_load(const Coord& c, uint32_t dst, uint32_t bar) {
    mbar_expect_tx(bar, 8192);
    asm volatile("cp.async.bulk.tensor.3d.shared::cluster.global.tile.mbarrier::complete_tx::bytes [%0], [%1, {%2, %3, %4}], [%5];"
                 :: "r"(dst), "l"(c.m), "r"(c.x), "r"(c.y), "r"(c.z), "r"(bar) : "memory");
}
__device__ __forceinline__ void raw_prefetch(const Coord& c) {
    asm volatile("cp.async.bulk.prefetch.tensor.3d.L2.global.tile [%0, {%1, %2, %3}];"
                 :: "l"(c.m), "r"(c.x), "r"(c.y), "r"(c.z) : "memory");
}
__host__ __device__ constexpr unsigned unit_mask(int piece, int s0, int s1) {
    unsigned m = 0;
    for (int s = s0; s < s1; s++) m |= 1u << (unit_of(piece, s) & 31);
    return m;
}
__host__ __device__ constexpr int slot_of(int u) {
    return u < UX ? (u % NSLOT) * (SLOT / 2048) : u < UX + NSTG ? NSLOT * (SLOT / 2048) + (u - UX) * 4 : ((u - NSTG) % NSLOT) * (SLOT / 2048);
}
__host__ __device__ constexpr uint64_t slot_table(int piece) {
    uint64_t t = 0;
    if (piece < 2) for (int s = 0; s < 16; s++) t |= (uint64_t)(unit_of(piece, s) % NSLOT) << (4 * s);
    else for (int s = 0; s < 8; s++) t |= (uint64_t)slot_of(unit_of(piece, 2 * s)) << (8 * s);
    return t;
}
struct Maps { CUtensorMap m[3]; };

__device__ __forceinline__ uint32_t bf2_op_epi(int a, int b, uint32_t zc, uint32_t sx, uint32_t sw, uint32_t bi) {
    uint32_t v;
    float fa = __int2float_rn(a), fb = __int2float_rn(b);
    asm("cvt.rn.bf16x2.f32 %0, %1, %2;" : "=r"(v) : "f"(fb), "f"(fa));
    asm("sub.rn.bf16x2 %0, %0, %1;" : "+r"(v) : "r"(zc));
    asm("mul.rn.bf16x2 %0, %0, %1;" : "+r"(v) : "r"(sx));
    asm("mul.rn.bf16x2 %0, %0, %1;" : "+r"(v) : "r"(sw));
    asm("add.rn.bf16x2 %0, %0, %1;" : "+r"(v) : "r"(bi));
    return v;
}

struct Par { uint4 zc, sw, bi; };
__device__ __forceinline__ Par ld_par(uint32_t p) { return {lds128(p), lds128(p + TN * 2), lds128(p + TN * 4)}; }
__device__ __forceinline__ void epi_row(const int (&a)[WA / 2], int o, const Par& p, uint32_t sx2, char* out) {
    uint4 r;
    r.x = bf2_op_epi(a[o + 0], a[o + 4], p.zc.x, sx2, p.sw.x, p.bi.x);
    r.y = bf2_op_epi(a[o + 8], a[o + 12], p.zc.y, sx2, p.sw.y, p.bi.y);
    r.z = bf2_op_epi(a[o + 1], a[o + 5], p.zc.z, sx2, p.sw.z, p.bi.z);
    r.w = bf2_op_epi(a[o + 9], a[o + 13], p.zc.w, sx2, p.sw.w, p.bi.w);
    stg128(out, r);
}
template <int J, int JN>
__device__ __forceinline__ void epilogue(const int (&a)[WA / 2], Par& p, uint32_t par, uint32_t sx2, char* out) {
    epi_row(a, J * 16, p, sx2, out + J * 64);
    Par n = p;
    if (JN != J) n = ld_par(par + JN * 64);
    epi_row(a, J * 16 + 2, p, sx2, out + 8 * (N_ * 2) + J * 64);
    p = n;
}

__global__ void __cluster_dims__(2, 1, 1) __launch_bounds__(512, 1)
w8a8_kernel(const __grid_constant__ Maps maps, const char* __restrict__ qx, const char* __restrict__ qw, const __nv_bfloat16* __restrict__ scale_x, const int* __restrict__ zero_x,
            const __nv_bfloat16* __restrict__ scale_w, const __nv_bfloat16* __restrict__ bias,
            __nv_bfloat16* __restrict__ out) {
    extern __shared__ __align__(1024) unsigned char smem_raw[];
    const uint32_t sb = (uint32_t)__cvta_generic_to_shared(smem_raw);
    const uint32_t bars = sb + SM_BAR;
    const int warp = __shfl_sync(~0u, threadIdx.x >> 5, 0), lane = threadIdx.x & 31;
    const int b = blockIdx.x, rank = b & 1, nb = (b >> 1) & 7, mb = (b >> 4) * 2 + rank;

    if (warp >= 8) {
        asm volatile("setmaxnreg.dec.sync.aligned.u32 56;");
        if (warp >= 16 - NCONV) {
            const int cw = warp - (16 - NCONV);
            unsigned t0;
            asm volatile("mov.u32 %0, %clock;" : "=r"(t0));
            t0 += 100;
            asm volatile("barrier.cluster.arrive.relaxed.aligned;" ::: "memory");
            const Job mj = decode_job(min(lane, NJOB - 1) * NCTA + b);
            static_assert(NCONV == NSTG + 2 && NJOB == 22, "");
            const uint32_t s = sb + (cw < NSTG ? SM_STG + cw * 8192 : SM_A + (14 - NSTG + cw) * 8192);
            const uint32_t sbar = bars + (B_FULLS + cw) * 8;
            {
                const Coord c = job_coord(maps.m, __shfl_sync(~0u, mj.src, cw));
                if (elect_one()) {
                    mbar_init(sbar, 1);
                    asm volatile("fence.mbarrier_init.release.cluster;" ::: "memory");
                    unsigned t;
                    do { asm volatile("mov.u32 %0, %clock;" : "=r"(t)); } while ((int)(t - t0) < cw * PFD + (cw ? b * 88 : b * 0) / 16);
                    raw_load(c, s, sbar);
                }
                __syncwarp();
            }
            asm volatile("barrier.cluster.wait.aligned;" ::: "memory");
            t0 += b * 88 / 16;
            const int c4 = lane & 3, ln = (lane >> 2) * 2 + (c4 >> 1);
            const uint32_t rdA = ln * 128 + ((((c4 & 1) << 2) ^ (ln & 7)) << 4);
            const uint32_t rdB = (lane >> 3) * 2048 + (lane & 7) * 16;
            const int wrA = (lane >> 2) * 4 + (c4 ^ ((lane >> 3) & 3));
            uint32_t par = 0;
#pragma unroll 1
            for (int j = cw, jn; j < NJOB; j = jn, par ^= 1) {
                jn = j < 13 ? j + NCONV : (j < 15 ? 31 : j + NSTG);
                const int src = __shfl_sync(~0u, mj.src, j), dst = __shfl_sync(~0u, mj.dst, j);
                const int nsrc = __shfl_sync(~0u, mj.src, jn);
                const int kind = src >> 16;
                uint4 o[4];
                uint4* d;
                int dstep;
                mbar_wait(sbar, par);
                if (kind == 0) {
                    const uint32_t a0 = s + rdA;
                    d = g_a8 + (dst & 0x3FFFF) + wrA;
                    dstep = 32;
#pragma unroll
                    for (int i = 0; i < 4; i++) {
                        uint4 v0 = lds128(a0 + i * 2048), v1 = lds128((a0 ^ 16) + i * 2048);
                        uint4 v2 = lds128((a0 ^ 32) + i * 2048), v3 = lds128((a0 ^ 48) + i * 2048);
                        o[i].x = pack4(v0.x, v0.y, v0.z, v0.w); o[i].y = pack4(v1.x, v1.y, v1.z, v1.w);
                        o[i].z = pack4(v2.x, v2.y, v2.z, v2.w); o[i].w = pack4(v3.x, v3.y, v3.z, v3.w);
                    }
                } else {
                    const uint32_t a0 = s + rdB;
                    d = g_b8 + (dst & 0x3FFFF) + (lane >> 3) * (kind == 1 ? WA : WB) + (lane & 7);
                    dstep = 8;
#define CV_B(m, f)                                                                                    \
                    {                                                                                 \
                        uint4 v0 = lds128(a0 + m * 512), v1 = lds128(a0 + m * 512 + 128);             \
                        uint4 v2 = lds128(a0 + m * 512 + 256), v3 = lds128(a0 + m * 512 + 384);       \
                        o[0].f = pack4(v0.x, v1.x, v2.x, v3.x); o[1].f = pack4(v0.y, v1.y, v2.y, v3.y); \
                        o[2].f = pack4(v0.z, v1.z, v2.z, v3.z); o[3].f = pack4(v0.w, v1.w, v2.w, v3.w); \
                    }
                    CV_B(0, x) CV_B(1, y) CV_B(2, z) CV_B(3, w)
                }
#pragma unroll
                for (int i = 0; i < 4; i++) stg128(d + i * dstep, o[i]);
                unsigned tn;
                asm volatile("mov.u32 %0, %clock;" : "=r"(tn));
                const bool late = jn < NJOB && (int)(tn - t0) < jn * PFD;
                if (!late && elect_one()) {
                    if (jn < NJOB) { raw_load(job_coord(maps.m, nsrc), s, sbar); }
                    else if (jn == 31) mbar_arrive(bars + (B_AFREE - NSTG + cw) * 8);
                    else if (0 != 1) {
                        uint32_t ra;
                        asm("mapa.shared::cluster.u32 %0, %1, %2;" : "=r"(ra) : "r"(bars + (B_GO + ((UX + cw) >> 1)) * 8), "r"((UX + cw) & 1));
                        mbar_arrive_cluster(ra);
                    }
                }
                const int* csp = (const int*)d;
                unsigned csv = o[0].x;
                if (kind != 0) {
                    int cs[4];
#pragma unroll
                    for (int i = 0; i < 4; i++)
                        cs[i] = __dp4a((int)o[i].x, 0x01010101, __dp4a((int)o[i].y, 0x01010101,
                                __dp4a((int)o[i].z, 0x01010101, __dp4a((int)o[i].w, 0x01010101, 0))));
                    const int p01 = cs[0] + cs[1] * 65536, p23 = cs[2] + cs[3] * 65536;
                    const bool odd = lane & 8;
                    int v = (odd ? p23 : p01) + __shfl_xor_sync(~0u, odd ? p01 : p23, 8);
                    v += __shfl_xor_sync(~0u, v, 16);
                    int* p = (int*)g_cs + ((src >> 12) & 15) * (N_ / 2) + ((src & 0xFFF) >> 1) + (lane & 15);
                    if (lane < 16) *p = v;
                    csp = p; csv = v;
                }
#pragma unroll 1
                for (int it = 0; it < 1000; it++) {
                    bool ok = true;
                    if ((lane & 3) == 0) {
                        unsigned rb[5];
#pragma unroll
                        for (int i = 0; i < 4; i++)
                            asm volatile("ld.relaxed.gpu.global.u32 %0, [%1];" : "=r"(rb[i]) : "l"(d + i * dstep) : "memory");
                        asm volatile("ld.relaxed.gpu.global.u32 %0, [%1];" : "=r"(rb[4]) : "l"(csp) : "memory");
                        ok = rb[0] == o[0].x && rb[1] == o[1].x && rb[2] == o[2].x && rb[3] == o[3].x && rb[4] == csv;
                    }
                    if (__all_sync(~0u, ok)) break;
                }
                if (elect_one()) asm volatile("red.relaxed.gpu.global.add.u32 [%0], 1;" :: "l"(g_flag + ((unsigned)dst >> 18)) : "memory");
                __syncwarp();
                if (late && elect_one()) {
                    do { asm volatile("mov.u32 %0, %clock;" : "=r"(tn)); } while ((int)(tn - t0) < jn * PFD);
                    raw_load(job_coord(maps.m, nsrc), s, sbar);
                }
                __syncwarp();
            }
        } else if (warp == 8) {
            asm volatile("barrier.cluster.arrive.relaxed.aligned;" ::: "memory");
            const unsigned ep = *(volatile unsigned*)&g_epoch[b] + 1;
            const unsigned* f1 = g_flag + 256 + nb * 64 + lane;
            const unsigned* f2 = lane < 16 ? f1 + 32 : g_flag + mb * 16 + lane - 16;
            const unsigned t1 = ep * (WA / 32), t2 = ep * 4;
            static_assert(WB / 16 == 4, "");
            const unsigned n1 = lane == 0 ? unit_mask(0, 0, 8) : lane == 1 ? unit_mask(1, 0, 8) : lane == 2 ? unit_mask(0, 8, 16)
                              : lane == 3 ? unit_mask(1, 8, 16) : 0u;
            const unsigned n2 = lane < 4 ? 0u : 0xFFFFu;
            bool d1 = false, d2 = false, d3 = lane >= 5, fr = lane < 30;
            asm volatile("barrier.cluster.wait.aligned;" ::: "memory");
            for (int it = 0; 0 != 1; it++) {
                unsigned v1 = t1, v2 = t2;
                if (!d1) v1 = ld_flag(f1);
                if (!d2) v2 = ld_flag(f2);
                if (!fr) fr = mbar_test(bars + (B_AFREE - 30 + lane) * 8);
                if (!d2 && fr && (int)(v2 - t2) >= 0) {
                    d2 = true;
                    if (lane >= 16) {
                        asm volatile("fence.proxy.async.global;" ::: "memory");
                        asm volatile("cp.async.bulk.shared::cluster.global.mbarrier::complete_tx::bytes [%0], [%1], %2, [%3];"
                                     :: "r"(sb + SM_A + (lane - 16) * 8192), "l"((const char*)g_a8 + (mb * 16 + lane - 16) * 8192),
                                        "r"(8192), "r"(bars + (B_FULLA + lane - 16) * 8) : "memory");
                    } else if ((lane & 1) == rank) mbar_arrive(bars + (B_GO + 16 + (lane >> 1)) * 8);
                }
                if (!d1 && (int)(v1 - t1) >= 0) {
                    d1 = true;
                    if ((lane & 1) == rank) mbar_arrive(bars + (B_GO + (lane >> 1)) * 8);
                }
                const unsigned m1 = __ballot_sync(~0u, d1), m2 = __ballot_sync(~0u, d2);
                if (!d3 && (m1 & n1) == n1 && (m2 & n2) == n2) { d3 = true; mbar_arrive(bars + (B_PSTEP + lane) * 8); }
                if ((m1 & m2) == ~0u) break;
                if (it > (1 << 22)) __trap();
            }
        } else if (warp == 9) {
            asm volatile("barrier.cluster.arrive.relaxed.aligned;" ::: "memory");
            const int u = 2 * lane + rank;
            int so, fb;
            if (u < 2 * X1) { so = (u & 1) * (WA * K_) + (u >> 1) * (WA * 64); fb = (u & 1) * 24 + (u >> 1); }
            else if (u < X1 + 16) { so = (u - X1) * (WA * 64); fb = u - X1; }
            else if (u < 32) { so = WA * K_ + (u - 16) * (WA * 64); fb = 24 + u - 16; }
            else { so = 2 * WA * K_ + (u - 32) * (WB * 128); fb = u < 40 ? u - 16 : u; }
            const char* srcB = (const char*)g_b8 + nb * TN * K_ + so;
            const uint32_t dstB = sb + SM_RING + slot_of(u) * 2048;
            asm volatile("barrier.cluster.wait.aligned;" ::: "memory");
#pragma unroll 1
            for (int i = 0; i < NU / 2 && 0 != 1; i++) {
                mbar_wait(bars + (B_GO + i) * 8);
                if (lane == i) {
                    asm volatile("fence.proxy.async.global;" ::: "memory");
                    asm volatile("cp.async.bulk.shared::cluster.global.mbarrier::complete_tx::bytes.multicast::cluster [%0], [%1], %2, [%3], %4;"
                                 :: "r"(dstB), "l"(srcB), "r"(u < 32 ? WA * 64 : WB * 128), "r"(bars + (B_FULLB + fb) * 8), "h"((uint16_t)3) : "memory");
                }
                __syncwarp();
            }
        } else if (warp == 10) {
            unsigned pv, pv2;
            {
                static_assert(X1 > 0 && nA == 64 && nWA == 40, "");
                const int i = b - (b < 104 ? 64 : 104), q = i / 5;
                const char* p = b < 64 ? qx + (b * 32 + (lane >> 1)) * (K_ * 4) + (lane & 1) * 128
                                       : qw + lane * (N_ * 4) + (q * TN + (b < 104 ? 0 : WA) + (i - q * 5) * 32) * 4;
                pv = pf_l2(p);
                pv2 = pf_l2(p + (b < 64 ? 16 * K_ * 4 : 32 * N_ * 4));
                if (lane < 3) asm volatile("prefetch.tensormap [%0];" :: "l"(maps.m + lane) : "memory");
            }
            asm volatile("barrier.cluster.arrive.relaxed.aligned;" ::: "memory");
            if ((pv ^ pv2) == 0x40000000u) g_sink = pv;
            const float zxf = __bfloat162float(__float2bfloat16_rn((float)__ldg(zero_x)));
#pragma unroll 1
            for (int i = lane; i < TN / 4; i += 32) {
                const bool hi = i >= TN / 8;
                sts128(sb + SM_PAR + TN * 2 + i * 16, __ldg((const uint4*)((hi ? bias : scale_w) + nb * TN) + (hi ? i - TN / 8 : i)));
            }
            asm volatile("barrier.cluster.wait.aligned;" ::: "memory");
            int c[8], cs[8];
#pragma unroll
            for (int i = 0; i < 8; i++) { c[i] = 0; cs[i] = 0; }
#pragma unroll 1
            for (int st = 0; st < 5 && 0 != 1; st++) {
                const bool wide = st < 4;
                const int half = wide ? (st >> 1) : (lane >> 4);
                const int col = wide ? (st & 1) * WA + min(lane, WA / 8 - 1) * 8 : 2 * WA + (lane & 15) * 8;
                const uint4* src = g_cs + (half * 8 * N_ + nb * TN + col) / 8;
                mbar_wait(bars + (B_PSTEP + st) * 8);
                uint4 v[8];
#pragma unroll
                for (int i = 0; i < 8; i++) v[i] = __ldcg(src + i * (N_ / 8));
#pragma unroll
                for (int h = 0; h < 8; h += 4) {
                    const unsigned sv[4] = {v[h].x + v[h + 1].x + v[h + 2].x + v[h + 3].x, v[h].y + v[h + 1].y + v[h + 2].y + v[h + 3].y,
                                            v[h].z + v[h + 1].z + v[h + 2].z + v[h + 3].z, v[h].w + v[h + 1].w + v[h + 2].w + v[h + 3].w};
#pragma unroll
                    for (int i = 0; i < 4; i++) {
                        const int lo = (int)(short)(sv[i] & 0xFFFF);
                        c[2 * i] += lo; c[2 * i + 1] += ((int)(sv[i] - (unsigned)lo)) >> 16;
                    }
                }
                if (st >= 2) {
                    uint32_t z[4];
#pragma unroll
                    for (int i = 0; i < 8; i++) {
                        const int o = __shfl_xor_sync(~0u, c[i], 16);
                        if (!wide) c[i] += o;
                    }
#pragma unroll
                    for (int i = 0; i < 4; i++) {
                        const float lo = __bfloat162float(__float2bfloat16_rn((float)c[2 * i])) * zxf;
                        const float hi = __bfloat162float(__float2bfloat16_rn((float)c[2 * i + 1])) * zxf;
                        asm("cvt.rn.bf16x2.f32 %0, %1, %2;" : "=r"(z[i]) : "f"(hi), "f"(lo));
                    }
                    const uint32_t za = sb + SM_PAR + ((col & ~31) + (col & 8) * 2 + ((col >> 3) & 2)) * 2;
#pragma unroll
                    for (int i = 0; i < 4; i++) sts32(za + i * 8, z[i]);
                    __syncwarp();
                    if (lane == 0) { mbar_arrive(bars + (B_PAR + st - 2) * 8); }
#pragma unroll
                    for (int i = 0; i < 8; i++) c[i] = 0;
                }
#pragma unroll
                for (int i = 0; i < 8; i++) { const int t = c[i]; c[i] = cs[i]; cs[i] = t; }
            }
        } else {
            asm volatile("barrier.cluster.arrive.relaxed.aligned;" ::: "memory");
            asm volatile("barrier.cluster.wait.aligned;" ::: "memory");
        }
    } else {
        asm volatile("setmaxnreg.inc.sync.aligned.u32 200;");
        {
            constexpr int PER = (B_NINIT + 7) / 8;
            if (elect_one()) {
#pragma unroll 1
                for (int i = warp * PER; i < min(warp * PER + PER, B_NINIT); i++)
                    {
                    const int u = 2 * (i - B_GO) + rank;
                    mbar_init(bars + i * 8, (i < B_GO || i >= B_PAR || u < NSLOT) ? 1 : (u >= UX && u < UX + NSTG) ? 3 : 9);
                }
            }
            __syncwarp();
            const int i = warp * PER + lane;
            if (lane < PER && i < B_GO) mbar_expect_tx(bars + i * 8, (i < 16 || (i >= 24 && i < 40)) ? WA * 64 : 8192);
            static_assert(WB * 128 == 8192, "");
            asm volatile("fence.mbarrier_init.release.cluster;" ::: "memory");
        }
        asm volatile("barrier.cluster.arrive.relaxed.aligned;" ::: "memory");
        const int wg = warp >> 2;
        const uint32_t sd = (sb & 0x3FFFF) >> 4;
        const unsigned short sxr = __ldg((const unsigned short*)scale_x);
        const uint32_t sx2 = (uint32_t)sxr * 0x10001u;
        char* orow = (char*)out + (size_t)(mb * 128 + (warp & 3) * 16 + (lane >> 2)) * (N_ * 2) + (nb * TN + (lane & 3) * 8 + wg * WA) * 2;
        const uint32_t par = sb + SM_PAR + (lane & 3) * 16 + wg * WA * 2;
        uint32_t reladdr;
        int rell;
        {
            const int u = lane < 16 ? (lane < X1 ? 2 * lane + wg : (wg ? 16 : X1) + lane) : 16 + wg * 8 + lane;
            const int v = u + (u < 32 ? NSLOT : NSLOT + NSTG);
            rell = (lane < 24 && v < NU) ? lane : 99;
            asm("mapa.shared::cluster.u32 %0, %1, %2;" : "=r"(reladdr) : "r"(bars + (B_GO + (v >> 1)) * 8), "r"(v & 1));
        }
        asm volatile("barrier.cluster.wait.aligned;" ::: "memory");
        int a0[WA / 2], a1[WA / 2];
        uint32_t barB = bars + (B_FULLB + wg * 24) * 8;
        bool ready = false;
#define HAND_BACK(done) if (rell <= (done)) { mbar_arrive_cluster(reladdr); rell = 99; }
        if (0 != 1) {
            wg_fence();
            {
                uint64_t tbl = wg ? slot_table(1) : slot_table(0);
                uint32_t da = (sd + (SM_A >> 4)) | (1 << 16);
#pragma unroll 1
                for (int s = 0; s < 16; s++) {
                    const uint32_t db = ((sd + (SM_RING >> 4)) | (WA << 16)) + ((uint32_t)tbl & 15) * (SLOT >> 4);
                    const bool starved = !ready && !mbar_test2(bars + (B_FULLA + s) * 8, barB);
                    if (starved) {
                        wg_wait<0>();
                        HAND_BACK(s - 1)
                        mbar_wait2(bars + (B_FULLA + s) * 8, barB);
                    }
                    wgmma_n160(a0, da, db, s);
                    wgmma_n160(a1, da + 256, db, s);
                    wgmma_n160(a0, da + 2, db + 2 * WA, 1);
                    wgmma_n160(a1, da + 258, db + 2 * WA, 1);
                    wg_commit();
                    HAND_BACK(s - 2)
                    tbl >>= 4; da += 512; barB += 8;
                    ready = mbar_test2(bars + (B_FULLA + min(s + 1, 15)) * 8, barB);
                    wg_wait<1>();
                }
            }
            HAND_BACK(14)
            wg_wait<0>();
            HAND_BACK(15)
            mbar_wait(bars + (B_PAR + wg) * 8);
            Par P = ld_par(par);
            char* const orow1 = orow + 64 * (N_ * 2);
            epilogue<0, 1>(a0, P, par, sx2, orow); epilogue<1, 2>(a0, P, par, sx2, orow);
            epilogue<2, 3>(a0, P, par, sx2, orow); epilogue<3, 0>(a0, P, par, sx2, orow);
            int t[64];
            wg_fence();
            {
                uint64_t tbl = wg ? slot_table(3) : slot_table(2);
                uint32_t da = (sd + (SM_A >> 4)) | (1 << 16);
#pragma unroll
                for (int i = 16; i < 24; i++) {
                    const uint32_t db = ((sd + (SM_RING >> 4)) | (WB << 16)) + ((uint32_t)tbl & 255) * 128;
                    const bool starved = !ready && !mbar_test(barB);
                    if (starved) {
                        wg_wait<0>();
                        HAND_BACK(i - 1)
                        mbar_wait(barB);
                    }
#pragma unroll
                    for (int k = 0; k < 4; k++) wgmma_t128(t, db + k * 2 * WB, da + (k >> 1) * 512 + (k & 1) * 2, k ? 1 : i - 16);
                    wg_commit();
                    HAND_BACK(i - 2)
                    tbl >>= 8; da += 1024; barB += 8;
                    ready = mbar_test(barB);
                    switch (i) {
                        case 16: epilogue<0, 0>(a1, P, par, sx2, orow1); break;
                        case 17: epilogue<1, 1>(a1, P, par, sx2, orow1); break;
                        case 18: epilogue<2, 2>(a1, P, par, sx2, orow1); break;
                        case 19: epilogue<3, 3>(a1, P, par, sx2, orow1); break;
                        case 20: epilogue<4, 4>(a1, P, par, sx2, orow1); break;
                        case 21: epilogue<4, 4>(a0, P, par, sx2, orow); break;
                        default: break;
                    }
                    if (i < 20) P = ld_par(par + (i - 15) * 64);
                    wg_wait<1>();
                }
            }
            HAND_BACK(22)
            mbar_wait(bars + (B_PAR + 2) * 8);
            const int w = warp & 3, q = lane >> 2, c0 = (w >> 1) * 32 + q * 4 + (w & 1) * 2;
            const uint32_t pp = sb + SM_PAR + (2 * WA + wg * WB + c0) * 2;
            const uint32_t zc = lds32(pp), sw = lds32(pp + TN * 2), bi = lds32(pp + TN * 4);
            const int r0 = (lane & 3) * 2;
            const uint32_t st0 = r0 * 128 + (((c0 >> 3) ^ r0) << 4) + (c0 & 7) * 2, st1 = (st0 ^ 16) + 128;
            wg_wait<0>();
            asm volatile("bar.sync %0, 128;" :: "r"(3 + wg) : "memory");
#pragma unroll
            for (int h = 0; h < 2; h++) {
                const uint32_t buf = sb + SM_RING + (wg ? slot_of(UX + 1 + h) : slot_of(UX - 1 + h)) * 2048;
#pragma unroll
                for (int j = 0; j < 8; j++) {
                    const int o = h * 32 + j * 4;
                    sts32(buf + st0 + j * 1024, bf2_op_epi(t[o], t[o + 2], zc, sx2, sw, bi));
                    sts32(buf + st1 + j * 1024, bf2_op_epi(t[o + 1], t[o + 3], zc, sx2, sw, bi));
                }
                asm volatile("fence.proxy.async.shared::cta;" ::: "memory");
                asm volatile("bar.sync %0, 128;" :: "r"(3 + wg) : "memory");
                if (w == 0 && elect_one())
                    asm volatile("cp.async.bulk.tensor.2d.global.shared::cta.tile.bulk_group [%0, {%1, %2}], [%3];"
                                 :: "l"(maps.m + 2), "r"(nb * TN + 2 * WA + wg * WB), "r"(mb * 128 + h * 64), "r"(buf) : "memory");
            }
            if (w == 0) {
                asm volatile("cp.async.bulk.commit_group;" ::: "memory");
                asm volatile("cp.async.bulk.wait_group.read 0;" ::: "memory");
            }
        }
        if (threadIdx.x == 128) asm volatile("red.relaxed.gpu.global.add.u32 [%0], 1;" :: "l"(g_epoch + b) : "memory");
    }
}

static void launch(EncodeFn encode, void* const* d_in, void* d_out) {
    Maps maps;
    CUtensorMap &mx = maps.m[0], &mw = maps.m[1];
    {
        const cuuint64_t dim[3] = {32, K_ / 32, M_}, str[2] = {128, K_ * 4};
        const cuuint32_t box[3] = {32, 2, 32}, es[3] = {1, 1, 1};
        encode(&mx, CU_TENSOR_MAP_DATA_TYPE_INT32, 3, d_in[0], dim, str, box, es, CU_TENSOR_MAP_INTERLEAVE_NONE,
               CU_TENSOR_MAP_SWIZZLE_128B, CU_TENSOR_MAP_L2_PROMOTION_NONE, CU_TENSOR_MAP_FLOAT_OOB_FILL_NONE);
    }
    {
        const cuuint64_t dim[3] = {N_, K_, 1}, str[2] = {N_ * 4, (cuuint64_t)N_ * K_ * 4};
        const cuuint32_t box[3] = {32, 64, 1}, es[3] = {1, 1, 1};
        encode(&mw, CU_TENSOR_MAP_DATA_TYPE_INT32, 3, d_in[1], dim, str, box, es, CU_TENSOR_MAP_INTERLEAVE_NONE,
               CU_TENSOR_MAP_SWIZZLE_NONE, CU_TENSOR_MAP_L2_PROMOTION_NONE, CU_TENSOR_MAP_FLOAT_OOB_FILL_NONE);
    }
    {
        const cuuint64_t dim[2] = {N_, M_}, str[1] = {N_ * 2};
        const cuuint32_t box[2] = {WB, 64}, es[2] = {1, 1};
        encode(&maps.m[2], CU_TENSOR_MAP_DATA_TYPE_BFLOAT16, 2, d_out, dim, str, box, es, CU_TENSOR_MAP_INTERLEAVE_NONE,
               CU_TENSOR_MAP_SWIZZLE_128B, CU_TENSOR_MAP_L2_PROMOTION_NONE, CU_TENSOR_MAP_FLOAT_OOB_FILL_NONE);
    }
    w8a8_kernel<<<NCTA, 512, SM_ALLOC>>>(maps, (const char*)d_in[0], (const char*)d_in[1], (const __nv_bfloat16*)d_in[2], (const int*)d_in[3],
                                         (const __nv_bfloat16*)d_in[4], (const __nv_bfloat16*)d_in[5],
                                         (__nv_bfloat16*)d_out);
}

}

extern "C" void kernel_launch(void* const* d_in, const int* in_sizes, int n_in, void* d_out, int out_size) {
    using namespace ra;
    static EncodeFn encode = nullptr;
    static Scratch* scr = nullptr;
    static const JobTable* jobs = nullptr;
    static bool fits = false;
    if (!encode) {
        void* fn = nullptr;
        cudaDriverEntryPointQueryResult qr;
        cudaGetDriverEntryPoint("cuTensorMapEncodeTiled", &fn, cudaEnableDefault, &qr);
        encode = (EncodeFn)fn;
        cudaGetSymbolAddress((void**)&scr, g_scratch);
        cudaGetSymbolAddress((void**)&jobs, g_jobs);
        cudaFuncSetAttribute(w8a8_kernel, cudaFuncAttributeMaxDynamicSharedMemorySize, SM_ALLOC);
        cudaFuncSetAttribute(w8a8_kernel, cudaFuncAttributeNonPortableClusterSizeAllowed, 1);
        cudaFuncSetAttribute(w8a8_side, cudaFuncAttributeMaxDynamicSharedMemorySize, SM_ALLOC);
        cudaFuncSetAttribute(w8::w8a8_kernel, cudaFuncAttributeMaxDynamicSharedMemorySize, w8::SM_ALLOC);
        cudaLaunchConfig_t oc = {};
        oc.gridDim = dim3(NCTA); oc.blockDim = dim3(512); oc.dynamicSmemBytes = SM_ALLOC;
        cudaLaunchAttribute oa[1];
        oa[0].id = cudaLaunchAttributeClusterDimension; oa[0].val.clusterDim.x = CS; oa[0].val.clusterDim.y = 1; oa[0].val.clusterDim.z = 1;
        oc.attrs = oa; oc.numAttrs = 1;
        int nc = 0;
        fits = cudaOccupancyMaxActiveClusters(&nc, w8a8_kernel, &oc) == cudaSuccess && nc >= NCTA / CS;
        cudaGetLastError();
    }
    if (!fits) { w8::launch(encode, d_in, d_out); return; }
    CUtensorMap map;
    {
        const cuuint64_t dim[2] = {N_, M_}, str[1] = {N_ * 2};
        const cuuint32_t box[2] = {64, 32}, es[2] = {1, 1};
        encode(&map, CU_TENSOR_MAP_DATA_TYPE_BFLOAT16, 2, d_out, dim, str, box, es, CU_TENSOR_MAP_INTERLEAVE_NONE,
               CU_TENSOR_MAP_SWIZZLE_128B, CU_TENSOR_MAP_L2_PROMOTION_NONE, CU_TENSOR_MAP_FLOAT_OOB_FILL_NONE);
    }
    w8a8_kernel<<<NCTA, 512, SM_ALLOC, cudaStreamPerThread>>>((const char*)d_in[0], (const char*)d_in[1], scr, jobs, (const __nv_bfloat16*)d_in[4],
                                                             (const __nv_bfloat16*)d_in[5], (const __nv_bfloat16*)d_in[2], (const int*)d_in[3], map);
    cudaLaunchConfig_t cfg = {};
    cfg.gridDim = dim3(16); cfg.blockDim = dim3(512); cfg.dynamicSmemBytes = SM_ALLOC; cfg.stream = cudaStreamPerThread;
    cudaLaunchAttribute at[1];
    at[0].id = cudaLaunchAttributeProgrammaticStreamSerialization; at[0].val.programmaticStreamSerializationAllowed = 1;
    cfg.attrs = at; cfg.numAttrs = 1;
    cudaLaunchKernelEx(&cfg, w8a8_side, (const char*)d_in[1], scr, (const __nv_bfloat16*)d_in[4], (const __nv_bfloat16*)d_in[5], (const __nv_bfloat16*)d_in[2],
                       (const int*)d_in[3], map);
}
```

```cpp
#include <cuda_runtime.h>
#include <cuda.h>
#include <cuda_bf16.h>
#include <stdint.h>

namespace ra {

constexpr int CFG_D = 3;
constexpr int CFG_P0 = 650;
constexpr int CFG_PF0 = 0;
constexpr int CFG_SLEEP = 200;
constexpr int CFG_NINIT = 2;
constexpr int CFG_NR = 10;
constexpr int CFG_PZ = 16;
constexpr int CFG_NOC = 12;
constexpr int CFG_YP = 1100;
constexpr int CFG_YH = 1000;
constexpr int CFG_YH0 = 2300;
constexpr int CFG_Y0 = 1200;

constexpr int M_ = 2048, K_ = 1024, N_ = 3584;
constexpr int CS = 16, NCTA = 112, NSIDE = 20, TN = 448;
constexpr int NRING = CFG_NR, NCONV = 6, NJOB = 26, NG = 56, NOUT = 4, D_ = CFG_D;

constexpr int SM_A = 0;
constexpr int SM_RING = 131072;
constexpr int SM_OUT = SM_RING + NRING * 8192;
constexpr int SM_PAR = SM_OUT + NOUT * 4096;
constexpr int SM_SUM = SM_PAR + 1024;
constexpr int SM_BAR = SM_SUM + 256;
constexpr int B_FULL = 0, B_PAR = 64, B_AFREE = 72, B_OFREE = 76, B_SUM = 108, B_GO = 112, B_OFULL = 144, B_END = 148;
constexpr int SM_TOTAL = SM_BAR + B_END * 8;

constexpr int FS = 32;
struct __align__(2048) Scratch {
    uint4 a8[M_ * K_ / 16];
    uint4 b8[N_ * K_ / 16];
    unsigned cs[32 * TN / 2];
    unsigned flag[CS * FS + 64];
    unsigned epoch[NCTA + NSIDE];
};
__device__ Scratch g_scratch;
constexpr int SM_ALLOC = SM_TOTAL;
static_assert(SM_ALLOC <= 232448, "");

__device__ __forceinline__ void mbar_init(uint32_t bar, uint32_t cnt) {
    asm volatile("mbarrier.init.shared::cta.b64 [%0], %1;" :: "r"(bar), "r"(cnt) : "memory");
}
__device__ __forceinline__ void mbar_expect_tx(uint32_t bar, uint32_t bytes) {
    asm volatile("mbarrier.arrive.expect_tx.shared::cta.b64 _, [%0], %1;" :: "r"(bar), "r"(bytes) : "memory");
}
__device__ __forceinline__ void mbar_arrive(uint32_t bar) {
    asm volatile("mbarrier.arrive.shared::cta.b64 _, [%0];" :: "r"(bar) : "memory");
}
__device__ __forceinline__ void mbar_arrive_cluster(uint32_t bar) {
    asm volatile("mbarrier.arrive.shared::cluster.b64 _, [%0];" :: "r"(bar) : "memory");
}
__device__ __forceinline__ void mbar_wait(uint32_t bar) {
    asm volatile("{\n.reg .pred p;\nWAIT_LOOP:\nmbarrier.try_wait.parity.shared::cta.b64 p, [%0], 0;\n@!p bra WAIT_LOOP;\n}" :: "r"(bar) : "memory");
}
__device__ __forceinline__ void mbar_wait_cluster(uint32_t bar) {
    asm volatile("{\n.reg .pred p;\nWAIT_LOOP:\nmbarrier.try_wait.parity.relaxed.cluster.shared::cta.b64 p, [%0], 0;\n@!p bra WAIT_LOOP;\n"
                 "fence.acquire.sync_restrict::shared::cluster.cluster;\n}" :: "r"(bar) : "memory");
}
__device__ __forceinline__ void mbar_wait2(uint32_t bar0, uint32_t bar1) { mbar_wait(bar0); mbar_wait(bar1); }
__device__ __forceinline__ bool mbar_test(uint32_t bar) {
    uint32_t ok;
    asm volatile("{\n.reg .pred p;\nmbarrier.test_wait.parity.shared::cta.b64 p, [%1], 0;\nselp.u32 %0, 1, 0, p;\n}" : "=r"(ok) : "r"(bar) : "memory");
    return ok;
}
__device__ __forceinline__ bool mbar_test2(uint32_t bar0, uint32_t bar1) {
    uint32_t ok;
    asm volatile("{\n.reg .pred p, q;\nmbarrier.test_wait.parity.shared::cta.b64 p, [%1], 0;\n"
                 "mbarrier.test_wait.parity.shared::cta.b64 q, [%2], 0;\nand.pred p, p, q;\nselp.u32 %0, 1, 0, p;\n}"
                 : "=r"(ok) : "r"(bar0), "r"(bar1) : "memory");
    return ok;
}
__device__ __forceinline__ bool elect_one() {
    uint32_t ok;
    asm volatile("{\n.reg .pred p;\nelect.sync _|p, 0xffffffff;\nselp.u32 %0, 1, 0, p;\n}" : "=r"(ok));
    return ok;
}
__device__ __forceinline__ uint32_t mapa(uint32_t a, uint32_t cta) {
    uint32_t r;
    asm("mapa.shared::cluster.u32 %0, %1, %2;" : "=r"(r) : "r"(a), "r"(cta));
    return r;
}
__device__ __forceinline__ void st_async32(uint32_t a, uint32_t v, uint32_t bar) {
    asm volatile("st.async.shared::cluster.mbarrier::complete_tx::bytes.b32 [%0], %1, [%2];" :: "r"(a), "r"(v), "r"(bar) : "memory");
}
__device__ __forceinline__ unsigned ld_flag(const unsigned* p) {
    unsigned v;
    asm volatile("ld.relaxed.gpu.global.u32 %0, [%1];" : "=r"(v) : "l"(p) : "memory");
    return v;
}
__device__ __forceinline__ unsigned clk() { unsigned t; asm volatile("mov.u32 %0, %clock;" : "=r"(t)); return t; }
__device__ __forceinline__ uint32_t lds32(uint32_t a) {
    uint32_t v;
    asm volatile("ld.shared.b32 %0, [%1];" : "=r"(v) : "r"(a) : "memory");
    return v;
}
__device__ __forceinline__ void sts32(uint32_t a, uint32_t v) {
    asm volatile("st.shared.b32 [%0], %1;" :: "r"(a), "r"(v) : "memory");
}
__device__ __forceinline__ void stg128(void* p, uint4 v) {
    asm volatile("st.global.v4.b32 [%0], {%1,%2,%3,%4};" :: "l"(p), "r"(v.x), "r"(v.y), "r"(v.z), "r"(v.w) : "memory");
}
__device__ __forceinline__ unsigned pack4(unsigned a, unsigned b, unsigned c, unsigned d) {
    unsigned lo, r;
    asm("cvt.pack.sat.s8.s32.b32 %0, %1, %2, 0;" : "=r"(lo) : "r"(d), "r"(c));
    asm("cvt.pack.sat.s8.s32.b32 %0, %1, %2, %3;" : "=r"(r) : "r"(b), "r"(a), "r"(lo));
    return r;
}
constexpr uint32_t DESC_A_HI = 256 >> 4;
constexpr uint32_t DESC_B_HI = 0x80000000u | (512 >> 4);
__device__ __forceinline__ void mma_unit2(int (&d)[64], int (&e)[64], uint32_t alo, uint32_t blo, int scale_d) {
    asm volatile("{\n.reg .pred p;\n.reg .b64 da, db;\nsetp.ne.b32 p, %130, 0;\n"
        "mov.b64 da, {%128, %131};\nmov.b64 db, {%129, %132};\n"
        "wgmma.mma_async.sync.aligned.m64n128k32.s32.s8.s8 "
        "{%0, %1, %2, %3, %4, %5, %6, %7, %8, %9, %10, %11, %12, %13, %14, %15, "
        "%16, %17, %18, %19, %20, %21, %22, %23, %24, %25, %26, %27, %28, %29, %30, %31, "
        "%32, %33, %34, %35, %36, %37, %38, %39, %40, %41, %42, %43, %44, %45, %46, %47, "
        "%48, %49, %50, %51, %52, %53, %54, %55, %56, %57, %58, %59, %60, %61, %62, %63}, "
        "da, db, p;\n"
        "add.s64 da, da, 128;\n"
        "wgmma.mma_async.sync.aligned.m64n128k32.s32.s8.s8 "
        "{%64, %65, %66, %67, %68, %69, %70, %71, %72, %73, %74, %75, %76, %77, %78, %79, "
        "%80, %81, %82, %83, %84, %85, %86, %87, %88, %89, %90, %91, %92, %93, %94, %95, "
        "%96, %97, %98, %99, %100, %101, %102, %103, %104, %105, %106, %107, %108, %109, %110, %111, "
        "%112, %113, %114, %115, %116, %117, %118, %119, %120, %121, %122, %123, %124, %125, %126, %127}, "
        "da, db, p;\n"
        "add.s64 da, da, 128;\nadd.s64 db, db, 2;\n"
        "wgmma.mma_async.sync.aligned.m64n128k32.s32.s8.s8 "
        "{%0, %1, %2, %3, %4, %5, %6, %7, %8, %9, %10, %11, %12, %13, %14, %15, "
        "%16, %17, %18, %19, %20, %21, %22, %23, %24, %25, %26, %27, %28, %29, %30, %31, "
        "%32, %33, %34, %35, %36, %37, %38, %39, %40, %41, %42, %43, %44, %45, %46, %47, "
        "%48, %49, %50, %51, %52, %53, %54, %55, %56, %57, %58, %59, %60, %61, %62, %63}, "
        "da, db, 1;\n"
        "add.s64 da, da, 128;\n"
        "wgmma.mma_async.sync.aligned.m64n128k32.s32.s8.s8 "
        "{%64, %65, %66, %67, %68, %69, %70, %71, %72, %73, %74, %75, %76, %77, %78, %79, "
        "%80, %81, %82, %83, %84, %85, %86, %87, %88, %89, %90, %91, %92, %93, %94, %95, "
        "%96, %97, %98, %99, %100, %101, %102, %103, %104, %105, %106, %107, %108, %109, %110, %111, "
        "%112, %113, %114, %115, %116, %117, %118, %119, %120, %121, %122, %123, %124, %125, %126, %127}, "
        "da, db, 1;\n"
        "wgmma.commit_group.sync.aligned;\n}\n"
        : "+r"(d[0]), "+r"(d[1]), "+r"(d[2]), "+r"(d[3]), "+r"(d[4]), "+r"(d[5]), "+r"(d[6]), "+r"(d[7]),
          "+r"(d[8]), "+r"(d[9]), "+r"(d[10]), "+r"(d[11]), "+r"(d[12]), "+r"(d[13]), "+r"(d[14]), "+r"(d[15]),
          "+r"(d[16]), "+r"(d[17]), "+r"(d[18]), "+r"(d[19]), "+r"(d[20]), "+r"(d[21]), "+r"(d[22]), "+r"(d[23]),
          "+r"(d[24]), "+r"(d[25]), "+r"(d[26]), "+r"(d[27]), "+r"(d[28]), "+r"(d[29]), "+r"(d[30]), "+r"(d[31]),
          "+r"(d[32]), "+r"(d[33]), "+r"(d[34]), "+r"(d[35]), "+r"(d[36]), "+r"(d[37]), "+r"(d[38]), "+r"(d[39]),
          "+r"(d[40]), "+r"(d[41]), "+r"(d[42]), "+r"(d[43]), "+r"(d[44]), "+r"(d[45]), "+r"(d[46]), "+r"(d[47]),
          "+r"(d[48]), "+r"(d[49]), "+r"(d[50]), "+r"(d[51]), "+r"(d[52]), "+r"(d[53]), "+r"(d[54]), "+r"(d[55]),
          "+r"(d[56]), "+r"(d[57]), "+r"(d[58]), "+r"(d[59]), "+r"(d[60]), "+r"(d[61]), "+r"(d[62]), "+r"(d[63]),
          "+r"(e[0]), "+r"(e[1]), "+r"(e[2]), "+r"(e[3]), "+r"(e[4]), "+r"(e[5]), "+r"(e[6]), "+r"(e[7]),
          "+r"(e[8]), "+r"(e[9]), "+r"(e[10]), "+r"(e[11]), "+r"(e[12]), "+r"(e[13]), "+r"(e[14]), "+r"(e[15]),
          "+r"(e[16]), "+r"(e[17]), "+r"(e[18]), "+r"(e[19]), "+r"(e[20]), "+r"(e[21]), "+r"(e[22]), "+r"(e[23]),
          "+r"(e[24]), "+r"(e[25]), "+r"(e[26]), "+r"(e[27]), "+r"(e[28]), "+r"(e[29]), "+r"(e[30]), "+r"(e[31]),
          "+r"(e[32]), "+r"(e[33]), "+r"(e[34]), "+r"(e[35]), "+r"(e[36]), "+r"(e[37]), "+r"(e[38]), "+r"(e[39]),
          "+r"(e[40]), "+r"(e[41]), "+r"(e[42]), "+r"(e[43]), "+r"(e[44]), "+r"(e[45]), "+r"(e[46]), "+r"(e[47]),
          "+r"(e[48]), "+r"(e[49]), "+r"(e[50]), "+r"(e[51]), "+r"(e[52]), "+r"(e[53]), "+r"(e[54]), "+r"(e[55]),
          "+r"(e[56]), "+r"(e[57]), "+r"(e[58]), "+r"(e[59]), "+r"(e[60]), "+r"(e[61]), "+r"(e[62]), "+r"(e[63])
        : "r"(alo), "r"(blo), "r"(scale_d), "n"(DESC_A_HI), "n"(DESC_B_HI) : "memory");
}
__device__ __forceinline__ bool mma_pair(int (&d)[64], uint32_t alo, uint32_t blo, int scale_d, uint32_t bar) {
    uint32_t ok;
    asm volatile("{\n.reg .pred p, q;\n.reg .b64 da, db;\nsetp.ne.b32 p, %67, 0;\n"
        "mov.b64 da, {%65, %68};\nmov.b64 db, {%66, %69};\n"
        "wgmma.mma_async.sync.aligned.m64n128k32.s32.s8.s8 "
        "{%0, %1, %2, %3, %4, %5, %6, %7, %8, %9, %10, %11, %12, %13, %14, %15, "
        "%16, %17, %18, %19, %20, %21, %22, %23, %24, %25, %26, %27, %28, %29, %30, %31, "
        "%32, %33, %34, %35, %36, %37, %38, %39, %40, %41, %42, %43, %44, %45, %46, %47, "
        "%48, %49, %50, %51, %52, %53, %54, %55, %56, %57, %58, %59, %60, %61, %62, %63}, "
        "da, db, p;\n"
        "add.s64 da, da, 128;\nadd.s64 db, db, 2;\n"
        "wgmma.mma_async.sync.aligned.m64n128k32.s32.s8.s8 "
        "{%0, %1, %2, %3, %4, %5, %6, %7, %8, %9, %10, %11, %12, %13, %14, %15, "
        "%16, %17, %18, %19, %20, %21, %22, %23, %24, %25, %26, %27, %28, %29, %30, %31, "
        "%32, %33, %34, %35, %36, %37, %38, %39, %40, %41, %42, %43, %44, %45, %46, %47, "
        "%48, %49, %50, %51, %52, %53, %54, %55, %56, %57, %58, %59, %60, %61, %62, %63}, "
        "da, db, 1;\n"
        "add.s64 da, da, 128;\nadd.s64 db, db, 510;\n"
        "wgmma.mma_async.sync.aligned.m64n128k32.s32.s8.s8 "
        "{%0, %1, %2, %3, %4, %5, %6, %7, %8, %9, %10, %11, %12, %13, %14, %15, "
        "%16, %17, %18, %19, %20, %21, %22, %23, %24, %25, %26, %27, %28, %29, %30, %31, "
        "%32, %33, %34, %35, %36, %37, %38, %39, %40, %41, %42, %43, %44, %45, %46, %47, "
        "%48, %49, %50, %51, %52, %53, %54, %55, %56, %57, %58, %59, %60, %61, %62, %63}, "
        "da, db, 1;\n"
        "add.s64 da, da, 128;\nadd.s64 db, db, 2;\n"
        "wgmma.mma_async.sync.aligned.m64n128k32.s32.s8.s8 "
        "{%0, %1, %2, %3, %4, %5, %6, %7, %8, %9, %10, %11, %12, %13, %14, %15, "
        "%16, %17, %18, %19, %20, %21, %22, %23, %24, %25, %26, %27, %28, %29, %30, %31, "
        "%32, %33, %34, %35, %36, %37, %38, %39, %40, %41, %42, %43, %44, %45, %46, %47, "
        "%48, %49, %50, %51, %52, %53, %54, %55, %56, %57, %58, %59, %60, %61, %62, %63}, "
        "da, db, 1;\n"
        "add.s64 da, da, 128;\nadd.s64 db, db, 510;\n"
        "wgmma.mma_async.sync.aligned.m64n128k32.s32.s8.s8 "
        "{%0, %1, %2, %3, %4, %5, %6, %7, %8, %9, %10, %11, %12, %13, %14, %15, "
        "%16, %17, %18, %19, %20, %21, %22, %23, %24, %25, %26, %27, %28, %29, %30, %31, "
        "%32, %33, %34, %35, %36, %37, %38, %39, %40, %41, %42, %43, %44, %45, %46, %47, "
        "%48, %49, %50, %51, %52, %53, %54, %55, %56, %57, %58, %59, %60, %61, %62, %63}, "
        "da, db, 1;\n"
        "add.s64 da, da, 128;\nadd.s64 db, db, 2;\n"
        "mbarrier.test_wait.parity.shared::cta.b64 q, [%70], 0;\n"
        "wgmma.mma_async.sync.aligned.m64n128k32.s32.s8.s8 "
        "{%0, %1, %2, %3, %4, %5, %6, %7, %8, %9, %10, %11, %12, %13, %14, %15, "
        "%16, %17, %18, %19, %20, %21, %22, %23, %24, %25, %26, %27, %28, %29, %30, %31, "
        "%32, %33, %34, %35, %36, %37, %38, %39, %40, %41, %42, %43, %44, %45, %46, %47, "
        "%48, %49, %50, %51, %52, %53, %54, %55, %56, %57, %58, %59, %60, %61, %62, %63}, "
        "da, db, 1;\n"
        "add.s64 da, da, 128;\nadd.s64 db, db, 510;\n"
        "wgmma.mma_async.sync.aligned.m64n128k32.s32.s8.s8 "
        "{%0, %1, %2, %3, %4, %5, %6, %7, %8, %9, %10, %11, %12, %13, %14, %15, "
        "%16, %17, %18, %19, %20, %21, %22, %23, %24, %25, %26, %27, %28, %29, %30, %31, "
        "%32, %33, %34, %35, %36, %37, %38, %39, %40, %41, %42, %43, %44, %45, %46, %47, "
        "%48, %49, %50, %51, %52, %53, %54, %55, %56, %57, %58, %59, %60, %61, %62, %63}, "
        "da, db, 1;\n"
        "add.s64 da, da, 128;\nadd.s64 db, db, 2;\n"
        "wgmma.mma_async.sync.aligned.m64n128k32.s32.s8.s8 "
        "{%0, %1, %2, %3, %4, %5, %6, %7, %8, %9, %10, %11, %12, %13, %14, %15, "
        "%16, %17, %18, %19, %20, %21, %22, %23, %24, %25, %26, %27, %28, %29, %30, %31, "
        "%32, %33, %34, %35, %36, %37, %38, %39, %40, %41, %42, %43, %44, %45, %46, %47, "
        "%48, %49, %50, %51, %52, %53, %54, %55, %56, %57, %58, %59, %60, %61, %62, %63}, "
        "da, db, 1;\n"
        "wgmma.commit_group.sync.aligned;\nselp.u32 %64, 1, 0, q;\n}\n"
        : "+r"(d[0]), "+r"(d[1]), "+r"(d[2]), "+r"(d[3]), "+r"(d[4]), "+r"(d[5]), "+r"(d[6]), "+r"(d[7]),
          "+r"(d[8]), "+r"(d[9]), "+r"(d[10]), "+r"(d[11]), "+r"(d[12]), "+r"(d[13]), "+r"(d[14]), "+r"(d[15]),
          "+r"(d[16]), "+r"(d[17]), "+r"(d[18]), "+r"(d[19]), "+r"(d[20]), "+r"(d[21]), "+r"(d[22]), "+r"(d[23]),
          "+r"(d[24]), "+r"(d[25]), "+r"(d[26]), "+r"(d[27]), "+r"(d[28]), "+r"(d[29]), "+r"(d[30]), "+r"(d[31]),
          "+r"(d[32]), "+r"(d[33]), "+r"(d[34]), "+r"(d[35]), "+r"(d[36]), "+r"(d[37]), "+r"(d[38]), "+r"(d[39]),
          "+r"(d[40]), "+r"(d[41]), "+r"(d[42]), "+r"(d[43]), "+r"(d[44]), "+r"(d[45]), "+r"(d[46]), "+r"(d[47]),
          "+r"(d[48]), "+r"(d[49]), "+r"(d[50]), "+r"(d[51]), "+r"(d[52]), "+r"(d[53]), "+r"(d[54]), "+r"(d[55]),
          "+r"(d[56]), "+r"(d[57]), "+r"(d[58]), "+r"(d[59]), "+r"(d[60]), "+r"(d[61]), "+r"(d[62]), "+r"(d[63]), "=r"(ok)
        : "r"(alo), "r"(blo), "r"(scale_d), "n"(DESC_A_HI), "n"(DESC_B_HI), "r"(bar) : "memory");
    return ok;
}
__device__ __forceinline__ void mma_rows2(int (&d)[64], int (&e)[64], uint32_t alo, uint32_t blo, int scale_d) {
    asm volatile("{\n.reg .pred p;\n.reg .b64 da, db;\nsetp.ne.b32 p, %130, 0;\n"
        "mov.b64 da, {%128, %131};\nmov.b64 db, {%129, %132};\n"
        "wgmma.mma_async.sync.aligned.m64n128k32.s32.s8.s8 "
        "{%0, %1, %2, %3, %4, %5, %6, %7, %8, %9, %10, %11, %12, %13, %14, %15, "
        "%16, %17, %18, %19, %20, %21, %22, %23, %24, %25, %26, %27, %28, %29, %30, %31, "
        "%32, %33, %34, %35, %36, %37, %38, %39, %40, %41, %42, %43, %44, %45, %46, %47, "
        "%48, %49, %50, %51, %52, %53, %54, %55, %56, %57, %58, %59, %60, %61, %62, %63}, "
        "da, db, p;\n"
        "add.s64 db, db, 512;\n"
        "wgmma.mma_async.sync.aligned.m64n128k32.s32.s8.s8 "
        "{%64, %65, %66, %67, %68, %69, %70, %71, %72, %73, %74, %75, %76, %77, %78, %79, "
        "%80, %81, %82, %83, %84, %85, %86, %87, %88, %89, %90, %91, %92, %93, %94, %95, "
        "%96, %97, %98, %99, %100, %101, %102, %103, %104, %105, %106, %107, %108, %109, %110, %111, "
        "%112, %113, %114, %115, %116, %117, %118, %119, %120, %121, %122, %123, %124, %125, %126, %127}, "
        "da, db, p;\n"
        "add.s64 da, da, 128;\nadd.s64 db, db, -510;\n"
        "wgmma.mma_async.sync.aligned.m64n128k32.s32.s8.s8 "
        "{%0, %1, %2, %3, %4, %5, %6, %7, %8, %9, %10, %11, %12, %13, %14, %15, "
        "%16, %17, %18, %19, %20, %21, %22, %23, %24, %25, %26, %27, %28, %29, %30, %31, "
        "%32, %33, %34, %35, %36, %37, %38, %39, %40, %41, %42, %43, %44, %45, %46, %47, "
        "%48, %49, %50, %51, %52, %53, %54, %55, %56, %57, %58, %59, %60, %61, %62, %63}, "
        "da, db, 1;\n"
        "add.s64 db, db, 512;\n"
        "wgmma.mma_async.sync.aligned.m64n128k32.s32.s8.s8 "
        "{%64, %65, %66, %67, %68, %69, %70, %71, %72, %73, %74, %75, %76, %77, %78, %79, "
        "%80, %81, %82, %83, %84, %85, %86, %87, %88, %89, %90, %91, %92, %93, %94, %95, "
        "%96, %97, %98, %99, %100, %101, %102, %103, %104, %105, %106, %107, %108, %109, %110, %111, "
        "%112, %113, %114, %115, %116, %117, %118, %119, %120, %121, %122, %123, %124, %125, %126, %127}, "
        "da, db, 1;\n"
        "wgmma.commit_group.sync.aligned;\n}\n"
        : "+r"(d[0]), "+r"(d[1]), "+r"(d[2]), "+r"(d[3]), "+r"(d[4]), "+r"(d[5]), "+r"(d[6]), "+r"(d[7]),
          "+r"(d[8]), "+r"(d[9]), "+r"(d[10]), "+r"(d[11]), "+r"(d[12]), "+r"(d[13]), "+r"(d[14]), "+r"(d[15]),
          "+r"(d[16]), "+r"(d[17]), "+r"(d[18]), "+r"(d[19]), "+r"(d[20]), "+r"(d[21]), "+r"(d[22]), "+r"(d[23]),
          "+r"(d[24]), "+r"(d[25]), "+r"(d[26]), "+r"(d[27]), "+r"(d[28]), "+r"(d[29]), "+r"(d[30]), "+r"(d[31]),
          "+r"(d[32]), "+r"(d[33]), "+r"(d[34]), "+r"(d[35]), "+r"(d[36]), "+r"(d[37]), "+r"(d[38]), "+r"(d[39]),
          "+r"(d[40]), "+r"(d[41]), "+r"(d[42]), "+r"(d[43]), "+r"(d[44]), "+r"(d[45]), "+r"(d[46]), "+r"(d[47]),
          "+r"(d[48]), "+r"(d[49]), "+r"(d[50]), "+r"(d[51]), "+r"(d[52]), "+r"(d[53]), "+r"(d[54]), "+r"(d[55]),
          "+r"(d[56]), "+r"(d[57]), "+r"(d[58]), "+r"(d[59]), "+r"(d[60]), "+r"(d[61]), "+r"(d[62]), "+r"(d[63]),
          "+r"(e[0]), "+r"(e[1]), "+r"(e[2]), "+r"(e[3]), "+r"(e[4]), "+r"(e[5]), "+r"(e[6]), "+r"(e[7]),
          "+r"(e[8]), "+r"(e[9]), "+r"(e[10]), "+r"(e[11]), "+r"(e[12]), "+r"(e[13]), "+r"(e[14]), "+r"(e[15]),
          "+r"(e[16]), "+r"(e[17]), "+r"(e[18]), "+r"(e[19]), "+r"(e[20]), "+r"(e[21]), "+r"(e[22]), "+r"(e[23]),
          "+r"(e[24]), "+r"(e[25]), "+r"(e[26]), "+r"(e[27]), "+r"(e[28]), "+r"(e[29]), "+r"(e[30]), "+r"(e[31]),
          "+r"(e[32]), "+r"(e[33]), "+r"(e[34]), "+r"(e[35]), "+r"(e[36]), "+r"(e[37]), "+r"(e[38]), "+r"(e[39]),
          "+r"(e[40]), "+r"(e[41]), "+r"(e[42]), "+r"(e[43]), "+r"(e[44]), "+r"(e[45]), "+r"(e[46]), "+r"(e[47]),
          "+r"(e[48]), "+r"(e[49]), "+r"(e[50]), "+r"(e[51]), "+r"(e[52]), "+r"(e[53]), "+r"(e[54]), "+r"(e[55]),
          "+r"(e[56]), "+r"(e[57]), "+r"(e[58]), "+r"(e[59]), "+r"(e[60]), "+r"(e[61]), "+r"(e[62]), "+r"(e[63])
        : "r"(alo), "r"(blo), "r"(scale_d), "n"(DESC_A_HI), "n"(DESC_B_HI) : "memory");
}

__device__ __forceinline__ void wg_fence() { asm volatile("wgmma.fence.sync.aligned;" ::: "memory"); }
template <int N> __device__ __forceinline__ void wg_wait() { asm volatile("wgmma.wait_group.sync.aligned %0;" :: "n"(N) : "memory"); }

__host__ __device__ constexpr int unit_of(int wg, int s) { return wg ? (s < 16 - D_ ? D_ + 2 * s : s + 16) : (s < D_ ? s : 2 * s - D_ + 1); }

__host__ __device__ constexpr int bar_of(int u) { return u >= 32 ? u & ~1 : u < D_ || u >= 32 - D_ ? u : ((u - D_) & 1) ? D_ + ((u - D_) >> 1) : 16 + ((u - D_) >> 1); }
constexpr uint32_t step_table(int wg) {
    uint32_t t = 0;
    for (int s = 0; s < 15; s++) t |= (uint32_t)(unit_of(wg, s + 1) - unit_of(wg, s) - 1) << s;
    return t;
}
constexpr uint32_t STEPS0 = step_table(0), STEPS1 = step_table(1);
__host__ __device__ constexpr int sum_owner(int g) { return g < 8 ? (g & 4) | (g & 1) << 1 | (~g >> 1 & 1) : g; }
__device__ __forceinline__ int sum_group(int r) { return r < 8 ? (r & 4) | (~r & 1) << 1 | (r >> 1 & 1) : r; }
__device__ __forceinline__ int col_of(int c, int blk) { return (c < 7 ? blk * 7 + c : 49 + blk) * 64; }

struct JobTable { uint2 e[NCTA][NJOB + NCONV]; };
__device__ const JobTable g_jobs = {{
    {{0x0, 0x0}, {0x20400, 0x1000000}, {0x90202, 0x20080a2}, {0x100004, 0x3010144}, {0x14000000, 0x3100020a}, {0x570e05, 0x4094281}, {0x14102a00, 0x3100430b}, {0x1d0207, 0x401c394}, {0x14204600, 0x3104847e}, {0x250209, 0x6024508}, {0x14306200, 0x3104c5ea}, {0x16c280b, 0x72ac647}, {0x14407e00, 0x31090730}, {0x1b3360c, 0x8330767}, {0x14509a00, 0x31094876}, {0xfb1e0e, 0x91b88a5}, {0x1460b600, 0x310d8991}, {0x1470d200, 0x310dca34}, {0x1480001c, 0x98020ad7}, {0x1490701c, 0x980a4b7a}, {0x14a00023, 0xba028c59}, {0x14b07023, 0xba0acd4c}, {0x14c0002a, 0xdc030e3e}, {0x14d0702a, 0xdc0b4f22}, {0x30000000, 0x0}, {0x30000000, 0x0}, {0x30000000, 0x0}, {0x30000000, 0x0}, {0x30000000, 0x0}, {0x30000000, 0x0}, {0x30000000, 0x0}, {0x30000000, 0x0}},
    {{0x0, 0x0}, {0x420c00, 0x1080001}, {0x490a02, 0x20880a3}, {0x500804, 0x3090145}, {0x14010007, 0x20000215}, {0x1973605, 0x431428f}, {0x14112a07, 0x20004322}, {0x15d2a07, 0x429c3a3}, {0x14214607, 0x20048495}, {0xa51209, 0x612450e}, {0x14316207, 0x2004c5ff}, {0x2ec580b, 0x75ac656}, {0x14417e07, 0x20090744}, {0x2b3560c, 0x8530771}, {0x14519a07, 0x2009488a}, {0x1fb3e0e, 0x93b88ae}, {0x1461b607, 0x200d899b}, {0x1471d207, 0x200dca3e}, {0x1481071c, 0x98020ae1}, {0x1491771c, 0x980a4b84}, {0x14a10723, 0xba028c68}, {0x14b17723, 0xba0acd5b}, {0x14c1072a, 0xdc030e4e}, {0x14d1772a, 0xdc0b4f2f}, {0x30000000, 0x0}, {0x30000000, 0x0}, {0x30000000, 0x0}, {0x30000000, 0x0}, {0x30000000, 0x0}, {0x30000000, 0x0}, {0x30000000, 0x0}, {0x30000000, 0x0}},
    {{0x0, 0x0}, {0x821400, 0x1100002}, {0x891202, 0x21080a4}, {0x901004, 0x3110146}, {0x14020700, 0x31000221}, {0x2975605, 0x451429b}, {0x14123100, 0x31004339}, {0x2a4e3f33, 0x4182c3aa}, {0x14224d00, 0x310484ac}, {0x1252209, 0x6224513}, {0x14326900, 0x3104c613}, {0x6d0a0b, 0x70ac666}, {0x14428500, 0x31090759}, {0x34000d, 0x8034780}, {0x1452a100, 0x3109489e}, {0x2bb560e, 0x95388b6}, {0x1462bd00, 0x310d89a6}, {0x1472d900, 0x310dca49}, {0x14820e1c, 0x98020aeb}, {0x14927e1c, 0x980a4b8e}, {0x14a20e23, 0xba028c77}, {0x14b27e23, 0xba0acd6a}, {0x14c20e2a, 0xdc030e5d}, {0x14d27e2a, 0xdc0b4f3d}, {0x30000000, 0x0}, {0x30000000, 0x0}, {0x30000000, 0x0}, {0x30000000, 0x0}, {0x30000000, 0x0}, {0x30000000, 0x0}, {0x30000000, 0x0}, {0x30000000, 0x0}},
    {{0x0, 0x0}, {0xc21c00, 0x1180004}, {0xc91a02, 0x21880a6}, {0xd01804, 0x3190148}, {0x14030707, 0x2000022d}, {0x3d77e05, 0x47942a8}, {0x14133107, 0x20004350}, {0x31d6207, 0x461c3b7}, {0x14234d07, 0x200484c4}, {0x2254209, 0x642451f}, {0x14336907, 0x2004c627}, {0x22d420b, 0x742c677}, {0xb0100c, 0x71306e2}, {0x14438507, 0x2009076d}, {0x1453a107, 0x200948b3}, {0x3fb7e0e, 0x97b88c2}, {0x1463bd07, 0x200d89b0}, {0x1473d907, 0x200dca53}, {0x1483151c, 0x98020af6}, {0x1493851c, 0x980a4b98}, {0x14a31523, 0xba028c86}, {0x14b38523, 0xba0acd79}, {0x14c3152a, 0xdc030e6c}, {0x14d3852a, 0xdc0b4f4a}, {0x30000000, 0x0}, {0x30000000, 0x0}, {0x30000000, 0x0}, {0x30000000, 0x0}, {0x30000000, 0x0}, {0x30000000, 0x0}, {0x30000000, 0x0}, {0x30000000, 0x0}},
    {{0x0, 0x0}, {0x1022400, 0x1200005}, {0x1092202, 0x22080a7}, {0x1102004, 0x3210149}, {0x14040e00, 0x31000238}, {0xd81806, 0x41982b5}, {0x14140e0e, 0x75004367}, {0x1e0407, 0x501c3c3}, {0x14242a0e, 0x750084db}, {0x2a55209, 0x6524525}, {0x1434460e, 0x7504c63c}, {0x36d6a0b, 0x76ac684}, {0x70080c, 0x70b06e0}, {0x1444620e, 0x75050781}, {0x1b7360d, 0x8334809}, {0x14547e0e, 0x750948c7}, {0x14649a0e, 0x750989ba}, {0x1474b60e, 0x750dca5d}, {0x14841c1c, 0x98020b00}, {0x14948c1c, 0x980a4ba3}, {0x14a41c23, 0xba028c95}, {0x14b48c23, 0xba0acd88}, {0x14c41c2a, 0xdc030e7b}, {0x14d48c2a, 0xdc0b4f57}, {0x30000000, 0x0}, {0x30000000, 0x0}, {0x30000000, 0x0}, {0x30000000, 0x0}, {0x30000000, 0x0}, {0x30000000, 0x0}, {0x30000000, 0x0}, {0x30000000, 0x0}},
    {{0x0, 0x0}, {0x1422c00, 0x1280007}, {0x1492a02, 0x22880a9}, {0x1502804, 0x329014b}, {0x14050e07, 0x20000244}, {0x2a442a33, 0x2c8242c2}, {0x14150e15, 0x6400437f}, {0x15e2c07, 0x529c3d1}, {0x14252a15, 0x640084f2}, {0x3256209, 0x662452b}, {0x14354615, 0x6404c650}, {0xae140b, 0x712c691}, {0x30000c, 0x70306dd}, {0x14456215, 0x64050796}, {0x3776e0d, 0x86b481b}, {0x14557e15, 0x640948db}, {0x14659a15, 0x640989c4}, {0x1475b615, 0x640dca67}, {0x1485231c, 0x98020b0a}, {0x1495931c, 0x980a4bb2}, {0x14a52323, 0xba028ca5}, {0x14b59323, 0xba0acd98}, {0x14c5232a, 0xdc030e8a}, {0x14d5932a, 0xdc0b4f65}, {0x30000000, 0x0}, {0x30000000, 0x0}, {0x30000000, 0x0}, {0x30000000, 0x0}, {0x30000000, 0x0}, {0x30000000, 0x0}, {0x30000000, 0x0}, {0x30000000, 0x0}},
    {{0x0, 0x0}, {0x1823400, 0x1300008}, {0x1893202, 0x23080aa}, {0x1903004, 0x331014c}, {0x14061500, 0x3100024f}, {0x3186006, 0x46182cf}, {0x1416150e, 0x75004396}, {0x21e4407, 0x541c3da}, {0x2214208, 0x5420465}, {0x1426310e, 0x75008509}, {0x14364d0e, 0x7504c664}, {0x22e440b, 0x742c6a0}, {0xf0180c, 0x71b06e5}, {0x1446690e, 0x750507aa}, {0x2b7560d, 0x8534814}, {0x1456850e, 0x750948f0}, {0x1466a10e, 0x750989ce}, {0x1476bd0e, 0x750dca71}, {0x14862a1c, 0x98020b14}, {0x14969a1c, 0x980a4bc1}, {0x14a62a23, 0xba028cb4}, {0x14b69a23, 0xba0acda7}, {0x14c62a2a, 0xdc030e9a}, {0x14d69a2a, 0xdc0b4f72}, {0x30000000, 0x0}, {0x30000000, 0x0}, {0x30000000, 0x0}, {0x30000000, 0x0}, {0x30000000, 0x0}, {0x30000000, 0x0}, {0x30000000, 0x0}, {0x30000000, 0x0}},
    {{0x0, 0x0}, {0x1c23c00, 0x138000a}, {0x1c93a02, 0x23880ac}, {0x1d03804, 0x339014e}, {0x14071507, 0x2000025b}, {0x190206, 0x40182db}, {0x2dc5807, 0x459c386}, {0x14171515, 0x640043ad}, {0x1612a08, 0x52a045d}, {0x14273115, 0x64008521}, {0x14374d15, 0x6404c679}, {0x3ae740b, 0x772c6af}, {0x2b2540c, 0x7530748}, {0x14476915, 0x640507be}, {0x237460d, 0x843480f}, {0x14578515, 0x64094904}, {0x1467a115, 0x640989d9}, {0x1477bd15, 0x640dca7b}, {0x1487311c, 0x98020b1e}, {0x1497a11c, 0x980a4bd0}, {0x14a73123, 0xba028cc3}, {0x14b7a123, 0xba0acdb6}, {0x14c7312a, 0xdc030ea9}, {0x14d7a12a, 0xdc0b4f7f}, {0x30000000, 0x0}, {0x30000000, 0x0}, {0x30000000, 0x0}, {0x30000000, 0x0}, {0x30000000, 0x0}, {0x30000000, 0x0}, {0x30000000, 0x0}, {0x30000000, 0x0}},
    {{0x0, 0x0}, {0x2024400, 0x140000b}, {0x2094202, 0x24080ad}, {0x2104004, 0x341014f}, {0x14081c00, 0x31000267}, {0x1592a06, 0x42982e9}, {0x9c1007, 0x411c36c}, {0x14183800, 0x310443c4}, {0x1e13a08, 0x53a0461}, {0x14285400, 0x31048538}, {0x14387000, 0x3108c68d}, {0x16f2e0b, 0x72ac6c1}, {0x32040c, 0x703072f}, {0x14488c00, 0x310907d3}, {0x2f75e0d, 0x85b4816}, {0x1458a800, 0x310d4918}, {0x1468c400, 0x310d89e3}, {0x1478c40e, 0x750dca86}, {0x1488381c, 0x98060b28}, {0x1498a81c, 0x980e4bdf}, {0x14a83823, 0xba068cd2}, {0x14b8a823, 0xba0ecdc5}, {0x14c8382a, 0xdc070eb8}, {0x14d8a82a, 0xdc0f4f8c}, {0x30000000, 0x0}, {0x30000000, 0x0}, {0x30000000, 0x0}, {0x30000000, 0x0}, {0x30000000, 0x0}, {0x30000000, 0x0}, {0x30000000, 0x0}, {0x30000000, 0x0}},
    {{0x0, 0x0}, {0x2424c00, 0x148000c}, {0x2494a02, 0x24880ae}, {0x2504804, 0x3490150}, {0x14091c07, 0x20000272}, {0x2594a06, 0x44982f5}, {0x39b7606, 0x4718360}, {0x14193807, 0x200443dc}, {0x2a15208, 0x552046b}, {0x14295407, 0x2004854f}, {0x14397007, 0x2008c6a1}, {0x32f660b, 0x762c6d3}, {0x3b1720c, 0x773072a}, {0x14498c07, 0x200907e7}, {0x3b7760d, 0x873481e}, {0x1459a807, 0x200d492d}, {0x1469c407, 0x200d89ed}, {0x1479c415, 0x640dca90}, {0x14893f1c, 0x98060b33}, {0x1499af1c, 0x980e4bef}, {0x14a93f23, 0xba068ce1}, {0x14b9af23, 0xba0ecdd4}, {0x14c93f2a, 0xdc070ec5}, {0x14d9af2a, 0xdc0f4f9a}, {0x30000000, 0x0}, {0x30000000, 0x0}, {0x30000000, 0x0}, {0x30000000, 0x0}, {0x30000000, 0x0}, {0x30000000, 0x0}, {0x30000000, 0x0}, {0x30000000, 0x0}},
    {{0x0, 0x0}, {0x2825400, 0x150000e}, {0x2895202, 0x25080b0}, {0x2905004, 0x3510152}, {0x2a200031, 0x8001e7}, {0x140a2300, 0x3100027f}, {0x5b0e06, 0x409833b}, {0x141a3f00, 0x310443f3}, {0x2e15a08, 0x55a046e}, {0x142a5b00, 0x31048566}, {0x1692a0a, 0x62a85cd}, {0x143a7700, 0x3108c6b6}, {0x2f0580c, 0x75b06f9}, {0x144a9300, 0x310907fb}, {0xb8100e, 0x8138828}, {0x145aaf00, 0x310d4941}, {0x13f260f, 0x923c94a}, {0x146acb00, 0x310d89f7}, {0x147acb0e, 0x750dca9a}, {0x148a461c, 0x98060b3d}, {0x149ab61c, 0x980e4bfe}, {0x14aa4623, 0xba068cf1}, {0x14bab623, 0xba0ecde3}, {0x14ca462a, 0xdc070ed2}, {0x14dab62a, 0xdc0f4fa7}, {0x30000000, 0x0}, {0x30000000, 0x0}, {0x30000000, 0x0}, {0x30000000, 0x0}, {0x30000000, 0x0}, {0x30000000, 0x0}, {0x30000000, 0x0}},
    {{0x0, 0x0}, {0x2c25c00, 0x158000f}, {0x2c95a02, 0x25880b1}, {0x2d05804, 0x3590153}, {0x2a210032, 0x18001e8}, {0x140b2307, 0x20000297}, {0x31a6406, 0x461832c}, {0x141b3f07, 0x2004440a}, {0x3616a08, 0x56a0474}, {0x142b5b07, 0x2004857d}, {0x1e93a0a, 0x63a85d1}, {0x143b7707, 0x2008c6ca}, {0x270480c, 0x74b06f4}, {0x144b9307, 0x20090810}, {0x138200e, 0x823882d}, {0x3ba740e, 0x9738898}, {0x145baf07, 0x200d4956}, {0x146bcb07, 0x200d8a01}, {0x147bcb15, 0x640dcaa4}, {0x148b4d1c, 0x98060b47}, {0x149bbd1c, 0x980e4c0d}, {0x14ab4d23, 0xba068d00}, {0x14bbbd23, 0xba0ecdf3}, {0x14cb4d2a, 0xdc070ee0}, {0x14dbbd2a, 0xdc0f4fb4}, {0x30000000, 0x0}, {0x30000000, 0x0}, {0x30000000, 0x0}, {0x30000000, 0x0}, {0x30000000, 0x0}, {0x30000000, 0x0}, {0x30000000, 0x0}},
    {{0x0, 0x0}, {0x3026400, 0x1600011}, {0x3096202, 0x26080b3}, {0x3106004, 0x3610155}, {0x2a220731, 0x78001ea}, {0x140c000e, 0x750002ae}, {0x2a485431, 0x5482831f}, {0x141c1c0e, 0x75004421}, {0x3e17a08, 0x57a0478}, {0x142c380e, 0x75048595}, {0x2e95a0a, 0x65a85dc}, {0x36b6e0a, 0x66a8633}, {0x143c540e, 0x7504c6de}, {0x74080d, 0x80b4783}, {0x144c700e, 0x75090824}, {0x13b260e, 0x92388a7}, {0x145c8c0e, 0x75094969}, {0x146ca80e, 0x750d8a0b}, {0x147cd20e, 0x750dcaae}, {0x148c541c, 0x98060b51}, {0x149cc41c, 0x980e4c1c}, {0x14ac5423, 0xba068d0f}, {0x14bcc423, 0xba0ece02}, {0x14cc542a, 0xdc070eed}, {0x14dcc42a, 0xdc0f4fc2}, {0x30000000, 0x0}, {0x30000000, 0x0}, {0x30000000, 0x0}, {0x30000000, 0x0}, {0x30000000, 0x0}, {0x30000000, 0x0}, {0x30000000, 0x0}},
    {{0x0, 0x0}, {0x3426c00, 0x1680012}, {0x3496a02, 0x26880b4}, {0x3506804, 0x3690156}, {0x2a230732, 0x88001eb}, {0x140d0015, 0x640002c5}, {0x11a2406, 0x4218315}, {0x141d1c15, 0x64004438}, {0xa21408, 0x5120482}, {0x1652a09, 0x62a4516}, {0x142d3815, 0x640485ac}, {0xeb1e0a, 0x61a8619}, {0x143d5415, 0x6404c6f3}, {0x3b3760c, 0x873077b}, {0x144d7015, 0x64090839}, {0x7b0e0e, 0x90b88a0}, {0x145d8c15, 0x64094973}, {0x146da815, 0x640d8a16}, {0x147dd215, 0x640dcab9}, {0x148d5b1c, 0x98060b5b}, {0x149dcb1c, 0x980e4c2b}, {0x14ad5b23, 0xba068d1e}, {0x14bdcb23, 0xba0ece11}, {0x14cd5b2a, 0xdc070efa}, {0x14ddcb2a, 0xdc0f4fcf}, {0x30000000, 0x0}, {0x30000000, 0x0}, {0x30000000, 0x0}, {0x30000000, 0x0}, {0x30000000, 0x0}, {0x30000000, 0x0}, {0x30000000, 0x0}},
    {{0x0, 0x0}, {0x3827400, 0x1700014}, {0x3897202, 0x27080b6}, {0x3907004, 0x3710158}, {0x2a240e31, 0xe8041ed}, {0x140e070e, 0x750002dc}, {0x9a1406, 0x411830f}, {0x141e230e, 0x75004450}, {0x1222408, 0x5220488}, {0x1a53209, 0x6324519}, {0x142e3f0e, 0x750485c1}, {0x2ab560a, 0x652862b}, {0x143e5b0e, 0x7504c707}, {0x134200d, 0x823478a}, {0x144e770e, 0x7509084d}, {0x1bb360e, 0x93388ac}, {0x145e930e, 0x7509497d}, {0x146eaf0e, 0x750d8a20}, {0x147ed90e, 0x750dcac3}, {0x148e621c, 0x98060b66}, {0x149ed21c, 0x980e4c3a}, {0x14ae6223, 0xba068d2d}, {0x14bed223, 0xba0ece20}, {0x14ce622a, 0xdc070f08}, {0x14ded22a, 0xdc0f4fdc}, {0x30000000, 0x0}, {0x30000000, 0x0}, {0x30000000, 0x0}, {0x30000000, 0x0}, {0x30000000, 0x0}, {0x30000000, 0x0}, {0x30000000, 0x0}},
    {{0x0, 0x0}, {0x3c27c00, 0x1780015}, {0x3c97a02, 0x27880b7}, {0x3d07804, 0x3790159}, {0x2a250e32, 0xf8041ee}, {0x140f0715, 0x640002f3}, {0x2a473134, 0x34824308}, {0x29d5207, 0x451c3b1}, {0x141f2315, 0x64004467}, {0xe51a09, 0x61a4511}, {0x142f3f15, 0x640485d6}, {0x12c200b, 0x722c644}, {0x143f5b15, 0x6404c71c}, {0x2f35e0c, 0x85b0773}, {0x144f7715, 0x64090861}, {0x17b2e0e, 0x92b88aa}, {0x145f9315, 0x64094987}, {0x146faf15, 0x640d8a2a}, {0x147fd915, 0x640dcacd}, {0x148f691c, 0x98060b70}, {0x149fd91c, 0x980e4c4a}, {0x14af6923, 0xba068d3c}, {0x14bfd923, 0xba0ece2f}, {0x14cf692a, 0xdc070f15}, {0x14dfd92a, 0xdc0f4fe9}, {0x30000000, 0x0}, {0x30000000, 0x0}, {0x30000000, 0x0}, {0x30000000, 0x0}, {0x30000000, 0x0}, {0x30000000, 0x0}, {0x30000000, 0x0}},
    {{0x0, 0x0}, {0x30600, 0x1000017}, {0xa0402, 0x20080b9}, {0x110204, 0x301015b}, {0x14e00001, 0x3100020b}, {0x971605, 0x4114284}, {0x14f02a01, 0x3100430e}, {0x2dd5a07, 0x459c3b4}, {0x15004601, 0x31048481}, {0x1e53a09, 0x63a451b}, {0x15106201, 0x3104c5ed}, {0x1ac300b, 0x732c64a}, {0x15207e01, 0x31090732}, {0x3f37e0c, 0x87b077c}, {0x15309a01, 0x31094878}, {0x23b460e, 0x94388b1}, {0x1540b601, 0x310d8993}, {0x1550d201, 0x310dca35}, {0x1560001d, 0x98020ad8}, {0x1570701d, 0x980a4b7b}, {0x15800024, 0xba028c5b}, {0x15907024, 0xba0acd4e}, {0x15a0002b, 0xdc030e40}, {0x15b0702b, 0xdc0b4f24}, {0x30000000, 0x0}, {0x30000000, 0x0}, {0x30000000, 0x0}, {0x30000000, 0x0}, {0x30000000, 0x0}, {0x30000000, 0x0}, {0x30000000, 0x0}, {0x30000000, 0x0}},
    {{0x0, 0x0}, {0x430e00, 0x1080018}, {0x4a0c02, 0x20880ba}, {0x510a04, 0x309015c}, {0x14e10008, 0x20000217}, {0x1d73e05, 0x4394291}, {0x14f12a08, 0x20004325}, {0x3dd7a07, 0x479c3bf}, {0x15014608, 0x20048498}, {0x2654a09, 0x64a4522}, {0x15116208, 0x2004c601}, {0x32c600b, 0x762c659}, {0x15217e08, 0x20090747}, {0xb4100d, 0x8134785}, {0x15319a08, 0x2009488c}, {0x33b660e, 0x96388bc}, {0x1541b608, 0x200d899d}, {0x1551d208, 0x200dca40}, {0x1561071d, 0x98020ae2}, {0x1571771d, 0x980a4b85}, {0x15810724, 0xba028c6a}, {0x15917724, 0xba0acd5d}, {0x15a1072b, 0xdc030e50}, {0x15b1772b, 0xdc0b4f31}, {0x30000000, 0x0}, {0x30000000, 0x0}, {0x30000000, 0x0}, {0x30000000, 0x0}, {0x30000000, 0x0}, {0x30000000, 0x0}, {0x30000000, 0x0}, {0x30000000, 0x0}},
    {{0x0, 0x0}, {0x831600, 0x1100019}, {0x8a1402, 0x21080bb}, {0x911204, 0x311015d}, {0x14e20701, 0x31000222}, {0x2d75e05, 0x459429e}, {0x14f23101, 0x3100433c}, {0xde1c07, 0x519c3cc}, {0x15024d01, 0x310484af}, {0x2e55a09, 0x65a4528}, {0x15126901, 0x3104c615}, {0xad120b, 0x712c668}, {0x15228501, 0x3109075b}, {0x1f4380d, 0x83b4791}, {0x1532a101, 0x310948a1}, {0x7c080f, 0x90bc8c8}, {0x1542bd01, 0x310d89a7}, {0x1552d901, 0x310dca4a}, {0x15620e1d, 0x98020aed}, {0x15727e1d, 0x980a4b90}, {0x15820e24, 0xba028c79}, {0x15927e24, 0xba0acd6c}, {0x15a20e2b, 0xdc030e5f}, {0x15b27e2b, 0xdc0b4f3f}, {0x30000000, 0x0}, {0x30000000, 0x0}, {0x30000000, 0x0}, {0x30000000, 0x0}, {0x30000000, 0x0}, {0x30000000, 0x0}, {0x30000000, 0x0}, {0x30000000, 0x0}},
    {{0x0, 0x0}, {0xc31e00, 0x118001b}, {0xca1c02, 0x21880bd}, {0xd11a04, 0x319015f}, {0x14e30708, 0x2000022e}, {0x2a434d32, 0x4e8202ab}, {0x14f33108, 0x20004353}, {0x1de3c07, 0x539c3d6}, {0x15034d08, 0x200484c7}, {0x3a57209, 0x6724531}, {0x15136908, 0x2004c62a}, {0x26d4a0b, 0x74ac67a}, {0x15238508, 0x2009076f}, {0x2b4500d, 0x8534799}, {0x1533a108, 0x200948b5}, {0xfc180f, 0x91bc8cd}, {0x1543bd08, 0x200d89b1}, {0x1553d908, 0x200dca54}, {0x1563151d, 0x98020af7}, {0x1573851d, 0x980a4b9a}, {0x15831524, 0xba028c88}, {0x15938524, 0xba0acd7b}, {0x15a3152b, 0xdc030e6e}, {0x15b3852b, 0xdc0b4f4c}, {0x30000000, 0x0}, {0x30000000, 0x0}, {0x30000000, 0x0}, {0x30000000, 0x0}, {0x30000000, 0x0}, {0x30000000, 0x0}, {0x30000000, 0x0}, {0x30000000, 0x0}},
    {{0x0, 0x0}, {0x1032600, 0x120001c}, {0x10a2402, 0x22080be}, {0x1112204, 0x3210160}, {0x14e40e01, 0x3100023a}, {0x1182006, 0x42182b8}, {0x14f40e0f, 0x7500436a}, {0x29e5407, 0x551c3e0}, {0x15042a0f, 0x750084de}, {0xa61409, 0x612453c}, {0x1514460f, 0x7504c63e}, {0x3ad720b, 0x772c687}, {0x1524620f, 0x75050784}, {0x3f4780d, 0x87b47a5}, {0x15347e0f, 0x750948ca}, {0x2bc500f, 0x953c8df}, {0x15449a0f, 0x750989bb}, {0x1554b60f, 0x750dca5e}, {0x15641c1d, 0x98020b01}, {0x15748c1d, 0x980a4ba5}, {0x15841c24, 0xba028c97}, {0x15948c24, 0xba0acd8a}, {0x15a41c2b, 0xdc030e7d}, {0x15b48c2b, 0xdc0b4f59}, {0x30000000, 0x0}, {0x30000000, 0x0}, {0x30000000, 0x0}, {0x30000000, 0x0}, {0x30000000, 0x0}, {0x30000000, 0x0}, {0x30000000, 0x0}, {0x30000000, 0x0}},
    {{0x0, 0x0}, {0x1432e00, 0x128001e}, {0x14a2c02, 0x22880c0}, {0x1512a04, 0x3290162}, {0x14e50e08, 0x20000245}, {0x2184006, 0x44182c4}, {0x14f50e16, 0x64004382}, {0x35e6c07, 0x569c3e9}, {0x15052a16, 0x640084f5}, {0x1262409, 0x6224542}, {0x15154616, 0x6404c652}, {0xee1c0b, 0x71ac693}, {0x31020c, 0x7030706}, {0x15256216, 0x64050798}, {0x3f77e0d, 0x87b481f}, {0x15357e16, 0x640948de}, {0x15459a16, 0x640989c5}, {0x1555b616, 0x640dca68}, {0x1565231d, 0x98020b0b}, {0x1575931d, 0x980a4bb4}, {0x15852324, 0xba028ca7}, {0x15959324, 0xba0acd99}, {0x15a5232b, 0xdc030e8c}, {0x15b5932b, 0xdc0b4f66}, {0x30000000, 0x0}, {0x30000000, 0x0}, {0x30000000, 0x0}, {0x30000000, 0x0}, {0x30000000, 0x0}, {0x30000000, 0x0}, {0x30000000, 0x0}, {0x30000000, 0x0}},
    {{0x0, 0x0}, {0x1833600, 0x130001f}, {0x18a3402, 0x23080c1}, {0x1913204, 0x3310163}, {0x14e61501, 0x31000251}, {0x3586806, 0x46982d2}, {0x14f6150f, 0x75004399}, {0x3de7c07, 0x579c3ed}, {0x1506310f, 0x7500850c}, {0x1a63409, 0x6324548}, {0x15164d0f, 0x7504c667}, {0x26e4c0b, 0x74ac6a3}, {0x170280c, 0x72b06ea}, {0x1526690f, 0x750507ad}, {0x1b8300e, 0x8338832}, {0x1536850f, 0x750948f2}, {0x1546a10f, 0x750989d0}, {0x1556bd0f, 0x750dca73}, {0x15662a1d, 0x98020b15}, {0x15769a1d, 0x980a4bc3}, {0x15862a24, 0xba028cb6}, {0x15969a24, 0xba0acda9}, {0x15a62a2b, 0xdc030e9b}, {0x15b69a2b, 0xdc0b4f74}, {0x30000000, 0x0}, {0x30000000, 0x0}, {0x30000000, 0x0}, {0x30000000, 0x0}, {0x30000000, 0x0}, {0x30000000, 0x0}, {0x30000000, 0x0}, {0x30000000, 0x0}},
    {{0x0, 0x0}, {0x1c33e00, 0x1380021}, {0x1ca3c02, 0x23880c3}, {0x1d13a04, 0x3390165}, {0x14e71508, 0x2000025d}, {0x590a06, 0x40982de}, {0x14f71516, 0x640043b0}, {0x5f0e07, 0x509c3f4}, {0x220408, 0x502047d}, {0x15073116, 0x64008523}, {0x15174d16, 0x6404c67b}, {0x2f060b, 0x702c6b4}, {0x330600c, 0x76306fc}, {0x15276916, 0x640507c1}, {0x78080e, 0x80b8825}, {0x15378516, 0x64094907}, {0x1547a116, 0x640989da}, {0x1557bd16, 0x640dca7d}, {0x1567311d, 0x98020b20}, {0x1577a11d, 0x980a4bd2}, {0x15873124, 0xba028cc5}, {0x1597a124, 0xba0acdb8}, {0x15a7312b, 0xdc030eab}, {0x15b7a12b, 0xdc0b4f81}, {0x30000000, 0x0}, {0x30000000, 0x0}, {0x30000000, 0x0}, {0x30000000, 0x0}, {0x30000000, 0x0}, {0x30000000, 0x0}, {0x30000000, 0x0}, {0x30000000, 0x0}},
    {{0x0, 0x0}, {0x2034600, 0x1400022}, {0x20a4402, 0x24080c4}, {0x2114204, 0x3410166}, {0x14e81c01, 0x31000268}, {0x1993206, 0x43182ec}, {0x1dc3807, 0x439c379}, {0x14f83801, 0x310443c7}, {0x3216208, 0x5620471}, {0x15085401, 0x3104853b}, {0x15187001, 0x3108c690}, {0x1af360b, 0x732c6c4}, {0x1722c0c, 0x72b073b}, {0x15288c01, 0x310907d5}, {0x38000e, 0x8038823}, {0x1538a801, 0x310d491b}, {0x1548c401, 0x310d89e4}, {0x1558c40f, 0x750dca87}, {0x1568381d, 0x98060b2a}, {0x1578a81d, 0x980e4be1}, {0x15883824, 0xba068cd4}, {0x1598a824, 0xba0ecdc7}, {0x15a8382b, 0xdc070eba}, {0x15b8a82b, 0xdc0f4f8e}, {0x30000000, 0x0}, {0x30000000, 0x0}, {0x30000000, 0x0}, {0x30000000, 0x0}, {0x30000000, 0x0}, {0x30000000, 0x0}, {0x30000000, 0x0}, {0x30000000, 0x0}},
    {{0x0, 0x0}, {0x2434e00, 0x1480023}, {0x24a4c02, 0x24880c5}, {0x2514a04, 0x3490167}, {0x2a2c0033, 0x280c1f8}, {0x14e91c08, 0x20000274}, {0x2a4b5b32, 0x5c828365}, {0x14f93808, 0x200443de}, {0x3a17208, 0x5720477}, {0x15095408, 0x20048552}, {0x2694a0a, 0x64a85d7}, {0x15197008, 0x2008c6a4}, {0x2714a0c, 0x74b071d}, {0x15298c08, 0x200907ea}, {0xf8180e, 0x81b882b}, {0x1539a808, 0x200d492f}, {0x17f2e0f, 0x92bc94d}, {0x1549c408, 0x200d89ee}, {0x1559c416, 0x640dca91}, {0x15693f1d, 0x98060b34}, {0x1579af1d, 0x980e4bf0}, {0x15893f24, 0xba068ce3}, {0x1599af24, 0xba0ecdd6}, {0x15a93f2b, 0xdc070ec7}, {0x15b9af2b, 0xdc0f4f9c}, {0x30000000, 0x0}, {0x30000000, 0x0}, {0x30000000, 0x0}, {0x30000000, 0x0}, {0x30000000, 0x0}, {0x30000000, 0x0}, {0x30000000, 0x0}},
    {{0x0, 0x0}, {0x2835600, 0x1500025}, {0x28a5402, 0x25080c7}, {0x2915204, 0x3510169}, {0x2a261531, 0x158041f0}, {0x14ea2301, 0x31000282}, {0x21b4606, 0x441834f}, {0x14fa3f01, 0x310443f6}, {0x620c08, 0x50a0480}, {0x150a5b01, 0x31048569}, {0x229420a, 0x64285d5}, {0x151a7701, 0x3108c6b8}, {0xb1120c, 0x713070b}, {0x152a9301, 0x310907fe}, {0x178280e, 0x82b8830}, {0x153aaf01, 0x310d4944}, {0x1ff3e0f, 0x93bc950}, {0x154acb01, 0x310d89f8}, {0x155acb0f, 0x750dca9b}, {0x156a461d, 0x98060b3e}, {0x157ab61d, 0x980e4c00}, {0x158a4624, 0xba068cf2}, {0x159ab624, 0xba0ecde5}, {0x15aa462b, 0xdc070ed4}, {0x15bab62b, 0xdc0f4fa9}, {0x30000000, 0x0}, {0x30000000, 0x0}, {0x30000000, 0x0}, {0x30000000, 0x0}, {0x30000000, 0x0}, {0x30000000, 0x0}, {0x30000000, 0x0}},
    {{0x0, 0x0}, {0x2c35e00, 0x1580026}, {0x2ca5c02, 0x25880c8}, {0x2d15a04, 0x359016a}, {0x2a271532, 0x168041f1}, {0x14eb2308, 0x20000299}, {0xdb1e06, 0x4198340}, {0x14fb3f08, 0x2004440d}, {0xe21c08, 0x51a0485}, {0x150b5b08, 0x20048580}, {0x329620a, 0x66285df}, {0x151b7708, 0x2008c6cd}, {0x3f0780c, 0x77b0702}, {0x152b9308, 0x20090812}, {0x278480e, 0x84b883a}, {0xff1e0f, 0x91bc948}, {0x153baf08, 0x200d4958}, {0x154bcb08, 0x200d8a03}, {0x155bcb16, 0x640dcaa5}, {0x156b4d1d, 0x98060b48}, {0x157bbd1d, 0x980e4c0f}, {0x158b4d24, 0xba068d02}, {0x159bbd24, 0xba0ecdf4}, {0x15ab4d2b, 0xdc070ee2}, {0x15bbbd2b, 0xdc0f4fb6}, {0x30000000, 0x0}, {0x30000000, 0x0}, {0x30000000, 0x0}, {0x30000000, 0x0}, {0x30000000, 0x0}, {0x30000000, 0x0}, {0x30000000, 0x0}},
    {{0x0, 0x0}, {0x3036600, 0x1600028}, {0x30a6402, 0x26080ca}, {0x3116204, 0x361016c}, {0x2a281c31, 0x1c8081f3}, {0x14ec000f, 0x750002b1}, {0x3da7c06, 0x4798333}, {0x14fc1c0f, 0x75004424}, {0x1a23408, 0x532048e}, {0x150c380f, 0x75048598}, {0x3e97a0a, 0x67a85e5}, {0x151c540f, 0x7504c6e1}, {0x370680c, 0x76b06fe}, {0x152c700f, 0x75090827}, {0x338600e, 0x8638841}, {0x27b4e0e, 0x94b88b4}, {0x153c8c0f, 0x7509496a}, {0x154ca80f, 0x750d8a0d}, {0x155cd20f, 0x750dcab0}, {0x156c541d, 0x98060b52}, {0x157cc41d, 0x980e4c1e}, {0x158c5424, 0xba068d11}, {0x159cc424, 0xba0ece04}, {0x15ac542b, 0xdc070eef}, {0x15bcc42b, 0xdc0f4fc3}, {0x30000000, 0x0}, {0x30000000, 0x0}, {0x30000000, 0x0}, {0x30000000, 0x0}, {0x30000000, 0x0}, {0x30000000, 0x0}, {0x30000000, 0x0}},
    {{0x0, 0x0}, {0x3436e00, 0x1680029}, {0x34a6c02, 0x26880cb}, {0x3516a04, 0x369016d}, {0x2a291c32, 0x1d8081f4}, {0x14ed0016, 0x640002c8}, {0x29a5406, 0x4518326}, {0x14fd1c16, 0x6400443b}, {0x2224408, 0x5420494}, {0x150d3816, 0x640485af}, {0xaa140a, 0x61285ee}, {0x1eb3e0a, 0x63a8622}, {0x151d5416, 0x6404c6f5}, {0x174280d, 0x82b478d}, {0x152d7016, 0x6409083b}, {0x37b6e0e, 0x96b88be}, {0x153d8c16, 0x64094974}, {0x154da816, 0x640d8a17}, {0x155dd216, 0x640dcaba}, {0x156d5b1d, 0x98060b5d}, {0x157dcb1d, 0x980e4c2d}, {0x158d5b24, 0xba068d20}, {0x159dcb24, 0xba0ece13}, {0x15ad5b2b, 0xdc070efc}, {0x15bdcb2b, 0xdc0f4fd1}, {0x30000000, 0x0}, {0x30000000, 0x0}, {0x30000000, 0x0}, {0x30000000, 0x0}, {0x30000000, 0x0}, {0x30000000, 0x0}, {0x30000000, 0x0}},
    {{0x0, 0x0}, {0x3837600, 0x170002b}, {0x38a7402, 0x27080cd}, {0x3917204, 0x371016f}, {0x2a2a2331, 0x238081f6}, {0x14ee070f, 0x750002df}, {0x1da3c06, 0x439831c}, {0x14fe230f, 0x75004453}, {0x2e25c08, 0x55a049d}, {0x3e57a09, 0x67a4532}, {0x150e3f0f, 0x750485c4}, {0x2eb5e0a, 0x65a862e}, {0x151e5b0f, 0x7504c70a}, {0x1b4300d, 0x833478f}, {0x152e770f, 0x7509084f}, {0x2fb5e0e, 0x95b88b9}, {0x153e930f, 0x7509497e}, {0x154eaf0f, 0x750d8a21}, {0x155ed90f, 0x750dcac4}, {0x156e621d, 0x98060b67}, {0x157ed21d, 0x980e4c3c}, {0x158e6224, 0xba068d2f}, {0x159ed224, 0xba0ece22}, {0x15ae622b, 0xdc070f09}, {0x15bed22b, 0xdc0f4fde}, {0x30000000, 0x0}, {0x30000000, 0x0}, {0x30000000, 0x0}, {0x30000000, 0x0}, {0x30000000, 0x0}, {0x30000000, 0x0}, {0x30000000, 0x0}},
    {{0x0, 0x0}, {0x3c37e00, 0x178002c}, {0x3ca7c02, 0x27880ce}, {0x3d17a04, 0x3790170}, {0x2a2b2332, 0x248081f7}, {0x170605, 0x401427e}, {0x14ef0716, 0x640002f6}, {0x14ff2316, 0x6400446a}, {0x3a27408, 0x57204a5}, {0x660c09, 0x60a4539}, {0x150f3f16, 0x640485d8}, {0xac100b, 0x712c63f}, {0x151f5b16, 0x6404c71e}, {0x334600d, 0x863479f}, {0x152f7716, 0x64090864}, {0x3c000f, 0x903c8c6}, {0x153f9316, 0x64094988}, {0x154faf16, 0x640d8a2b}, {0x155fd916, 0x640dcace}, {0x156f691d, 0x98060b71}, {0x157fd91d, 0x980e4c4b}, {0x158f6924, 0xba068d3e}, {0x159fd924, 0xba0ece31}, {0x15af692b, 0xdc070f17}, {0x15bfd92b, 0xdc0f4feb}, {0x30000000, 0x0}, {0x30000000, 0x0}, {0x30000000, 0x0}, {0x30000000, 0x0}, {0x30000000, 0x0}, {0x30000000, 0x0}, {0x30000000, 0x0}},
    {{0x0, 0x0}, {0x40001, 0x100402e}, {0xb0602, 0x20080d0}, {0x120404, 0x3010172}, {0x15c00002, 0x3100020d}, {0xd71e05, 0x4194287}, {0x15d02a02, 0x31004310}, {0x2de5c07, 0x559c3e3}, {0x15e04602, 0x31048484}, {0x3656a09, 0x66a452e}, {0x15f06202, 0x3104c5ef}, {0x1ec380b, 0x73ac64b}, {0x16007e02, 0x31090735}, {0x234400d, 0x8434794}, {0x16109a02, 0x3109487b}, {0x3bb760e, 0x97388c1}, {0x1620b602, 0x310d8994}, {0x1630d202, 0x310dca37}, {0x1640001e, 0x98020ada}, {0x1650701e, 0x980a4b7c}, {0x16600025, 0xba028c5d}, {0x16707025, 0xba0acd4f}, {0x1680002c, 0xdc030e42}, {0x1690702c, 0xdc0b4f26}, {0x30000000, 0x0}, {0x30000000, 0x0}, {0x30000000, 0x0}, {0x30000000, 0x0}, {0x30000000, 0x0}, {0x30000000, 0x0}, {0x30000000, 0x0}, {0x30000000, 0x0}},
    {{0x0, 0x0}, {0x440801, 0x108402f}, {0x4b0e02, 0x20880d1}, {0x520c04, 0x3090173}, {0x15c10009, 0x20000218}, {0x2a424d31, 0x4d820294}, {0x15d12a09, 0x20004328}, {0x25e4c07, 0x549c3dd}, {0x15e14609, 0x2004849b}, {0x260409, 0x6024536}, {0x15f16209, 0x2004c604}, {0x36c680b, 0x76ac65b}, {0x16017e09, 0x20090749}, {0x274480d, 0x84b4797}, {0x16119a09, 0x2009488f}, {0xbc100f, 0x913c8cb}, {0x1621b609, 0x200d899e}, {0x1631d209, 0x200dca41}, {0x1641071e, 0x98020ae4}, {0x1651771e, 0x980a4b87}, {0x16610725, 0xba028c6c}, {0x16717725, 0xba0acd5f}, {0x1681072c, 0xdc030e51}, {0x1691772c, 0xdc0b4f33}, {0x30000000, 0x0}, {0x30000000, 0x0}, {0x30000000, 0x0}, {0x30000000, 0x0}, {0x30000000, 0x0}, {0x30000000, 0x0}, {0x30000000, 0x0}, {0x30000000, 0x0}},
    {{0x0, 0x0}, {0x841001, 0x1104030}, {0x8b1602, 0x21080d2}, {0x921404, 0x3110174}, {0x15c20702, 0x31000224}, {0x3176605, 0x46142a1}, {0x15d23102, 0x3100433f}, {0x31e6407, 0x561c3e6}, {0x15e24d02, 0x310484b2}, {0xe61c09, 0x61a453f}, {0x15f26902, 0x3104c618}, {0x12d220b, 0x722c66d}, {0x16028502, 0x3109075e}, {0x374680d, 0x86b47a1}, {0x1612a102, 0x310948a3}, {0x1bc300f, 0x933c8d5}, {0x1622bd02, 0x310d89a8}, {0x1632d902, 0x310dca4b}, {0x16420e1e, 0x98020aee}, {0x16527e1e, 0x980a4b91}, {0x16620e25, 0xba028c7b}, {0x16727e25, 0xba0acd6e}, {0x16820e2c, 0xdc030e61}, {0x16927e2c, 0xdc0b4f41}, {0x30000000, 0x0}, {0x30000000, 0x0}, {0x30000000, 0x0}, {0x30000000, 0x0}, {0x30000000, 0x0}, {0x30000000, 0x0}, {0x30000000, 0x0}, {0x30000000, 0x0}},
    {{0x0, 0x0}, {0xc41801, 0x1184032}, {0xcb1e02, 0x21880d4}, {0xd21c04, 0x3190176}, {0x15c30709, 0x20000230}, {0x180006, 0x40182ac}, {0x15d33109, 0x20004356}, {0x39e7407, 0x571c3ec}, {0x15e34d09, 0x200484ca}, {0x1662c09, 0x62a4545}, {0x15f36909, 0x2004c62c}, {0x2ad520b, 0x752c67c}, {0x16038509, 0x20090772}, {0x35020d, 0x80347a9}, {0x1613a109, 0x200948b8}, {0x33c600f, 0x963c8e4}, {0x1623bd09, 0x200d89b2}, {0x1633d909, 0x200dca55}, {0x1643151e, 0x98020af8}, {0x1653851e, 0x980a4b9b}, {0x16631525, 0xba028c8a}, {0x16738525, 0xba0acd7d}, {0x1683152c, 0xdc030e70}, {0x1693852c, 0xdc0b4f4e}, {0x30000000, 0x0}, {0x30000000, 0x0}, {0x30000000, 0x0}, {0x30000000, 0x0}, {0x30000000, 0x0}, {0x30000000, 0x0}, {0x30000000, 0x0}, {0x30000000, 0x0}},
    {{0x0, 0x0}, {0x1042001, 0x1204033}, {0x10b2602, 0x22080d5}, {0x1122404, 0x3210177}, {0x15c40e02, 0x3100023b}, {0x1582806, 0x42982bb}, {0x15d40e10, 0x7500436d}, {0x1f0607, 0x501c3f1}, {0x15e42a10, 0x750084e1}, {0x2264409, 0x642454e}, {0x15f44610, 0x7504c641}, {0x3ed7a0b, 0x77ac688}, {0x16046210, 0x75050786}, {0xf51a0d, 0x81b47b0}, {0x16147e10, 0x750948cc}, {0x3fc780f, 0x97bc8eb}, {0x16249a10, 0x750989bd}, {0x1634b610, 0x750dca5f}, {0x16441c1e, 0x98020b02}, {0x16548c1e, 0x980a4ba6}, {0x16641c25, 0xba028c99}, {0x16748c25, 0xba0acd8c}, {0x16841c2c, 0xdc030e7f}, {0x16948c2c, 0xdc0b4f5b}, {0x30000000, 0x0}, {0x30000000, 0x0}, {0x30000000, 0x0}, {0x30000000, 0x0}, {0x30000000, 0x0}, {0x30000000, 0x0}, {0x30000000, 0x0}, {0x30000000, 0x0}},
    {{0x0, 0x0}, {0x1442801, 0x1284035}, {0x14b2e02, 0x22880d7}, {0x1522c04, 0x3290179}, {0x15c50e09, 0x20000247}, {0x2584806, 0x44982c6}, {0x15d50e17, 0x64004385}, {0xdf1e07, 0x519c3fa}, {0x15e52a17, 0x640084f8}, {0x2e65c09, 0x65a4556}, {0x15f54617, 0x6404c655}, {0x12e240b, 0x722c696}, {0x16056217, 0x6405079b}, {0x1f53a0d, 0x83b47b9}, {0xb9120e, 0x8138851}, {0x16157e17, 0x640948e0}, {0x16259a17, 0x640989c7}, {0x1635b617, 0x640dca6a}, {0x1645231e, 0x98020b0c}, {0x1655931e, 0x980a4bb6}, {0x16652325, 0xba028ca8}, {0x16759325, 0xba0acd9b}, {0x1685232c, 0xdc030e8e}, {0x1695932c, 0xdc0b4f68}, {0x30000000, 0x0}, {0x30000000, 0x0}, {0x30000000, 0x0}, {0x30000000, 0x0}, {0x30000000, 0x0}, {0x30000000, 0x0}, {0x30000000, 0x0}, {0x30000000, 0x0}},
    {{0x0, 0x0}, {0x1843001, 0x1304036}, {0x18b3602, 0x23080d8}, {0x1923404, 0x331017a}, {0x15c61502, 0x31000252}, {0x3987006, 0x47182d5}, {0x15d61510, 0x7500439c}, {0x19f3607, 0x531c403}, {0x15e63110, 0x7500850f}, {0x3a67409, 0x672455f}, {0x15f64d10, 0x7504c669}, {0x2ae540b, 0x752c6a5}, {0x16066910, 0x750507af}, {0x335620d, 0x86347c7}, {0x2f8580e, 0x85b883f}, {0x16168510, 0x750948f5}, {0x1626a110, 0x750989d1}, {0x1636bd10, 0x750dca74}, {0x16462a1e, 0x98020b17}, {0x16569a1e, 0x980a4bc5}, {0x16662a25, 0xba028cb8}, {0x16769a25, 0xba0acdaa}, {0x16862a2c, 0xdc030e9d}, {0x16969a2c, 0xdc0b4f76}, {0x30000000, 0x0}, {0x30000000, 0x0}, {0x30000000, 0x0}, {0x30000000, 0x0}, {0x30000000, 0x0}, {0x30000000, 0x0}, {0x30000000, 0x0}, {0x30000000, 0x0}},
    {{0x0, 0x0}, {0x1c43801, 0x1384038}, {0x1cb3e02, 0x23880da}, {0x1d23c04, 0x339017c}, {0x15c71509, 0x2000025e}, {0x991206, 0x41182e1}, {0x15d71517, 0x640043b3}, {0x21f4607, 0x541c409}, {0x15e73117, 0x64008526}, {0x270609, 0x6024565}, {0x15f74d17, 0x6404c67e}, {0x6f0e0b, 0x70ac6b7}, {0x3b0700c, 0x7730701}, {0x16076917, 0x640507c3}, {0x3f8780e, 0x87b8848}, {0x16178517, 0x64094909}, {0x1627a117, 0x640989db}, {0x1637bd17, 0x640dca7e}, {0x1647311e, 0x98020b21}, {0x1657a11e, 0x980a4bd4}, {0x16673125, 0xba028cc7}, {0x1677a125, 0xba0acdba}, {0x1687312c, 0xdc030ead}, {0x1697a12c, 0xdc0b4f83}, {0x30000000, 0x0}, {0x30000000, 0x0}, {0x30000000, 0x0}, {0x30000000, 0x0}, {0x30000000, 0x0}, {0x30000000, 0x0}, {0x30000000, 0x0}, {0x30000000, 0x0}},
    {{0x0, 0x0}, {0x2044001, 0x1404039}, {0x20b4602, 0x24080db}, {0x2124404, 0x341017d}, {0x15c81c02, 0x3100026a}, {0x1d93a06, 0x43982ee}, {0x15d83802, 0x310443ca}, {0x29f5607, 0x551c40e}, {0x2624c08, 0x54a0497}, {0x15e85402, 0x3104853e}, {0x15f87002, 0x3108c692}, {0x1ef3e0b, 0x73ac6c5}, {0x1f13a0c, 0x73b0716}, {0x16088c02, 0x310907d8}, {0x238400e, 0x8438837}, {0x1618a802, 0x310d491e}, {0x1628c402, 0x310d89e5}, {0x1638c410, 0x750dca88}, {0x1648381e, 0x98060b2b}, {0x1658a81e, 0x980e4be3}, {0x16683825, 0xba068cd6}, {0x1678a825, 0xba0ecdc9}, {0x1688382c, 0xdc070ebc}, {0x1698a82c, 0xdc0f4f90}, {0x30000000, 0x0}, {0x30000000, 0x0}, {0x30000000, 0x0}, {0x30000000, 0x0}, {0x30000000, 0x0}, {0x30000000, 0x0}, {0x30000000, 0x0}, {0x30000000, 0x0}},
    {{0x0, 0x0}, {0x2444801, 0x148403a}, {0x24b4e02, 0x24880dc}, {0x2524c04, 0x349017e}, {0x2a2d0034, 0x380c1fa}, {0x15c91c09, 0x20000275}, {0x19c3007, 0x431c377}, {0x15d93809, 0x200443e1}, {0x1622c08, 0x52a048b}, {0x15e95409, 0x20048555}, {0x2a9520a, 0x65285da}, {0x15f97009, 0x2008c6a6}, {0x720c0c, 0x70b0731}, {0x16098c09, 0x200907ec}, {0x1f8380e, 0x83b8833}, {0x1619a809, 0x200d4932}, {0x1bf360f, 0x933c94f}, {0x1629c409, 0x200d89ef}, {0x1639c417, 0x640dca92}, {0x16493f1e, 0x98060b35}, {0x1659af1e, 0x980e4bf2}, {0x16693f25, 0xba068ce5}, {0x1679af25, 0xba0ecdd8}, {0x16893f2c, 0xdc070ec9}, {0x1699af2c, 0xdc0f4f9d}, {0x30000000, 0x0}, {0x30000000, 0x0}, {0x30000000, 0x0}, {0x30000000, 0x0}, {0x30000000, 0x0}, {0x30000000, 0x0}, {0x30000000, 0x0}},
    {{0x0, 0x0}, {0x2845001, 0x150403c}, {0x28b5602, 0x25080de}, {0x2925404, 0x3510180}, {0x2a2e0733, 0x980c1fb}, {0x15ca2302, 0x31000285}, {0x3db7e06, 0x4798362}, {0x15da3f02, 0x310443f9}, {0x1e23c08, 0x53a048f}, {0x15ea5b02, 0x3104856c}, {0x3696a0a, 0x66a85e1}, {0x15fa7702, 0x3108c6bb}, {0x331620c, 0x7630724}, {0x160a9302, 0x31090801}, {0x2b8500e, 0x853883c}, {0x161aaf02, 0x310d4946}, {0x27f4e0f, 0x94bc957}, {0x162acb02, 0x310d89fa}, {0x163acb10, 0x750dca9d}, {0x164a461e, 0x98060b3f}, {0x165ab61e, 0x980e4c01}, {0x166a4625, 0xba068cf4}, {0x167ab625, 0xba0ecde7}, {0x168a462c, 0xdc070ed6}, {0x169ab62c, 0xdc0f4fab}, {0x30000000, 0x0}, {0x30000000, 0x0}, {0x30000000, 0x0}, {0x30000000, 0x0}, {0x30000000, 0x0}, {0x30000000, 0x0}, {0x30000000, 0x0}},
    {{0x0, 0x0}, {0x2c45801, 0x158403d}, {0x2cb5e02, 0x25880df}, {0x2d25c04, 0x3590181}, {0x2a2f0734, 0xa80c1fd}, {0x15cb2309, 0x2000029c}, {0x2a4a5b31, 0x5b82834d}, {0x15db3f09, 0x20044410}, {0x2a25408, 0x552049a}, {0x15eb5b09, 0x20048583}, {0x2a040a, 0x60285e9}, {0x15fb7709, 0x2008c6cf}, {0x1712a0c, 0x72b0713}, {0x160b9309, 0x20090815}, {0x3b8700e, 0x8738847}, {0x161baf09, 0x200d495b}, {0x33f660f, 0x963c95e}, {0x162bcb09, 0x200d8a04}, {0x163bcb17, 0x640dcaa7}, {0x164b4d1e, 0x98060b4a}, {0x165bbd1e, 0x980e4c11}, {0x166b4d25, 0xba068d04}, {0x167bbd25, 0xba0ecdf6}, {0x168b4d2c, 0xdc070ee4}, {0x169bbd2c, 0xdc0f4fb8}, {0x30000000, 0x0}, {0x30000000, 0x0}, {0x30000000, 0x0}, {0x30000000, 0x0}, {0x30000000, 0x0}, {0x30000000, 0x0}, {0x30000000, 0x0}},
    {{0x0, 0x0}, {0x3046001, 0x160403f}, {0x30b6602, 0x26080e1}, {0x3126404, 0x3610183}, {0x2a302a31, 0x2a8101fe}, {0x15cc0010, 0x750002b4}, {0x15b2e06, 0x4298346}, {0x15dc1c10, 0x75004427}, {0x3626c08, 0x56a04a2}, {0x15ec3810, 0x7504859a}, {0xea1c0a, 0x61a85f1}, {0x15fc5410, 0x7504c6e4}, {0x131220c, 0x7230710}, {0x160c7010, 0x75090829}, {0x790a0e, 0x80b884e}, {0x1fc380f, 0x93bc8d6}, {0x161c8c10, 0x7509496b}, {0x162ca810, 0x750d8a0e}, {0x163cd210, 0x750dcab1}, {0x164c541e, 0x98060b54}, {0x165cc41e, 0x980e4c20}, {0x166c5425, 0xba068d13}, {0x167cc425, 0xba0ece06}, {0x168c542c, 0xdc070ef1}, {0x169cc42c, 0xdc0f4fc5}, {0x30000000, 0x0}, {0x30000000, 0x0}, {0x30000000, 0x0}, {0x30000000, 0x0}, {0x30000000, 0x0}, {0x30000000, 0x0}, {0x30000000, 0x0}},
    {{0x0, 0x0}, {0x3446801, 0x1684040}, {0x34b6e02, 0x26880e2}, {0x3526c04, 0x3690184}, {0x2a312a32, 0x2b810200}, {0x15cd0017, 0x640002cb}, {0x1b0606, 0x4018338}, {0x15dd1c17, 0x6400443e}, {0x230608, 0x50204ab}, {0x15ed3817, 0x640485b2}, {0x16a2c0a, 0x62a85f6}, {0xed1a0b, 0x71ac66b}, {0x15fd5417, 0x6404c6f8}, {0x160d7017, 0x6409083e}, {0x1b9320e, 0x833885b}, {0x13c200f, 0x923c8d0}, {0x161d8c17, 0x64094975}, {0x162da817, 0x640d8a18}, {0x163dd217, 0x640dcabb}, {0x164d5b1e, 0x98060b5e}, {0x165dcb1e, 0x980e4c2f}, {0x166d5b25, 0xba068d22}, {0x167dcb25, 0xba0ece15}, {0x168d5b2c, 0xdc070efe}, {0x169dcb2c, 0xdc0f4fd3}, {0x30000000, 0x0}, {0x30000000, 0x0}, {0x30000000, 0x0}, {0x30000000, 0x0}, {0x30000000, 0x0}, {0x30000000, 0x0}, {0x30000000, 0x0}},
    {{0x0, 0x0}, {0x3847001, 0x1704042}, {0x38b7602, 0x27080e4}, {0x3927404, 0x3710186}, {0x2a323131, 0x31810201}, {0x15ce0710, 0x750002e2}, {0x2da5c06, 0x4598329}, {0x15de2310, 0x75004455}, {0xa31608, 0x51204b1}, {0x15ee3f10, 0x750485c7}, {0x1ea3c0a, 0x63a85f9}, {0x3eb7e0a, 0x67a8637}, {0x15fe5b10, 0x7504c70c}, {0x2f4580d, 0x85b479c}, {0x160e7710, 0x75090852}, {0x17c280f, 0x92bc8d2}, {0x161e9310, 0x75094980}, {0x162eaf10, 0x750d8a22}, {0x163ed910, 0x750dcac5}, {0x164e621e, 0x98060b68}, {0x165ed21e, 0x980e4c3e}, {0x166e6225, 0xba068d31}, {0x167ed225, 0xba0ece24}, {0x168e622c, 0xdc070f0b}, {0x169ed22c, 0xdc0f4fe0}, {0x30000000, 0x0}, {0x30000000, 0x0}, {0x30000000, 0x0}, {0x30000000, 0x0}, {0x30000000, 0x0}, {0x30000000, 0x0}, {0x30000000, 0x0}},
    {{0x0, 0x0}, {0x3c47801, 0x1784043}, {0x3cb7e02, 0x27880e5}, {0x3d27c04, 0x3790187}, {0x2a333132, 0x32810203}, {0x2a414632, 0x4782027c}, {0x15cf0717, 0x640002f9}, {0x15df2317, 0x6400446d}, {0x1232608, 0x52204b7}, {0x3266409, 0x6624559}, {0x15ef3f17, 0x640485db}, {0x6c080b, 0x70ac63d}, {0x15ff5b17, 0x6404c721}, {0x3b4700d, 0x87347a4}, {0x160f7717, 0x64090866}, {0x27c480f, 0x94bc8dd}, {0x161f9317, 0x6409498a}, {0x162faf17, 0x640d8a2d}, {0x163fd917, 0x640dcacf}, {0x164f691e, 0x98060b72}, {0x165fd91e, 0x980e4c4d}, {0x166f6925, 0xba068d40}, {0x167fd925, 0xba0ece33}, {0x168f692c, 0xdc070f19}, {0x169fd92c, 0xdc0f4fed}, {0x30000000, 0x0}, {0x30000000, 0x0}, {0x30000000, 0x0}, {0x30000000, 0x0}, {0x30000000, 0x0}, {0x30000000, 0x0}, {0x30000000, 0x0}},
    {{0x0, 0x0}, {0x50201, 0x1004045}, {0xc0003, 0x200c0e7}, {0x130604, 0x3010189}, {0x16a00003, 0x3100020e}, {0x1172605, 0x421428a}, {0x16b02a03, 0x31004313}, {0x16c04603, 0x31048487}, {0x1e33e08, 0x53a04be}, {0x2a65409, 0x6524553}, {0x16d06203, 0x3104c5f2}, {0x22c400b, 0x742c64f}, {0x16e07e03, 0x31090738}, {0x1b5320d, 0x83347b8}, {0x16f09a03, 0x3109487d}, {0x2fc580f, 0x95bc8e2}, {0x1700b603, 0x310d8995}, {0x1710d203, 0x310dca38}, {0x1720001f, 0x98020adb}, {0x1730701f, 0x980a4b7e}, {0x17400026, 0xba028c5e}, {0x17507026, 0xba0acd51}, {0x1760002d, 0xdc030e44}, {0x1770702d, 0xdc0b4f28}, {0x30000000, 0x0}, {0x30000000, 0x0}, {0x30000000, 0x0}, {0x30000000, 0x0}, {0x30000000, 0x0}, {0x30000000, 0x0}, {0x30000000, 0x0}, {0x30000000, 0x0}},
    {{0x0, 0x0}, {0x450a01, 0x1084046}, {0x4c0803, 0x208c0e8}, {0x530e04, 0x309018a}, {0x16a1000a, 0x2000021a}, {0x2174605, 0x4414295}, {0x16b12a0a, 0x2000432b}, {0x11f2607, 0x521c3fd}, {0x16c1460a, 0x2004849e}, {0x1e63c09, 0x63a4549}, {0x16d1620a, 0x2004c606}, {0x3ec780b, 0x77ac65f}, {0x16e17e0a, 0x2009074c}, {0x750a0d, 0x80b47ab}, {0x16f19a0a, 0x20094892}, {0x23c400f, 0x943c8da}, {0x1701b60a, 0x200d899f}, {0x1711d20a, 0x200dca42}, {0x1721071f, 0x98020ae5}, {0x1731771f, 0x980a4b88}, {0x17410726, 0xba028c6e}, {0x17517726, 0xba0acd60}, {0x1761072d, 0xdc030e53}, {0x1771772d, 0xdc0b4f35}, {0x30000000, 0x0}, {0x30000000, 0x0}, {0x30000000, 0x0}, {0x30000000, 0x0}, {0x30000000, 0x0}, {0x30000000, 0x0}, {0x30000000, 0x0}, {0x30000000, 0x0}},
    {{0x0, 0x0}, {0x851201, 0x1104047}, {0x8c1003, 0x210c0e9}, {0x931604, 0x311018b}, {0x16a20703, 0x31000225}, {0x3576e05, 0x46942a4}, {0x16b23103, 0x31004342}, {0x9f1607, 0x511c3f7}, {0x16c24d03, 0x310484b5}, {0x2664c09, 0x64a4550}, {0x16d26903, 0x3104c61b}, {0x16d2a0b, 0x72ac670}, {0x16e28503, 0x31090760}, {0xb5120d, 0x81347ae}, {0x16f2a103, 0x310948a6}, {0x37c680f, 0x96bc8e7}, {0x1702bd03, 0x310d89a9}, {0x1712d903, 0x310dca4c}, {0x17220e1f, 0x98020aef}, {0x17327e1f, 0x980a4b92}, {0x17420e26, 0xba028c7d}, {0x17527e26, 0xba0acd70}, {0x17620e2d, 0xdc030e63}, {0x17727e2d, 0xdc0b4f42}, {0x30000000, 0x0}, {0x30000000, 0x0}, {0x30000000, 0x0}, {0x30000000, 0x0}, {0x30000000, 0x0}, {0x30000000, 0x0}, {0x30000000, 0x0}, {0x30000000, 0x0}},
    {{0x0, 0x0}, {0xc51a01, 0x1184049}, {0xcc1803, 0x218c0eb}, {0xd31e04, 0x319018d}, {0x16a3070a, 0x20000231}, {0x580806, 0x40982af}, {0x16b3310a, 0x20004359}, {0x15f2e07, 0x529c400}, {0x16c34d0a, 0x200484cc}, {0x3666c09, 0x66a455c}, {0x16d3690a, 0x2004c62f}, {0x2ed5a0b, 0x75ac67f}, {0x16e3850a, 0x20090775}, {0x1752a0d, 0x82b47b5}, {0x16f3a10a, 0x200948ba}, {0x7d0a0f, 0x90bc8f1}, {0x1703bd0a, 0x200d89b4}, {0x1713d90a, 0x200dca57}, {0x1723151f, 0x98020af9}, {0x1733851f, 0x980a4b9c}, {0x17431526, 0xba028c8c}, {0x17538526, 0xba0acd7f}, {0x1763152d, 0xdc030e72}, {0x1773852d, 0xdc0b4f50}, {0x30000000, 0x0}, {0x30000000, 0x0}, {0x30000000, 0x0}, {0x30000000, 0x0}, {0x30000000, 0x0}, {0x30000000, 0x0}, {0x30000000, 0x0}, {0x30000000, 0x0}},
    {{0x0, 0x0}, {0x1052201, 0x120404a}, {0x10c2003, 0x220c0ec}, {0x1132604, 0x321018e}, {0x16a40e03, 0x3100023d}, {0x1983006, 0x43182be}, {0x16b40e11, 0x75004370}, {0x1df3e07, 0x539c404}, {0x16c42a11, 0x750084e4}, {0x3e67c09, 0x67a4560}, {0x16d44611, 0x7504c643}, {0x2e040b, 0x702c68c}, {0x16e46211, 0x75050789}, {0x2754a0d, 0x84b47c0}, {0x16f47e11, 0x750948cf}, {0x17d2a0f, 0x92bc8fb}, {0x17049a11, 0x750989be}, {0x1714b611, 0x750dca61}, {0x17241c1f, 0x98020b04}, {0x17348c1f, 0x980a4ba8}, {0x17441c26, 0xba028c9b}, {0x17548c26, 0xba0acd8e}, {0x17641c2d, 0xdc030e81}, {0x17748c2d, 0xdc0b4f5d}, {0x30000000, 0x0}, {0x30000000, 0x0}, {0x30000000, 0x0}, {0x30000000, 0x0}, {0x30000000, 0x0}, {0x30000000, 0x0}, {0x30000000, 0x0}, {0x30000000, 0x0}},
    {{0x0, 0x0}, {0x1452a01, 0x128404c}, {0x14c2803, 0x228c0ee}, {0x1532e04, 0x3290190}, {0x16a50e0a, 0x20000248}, {0x2985006, 0x45182c9}, {0x16b50e18, 0x64004387}, {0x25f4e07, 0x549c40b}, {0x16c52a18, 0x640084fb}, {0xa71609, 0x612456b}, {0x16d54618, 0x6404c658}, {0x16e2c0b, 0x72ac698}, {0x16e56218, 0x6405079d}, {0x3756a0d, 0x86b47ca}, {0x16f57e18, 0x640948e3}, {0x23d420f, 0x943c903}, {0x17059a18, 0x640989c8}, {0x1715b618, 0x640dca6b}, {0x1725231f, 0x98020b0e}, {0x1735931f, 0x980a4bb7}, {0x17452326, 0xba028caa}, {0x17559326, 0xba0acd9d}, {0x1765232d, 0xdc030e90}, {0x1775932d, 0xdc0b4f6a}, {0x30000000, 0x0}, {0x30000000, 0x0}, {0x30000000, 0x0}, {0x30000000, 0x0}, {0x30000000, 0x0}, {0x30000000, 0x0}, {0x30000000, 0x0}, {0x30000000, 0x0}},
    {{0x0, 0x0}, {0x1853201, 0x130404d}, {0x18c3003, 0x230c0ef}, {0x1933604, 0x3310191}, {0x16a61503, 0x31000254}, {0x3d87806, 0x47982d6}, {0x16b61511, 0x7500439f}, {0x31f6607, 0x561c414}, {0x16c63111, 0x75008512}, {0x1672e09, 0x62a4573}, {0x16d64d11, 0x7504c66c}, {0x2ee5c0b, 0x75ac6a8}, {0x16e66911, 0x750507b2}, {0x36040d, 0x80347d1}, {0x16f68511, 0x750948f7}, {0x2bd520f, 0x953c908}, {0x1706a111, 0x750989d2}, {0x1716bd11, 0x750dca75}, {0x17262a1f, 0x98020b18}, {0x17369a1f, 0x980a4bc7}, {0x17462a26, 0xba028cba}, {0x17569a26, 0xba0acdac}, {0x17662a2d, 0xdc030e9f}, {0x17769a2d, 0xdc0b4f78}, {0x30000000, 0x0}, {0x30000000, 0x0}, {0x30000000, 0x0}, {0x30000000, 0x0}, {0x30000000, 0x0}, {0x30000000, 0x0}, {0x30000000, 0x0}, {0x30000000, 0x0}},
    {{0x0, 0x0}, {0x1c53a01, 0x138404f}, {0x1cc3803, 0x238c0f1}, {0x1d33e04, 0x3390193}, {0x16a7150a, 0x2000025f}, {0xd91a06, 0x41982e3}, {0x16b71518, 0x640043b6}, {0x3df7e07, 0x579c41b}, {0x16c73118, 0x64008529}, {0x2274609, 0x642457c}, {0x16d74d18, 0x6404c680}, {0xaf160b, 0x712c6ba}, {0x16e76918, 0x640507c6}, {0x136240d, 0x82347dc}, {0x139220e, 0x8238856}, {0x16f78518, 0x6409490c}, {0x1707a118, 0x640989dc}, {0x1717bd18, 0x640dca7f}, {0x1727311f, 0x98020b22}, {0x1737a11f, 0x980a4bd6}, {0x17473126, 0xba028cc9}, {0x1757a126, 0xba0acdbc}, {0x1767312d, 0xdc030eae}, {0x1777a12d, 0xdc0b4f85}, {0x30000000, 0x0}, {0x30000000, 0x0}, {0x30000000, 0x0}, {0x30000000, 0x0}, {0x30000000, 0x0}, {0x30000000, 0x0}, {0x30000000, 0x0}, {0x30000000, 0x0}},
    {{0x0, 0x0}, {0x2054201, 0x1404050}, {0x20c4003, 0x240c0f2}, {0x2134604, 0x3410194}, {0x16a81c03, 0x3100026b}, {0x2a463133, 0x338242f1}, {0x16b83803, 0x310443cd}, {0x600808, 0x50a0423}, {0x16c85403, 0x31048540}, {0x2a75609, 0x6524582}, {0x16d87003, 0x3108c695}, {0x26f4e0b, 0x74ac6cb}, {0x2f25c0c, 0x75b074b}, {0x16e88c03, 0x310907da}, {0x239420e, 0x8438860}, {0x16f8a803, 0x310d4920}, {0x1708c403, 0x310d89e7}, {0x1718c411, 0x750dca89}, {0x1728381f, 0x98060b2c}, {0x1738a81f, 0x980e4be5}, {0x17483826, 0xba068cd8}, {0x1758a826, 0xba0ecdcb}, {0x1768382d, 0xdc070ebe}, {0x1778a82d, 0xdc0f4f92}, {0x30000000, 0x0}, {0x30000000, 0x0}, {0x30000000, 0x0}, {0x30000000, 0x0}, {0x30000000, 0x0}, {0x30000000, 0x0}, {0x30000000, 0x0}, {0x30000000, 0x0}},
    {{0x0, 0x0}, {0x2454a01, 0x1484051}, {0x24c4803, 0x248c0f3}, {0x2534e04, 0x3490195}, {0x2a340e33, 0x10814204}, {0x16a91c0a, 0x20000277}, {0x25c4807, 0x449c380}, {0x16b9380a, 0x200443e4}, {0x3226408, 0x562049f}, {0x16c9540a, 0x20048558}, {0x3a9720a, 0x67285e4}, {0x16d9700a, 0x2008c6a9}, {0x132240c, 0x7230739}, {0x16e98c0a, 0x200907ef}, {0x378680e, 0x86b8844}, {0x16f9a80a, 0x200d4934}, {0x23f460f, 0x943c954}, {0x1709c40a, 0x200d89f1}, {0x1719c418, 0x640dca94}, {0x17293f1f, 0x98060b36}, {0x1739af1f, 0x980e4bf4}, {0x17493f26, 0xba068ce7}, {0x1759af26, 0xba0ecdda}, {0x17693f2d, 0xdc070ecb}, {0x1779af2d, 0xdc0f4f9f}, {0x30000000, 0x0}, {0x30000000, 0x0}, {0x30000000, 0x0}, {0x30000000, 0x0}, {0x30000000, 0x0}, {0x30000000, 0x0}, {0x30000000, 0x0}},
    {{0x0, 0x0}, {0x2855201, 0x1504053}, {0x28c5003, 0x250c0f5}, {0x2935604, 0x3510197}, {0x2a350e34, 0x11814205}, {0x16aa2303, 0x31000288}, {0x11c2007, 0x421c372}, {0x16ba3f03, 0x310443fb}, {0x3e27c08, 0x57a04a7}, {0x16ca5b03, 0x3104856f}, {0x6a0c0a, 0x60a85eb}, {0x16da7703, 0x3108c6bd}, {0xb2140c, 0x7130734}, {0x16ea9303, 0x31090803}, {0x39020e, 0x803884c}, {0x16faaf03, 0x310d4949}, {0x2ff5e0f, 0x95bc95c}, {0x170acb03, 0x310d89fb}, {0x171acb11, 0x750dca9e}, {0x172a461f, 0x98060b41}, {0x173ab61f, 0x980e4c03}, {0x174a4626, 0xba068cf6}, {0x175ab626, 0xba0ecde9}, {0x176a462d, 0xdc070ed8}, {0x177ab62d, 0xdc0f4fad}, {0x30000000, 0x0}, {0x30000000, 0x0}, {0x30000000, 0x0}, {0x30000000, 0x0}, {0x30000000, 0x0}, {0x30000000, 0x0}, {0x30000000, 0x0}},
    {{0x0, 0x0}, {0x2c55a01, 0x1584054}, {0x2cc5803, 0x258c0f6}, {0x2d35e04, 0x3590198}, {0x2a361533, 0x17814207}, {0x16ab230a, 0x2000029f}, {0x35b6e06, 0x469835d}, {0x16bb3f0a, 0x20044413}, {0x630e08, 0x50a04ae}, {0x16cb5b0a, 0x20048586}, {0x12a240a, 0x62285f3}, {0x16db770a, 0x2008c6d2}, {0x3716a0c, 0x76b0727}, {0x16eb930a, 0x20090817}, {0xf91a0e, 0x81b8853}, {0x16fbaf0a, 0x200d495d}, {0x3bf760f, 0x973c964}, {0x170bcb0a, 0x200d8a05}, {0x171bcb18, 0x640dcaa8}, {0x172b4d1f, 0x98060b4b}, {0x173bbd1f, 0x980e4c13}, {0x174b4d26, 0xba068d05}, {0x175bbd26, 0xba0ecdf8}, {0x176b4d2d, 0xdc070ee5}, {0x177bbd2d, 0xdc0f4fba}, {0x30000000, 0x0}, {0x30000000, 0x0}, {0x30000000, 0x0}, {0x30000000, 0x0}, {0x30000000, 0x0}, {0x30000000, 0x0}, {0x30000000, 0x0}},
    {{0x0, 0x0}, {0x3056201, 0x1604056}, {0x30c6003, 0x260c0f8}, {0x3136604, 0x361019a}, {0x2a371534, 0x18814208}, {0x16ac0011, 0x750002b6}, {0x25b4e06, 0x4498352}, {0x16bc1c11, 0x7500442a}, {0xe31e08, 0x51a04b4}, {0x16cc3811, 0x7504859d}, {0x1aa340a, 0x63285f8}, {0x16dc5411, 0x7504c6e6}, {0x2f15a0c, 0x75b0722}, {0x16ec7011, 0x7509082c}, {0x1f93a0e, 0x83b885c}, {0x7f0e0f, 0x90bc942}, {0x16fc8c11, 0x7509496c}, {0x170ca811, 0x750d8a0f}, {0x171cd211, 0x750dcab2}, {0x172c541f, 0x98060b55}, {0x173cc41f, 0x980e4c22}, {0x174c5426, 0xba068d15}, {0x175cc426, 0xba0ece07}, {0x176c542d, 0xdc070ef3}, {0x177cc42d, 0xdc0f4fc7}, {0x30000000, 0x0}, {0x30000000, 0x0}, {0x30000000, 0x0}, {0x30000000, 0x0}, {0x30000000, 0x0}, {0x30000000, 0x0}, {0x30000000, 0x0}},
    {{0x0, 0x0}, {0x3456a01, 0x1684057}, {0x34c6803, 0x268c0f9}, {0x3536e04, 0x369019b}, {0x2a383831, 0x38818214}, {0x16ad0018, 0x640002ce}, {0x19b3606, 0x4318349}, {0x16bd1c18, 0x64004441}, {0x1a33608, 0x53204bc}, {0x16cd3818, 0x640485b5}, {0x22a440a, 0x64285fd}, {0x16dd5418, 0x6404c6fa}, {0x231420c, 0x743071a}, {0x16ed7018, 0x64090840}, {0x2b9520e, 0x8538865}, {0x1fd3a0f, 0x93bc8ff}, {0x16fd8c18, 0x64094977}, {0x170da818, 0x640d8a19}, {0x171dd218, 0x640dcabc}, {0x172d5b1f, 0x98060b5f}, {0x173dcb1f, 0x980e4c31}, {0x174d5b26, 0xba068d24}, {0x175dcb26, 0xba0ece17}, {0x176d5b2d, 0xdc070f00}, {0x177dcb2d, 0xdc0f4fd4}, {0x30000000, 0x0}, {0x30000000, 0x0}, {0x30000000, 0x0}, {0x30000000, 0x0}, {0x30000000, 0x0}, {0x30000000, 0x0}, {0x30000000, 0x0}},
    {{0x0, 0x0}, {0x3857201, 0x1704059}, {0x38c7003, 0x270c0fb}, {0x3937604, 0x371019d}, {0x2a393832, 0x39818220}, {0x16ae0711, 0x750002e5}, {0x9b1606, 0x411833d}, {0x16be2311, 0x75004458}, {0x2634e08, 0x54a04c5}, {0x16ce3f11, 0x750485c9}, {0x2aa540a, 0x6528602}, {0xec180b, 0x71ac642}, {0x16de5b11, 0x7504c70f}, {0x16ee7711, 0x75090855}, {0x3796a0e, 0x86b886d}, {0x3d020f, 0x903c8ee}, {0x16fe9311, 0x75094981}, {0x170eaf11, 0x750d8a24}, {0x171ed911, 0x750dcac6}, {0x172e621f, 0x98060b69}, {0x173ed21f, 0x980e4c40}, {0x174e6226, 0xba068d33}, {0x175ed226, 0xba0ece26}, {0x176e622d, 0xdc070f0d}, {0x177ed22d, 0xdc0f4fe2}, {0x30000000, 0x0}, {0x30000000, 0x0}, {0x30000000, 0x0}, {0x30000000, 0x0}, {0x30000000, 0x0}, {0x30000000, 0x0}, {0x30000000, 0x0}},
    {{0x0, 0x0}, {0x3c57a01, 0x178405a}, {0x3cc7803, 0x278c0fc}, {0x3d37e04, 0x379019e}, {0x2a3a3f31, 0x3f81822b}, {0x16af0718, 0x640002fc}, {0x35a6c06, 0x469832f}, {0x16bf2318, 0x64004470}, {0x2e35e08, 0x55a04cb}, {0x16cf3f18, 0x640485dd}, {0x32a640a, 0x6628607}, {0x2ac500b, 0x752c654}, {0x16df5b18, 0x6404c723}, {0x135220d, 0x82347b3}, {0x16ef7718, 0x64090869}, {0x3bc700f, 0x973c8e9}, {0x16ff9318, 0x6409498b}, {0x170faf18, 0x640d8a2e}, {0x171fd918, 0x640dcad1}, {0x172f691f, 0x98060b74}, {0x173fd91f, 0x980e4c4f}, {0x174f6926, 0xba068d42}, {0x175fd926, 0xba0ece35}, {0x176f692d, 0xdc070f1b}, {0x177fd92d, 0xdc0f4fef}, {0x30000000, 0x0}, {0x30000000, 0x0}, {0x30000000, 0x0}, {0x30000000, 0x0}, {0x30000000, 0x0}, {0x30000000, 0x0}, {0x30000000, 0x0}},
    {{0x0, 0x0}, {0x60401, 0x100405c}, {0xd0203, 0x200c0fe}, {0x140005, 0x30141a0}, {0x17800004, 0x31000210}, {0x1572e05, 0x429428c}, {0x17902a04, 0x31004316}, {0x17a04604, 0x3104848a}, {0x3636e08, 0x56a04d1}, {0x1e73e09, 0x63a4578}, {0x17b06204, 0x3104c5f4}, {0x26c480b, 0x74ac651}, {0x17c07e04, 0x3109073a}, {0x235420d, 0x84347bd}, {0x17d09a04, 0x31094880}, {0x13d220f, 0x923c8f9}, {0x17e0b604, 0x310d8996}, {0x17f0d204, 0x310dca39}, {0x18000020, 0x98020adc}, {0x18107020, 0x980a4b7f}, {0x18200027, 0xba028c60}, {0x18307027, 0xba0acd53}, {0x1840002e, 0xdc030e46}, {0x1850702e, 0xdc0b4f2a}, {0x30000000, 0x0}, {0x30000000, 0x0}, {0x30000000, 0x0}, {0x30000000, 0x0}, {0x30000000, 0x0}, {0x30000000, 0x0}, {0x30000000, 0x0}, {0x30000000, 0x0}},
    {{0x0, 0x0}, {0x460c01, 0x108405d}, {0x4d0a03, 0x208c0ff}, {0x540805, 0x30941a1}, {0x1781000b, 0x2000021b}, {0x2574e05, 0x4494298}, {0x17912a0b, 0x2000432d}, {0x17a1460b, 0x200484a1}, {0x3e37e08, 0x57a04d5}, {0xe71e09, 0x61a456d}, {0x17b1620b, 0x2004c609}, {0x2d020b, 0x702c663}, {0x17c17e0b, 0x2009074e}, {0x3f57a0d, 0x87b47ce}, {0x17d19a0b, 0x20094894}, {0xbd120f, 0x913c8f4}, {0x17e1b60b, 0x200d89a1}, {0x17f1d20b, 0x200dca43}, {0x18010720, 0x98020ae6}, {0x18117720, 0x980a4b89}, {0x18210727, 0xba028c70}, {0x18317727, 0xba0acd62}, {0x1841072e, 0xdc030e55}, {0x1851772e, 0xdc0b4f37}, {0x30000000, 0x0}, {0x30000000, 0x0}, {0x30000000, 0x0}, {0x30000000, 0x0}, {0x30000000, 0x0}, {0x30000000, 0x0}, {0x30000000, 0x0}, {0x30000000, 0x0}},
    {{0x0, 0x0}, {0x861401, 0x110405e}, {0x8d1203, 0x210c100}, {0x941005, 0x31141a2}, {0x17820704, 0x31000227}, {0x3977605, 0x47142a7}, {0x17923104, 0x31004345}, {0x35f6e07, 0x569c417}, {0x17a24d04, 0x310484b8}, {0x670e09, 0x60a4568}, {0x17b26904, 0x3104c61d}, {0x1ad320b, 0x732c672}, {0x17c28504, 0x31090763}, {0x2b5520d, 0x85347c2}, {0x17d2a104, 0x310948a8}, {0xfd1a0f, 0x91bc8f6}, {0x17e2bd04, 0x310d89ab}, {0x17f2d904, 0x310dca4e}, {0x18020e20, 0x98020af0}, {0x18127e20, 0x980a4b93}, {0x18220e27, 0xba028c7f}, {0x18327e27, 0xba0acd72}, {0x18420e2e, 0xdc030e64}, {0x18527e2e, 0xdc0b4f44}, {0x30000000, 0x0}, {0x30000000, 0x0}, {0x30000000, 0x0}, {0x30000000, 0x0}, {0x30000000, 0x0}, {0x30000000, 0x0}, {0x30000000, 0x0}, {0x30000000, 0x0}},
    {{0x0, 0x0}, {0xc61c01, 0x1184060}, {0xcd1a03, 0x218c102}, {0xd41805, 0x31941a4}, {0x1783070b, 0x20000232}, {0x981006, 0x41182b2}, {0x1793310b, 0x2000435c}, {0x2df5e07, 0x559c411}, {0x17a34d0b, 0x200484cf}, {0x1272609, 0x6224570}, {0x17b3690b, 0x2004c631}, {0x32d620b, 0x762c682}, {0x17c3850b, 0x20090777}, {0x2f55a0d, 0x85b47c5}, {0x17d3a10b, 0x200948bd}, {0x1bd320f, 0x933c8fe}, {0x17e3bd0b, 0x200d89b5}, {0x17f3d90b, 0x200dca58}, {0x18031520, 0x98020afb}, {0x18138520, 0x980a4b9e}, {0x18231527, 0xba028c8e}, {0x18338527, 0xba0acd81}, {0x1843152e, 0xdc030e74}, {0x1853852e, 0xdc0b4f52}, {0x30000000, 0x0}, {0x30000000, 0x0}, {0x30000000, 0x0}, {0x30000000, 0x0}, {0x30000000, 0x0}, {0x30000000, 0x0}, {0x30000000, 0x0}, {0x30000000, 0x0}},
    {{0x0, 0x0}, {0x1062401, 0x1204061}, {0x10d2203, 0x220c103}, {0x1142005, 0x32141a5}, {0x17840e04, 0x3100023e}, {0x1d83806, 0x43982bf}, {0x17940e12, 0x75004373}, {0x39f7607, 0x571c41a}, {0x17a42a12, 0x750084e7}, {0x1a73609, 0x6324576}, {0x17b44612, 0x7504c646}, {0x6e0c0b, 0x70ac68e}, {0x17c46212, 0x7505078b}, {0x3b5720d, 0x87347cc}, {0x17d47e12, 0x750948d1}, {0x27d4a0f, 0x94bc905}, {0x17e49a12, 0x750989bf}, {0x17f4b612, 0x750dca62}, {0x18041c20, 0x98020b05}, {0x18148c20, 0x980a4baa}, {0x18241c27, 0xba028c9d}, {0x18348c27, 0xba0acd90}, {0x18441c2e, 0xdc030e83}, {0x18548c2e, 0xdc0b4f5f}, {0x30000000, 0x0}, {0x30000000, 0x0}, {0x30000000, 0x0}, {0x30000000, 0x0}, {0x30000000, 0x0}, {0x30000000, 0x0}, {0x30000000, 0x0}, {0x30000000, 0x0}},
    {{0x0, 0x0}, {0x1462c01, 0x1284063}, {0x14d2a03, 0x228c105}, {0x1542805, 0x32941a7}, {0x17850e0b, 0x2000024a}, {0x2d85806, 0x45982cc}, {0x17950e19, 0x6400438a}, {0x200008, 0x5020420}, {0x17a52a19, 0x640084fe}, {0x2674e09, 0x64a457f}, {0x17b54619, 0x6404c65a}, {0x1ae340b, 0x732c69b}, {0x17c56219, 0x640507a0}, {0x760c0d, 0x80b47d4}, {0x17d57e19, 0x640948e6}, {0x37d6a0f, 0x96bc910}, {0x17e59a19, 0x640989c9}, {0x17f5b619, 0x640dca6c}, {0x18052320, 0x98020b0f}, {0x18159320, 0x980a4bb9}, {0x18252327, 0xba028cac}, {0x18359327, 0xba0acd9f}, {0x1845232e, 0xdc030e92}, {0x1855932e, 0xdc0b4f6c}, {0x30000000, 0x0}, {0x30000000, 0x0}, {0x30000000, 0x0}, {0x30000000, 0x0}, {0x30000000, 0x0}, {0x30000000, 0x0}, {0x30000000, 0x0}, {0x30000000, 0x0}},
    {{0x0, 0x0}, {0x1863401, 0x1304064}, {0x18d3203, 0x230c106}, {0x1943005, 0x33141a8}, {0x17861504, 0x31000255}, {0x2a452a34, 0x2d8242d9}, {0x17961512, 0x750043a2}, {0xa01008, 0x5120426}, {0x17a63112, 0x75008515}, {0x3276609, 0x6624588}, {0x17b64d12, 0x7504c66e}, {0x36e6c0b, 0x76ac6ad}, {0x17c66912, 0x750507b4}, {0x1762c0d, 0x82b47de}, {0x17d68512, 0x750948fa}, {0x7e0c0f, 0x90bc91a}, {0x17e6a112, 0x750989d3}, {0x17f6bd12, 0x750dca76}, {0x18062a20, 0x98020b19}, {0x18169a20, 0x980a4bc9}, {0x18262a27, 0xba028cbb}, {0x18369a27, 0xba0acdae}, {0x18462a2e, 0xdc030ea1}, {0x18569a2e, 0xdc0b4f79}, {0x30000000, 0x0}, {0x30000000, 0x0}, {0x30000000, 0x0}, {0x30000000, 0x0}, {0x30000000, 0x0}, {0x30000000, 0x0}, {0x30000000, 0x0}, {0x30000000, 0x0}},
    {{0x0, 0x0}, {0x1c63c01, 0x1384066}, {0x1cd3a03, 0x238c108}, {0x1d43805, 0x33941aa}, {0x1787150b, 0x20000261}, {0x1192206, 0x42182e6}, {0x17971519, 0x640043b9}, {0xe01808, 0x51a0428}, {0x17a73119, 0x6400852c}, {0x3a77609, 0x672458d}, {0x17b74d19, 0x6404c683}, {0x12f260b, 0x722c6bf}, {0x17c76919, 0x640507c9}, {0x1f63c0d, 0x83b47e2}, {0x13a240e, 0x923887e}, {0x17d78519, 0x6409490e}, {0x17e7a119, 0x640989de}, {0x17f7bd19, 0x640dca81}, {0x18073120, 0x98020b23}, {0x1817a120, 0x980a4bd8}, {0x18273127, 0xba028ccb}, {0x1837a127, 0xba0acdbd}, {0x1847312e, 0xdc030eb0}, {0x1857a12e, 0xdc0b4f87}, {0x30000000, 0x0}, {0x30000000, 0x0}, {0x30000000, 0x0}, {0x30000000, 0x0}, {0x30000000, 0x0}, {0x30000000, 0x0}, {0x30000000, 0x0}, {0x30000000, 0x0}},
    {{0x0, 0x0}, {0x2064401, 0x1404067}, {0x20d4203, 0x240c109}, {0x2144005, 0x34141ab}, {0x17881c04, 0x3100026c}, {0x2194206, 0x44182f2}, {0x17983804, 0x310443d0}, {0x1202008, 0x522042b}, {0x17a85404, 0x31048543}, {0x68080a, 0x60a8596}, {0x17b87004, 0x3108c697}, {0x2ef5e0b, 0x75ac6d0}, {0x17c88c04, 0x310907dd}, {0x2f65c0d, 0x85b47ed}, {0x2f95a0e, 0x85b8868}, {0x17d8a804, 0x310d4923}, {0x17e8c404, 0x310d89e8}, {0x17f8c412, 0x750dca8b}, {0x18083820, 0x98060b2e}, {0x1818a820, 0x980e4be7}, {0x18283827, 0xba068cda}, {0x1838a827, 0xba0ecdcd}, {0x1848382e, 0xdc070ebf}, {0x1858a82e, 0xdc0f4f94}, {0x30000000, 0x0}, {0x30000000, 0x0}, {0x30000000, 0x0}, {0x30000000, 0x0}, {0x30000000, 0x0}, {0x30000000, 0x0}, {0x30000000, 0x0}, {0x30000000, 0x0}},
    {{0x0, 0x0}, {0x2464c01, 0x1484068}, {0x24d4a03, 0x248c10a}, {0x2544805, 0x34941ac}, {0x17891c0b, 0x20000278}, {0x2995206, 0x45182f8}, {0x1799380b, 0x200443e7}, {0x1602808, 0x52a042e}, {0x17a9540b, 0x2004855b}, {0x128200a, 0x622859f}, {0x17b9700b, 0x2008c6ac}, {0x36f6e0b, 0x76ac6d6}, {0x2724c0c, 0x74b0746}, {0x17c98c0b, 0x200907f1}, {0x3f97a0e, 0x87b8871}, {0x17d9a80b, 0x200d4937}, {0x17e9c40b, 0x200d89f2}, {0x17f9c419, 0x640dca95}, {0x18093f20, 0x98060b38}, {0x1819af20, 0x980e4bf6}, {0x18293f27, 0xba068ce9}, {0x1839af27, 0xba0ecddc}, {0x18493f2e, 0xdc070ecd}, {0x1859af2e, 0xdc0f4fa1}, {0x30000000, 0x0}, {0x30000000, 0x0}, {0x30000000, 0x0}, {0x30000000, 0x0}, {0x30000000, 0x0}, {0x30000000, 0x0}, {0x30000000, 0x0}, {0x30000000, 0x0}},
    {{0x0, 0x0}, {0x2865401, 0x150406a}, {0x28d5203, 0x250c10c}, {0x2945005, 0x35141ae}, {0x178a2304, 0x3100028b}, {0x2d95a06, 0x45982fb}, {0x2a4c3833, 0x3a82c37c}, {0x179a3f04, 0x310443fe}, {0x1632e08, 0x52a04ba}, {0x17aa5b04, 0x31048572}, {0x2ea5c0a, 0x65a8605}, {0x17ba7704, 0x3108c6c0}, {0x1f23c0c, 0x73b073f}, {0x17ca9304, 0x31090806}, {0x1792a0e, 0x82b8858}, {0x17daaf04, 0x310d494b}, {0x17eacb04, 0x310d89fc}, {0x17facb12, 0x750dca9f}, {0x180a4620, 0x98060b42}, {0x181ab620, 0x980e4c05}, {0x182a4627, 0xba068cf8}, {0x183ab627, 0xba0ecdeb}, {0x184a462e, 0xdc070eda}, {0x185ab62e, 0xdc0f4faf}, {0x30000000, 0x0}, {0x30000000, 0x0}, {0x30000000, 0x0}, {0x30000000, 0x0}, {0x30000000, 0x0}, {0x30000000, 0x0}, {0x30000000, 0x0}, {0x30000000, 0x0}},
    {{0x0, 0x0}, {0x2c65c01, 0x158406b}, {0x2cd5a03, 0x258c10d}, {0x2d45805, 0x35941af}, {0x178b230b, 0x200002a2}, {0x3196206, 0x46182fe}, {0x15c2807, 0x429c375}, {0x179b3f0b, 0x20044416}, {0x2234608, 0x54204c2}, {0x17ab5b0b, 0x20048589}, {0x26a4c0a, 0x64a8600}, {0x17bb770b, 0x2008c6d4}, {0x1b2340c, 0x733073e}, {0x17cb930b, 0x2009081a}, {0x2794a0e, 0x84b8863}, {0x17dbaf0b, 0x200d4960}, {0x17ebcb0b, 0x200d8a06}, {0x17fbcb19, 0x640dcaa9}, {0x180b4d20, 0x98060b4c}, {0x181bbd20, 0x980e4c14}, {0x182b4d27, 0xba068d07}, {0x183bbd27, 0xba0ecdfa}, {0x184b4d2e, 0xdc070ee7}, {0x185bbd2e, 0xdc0f4fbc}, {0x30000000, 0x0}, {0x30000000, 0x0}, {0x30000000, 0x0}, {0x30000000, 0x0}, {0x30000000, 0x0}, {0x30000000, 0x0}, {0x30000000, 0x0}, {0x30000000, 0x0}},
    {{0x0, 0x0}, {0x3066401, 0x160406d}, {0x30d6203, 0x260c10f}, {0x3146005, 0x36141b1}, {0x178c0012, 0x750002b9}, {0x3596a06, 0x4698300}, {0x1c0007, 0x401c366}, {0x179c1c12, 0x7500442d}, {0x2a35608, 0x55204c8}, {0x17ac3812, 0x750485a0}, {0x3aa740a, 0x672860d}, {0x17bc5412, 0x7504c6e9}, {0xf21c0c, 0x71b0736}, {0x17cc7012, 0x7509082e}, {0x339620e, 0x863886a}, {0x17dc8c12, 0x7509496e}, {0x17eca812, 0x750d8a11}, {0x17fcd212, 0x750dcab3}, {0x180c5420, 0x98060b56}, {0x181cc420, 0x980e4c24}, {0x182c5427, 0xba068d16}, {0x183cc427, 0xba0ece09}, {0x184c542e, 0xdc070ef5}, {0x185cc42e, 0xdc0f4fc9}, {0x30000000, 0x0}, {0x30000000, 0x0}, {0x30000000, 0x0}, {0x30000000, 0x0}, {0x30000000, 0x0}, {0x30000000, 0x0}, {0x30000000, 0x0}, {0x30000000, 0x0}},
    {{0x0, 0x0}, {0x3466c01, 0x168406e}, {0x34d6a03, 0x268c110}, {0x3546805, 0x36941b2}, {0x2a3b3f32, 0x40818237}, {0x178d0019, 0x640002d1}, {0x2db5e06, 0x4598358}, {0x179d1c19, 0x64004444}, {0x3236608, 0x56204ce}, {0x17ad3819, 0x640485b7}, {0x36a6c0a, 0x66a860a}, {0x17bd5419, 0x6404c6fd}, {0x3f17a0c, 0x77b072b}, {0x17cd7019, 0x64090843}, {0x3b9720e, 0x873886f}, {0x2bf560f, 0x953c959}, {0x17dd8c19, 0x64094978}, {0x17eda819, 0x640d8a1b}, {0x17fdd219, 0x640dcabe}, {0x180d5b20, 0x98060b60}, {0x181dcb20, 0x980e4c33}, {0x182d5b27, 0xba068d26}, {0x183dcb27, 0xba0ece19}, {0x184d5b2e, 0xdc070f02}, {0x185dcb2e, 0xdc0f4fd6}, {0x30000000, 0x0}, {0x30000000, 0x0}, {0x30000000, 0x0}, {0x30000000, 0x0}, {0x30000000, 0x0}, {0x30000000, 0x0}, {0x30000000, 0x0}},
    {{0x0, 0x0}, {0x3867401, 0x1704070}, {0x38d7203, 0x270c112}, {0x3947005, 0x37141b4}, {0x2a3c1c33, 0x1e81c242}, {0x178e0712, 0x750002e8}, {0x1db3e06, 0x439834a}, {0x179e2312, 0x7500445b}, {0x3a37608, 0x57204d4}, {0x17ae3f12, 0x750485cc}, {0x6b0e0a, 0x60a8614}, {0x1ed3a0b, 0x73ac674}, {0x17be5b12, 0x7504c711}, {0x17ce7712, 0x75090857}, {0xba140e, 0x9138879}, {0x3fe7c0f, 0x97bc93c}, {0x17de9312, 0x75094982}, {0x17eeaf12, 0x750d8a25}, {0x17fed912, 0x750dcac8}, {0x180e6220, 0x98060b6b}, {0x181ed220, 0x980e4c42}, {0x182e6227, 0xba068d35}, {0x183ed227, 0xba0ece28}, {0x184e622e, 0xdc070f0f}, {0x185ed22e, 0xdc0f4fe4}, {0x30000000, 0x0}, {0x30000000, 0x0}, {0x30000000, 0x0}, {0x30000000, 0x0}, {0x30000000, 0x0}, {0x30000000, 0x0}, {0x30000000, 0x0}},
    {{0x0, 0x0}, {0x3c67c01, 0x1784071}, {0x3cd7a03, 0x278c113}, {0x3d47805, 0x37941b5}, {0x2a3d1c34, 0x1f81c24e}, {0x178f0719, 0x640002ff}, {0x11b2606, 0x4218343}, {0x179f2319, 0x64004472}, {0x640809, 0x50a44dc}, {0x17af3f19, 0x640485e0}, {0x12b260a, 0x622861c}, {0x3ac700b, 0x772c65e}, {0x17bf5b19, 0x6404c726}, {0x17cf7719, 0x6409086b}, {0x1ba340e, 0x9338884}, {0xfe1c0f, 0x91bc91f}, {0x17df9319, 0x6409498c}, {0x17efaf19, 0x640d8a2f}, {0x17ffd919, 0x640dcad2}, {0x180f6920, 0x98060b75}, {0x181fd920, 0x980e4c51}, {0x182f6927, 0xba068d44}, {0x183fd927, 0xba0ece37}, {0x184f692e, 0xdc070f1c}, {0x185fd92e, 0xdc0f4ff1}, {0x30000000, 0x0}, {0x30000000, 0x0}, {0x30000000, 0x0}, {0x30000000, 0x0}, {0x30000000, 0x0}, {0x30000000, 0x0}, {0x30000000, 0x0}},
    {{0x0, 0x0}, {0x70601, 0x1004073}, {0xe0403, 0x200c115}, {0x150205, 0x30141b7}, {0x18600005, 0x31000211}, {0x18702a05, 0x31004319}, {0xdd1a07, 0x419c39d}, {0x18804605, 0x3104848d}, {0x1242009, 0x52244e5}, {0x168280a, 0x62a85a2}, {0x18906205, 0x3104c5f7}, {0x18a07e05, 0x3109073d}, {0x233460c, 0x843076c}, {0x336640d, 0x86347f0}, {0x18b09a05, 0x31094882}, {0x3e040f, 0x903c917}, {0x18c0b605, 0x310d8998}, {0x18d0d205, 0x310dca3b}, {0x18e00021, 0x98020add}, {0x18f07021, 0x980a4b80}, {0x19000028, 0xba028c62}, {0x19107028, 0xba0acd55}, {0x1920002f, 0xdc030e48}, {0x1930702f, 0xdc0b4f2c}, {0x30000000, 0x0}, {0x30000000, 0x0}, {0x30000000, 0x0}, {0x30000000, 0x0}, {0x30000000, 0x0}, {0x30000000, 0x0}, {0x30000000, 0x0}, {0x30000000, 0x0}},
    {{0x400800, 0x80000}, {0x470e01, 0x1084074}, {0x4e0c03, 0x208c116}, {0x550a05, 0x30941b8}, {0x1861000c, 0x2000021d}, {0x18712a0c, 0x20004330}, {0x19d3207, 0x431c3a6}, {0x1881460c, 0x200484a4}, {0x1a43009, 0x53244eb}, {0xa8100a, 0x6128599}, {0x1891620c, 0x2004c60b}, {0x18a17e0c, 0x20090751}, {0x333660c, 0x8630776}, {0xb6140d, 0x81347d7}, {0x18b19a0c, 0x20094897}, {0x3bd720f, 0x973c912}, {0x18c1b60c, 0x200d89a2}, {0x18d1d20c, 0x200dca45}, {0x18e10721, 0x98020ae8}, {0x18f17721, 0x980a4b8a}, {0x19010728, 0xba028c71}, {0x19117728, 0xba0acd64}, {0x1921072f, 0xdc030e57}, {0x1931772f, 0xdc0b4f39}, {0x30000000, 0x0}, {0x30000000, 0x0}, {0x30000000, 0x0}, {0x30000000, 0x0}, {0x30000000, 0x0}, {0x30000000, 0x0}, {0x30000000, 0x0}, {0x30000000, 0x0}},
    {{0x801000, 0x100000}, {0x871601, 0x1104075}, {0x8e1403, 0x210c117}, {0x951205, 0x31141b9}, {0x18620705, 0x31000228}, {0x18723105, 0x31004348}, {0x21d4207, 0x441c3ac}, {0x18824d05, 0x310484bb}, {0x2644809, 0x54a44f4}, {0x3e77e09, 0x67a458f}, {0x18926905, 0x3104c620}, {0x1ee3c0b, 0x73ac69c}, {0x18a28505, 0x31090765}, {0x236440d, 0x84347e6}, {0x18b2a105, 0x310948ab}, {0x33d620f, 0x963c90d}, {0x18c2bd05, 0x310d89ac}, {0x18d2d905, 0x310dca4f}, {0x18e20e21, 0x98020af2}, {0x18f27e21, 0x980a4b95}, {0x19020e28, 0xba028c81}, {0x19127e28, 0xba0acd73}, {0x19220e2f, 0xdc030e66}, {0x19327e2f, 0xdc0b4f46}, {0x30000000, 0x0}, {0x30000000, 0x0}, {0x30000000, 0x0}, {0x30000000, 0x0}, {0x30000000, 0x0}, {0x30000000, 0x0}, {0x30000000, 0x0}, {0x30000000, 0x0}},
    {{0xc01800, 0x180000}, {0xc71e01, 0x1184077}, {0xce1c03, 0x218c119}, {0xd51a05, 0x31941bb}, {0x1863070c, 0x20000234}, {0x1873310c, 0x2000435f}, {0x35d6a07, 0x469c3ba}, {0x1a03008, 0x5320431}, {0x18834d0c, 0x200484d2}, {0x2e75e09, 0x65a4585}, {0x1893690c, 0x2004c634}, {0x3ee7c0b, 0x77ac6b1}, {0x18a3850c, 0x2009077a}, {0xf61c0d, 0x81b47d9}, {0x18b3a10c, 0x200948bf}, {0x2fd5a0f, 0x95bc90a}, {0x18c3bd0c, 0x200d89b6}, {0x18d3d90c, 0x200dca59}, {0x18e31521, 0x98020afc}, {0x18f38521, 0x980a4b9f}, {0x19031528, 0xba028c90}, {0x19138528, 0xba0acd83}, {0x1923152f, 0xdc030e75}, {0x1933852f, 0xdc0b4f53}, {0x30000000, 0x0}, {0x30000000, 0x0}, {0x30000000, 0x0}, {0x30000000, 0x0}, {0x30000000, 0x0}, {0x30000000, 0x0}, {0x30000000, 0x0}, {0x30000000, 0x0}},
    {{0x1002000, 0x200000}, {0x1072601, 0x1204078}, {0x10e2403, 0x220c11a}, {0x1152205, 0x32141bc}, {0x18640e05, 0x31000240}, {0x18740e13, 0x75004376}, {0x2a4f3f34, 0x4282c3c1}, {0x1e03808, 0x53a0433}, {0x18842a13, 0x750084e9}, {0x3676e09, 0x66a458a}, {0x18944613, 0x7504c648}, {0x22f460b, 0x742c6c9}, {0x18a46213, 0x7505078e}, {0x1b6340d, 0x83347e1}, {0x18b47e13, 0x750948d4}, {0x3fd7a0f, 0x97bc913}, {0x18c49a13, 0x750989c0}, {0x18d4b613, 0x750dca63}, {0x18e41c21, 0x98020b06}, {0x18f48c21, 0x980a4bac}, {0x19041c28, 0xba028c9f}, {0x19148c28, 0xba0acd92}, {0x19241c2f, 0xdc030e85}, {0x19348c2f, 0xdc0b4f61}, {0x30000000, 0x0}, {0x30000000, 0x0}, {0x30000000, 0x0}, {0x30000000, 0x0}, {0x30000000, 0x0}, {0x30000000, 0x0}, {0x30000000, 0x0}, {0x30000000, 0x0}},
    {{0x1402800, 0x280000}, {0x1472e01, 0x128407a}, {0x14e2c03, 0x228c11c}, {0x1552a05, 0x32941be}, {0x18650e0c, 0x2000024b}, {0x18750e1a, 0x6400438d}, {0x9e1407, 0x511c3c9}, {0x2604808, 0x54a043a}, {0x18852a1a, 0x64008501}, {0x28000a, 0x6028593}, {0x1895461a, 0x6404c65d}, {0x3af760b, 0x772c6d8}, {0x18a5621a, 0x640507a2}, {0x2764c0d, 0x84b47e8}, {0x18b57e1a, 0x640948e8}, {0xbe140f, 0x913c91c}, {0x18c59a1a, 0x640989cb}, {0x18d5b61a, 0x640dca6d}, {0x18e52321, 0x98020b10}, {0x18f59321, 0x980a4bbb}, {0x19052328, 0xba028cae}, {0x19159328, 0xba0acda1}, {0x1925232f, 0xdc030e94}, {0x1935932f, 0xdc0b4f6e}, {0x30000000, 0x0}, {0x30000000, 0x0}, {0x30000000, 0x0}, {0x30000000, 0x0}, {0x30000000, 0x0}, {0x30000000, 0x0}, {0x30000000, 0x0}, {0x30000000, 0x0}},
    {{0x1803000, 0x300000}, {0x1873601, 0x130407b}, {0x18e3403, 0x230c11d}, {0x1953205, 0x33141bf}, {0x18661505, 0x31000257}, {0x18761513, 0x750043a4}, {0x19e3407, 0x531c3d4}, {0x2a05008, 0x552043d}, {0x18863113, 0x75008518}, {0xe8180a, 0x61a859c}, {0x18964d13, 0x7504c671}, {0x130200c, 0x72306e7}, {0x18a66913, 0x750507b7}, {0x3766c0d, 0x86b47f3}, {0x18b68513, 0x750948fc}, {0x17e2c0f, 0x92bc924}, {0x18c6a113, 0x750989d5}, {0x18d6bd13, 0x750dca78}, {0x18e62a21, 0x98020b1a}, {0x18f69a21, 0x980a4bca}, {0x19062a28, 0xba028cbd}, {0x19169a28, 0xba0acdb0}, {0x19262a2f, 0xdc030ea3}, {0x19369a2f, 0xdc0b4f7b}, {0x30000000, 0x0}, {0x30000000, 0x0}, {0x30000000, 0x0}, {0x30000000, 0x0}, {0x30000000, 0x0}, {0x30000000, 0x0}, {0x30000000, 0x0}, {0x30000000, 0x0}},
    {{0x1c03800, 0x380000}, {0x1c73e01, 0x138407d}, {0x1ce3c03, 0x238c11f}, {0x1d53a05, 0x33941c1}, {0x1867150c, 0x20000262}, {0xdc1807, 0x419c36f}, {0x1877151a, 0x640043bc}, {0x2204008, 0x5420437}, {0x1887311a, 0x6400852f}, {0x1a8300a, 0x63285a5}, {0x18974d1a, 0x6404c685}, {0x2b1520c, 0x753071f}, {0x18a7691a, 0x640507cb}, {0x3b6740d, 0x87347f5}, {0x18b7851a, 0x64094911}, {0x27e4c0f, 0x94bc92e}, {0x18c7a11a, 0x640989df}, {0x18d7bd1a, 0x640dca82}, {0x18e73121, 0x98020b25}, {0x18f7a121, 0x980a4bda}, {0x19073128, 0xba028ccc}, {0x1917a128, 0xba0acdbf}, {0x1927312f, 0xdc030eb2}, {0x1937a12f, 0xdc0b4f89}, {0x30000000, 0x0}, {0x30000000, 0x0}, {0x30000000, 0x0}, {0x30000000, 0x0}, {0x30000000, 0x0}, {0x30000000, 0x0}, {0x30000000, 0x0}, {0x30000000, 0x0}},
    {{0x2004000, 0x400000}, {0x2074601, 0x140407e}, {0x20e4403, 0x240c120}, {0x2154205, 0x34141c2}, {0x18681c05, 0x3100026e}, {0x31b6606, 0x461835a}, {0x18783805, 0x310443d3}, {0x2e05808, 0x55a0440}, {0x18885405, 0x31048546}, {0x268480a, 0x64a85ad}, {0x18987005, 0x3108c69a}, {0xf11a0c, 0x71b070e}, {0x18a88c05, 0x310907df}, {0x770e0d, 0x80b47fd}, {0x18b8a805, 0x310d4925}, {0x33e640f, 0x963c936}, {0x18c8c405, 0x310d89e9}, {0x18d8c413, 0x750dca8c}, {0x18e83821, 0x98060b2f}, {0x18f8a821, 0x980e4be9}, {0x19083828, 0xba068cdc}, {0x1918a828, 0xba0ecdcf}, {0x1928382f, 0xdc070ec1}, {0x1938a82f, 0xdc0f4f96}, {0x30000000, 0x0}, {0x30000000, 0x0}, {0x30000000, 0x0}, {0x30000000, 0x0}, {0x30000000, 0x0}, {0x30000000, 0x0}, {0x30000000, 0x0}, {0x30000000, 0x0}},
    {{0x2404800, 0x480000}, {0x2474e01, 0x148407f}, {0x24e4c03, 0x248c121}, {0x2554a05, 0x34941c3}, {0x18691c0c, 0x2000027a}, {0x2a495432, 0x55828336}, {0x1879380c, 0x200443ea}, {0x3606808, 0x56a0445}, {0x1889540c, 0x2004855d}, {0x328600a, 0x66285b6}, {0x1899700c, 0x2008c6ae}, {0x2b0500c, 0x75306f7}, {0x18a98c0c, 0x200907f4}, {0x1772e0d, 0x82b4807}, {0x27a4c0e, 0x94b888b}, {0x18b9a80c, 0x200d493a}, {0x18c9c40c, 0x200d89f3}, {0x18d9c41a, 0x640dca96}, {0x18e93f21, 0x98060b39}, {0x18f9af21, 0x980e4bf8}, {0x19093f28, 0xba068ceb}, {0x1919af28, 0xba0ecdde}, {0x19293f2f, 0xdc070ecf}, {0x1939af2f, 0xdc0f4fa3}, {0x30000000, 0x0}, {0x30000000, 0x0}, {0x30000000, 0x0}, {0x30000000, 0x0}, {0x30000000, 0x0}, {0x30000000, 0x0}, {0x30000000, 0x0}, {0x30000000, 0x0}},
    {{0x2805000, 0x500000}, {0x2875601, 0x1504081}, {0x28e5403, 0x250c123}, {0x2955205, 0x35141c5}, {0x186a2305, 0x3100028e}, {0x25a4c06, 0x4498323}, {0x187a3f05, 0x31044401}, {0x210208, 0x502044e}, {0x188a5b05, 0x31048575}, {0x3e8780a, 0x67a85bc}, {0x189a7705, 0x3108c6c2}, {0x1f0380c, 0x73b06ee}, {0x1f33e0c, 0x83b0768}, {0x18aa9305, 0x31090808}, {0x23a440e, 0x9438889}, {0x18baaf05, 0x310d494e}, {0x18cacb05, 0x310d89fd}, {0x18dacb13, 0x750dcaa0}, {0x18ea4621, 0x98060b43}, {0x18fab621, 0x980e4c07}, {0x190a4628, 0xba068cfa}, {0x191ab628, 0xba0ecded}, {0x192a462f, 0xdc070edc}, {0x193ab62f, 0xdc0f4fb0}, {0x30000000, 0x0}, {0x30000000, 0x0}, {0x30000000, 0x0}, {0x30000000, 0x0}, {0x30000000, 0x0}, {0x30000000, 0x0}, {0x30000000, 0x0}, {0x30000000, 0x0}},
    {{0x2c05800, 0x580000}, {0x2c75e01, 0x1584082}, {0x2ce5c03, 0x258c124}, {0x2d55a05, 0x35941c6}, {0x186b230c, 0x200002a5}, {0x19a3406, 0x431831b}, {0x187b3f0c, 0x20044418}, {0xe11a08, 0x51a0457}, {0xe41809, 0x51a44e2}, {0x188b5b0c, 0x2004858c}, {0x2b060a, 0x6028612}, {0x189b770c, 0x2008c6d7}, {0xf31e0c, 0x81b075f}, {0x18ab930c, 0x2009081d}, {0x7a0c0e, 0x90b8877}, {0x18bbaf0c, 0x200d4962}, {0x18cbcb0c, 0x200d8a08}, {0x18dbcb1a, 0x640dcaab}, {0x18eb4d21, 0x98060b4d}, {0x18fbbd21, 0x980e4c16}, {0x190b4d28, 0xba068d09}, {0x191bbd28, 0xba0ecdfc}, {0x192b4d2f, 0xdc070ee9}, {0x193bbd2f, 0xdc0f4fbe}, {0x30000000, 0x0}, {0x30000000, 0x0}, {0x30000000, 0x0}, {0x30000000, 0x0}, {0x30000000, 0x0}, {0x30000000, 0x0}, {0x30000000, 0x0}, {0x30000000, 0x0}},
    {{0x3006000, 0x600000}, {0x3076601, 0x1604084}, {0x30e6403, 0x260c126}, {0x3156205, 0x36141c8}, {0x186c0013, 0x750002bc}, {0xda1c06, 0x4198312}, {0x9d1207, 0x411c39a}, {0x187c1c13, 0x75004430}, {0x240009, 0x50244d9}, {0x188c3813, 0x750485a3}, {0x3ea7c0a, 0x67a860e}, {0x189c5413, 0x7504c6eb}, {0x730e0c, 0x80b075a}, {0x18ac7013, 0x75090831}, {0x3a040e, 0x9038874}, {0x18bc8c13, 0x7509496f}, {0x18cca813, 0x750d8a12}, {0x18dcd213, 0x750dcab5}, {0x18ec5421, 0x98060b58}, {0x18fcc421, 0x980e4c26}, {0x190c5428, 0xba068d18}, {0x191cc428, 0xba0ece0b}, {0x192c542f, 0xdc070ef7}, {0x193cc42f, 0xdc0f4fcb}, {0x30000000, 0x0}, {0x30000000, 0x0}, {0x30000000, 0x0}, {0x30000000, 0x0}, {0x30000000, 0x0}, {0x30000000, 0x0}, {0x30000000, 0x0}, {0x30000000, 0x0}},
    {{0x3406800, 0x680000}, {0x3476e01, 0x1684085}, {0x34e6c03, 0x268c127}, {0x3556a05, 0x36941c9}, {0x186d001a, 0x640002d3}, {0x1a0406, 0x4018309}, {0x2a4d3834, 0x3b82c393}, {0x187d1c1a, 0x64004447}, {0xa41009, 0x51244df}, {0x188d381a, 0x640485ba}, {0x1ab360a, 0x6328621}, {0x189d541a, 0x6404c700}, {0x3f27c0c, 0x77b0754}, {0x18ad701a, 0x64090845}, {0xfa1c0e, 0x91b887c}, {0x18bd8c1a, 0x64094979}, {0x18cda81a, 0x640d8a1c}, {0x18ddd21a, 0x640dcabf}, {0x18ed5b21, 0x98060b62}, {0x18fdcb21, 0x980e4c35}, {0x190d5b28, 0xba068d28}, {0x191dcb28, 0xba0ece1a}, {0x192d5b2f, 0xdc070f04}, {0x193dcb2f, 0xdc0f4fd8}, {0x30000000, 0x0}, {0x30000000, 0x0}, {0x30000000, 0x0}, {0x30000000, 0x0}, {0x30000000, 0x0}, {0x30000000, 0x0}, {0x30000000, 0x0}, {0x30000000, 0x0}},
    {{0x3807000, 0x700000}, {0x3877601, 0x1704087}, {0x38e7403, 0x270c129}, {0x3957205, 0x37141cb}, {0x2a3e2333, 0x2581c25a}, {0x186e0713, 0x750002eb}, {0x29c5007, 0x451c383}, {0x187e2313, 0x7500445e}, {0x1642809, 0x52a44e8}, {0x188e3f13, 0x750485ce}, {0x16b2e0a, 0x62a861e}, {0x189e5b13, 0x7504c714}, {0x332640c, 0x763074d}, {0x18ae7713, 0x7509085a}, {0x1fa3c0e, 0x93b8885}, {0x37f6e0f, 0x96bc961}, {0x18be9313, 0x75094983}, {0x18ceaf13, 0x750d8a26}, {0x18ded913, 0x750dcac9}, {0x18ee6221, 0x98060b6c}, {0x18fed221, 0x980e4c44}, {0x190e6228, 0xba068d37}, {0x191ed228, 0xba0ece2a}, {0x192e622f, 0xdc070f11}, {0x193ed22f, 0xdc0f4fe6}, {0x30000000, 0x0}, {0x30000000, 0x0}, {0x30000000, 0x0}, {0x30000000, 0x0}, {0x30000000, 0x0}, {0x30000000, 0x0}, {0x30000000, 0x0}},
    {{0x3c07800, 0x780000}, {0x3c77e01, 0x1784088}, {0x3ce7c03, 0x278c12a}, {0x3d57a05, 0x37941cc}, {0x2a3f2334, 0x2681c265}, {0x186f071a, 0x64000302}, {0x31c6007, 0x461c389}, {0x187f231a, 0x64004475}, {0x2244009, 0x54244f1}, {0x188f3f1a, 0x640485e3}, {0x32b660a, 0x6628630}, {0x189f5b1a, 0x6404c728}, {0xb3160c, 0x813075c}, {0x18af771a, 0x6409086e}, {0x33a640e, 0x9638893}, {0x3ff7e0f, 0x97bc965}, {0x18bf931a, 0x6409498e}, {0x18cfaf1a, 0x640d8a30}, {0x18dfd91a, 0x640dcad3}, {0x18ef6921, 0x98060b76}, {0x18ffd921, 0x980e4c53}, {0x190f6928, 0xba068d46}, {0x191fd928, 0xba0ece39}, {0x192f692f, 0xdc070f1e}, {0x193fd92f, 0xdc0f4ff3}, {0x30000000, 0x0}, {0x30000000, 0x0}, {0x30000000, 0x0}, {0x30000000, 0x0}, {0x30000000, 0x0}, {0x30000000, 0x0}, {0x30000000, 0x0}},
    {{0x10200, 0x0}, {0x80002, 0x100808a}, {0xf0603, 0x200c12c}, {0x160405, 0x30141ce}, {0x19400006, 0x31000213}, {0x19502a06, 0x3100431d}, {0x11d2207, 0x421c3a0}, {0x19604606, 0x31048491}, {0x2e45809, 0x55a44f9}, {0xe91a0a, 0x61a85c8}, {0x19706206, 0x3104c5fb}, {0x19807e06, 0x31090740}, {0x2734e0c, 0x84b076e}, {0x19909a06, 0x31094886}, {0x3fa7c0e, 0x97b8899}, {0x37e6c0f, 0x96bc938}, {0x19a0b606, 0x310d8999}, {0x19b0d206, 0x310dca3c}, {0x19c00022, 0x98020adf}, {0x19d07022, 0x980a4b82}, {0x19e00029, 0xba028c64}, {0x19f07029, 0xba0acd57}, {0x1a000030, 0xdc030e4a}, {0x1a107030, 0xdc0b4f2e}, {0x30000000, 0x0}, {0x30000000, 0x0}, {0x30000000, 0x0}, {0x30000000, 0x0}, {0x30000000, 0x0}, {0x30000000, 0x0}, {0x30000000, 0x0}, {0x30000000, 0x0}},
    {{0x410a00, 0x80000}, {0x480802, 0x108808b}, {0x4f0e03, 0x208c12d}, {0x560c05, 0x30941cf}, {0x1941000d, 0x2000021e}, {0x19512a0d, 0x20004335}, {0x1dd3a07, 0x439c3a7}, {0x1961460d, 0x200484a8}, {0x3646809, 0x56a44ff}, {0x690a0a, 0x60a85c3}, {0x1971620d, 0x2004c60f}, {0x19817e0d, 0x20090755}, {0x3736e0c, 0x86b0778}, {0x1f73e0d, 0x83b480b}, {0x19919a0d, 0x2009489a}, {0x2be540f, 0x953c931}, {0x19a1b60d, 0x200d89a3}, {0x19b1d20d, 0x200dca46}, {0x19c10722, 0x98020ae9}, {0x19d17722, 0x980a4b8c}, {0x19e10729, 0xba028c73}, {0x19f17729, 0xba0acd66}, {0x1a010730, 0xdc030e59}, {0x1a117730, 0xdc0b4f3b}, {0x30000000, 0x0}, {0x30000000, 0x0}, {0x30000000, 0x0}, {0x30000000, 0x0}, {0x30000000, 0x0}, {0x30000000, 0x0}, {0x30000000, 0x0}, {0x30000000, 0x0}},
    {{0x811200, 0x100000}, {0x881002, 0x110808c}, {0x8f1603, 0x210c12e}, {0x961405, 0x31141d0}, {0x19420706, 0x3100022a}, {0x19523106, 0x3100434c}, {0x25d4a07, 0x449c3af}, {0x19624d06, 0x310484bf}, {0x3e47809, 0x57a4504}, {0x368680a, 0x66a85b9}, {0x19726906, 0x3104c623}, {0x32e640b, 0x762c6aa}, {0x19828506, 0x31090769}, {0x2b6540d, 0x85347eb}, {0x1992a106, 0x310948af}, {0x1fe3c0f, 0x93bc928}, {0x19a2bd06, 0x310d89ad}, {0x19b2d906, 0x310dca50}, {0x19c20e22, 0x98020af3}, {0x19d27e22, 0x980a4b96}, {0x19e20e29, 0xba028c82}, {0x19f27e29, 0xba0acd75}, {0x1a020e30, 0xdc030e68}, {0x1a127e30, 0xdc0b4f48}, {0x30000000, 0x0}, {0x30000000, 0x0}, {0x30000000, 0x0}, {0x30000000, 0x0}, {0x30000000, 0x0}, {0x30000000, 0x0}, {0x30000000, 0x0}, {0x30000000, 0x0}},
    {{0xc11a00, 0x180000}, {0xc81802, 0x118808e}, {0xcf1e03, 0x218c130}, {0xd61c05, 0x31941d2}, {0x1943070d, 0x20000235}, {0x1953310d, 0x20004363}, {0x39d7207, 0x471c3bd}, {0x19634d0d, 0x200484d7}, {0x650a09, 0x60a450b}, {0x2a8500a, 0x65285b0}, {0x1973690d, 0x2004c638}, {0xef1e0b, 0x71ac6bc}, {0x1983850d, 0x2009077d}, {0x137260d, 0x8234804}, {0x1993a10d, 0x200948c3}, {0x1be340f, 0x933c926}, {0x19a3bd0d, 0x200d89b7}, {0x19b3d90d, 0x200dca5a}, {0x19c31522, 0x98020afd}, {0x19d38522, 0x980a4ba0}, {0x19e31529, 0xba028c92}, {0x19f38529, 0xba0acd85}, {0x1a031530, 0xdc030e77}, {0x1a138530, 0xdc0b4f55}, {0x30000000, 0x0}, {0x30000000, 0x0}, {0x30000000, 0x0}, {0x30000000, 0x0}, {0x30000000, 0x0}, {0x30000000, 0x0}, {0x30000000, 0x0}, {0x30000000, 0x0}},
    {{0x1012200, 0x200000}, {0x1082002, 0x120808f}, {0x10f2603, 0x220c131}, {0x1162405, 0x32141d3}, {0x19440e06, 0x31000241}, {0x19540e14, 0x7500437a}, {0x5e0c07, 0x509c3c6}, {0x3a07008, 0x5720448}, {0x19642a14, 0x750084ee}, {0x1e8380a, 0x63a85a6}, {0x19744614, 0x7504c64c}, {0x2af560b, 0x752c6ce}, {0x19846214, 0x75050792}, {0x3f67c0d, 0x87b47f6}, {0x19947e14, 0x750948d8}, {0x13e240f, 0x923c921}, {0x19a49a14, 0x750989c2}, {0x19b4b614, 0x750dca65}, {0x19c41c22, 0x98020b07}, {0x19d48c22, 0x980a4bae}, {0x19e41c29, 0xba028ca1}, {0x19f48c29, 0xba0acd94}, {0x1a041c30, 0xdc030e87}, {0x1a148c30, 0xdc0b4f63}, {0x30000000, 0x0}, {0x30000000, 0x0}, {0x30000000, 0x0}, {0x30000000, 0x0}, {0x30000000, 0x0}, {0x30000000, 0x0}, {0x30000000, 0x0}, {0x30000000, 0x0}},
    {{0x1412a00, 0x280000}, {0x1482802, 0x1288091}, {0x14f2e03, 0x228c133}, {0x1562c05, 0x32941d5}, {0x19450e0d, 0x2000024d}, {0x19550e1b, 0x64004392}, {0x11e2407, 0x521c3ce}, {0x610a08, 0x50a0451}, {0x19652a1b, 0x64008505}, {0x228400a, 0x64285aa}, {0x1975461b, 0x6404c660}, {0x3ef7e0b, 0x77ac6d9}, {0x1985621b, 0x640507a6}, {0xb7160d, 0x81347ff}, {0x19957e1b, 0x640948ec}, {0x23e440f, 0x943c92c}, {0x19a59a1b, 0x640989cc}, {0x19b5b61b, 0x640dca6f}, {0x19c52322, 0x98020b12}, {0x19d59322, 0x980a4bbd}, {0x19e52329, 0xba028cb0}, {0x19f59329, 0xba0acda3}, {0x1a052330, 0xdc030e96}, {0x1a159330, 0xdc0b4f70}, {0x30000000, 0x0}, {0x30000000, 0x0}, {0x30000000, 0x0}, {0x30000000, 0x0}, {0x30000000, 0x0}, {0x30000000, 0x0}, {0x30000000, 0x0}, {0x30000000, 0x0}},
    {{0x1813200, 0x300000}, {0x1883002, 0x1308092}, {0x18f3603, 0x230c134}, {0x1963405, 0x33141d6}, {0x19461506, 0x31000258}, {0x21c4007, 0x441c37d}, {0x19561514, 0x750043a9}, {0x3206008, 0x5620443}, {0x19663114, 0x7500851c}, {0x2e8580a, 0x65a85b3}, {0x19764d14, 0x7504c675}, {0x232440c, 0x7430743}, {0x19866914, 0x750507bb}, {0x37060d, 0x80347fa}, {0x19968514, 0x75094900}, {0x2fe5c0f, 0x95bc933}, {0x19a6a114, 0x750989d6}, {0x19b6bd14, 0x750dca79}, {0x19c62a22, 0x98020b1c}, {0x19d69a22, 0x980a4bcc}, {0x19e62a29, 0xba028cbf}, {0x19f69a29, 0xba0acdb2}, {0x1a062a30, 0xdc030ea5}, {0x1a169a30, 0xdc0b4f7d}, {0x30000000, 0x0}, {0x30000000, 0x0}, {0x30000000, 0x0}, {0x30000000, 0x0}, {0x30000000, 0x0}, {0x30000000, 0x0}, {0x30000000, 0x0}, {0x30000000, 0x0}},
    {{0x1c13a00, 0x380000}, {0x1c83802, 0x1388094}, {0x1cf3e03, 0x238c136}, {0x1d63c05, 0x33941d8}, {0x1947150d, 0x20000264}, {0x5c0807, 0x409c369}, {0x1957151b, 0x640043c0}, {0x3e07808, 0x57a044a}, {0x1967311b, 0x64008533}, {0x3a8700a, 0x67285bb}, {0x19774d1b, 0x6404c689}, {0x1b1320c, 0x7330715}, {0x1987691b, 0x640507cf}, {0xf71e0d, 0x81b4802}, {0x1997851b, 0x64094915}, {0x3be740f, 0x973c93b}, {0x19a7a11b, 0x640989e0}, {0x19b7bd1b, 0x640dca83}, {0x19c73122, 0x98020b26}, {0x19d7a122, 0x980a4bdc}, {0x19e73129, 0xba028cce}, {0x19f7a129, 0xba0acdc1}, {0x1a073130, 0xdc030eb4}, {0x1a17a130, 0xdc0b4f8a}, {0x30000000, 0x0}, {0x30000000, 0x0}, {0x30000000, 0x0}, {0x30000000, 0x0}, {0x30000000, 0x0}, {0x30000000, 0x0}, {0x30000000, 0x0}, {0x30000000, 0x0}},
    {{0x2014200, 0x400000}, {0x2084002, 0x1408095}, {0x20f4603, 0x240c137}, {0x2164405, 0x34141d9}, {0x19481c06, 0x3100026f}, {0x29b5606, 0x4518355}, {0x19583806, 0x310443d7}, {0xa11208, 0x5120454}, {0x19685406, 0x3104854b}, {0x29020a, 0x60285c0}, {0x19787006, 0x3108c69e}, {0x710a0c, 0x70b0708}, {0x19888c06, 0x310907e3}, {0x2774e0d, 0x84b4811}, {0x1998a806, 0x310d4929}, {0x3f060f, 0x903c940}, {0x19a8c406, 0x310d89ea}, {0x19b8c414, 0x750dca8d}, {0x19c83822, 0x98060b30}, {0x19d8a822, 0x980e4beb}, {0x19e83829, 0xba068cde}, {0x19f8a829, 0xba0ecdd0}, {0x1a083830, 0xdc070ec3}, {0x1a18a830, 0xdc0f4f98}, {0x30000000, 0x0}, {0x30000000, 0x0}, {0x30000000, 0x0}, {0x30000000, 0x0}, {0x30000000, 0x0}, {0x30000000, 0x0}, {0x30000000, 0x0}, {0x30000000, 0x0}},
    {{0x2414a00, 0x480000}, {0x2484802, 0x1488096}, {0x24f4e03, 0x248c138}, {0x2564c05, 0x34941da}, {0x19491c0d, 0x2000027b}, {0x39a7406, 0x4718332}, {0x1959380d, 0x200443ee}, {0x1212208, 0x522045a}, {0x1969540d, 0x20048562}, {0xa9120a, 0x61285c5}, {0x1979700d, 0x2008c6b2}, {0x230400c, 0x74306f2}, {0x19898c0d, 0x200907f8}, {0x337660d, 0x8634819}, {0x1999a80d, 0x200d493d}, {0xbf160f, 0x913c945}, {0x19a9c40d, 0x200d89f5}, {0x19b9c41b, 0x640dca97}, {0x19c93f22, 0x98060b3a}, {0x19d9af22, 0x980e4bfa}, {0x19e93f29, 0xba068ced}, {0x19f9af29, 0xba0ecde0}, {0x1a093f30, 0xdc070ed1}, {0x1a19af30, 0xdc0f4fa5}, {0x30000000, 0x0}, {0x30000000, 0x0}, {0x30000000, 0x0}, {0x30000000, 0x0}, {0x30000000, 0x0}, {0x30000000, 0x0}, {0x30000000, 0x0}, {0x30000000, 0x0}},
    {{0x2815200, 0x500000}, {0x2885002, 0x1508098}, {0x28f5603, 0x250c13a}, {0x2965405, 0x35141dc}, {0x194a2306, 0x31000292}, {0x21a4406, 0x4418320}, {0x195a3f06, 0x31044406}, {0x1a13208, 0x5320460}, {0x196a5b06, 0x31048579}, {0x129220a, 0x62285ca}, {0x197a7706, 0x3108c6c6}, {0x1b0300c, 0x73306ec}, {0xf4180d, 0x81b4788}, {0x198a9306, 0x3109080c}, {0x2ba540e, 0x953888e}, {0x199aaf06, 0x310d4952}, {0x19aacb06, 0x310d89ff}, {0x19bacb14, 0x750dcaa2}, {0x19ca4622, 0x98060b44}, {0x19dab622, 0x980e4c09}, {0x19ea4629, 0xba068cfc}, {0x19fab629, 0xba0ecdef}, {0x1a0a4630, 0xdc070ede}, {0x1a1ab630, 0xdc0f4fb2}, {0x30000000, 0x0}, {0x30000000, 0x0}, {0x30000000, 0x0}, {0x30000000, 0x0}, {0x30000000, 0x0}, {0x30000000, 0x0}, {0x30000000, 0x0}, {0x30000000, 0x0}},
    {{0x2c15a00, 0x580000}, {0x2c85802, 0x1588099}, {0x2cf5e03, 0x258c13b}, {0x2d65c05, 0x35941dd}, {0x194b230d, 0x200002a9}, {0x15a2c06, 0x4298318}, {0x195b3f0d, 0x2004441d}, {0x2614a08, 0x54a0468}, {0x196b5b0d, 0x20048590}, {0x1a9320a, 0x63285cf}, {0x26b4e0a, 0x64a8629}, {0x197b770d, 0x2008c6db}, {0x1732e0c, 0x82b0764}, {0x198b930d, 0x20090820}, {0xbb160e, 0x91388a2}, {0x199baf0d, 0x200d4966}, {0x19abcb0d, 0x200d8a09}, {0x19bbcb1b, 0x640dcaac}, {0x19cb4d22, 0x98060b4f}, {0x19dbbd22, 0x980e4c18}, {0x19eb4d29, 0xba068d0b}, {0x19fbbd29, 0xba0ecdfe}, {0x1a0b4d30, 0xdc070eeb}, {0x1a1bbd30, 0xdc0f4fc0}, {0x30000000, 0x0}, {0x30000000, 0x0}, {0x30000000, 0x0}, {0x30000000, 0x0}, {0x30000000, 0x0}, {0x30000000, 0x0}, {0x30000000, 0x0}, {0x30000000, 0x0}},
    {{0x3016200, 0x600000}, {0x3086002, 0x160809b}, {0x30f6603, 0x260c13d}, {0x3166405, 0x36141df}, {0x194c0014, 0x750002c1}, {0x5a0c06, 0x409830c}, {0x5d0a07, 0x409c397}, {0x195c1c14, 0x75004434}, {0x1e43809, 0x53a44ec}, {0x196c3814, 0x750485a7}, {0xab160a, 0x6128617}, {0x197c5414, 0x7504c6ef}, {0x3b2740c, 0x7730752}, {0x198c7014, 0x75090835}, {0x17a2c0e, 0x92b8881}, {0x199c8c14, 0x75094970}, {0x19aca814, 0x750d8a13}, {0x19bcd214, 0x750dcab6}, {0x19cc5422, 0x98060b59}, {0x19dcc422, 0x980e4c27}, {0x19ec5429, 0xba068d1a}, {0x19fcc429, 0xba0ece0d}, {0x1a0c5430, 0xdc070ef8}, {0x1a1cc430, 0xdc0f4fcd}, {0x30000000, 0x0}, {0x30000000, 0x0}, {0x30000000, 0x0}, {0x30000000, 0x0}, {0x30000000, 0x0}, {0x30000000, 0x0}, {0x30000000, 0x0}, {0x30000000, 0x0}},
    {{0x3416a00, 0x680000}, {0x3486802, 0x168809c}, {0x34f6e03, 0x268c13e}, {0x3566c05, 0x36941e0}, {0x194d001b, 0x640002d8}, {0x3d97a06, 0x4798305}, {0x39c7007, 0x471c38f}, {0x195d1c1b, 0x6400444b}, {0x2a45009, 0x55244f6}, {0x196d381b, 0x640485be}, {0x22b460a, 0x6428626}, {0x197d541b, 0x6404c703}, {0x3726c0c, 0x76b0750}, {0x198d701b, 0x64090849}, {0x2fa5c0e, 0x95b8890}, {0x199d8c1b, 0x6409497a}, {0x19ada81b, 0x640d8a1d}, {0x19bdd21b, 0x640dcac0}, {0x19cd5b22, 0x98060b63}, {0x19ddcb22, 0x980e4c37}, {0x19ed5b29, 0xba068d29}, {0x19fdcb29, 0xba0ece1c}, {0x1a0d5b30, 0xdc070f06}, {0x1a1dcb30, 0xdc0f4fda}, {0x30000000, 0x0}, {0x30000000, 0x0}, {0x30000000, 0x0}, {0x30000000, 0x0}, {0x30000000, 0x0}, {0x30000000, 0x0}, {0x30000000, 0x0}, {0x30000000, 0x0}},
    {{0x3817200, 0x700000}, {0x3887002, 0x170809e}, {0x38f7603, 0x270c140}, {0x3967405, 0x37141e2}, {0x194e0714, 0x750002ef}, {0x3997206, 0x4718303}, {0x35c6807, 0x469c38c}, {0x195e2314, 0x75004462}, {0x3246009, 0x56244fc}, {0x196e3f14, 0x750485d2}, {0x2c000b, 0x702c63a}, {0x197e5b14, 0x7504c718}, {0x33060c, 0x8030757}, {0x198e7714, 0x7509085d}, {0x37a6c0e, 0x96b8895}, {0x199e9314, 0x75094985}, {0x19aeaf14, 0x750d8a27}, {0x19bed914, 0x750dcaca}, {0x19ce6222, 0x98060b6d}, {0x19ded222, 0x980e4c46}, {0x19ee6229, 0xba068d39}, {0x19fed229, 0xba0ece2b}, {0x1a0e6230, 0xdc070f13}, {0x1a1ed230, 0xdc0f4fe7}, {0x30000000, 0x0}, {0x30000000, 0x0}, {0x30000000, 0x0}, {0x30000000, 0x0}, {0x30000000, 0x0}, {0x30000000, 0x0}, {0x30000000, 0x0}, {0x30000000, 0x0}},
    {{0x3c17a00, 0x780000}, {0x3c87802, 0x178809f}, {0x3cf7e03, 0x278c141}, {0x3d67c05, 0x37941e3}, {0x2a404631, 0x46820271}, {0x194f071b, 0x64000306}, {0x3dc7807, 0x479c390}, {0x195f231b, 0x6400447a}, {0x3a47009, 0x5724502}, {0x196f3f1b, 0x640485e6}, {0x3ab760a, 0x6728635}, {0x197f5b1b, 0x6404c72c}, {0x133260c, 0x8230761}, {0x198f771b, 0x64090872}, {0x3b060e, 0x903889d}, {0x199f931b, 0x6409498f}, {0x19afaf1b, 0x640d8a32}, {0x19bfd91b, 0x640dcad4}, {0x19cf6922, 0x98060b77}, {0x19dfd922, 0x980e4c55}, {0x19ef6929, 0xba068d48}, {0x19ffd929, 0xba0ece3b}, {0x1a0f6930, 0xdc070f20}, {0x1a1fd930, 0xdc0f4ff5}, {0x30000000, 0x0}, {0x30000000, 0x0}, {0x30000000, 0x0}, {0x30000000, 0x0}, {0x30000000, 0x0}, {0x30000000, 0x0}, {0x30000000, 0x0}, {0x30000000, 0x0}}
}};
static_assert(NJOB + NCONV == 32, "");

__device__ __forceinline__ unsigned read_back(const void* p) {
    unsigned v = 0;
    asm volatile("ld.relaxed.gpu.global.u32 %0, [%1];" : "=r"(v) : "l"(p) : "memory");
    return v;
}
__device__ __forceinline__ void publish(unsigned* flag, unsigned seen, unsigned zero) {
    asm volatile("{\n.reg .pred p;\n.reg .u32 t;\nredux.sync.or.b32 t, %1, 0xffffffff;\nand.b32 t, t, %2;\nadd.u32 t, t, 1;\n"
                 "elect.sync _|p, 0xffffffff;\n@p red.relaxed.gpu.global.add.u32 [%0], t;\n}" :: "l"(flag), "r"(seen), "r"(zero) : "memory");
}

__device__ __forceinline__ void load_w(uint2 (&v)[32], const char* g) {
#pragma unroll
    for (int k = 0; k < 32; k++)
        asm volatile("ld.global.nc.L1::no_allocate.v2.b32 {%0,%1}, [%2];" : "=r"(v[k].x), "=r"(v[k].y) : "l"(g + k * (N_ * 4)));
}
__device__ __forceinline__ void store_w(const uint2 (&v)[32], unsigned (&o)[16], char* d) {
#pragma unroll
    for (int i = 0; i < 8; i++) {
        o[i] = pack4(v[4 * i].x, v[4 * i + 1].x, v[4 * i + 2].x, v[4 * i + 3].x);
        o[8 + i] = pack4(v[4 * i].y, v[4 * i + 1].y, v[4 * i + 2].y, v[4 * i + 3].y);
        if ((i & 3) == 3) {
            stg128(d + (i >> 2) * 128, make_uint4(o[i - 3], o[i - 2], o[i - 1], o[i]));
            stg128(d + (i >> 2) * 128 + 256, make_uint4(o[i + 5], o[i + 6], o[i + 7], o[i + 8]));
        }
    }
}
__device__ __forceinline__ unsigned col_sums(const unsigned (&o)[16]) {
    int cs[4];
#pragma unroll
    for (int i = 0; i < 4; i++)
        cs[i] = __dp4a((int)o[4 * i], 0x01010101, __dp4a((int)o[4 * i + 1], 0x01010101,
                __dp4a((int)o[4 * i + 2], 0x01010101, __dp4a((int)o[4 * i + 3], 0x01010101, 0))));
    return cs[0] + cs[1] + (cs[2] + cs[3]) * 65536;
}
__device__ __forceinline__ void wait_until(int due, unsigned t0) {
    for (int rem; (rem = due - (int)(clk() - t0)) > 0;) if (rem > CFG_SLEEP) __nanosleep(CFG_SLEEP / 4);
}

__device__ __forceinline__ uint32_t zero_term(const unsigned (&sv)[4], float zxf) {
    int lo = 0, hi = 0;
#pragma unroll
    for (int h = 0; h < 4; h++) {
        const int l = (int)(short)(sv[h] & 0xFFFF);
        lo += l; hi += ((int)(sv[h] - (unsigned)l)) >> 16;
    }
    const float fl = __bfloat162float(__float2bfloat16_rn((float)lo)) * zxf, fh = __bfloat162float(__float2bfloat16_rn((float)hi)) * zxf;
    uint32_t z;
    asm("cvt.rn.bf16x2.f32 %0, %1, %2;" : "=r"(z) : "f"(fh), "f"(fl));
    return z;
}

__device__ __forceinline__ void load_x(Scratch* scr, uint32_t sb, int b, int lane) {
    const uint32_t bars = sb + SM_BAR;
    const int r = b & 15;
    const unsigned tgt = (*(volatile unsigned*)&scr->epoch[b] + 1) * 4;
    const unsigned* f = scr->flag + r * FS + (lane & 15);
    unsigned todo = 0xFFFF, v = ld_flag(f);
    asm volatile("barrier.cluster.wait.aligned;" ::: "memory");
#pragma unroll 1
    for (int it = 0; todo; it++) {
        unsigned m = __ballot_sync(~0u, (int)(v - tgt) >= 0) & todo;
        v = ld_flag(f);
        todo &= ~m;
        while (m) {
            const int sl = __ffs(m) - 1;
            m &= m - 1;
            if (elect_one()) {
                asm volatile("cp.async.bulk.shared::cluster.global.mbarrier::complete_tx::bytes [%0], [%1], %2, [%3];"
                             :: "r"(sb + SM_A + sl * 8192), "l"((const char*)scr->a8 + (r * 16 + sl) * 8192),
                                "r"(8192), "r"(bars + (B_FULL + sl) * 8) : "memory");
            }
        }
        if (it > (1 << 20)) __trap();
    }
}

__device__ __forceinline__ void load_x4(Scratch* scr, uint32_t sb, int b, int h, int lane) {
    const uint32_t bars = sb + SM_BAR;
    const unsigned tgt = (*(volatile unsigned*)&scr->epoch[b] + 1) * 4;
    const unsigned* f = scr->flag + (4 * h + (lane >> 4)) * FS + (lane & 15);
    asm volatile("barrier.cluster.wait.aligned;" ::: "memory");
#pragma unroll 1
    for (int it = 0, sl = 0; sl < 16; it++) {
        const unsigned v0 = ld_flag(f), v1 = ld_flag(f + 2 * FS);
        unsigned m = __ballot_sync(~0u, (int)(v0 - tgt) >= 0 && (int)(v1 - tgt) >= 0);
        m &= m >> 16;
#pragma unroll 1
        for (; m >> sl & 1; sl++) {
            if (sl >= 4) mbar_wait(bars + (B_GO + sl - 4) * 8);
            if (elect_one()) {
#pragma unroll
                for (int k = 0; k < 4; k++)
                    asm volatile("cp.async.bulk.shared::cluster.global.mbarrier::complete_tx::bytes [%0], [%1], %2, [%3];"
                                 :: "r"(sb + SM_A + ((sl & 3) * 4 + k) * 8192), "l"((const char*)scr->a8 + ((4 * h + k) * 16 + sl) * 8192),
                                    "r"(8192), "r"(bars + (B_FULL + (k >> 1) * 16 + sl) * 8) : "memory");
            }
        }
        if (it > (1 << 20)) __trap();
    }
}

__device__ __forceinline__ void store_out(const CUtensorMap* map, uint32_t sb, int b, int agent, int lane, int n, unsigned seq, int col, int dcol, int row, int drow) {
    const uint32_t bars = sb + SM_BAR;
    const uint32_t buf = sb + SM_OUT + agent * 4096, full = bars + (B_OFULL + agent) * 8;
#pragma unroll 1
    for (int t = 0; t < n; t++, seq >>= 4) {
        asm volatile("{\n.reg .pred p;\n.reg .u32 c;\nmov.u32 c, 0;\n"
                     "WAIT_LOOP:\n"
                     "mbarrier.try_wait.parity.shared::cta.b64 p, [%4], %5;\n"
                     "@p bra WAIT_DONE;\n"
                     "add.u32 c, c, 1;\nsetp.lt.u32 p, c, 0x100000;\n"
                     "@p bra WAIT_LOOP;\n"
                     "trap;\n"
                     "WAIT_DONE:\n"
                     "fence.proxy.async.shared::cta;\n"
                     "elect.sync _|p, 0xffffffff;\n"
                     "@p cp.async.bulk.tensor.2d.global.shared::cta.tile.bulk_group [%0, {%1, %2}], [%3];\n"
                     "cp.async.bulk.commit_group;\n}"
                     :: "l"(map), "r"(col + (seq & 7) * dcol), "r"(row + agent * 32 + (seq & 7) * drow), "r"(buf), "r"(full), "r"(t & 1) : "memory");
        asm volatile("cp.async.bulk.wait_group.read 0;" ::: "memory");
        if (elect_one()) mbar_arrive(bars + (B_OFREE + t * 4 + 4 + agent) * 8);
    }
}

template <int V> struct I { static constexpr int v = V; };
template <int MODE>
__device__ __forceinline__ void consume(Scratch* scr, const __nv_bfloat16* __restrict__ scale_w, const __nv_bfloat16* __restrict__ bias,
                                        const __nv_bfloat16* __restrict__ scale_x, uint32_t sb, int b, int warp, int lane) {
    constexpr bool SIDE = MODE != 0;
    constexpr int NR = NRING, NG = SIDE ? 48 : 56;
    const uint32_t bars = sb + SM_BAR;
    const int c = SIDE ? 7 : b >> 4;
    constexpr uint32_t SD = 0x400 >> 4;
    if ((sb & 0xFFFFFF) != 0x400) __trap();
    const int wg = warp >> 2;
    const unsigned short sxr = __ldg((const unsigned short*)scale_x);
    const uint32_t sx2 = (uint32_t)sxr * 0x10001u;
    const int c0 = (warp & 3) * 16 + (lane >> 2) * 2;
    uint32_t sw[4], bi[4];
#pragma unroll
    for (int i = 0; i < 4; i++) {
        const int col = col_of(c, i < 2 ? wg * 2 + i : i == 2 ? 4 + wg : 6) + c0;
        sw[i] = __ldg((const uint32_t*)(scale_w + col));
        bi[i] = __ldg((const uint32_t*)(bias + col));
    }
    const uint32_t st0 = sb + SM_OUT + (lane & 3) * 256 + (((c0 >> 3) ^ ((lane & 3) * 2)) << 4) + (c0 & 7) * 2;
    constexpr uint32_t DX0 = (SD + (SM_A >> 4)) | (1 << 16), DW0 = (SD + (SM_RING >> 4)) | (8 << 16);
    asm volatile("barrier.cluster.wait.aligned;" ::: "memory");
    int a0[64], a1[64];
    constexpr int MUL = SIDE ? 4 : 2, NONE = 64 * MUL, BIAS = NR + 64 - NG;
    const uint32_t go = mapa(bars + B_GO * 8, lane & (SIDE ? 1 : 15)) - (64 - NG) * MUL;
    const int key = SIDE ? (lane < 2 ? lane * 4 : 1) : (lane < 16 ? (lane >> 2) * 2 : 1);
    int pend = NONE;
    uint32_t bb = bars + (B_FULL + wg * 16) * 8;
#define RELEASE() { if ((pend & (NONE + 8 - MUL)) == key) mbar_arrive_cluster(go + (pend & ~7)); }
    struct Par { uint32_t a, b, c, d; };
    auto load_par = [&](int blk, uint32_t swv, uint32_t biv) {
        mbar_wait_cluster(bars + (B_PAR + blk) * 8);
        const uint32_t zc = lds32(sb + SM_PAR + (blk * 64 + c0) * 2);
        const float sxf = __uint_as_float(sx2 << 16);
        const float s0 = sxf * __uint_as_float(swv << 16), s1 = sxf * __uint_as_float(swv & 0xFFFF0000u);
        Par P = {__float_as_uint(s0), __float_as_uint(s1), __float_as_uint(fmaf(-__uint_as_float(zc << 16), s0, __uint_as_float(biv << 16))),
                 __float_as_uint(fmaf(-__uint_as_float(zc & 0xFFFF0000u), s1, __uint_as_float(biv & 0xFFFF0000u)))};
        asm volatile("" : "+r"(P.a), "+r"(P.b), "+r"(P.c), "+r"(P.d));
        return P;
    };
    auto drain = [&](int (&a)[64], auto Q, int t, const Par& P) {
#pragma unroll
        for (int q = Q.v; q < Q.v + 2; q++) {
#pragma unroll
            for (int j = 0; j < 8; j++) {
                const int o = q * 16 + (j >> 1) * 4 + (j & 1);
                asm("cvt.rn.f32.s32 %0, %0;\n\tcvt.rn.f32.s32 %1, %1;\n\tfma.rn.f32 %0, %0, %2, %4;\n\tfma.rn.f32 %1, %1, %3, %5;\n\t"
                    "cvt.rn.bf16x2.f32 %0, %1, %0;" : "+r"(a[o]), "+r"(a[o + 2]) : "r"(P.a), "r"(P.b), "r"(P.c), "r"(P.d));
            }
            mbar_wait(bars + (B_OFREE + t * 4 + q) * 8);
#pragma unroll
            for (int j = 0; j < 8; j++) sts32((st0 ^ ((j & 1) * 16)) + q * 4096 + (j >> 1) * 1024 + (j & 1) * 128, a[q * 16 + (j >> 1) * 4 + (j & 1)]);
            __syncwarp();
            if (lane == 0) mbar_arrive(bars + (B_OFULL + q) * 8);
        }
    };
    wg_fence();
    if (MODE == 2) {
#pragma unroll 1
        for (int s = 0; s < 16; s++) {
            mbar_wait2(bars + (B_FULL + 48 + (s >> 2) * 2) * 8, bb + s * 8);
            mma_rows2(a0, a1, DW0 + s * 256, DX0 + ((s & 3) * 4 + 2 * wg) * 512, s);
            wg_wait<1>();
            if (s && lane == 0) mbar_arrive(bars + (B_GO + s - 1) * 8);
        }
        const Par P = load_par(6, sw[3], bi[3]);
        wg_wait<0>();
        drain(a0, I<0>(), wg, P); drain(a0, I<2>(), wg, P);
        drain(a1, I<0>(), 2 + wg, P); drain(a1, I<2>(), 2 + wg, P);
    } else {
    {
        uint32_t tbl = wg ? STEPS1 : STEPS0;
        uint32_t ba = bars + B_FULL * 8;
        int u = MUL * (wg * D_ + BIAS);
        uint32_t dw = DW0 + wg * D_ * 512;
        static_assert(D_ < NR, "");
        mbar_wait2(ba, bb);
#pragma unroll 1
        for (uint32_t dx = DX0;;) {
            mma_unit2(a0, a1, dw, dx, dx - DX0);
            dx += 512; ba += 8; bb += 8;
            const bool ready = mbar_test2(ba, bb);
            wg_wait<1>();
            RELEASE()
            pend = u;
            if (dx == DX0 + 16 * 512) break;
            u += MUL + (tbl & 1) * MUL;
            dw += 512 + (tbl & 1) * 512;
            if (dw >= DW0 + NR * 512) dw -= NR * 512;
            tbl >>= 1;
            if (!ready && !mbar_test2(ba, bb)) {
                wg_wait<0>();
                RELEASE()
                pend = NONE;
                mbar_wait2(ba, bb);
            }
        }
    }
    Par P0 = load_par(2 * wg, sw[0], bi[0]);
    const Par P1 = load_par(2 * wg + 1, sw[1], bi[1]);
    wg_wait<0>();
    RELEASE()
#pragma unroll 1
    for (int ph = 0; ph < 3; ph++) {
        if (ph + wg == 1) drain(a1, I<2>(), 3 - 2 * wg, P1);
        drain(a0, I<0>(), wg ? 4 * ph + 1 : 3 * ph, P0);
        const int u0 = 32 + ph * 16 + wg * 8;
        uint32_t dw = DW0 + (ph ? 48 % NR : wg ? 40 % NR : 32 % NR) * 512;
        bb = bars + (B_FULL + u0) * 8;
        const bool first = mbar_test(bb);
        drain(a0, I<2>(), ph ? 2 * ph + 2 + wg : 2 * wg, P0);
        if (SIDE ? ph == 1 : ph + wg == 2) break;
#define RELEASE2() { if ((pend & (NONE + 8 - 2 * MUL)) == (key & ~MUL)) mbar_arrive_cluster(go + (pend & ~7)); }
        static_assert(NR % 2 == 0, "");
        pend = NONE;
        if (!first) mbar_wait(bb);
        wg_fence();
#pragma unroll 1
        for (int n = 0;; n += 2) {
            RELEASE2()
            const bool ready = mma_pair(a0, dw, DX0 + n * 1024, n, bb + n * 8 + 16);
            wg_wait<1>();
            pend = n ? MUL * (u0 + BIAS + n - 2) : NONE;
            if (n == 6) break;
            dw += 1024;
            if (dw == DW0 + NR * 512) dw = DW0;
            if (!ready) {
                RELEASE2()
                pend = NONE;
                mbar_wait(bb + n * 8 + 16);
            }
        }
        RELEASE2()
        pend = MUL * (u0 + BIAS + 6);
        if (ph == 0) drain(a1, I<0>(), 2 + 2 * wg, P1);
        P0 = load_par(4 + 2 * ph + wg, ph ? sw[3] : sw[2], ph ? bi[3] : bi[2]);
        wg_wait<0>();
        RELEASE2()
    }
    }
    if (threadIdx.x == 128) asm volatile("red.relaxed.gpu.global.add.u32 [%0], 1;" :: "l"(scr->epoch + b) : "memory");
}

__global__ void __cluster_dims__(CS, 1, 1) __launch_bounds__(512, 1)
w8a8_kernel(const char* __restrict__ qx, const char* __restrict__ qw, Scratch* scr, const JobTable* __restrict__ jobs, const __nv_bfloat16* __restrict__ scale_w,
            const __nv_bfloat16* __restrict__ bias, const __nv_bfloat16* __restrict__ scale_x, const int* __restrict__ zero_x,
            const __grid_constant__ CUtensorMap map) {
    extern __shared__ __align__(1024) unsigned char smem_raw[];
    const uint32_t sb = (uint32_t)__cvta_generic_to_shared(smem_raw);
    const uint32_t bars = sb + SM_BAR;
    const int warp = __shfl_sync(~0u, threadIdx.x >> 5, 0), lane = threadIdx.x & 31;
    const int b = blockIdx.x, r = b & 15, c = b >> 4;
    const unsigned t0 = clk() + CFG_PF0;
    if (warp < CFG_NINIT) {
#pragma unroll 1
        for (int w = warp; w < 8; w += CFG_NINIT) {
            if (elect_one()) {
                const uint32_t cnt = w < B_GO / 16 ? 1 : 4 * CS + 1;
#pragma unroll
                for (int i = 0; i < 16; i++) mbar_init(bars + (w * 16 + i) * 8, cnt);
            }
            __syncwarp();
            const int i = w * 16 + lane;
            if (lane < 16 && i < B_OFREE + NOUT) mbar_expect_tx(bars + i * 8, i >= B_AFREE ? 0 : i >= B_PAR ? 128 : w == 1 ? 8192 : 16384);
            if (w == B_GO / 16 && 4 * lane + (r >> 2) < NRING)
                asm volatile("mbarrier.arrive.shared::cta.b64 _, [%0], %1;" :: "r"(bars + i * 8), "r"(4 * CS) : "memory");
        }
        if (warp == (B_SUM / 16) % CFG_NINIT) {
            if (elect_one()) {
#pragma unroll
                for (int k = 0; k < NOUT; k++) mbar_init(bars + (B_OFULL + k) * 8, 4);
                mbar_init(bars + B_SUM * 8, r < 8 ? 1 : 3);
                mbar_expect_tx(bars + B_SUM * 8, r < 8 ? 32 * 64 : 30 * 64);
            }
        }
        asm volatile("fence.mbarrier_init.release.cluster;" ::: "memory");
    } else if (warp == 7) {
        asm volatile("st.shared.v2.b32 [%0], {%1, %1};" :: "r"(sb + SM_SUM + lane * 8), "r"(0) : "memory");
        asm volatile("fence.release.sync_restrict::shared::cta.cluster;" ::: "memory");
    } else if (warp == 9) {
        asm volatile("griddepcontrol.launch_dependents;");
        if (elect_one()) asm volatile("prefetch.tensormap [%0];" :: "l"(&map) : "memory");
    } else if (warp >= 14) {
        const char* pf = qx + (r * 128 + ((threadIdx.x >> 1) & 31)) * (K_ * 4) + (lane & 1) * 128;
        if (c >= 5) asm volatile("prefetch.global.L2 [%0];" :: "l"(pf + (c - 5) * (32 * K_ * 4)) : "memory");
        asm volatile("prefetch.global.L2 [%0];" :: "l"(pf + ((c + 2) & 3) * (32 * K_ * 4) + ((c + 2) >> 2) * 256) : "memory");
    }
    asm volatile("barrier.cluster.arrive.relaxed.aligned;" ::: "memory");

    if (warp >= 8) {
        asm volatile("setmaxnreg.dec.sync.aligned.u32 88;");
        int agent = -1;
        if (warp >= 16 - NCONV) {
            const int cw = warp - (16 - NCONV);
            const unsigned zero = blockIdx.y;
            const char* const gx = qx + (lane >> 4) * (K_ * 4) + (lane & 15) * 16;
            const char* const gw = qw + lane * 8;
            const int wrB = ((lane >> 3) * 32 + (lane & 7)) * 16;
            uint2 tab;
            asm volatile("ld.global.nc.v2.u32 {%0, %1}, [%2];" : "=r"(tab.x), "=r"(tab.y) : "l"(&jobs->e[b][lane]));
            bool synced = false;
#pragma unroll 1
            for (int p = cw || c >= 5 ? cw : NCONV;; p = p < CFG_PZ ? p + NCONV : p < CFG_PZ + 3 ? 31 : p + 3) {
                uint2 j;
                if (p < 4) {
                    const int g = 7 * p + c - 5;
                    j.x = ((r * 128 + (g & 3) * 32) * 16 + (g >> 2)) | (r * 64 + g) << 16;
                    j.y = max((p - 1) * (CFG_P0 / 4) + b * (CFG_P0 * 4 / NCTA) / 16, 0) | (r * FS + (g >> 2)) << 14 | p << 24;
                } else { j.x = __shfl_sync(~0u, tab.x, p); j.y = __shfl_sync(~0u, tab.y, p); }
                if (j.x >= 3u << 28) break;
                const int kind = j.x >> 28, sig = (j.y >> 14) & 0x3FF;
                char* tile = (char*)scr + ((j.x >> 16) & 0xFFF) * 2048;
                const char* g = (kind ? gw : gx) + (j.x & 0xFFFF) * 256;
                wait_until((j.y & 0x3FFF) * 4, t0);
                if (kind == 0) {
                    uint4 v[16];
#pragma unroll
                    for (int i = 0; i < 16; i++)
                        asm volatile("ld.global.nc.L1::no_allocate.v4.b32 {%0,%1,%2,%3}, [%4];"
                                     : "=r"(v[i].x), "=r"(v[i].y), "=r"(v[i].z), "=r"(v[i].w) : "l"(g + i * (2 * K_ * 4)));
#pragma unroll
                    for (int i = 0; i < 16; i++)
                        asm volatile("st.global.b32 [%0], %1;" :: "l"(tile + ((lane * 4) ^ ((i & 3) * 16)) + i * 128),
                                     "r"(pack4(v[i].x, v[i].y, v[i].z, v[i].w)) : "memory");
                    asm volatile("fence.proxy.async.global;" ::: "memory");
                    __syncwarp();
                    publish(scr->flag + sig, read_back(tile + lane * 64), zero);
                } else {
                    uint2 v[32];
                    unsigned o[16];
                    load_w(v, g);
                    if (!synced) asm volatile("barrier.cluster.wait.aligned;" ::: "memory");
                    synced = true;
                    store_w(v, o, tile + wrB);
                    asm volatile("{\n.reg .pred p;\nsetp.eq.u32 p, %1, 0;\nfence.proxy.async.global;\nbar.warp.sync 0xffffffff;\n"
                                 "@p mbarrier.arrive.shared::cta.b64 _, [%0];\n}" :: "r"(bars + (B_GO + (sig & 15)) * 8), "r"(lane | (kind & 2)) : "memory");
                    const unsigned csv = col_sums(o);
                    if (kind == 1) {
                        const int own = (j.y >> (24 + (lane >> 4) * 4)) & 15;
                        const uint32_t so = SM_SUM + (sig & 48) * 4 + (lane & 15) * 4;
                        if (own != r) {
                            const uint32_t ro = mapa(sb, own);
                            asm volatile("red.async.relaxed.cluster.shared::cluster.mbarrier::complete_tx::bytes.add.u32 [%0], %1, [%2];"
                                         :: "r"(ro + so), "r"(csv), "r"(ro + SM_BAR + B_SUM * 8) : "memory");
                        } else asm volatile("red.relaxed.cluster.shared::cta.add.u32 [%0], %1;" :: "r"(sb + so), "r"(csv) : "memory");
                        __syncwarp();
                        if (own == r && (lane & 15) == 0) mbar_arrive(bars + B_SUM * 8);
                    } else {
                        unsigned* csp = scr->cs + (j.y >> 24) * 32 + lane;
                        asm volatile("st.global.u32 [%0], %1;" :: "l"(csp), "r"(csv) : "memory");
                        publish(scr->flag + sig, read_back(tile + lane * 64) | read_back(csp), zero);
                    }
                }
                __syncwarp();
            }
            if (!synced) asm volatile("barrier.cluster.wait.aligned;" ::: "memory");
            agent = (cw + 6 * NCONV - CFG_PZ) % NCONV + 1;
            if (agent > 3) agent = -1;
        } else if (warp == 9) {
            asm volatile("barrier.cluster.wait.aligned;" ::: "memory");
        } else {
            load_x(scr, sb, b, lane);
            agent = 0;
        }
        const char* src = (const char*)scr->b8 + (c * 224 + r) * 2048;
        const int zxi = __ldg(zero_x);
#pragma unroll 1
        for (int i = 0, slot = r >> 2, end = 8;; end = NG / 4) {
#pragma unroll 1
            for (; warp == 9 && i < end; i++) {
                asm volatile("{\n.reg .pred p;\nWAIT_LOOP:\nmbarrier.try_wait.parity.shared::cta.b64 p, [%4], 0;\n@!p bra WAIT_LOOP;\n"
                             "elect.sync _|p, 0xffffffff;\n"
                             "@p cp.async.bulk.shared::cluster.global.mbarrier::complete_tx::bytes.multicast::cluster [%0], [%1], 2048, [%2], %3;\n}"
                             :: "r"(sb + SM_RING + slot * 8192 + (r & 3) * 2048), "l"(src + i * 32768),
                                "r"(bars + (B_FULL + bar_of(4 * i + (r >> 2))) * 8), "h"((uint16_t)0xFFFF), "r"(bars + (B_GO + i) * 8) : "memory");
                slot += slot >= NRING - 4 ? 4 - NRING : 4;
            }
            if (end != 8) break;
            if (warp == (r < 8 ? 9 : r < 10 ? 8 : r < 14 ? 16 - NCONV + (CFG_PZ + 3) % NCONV : 0)) {
                const float zxf = __bfloat162float(__float2bfloat16_rn((float)zxi));
                const int grp = sum_group(r);
                mbar_wait_cluster(bars + B_SUM * 8);
                unsigned sv[4];
#pragma unroll
                for (int h = 0; h < 4; h++) sv[h] = lds32(sb + SM_SUM + h * 64 + (lane & 15) * 4);
                const uint32_t z = zero_term(sv, zxf);
#pragma unroll 2
                for (int k = 0; k < 8; k++) {
                    const uint32_t rb = mapa(sb, k * 2 + (lane >> 4));
                    st_async32(rb + SM_PAR + grp * 64 + (lane & 15) * 4, z, rb + SM_BAR + (B_PAR + (grp >> 1)) * 8);
                }
            }
        }
        __syncwarp();
        if (agent >= 0) store_out(&map, sb, b, agent, lane, 7, agent < 2 ? 0x6534120 : 0x6541230, c * 64, 7 * 64, r * 128, 0);
    } else {
        asm volatile("setmaxnreg.inc.sync.aligned.u32 168;");
        consume<0>(scr, scale_w, bias, scale_x, sb, b, warp, lane);
    }
}

__global__ void __cluster_dims__(2, 1, 1) __launch_bounds__(512, 1)
w8a8_side(const char* __restrict__ qw, Scratch* scr, const __nv_bfloat16* __restrict__ scale_w, const __nv_bfloat16* __restrict__ bias,
          const __nv_bfloat16* __restrict__ scale_x, const int* __restrict__ zero_x, const __grid_constant__ CUtensorMap map) {
    extern __shared__ __align__(1024) unsigned char smem_raw[];
    const uint32_t sb = (uint32_t)__cvta_generic_to_shared(smem_raw);
    const uint32_t bars = sb + SM_BAR;
    const int warp = __shfl_sync(~0u, threadIdx.x >> 5, 0), lane = threadIdx.x & 31;
    const int b = NCTA + blockIdx.x, rank = b & 1;
    const bool helper = blockIdx.x >= 16;
    constexpr int NR = NRING;
    const unsigned t0 = clk();
    if (warp < 3) {
#pragma unroll 1
        for (int w = warp; w < B_OFULL / 16; w += 3) {
            if (elect_one()) {
                const uint32_t cnt = w < B_GO / 16 ? 1 : !helper ? 9 : w == B_GO / 16 ? 8 : 1;
#pragma unroll
                for (int i = 0; i < 16; i++) mbar_init(bars + (w * 16 + i) * 8, cnt);
            }
            __syncwarp();
            const int i = w * 16 + lane;
            if (lane < 16 && i < B_PAR) mbar_expect_tx(bars + i * 8, w == 1 && !helper ? 8192 : 16384);
            if (lane < 16 && i >= B_OFREE && i < B_OFREE + NOUT) mbar_arrive(bars + i * 8);
            if (w == B_GO / 16 && 2 * lane + rank < NR && !helper)
                asm volatile("mbarrier.arrive.shared::cta.b64 _, [%0], %1;" :: "r"(bars + i * 8), "r"(8) : "memory");
        }
        asm volatile("fence.mbarrier_init.release.cluster;" ::: "memory");
    } else if (warp == 3) {
        if (elect_one()) {
#pragma unroll
            for (int i = 0; i < NOUT; i++) mbar_init(bars + (B_OFULL + i) * 8, 4);
            asm volatile("fence.mbarrier_init.release.cluster;" ::: "memory");
        }
        __syncwarp();
    } else if (warp == 11 && elect_one()) asm volatile("prefetch.tensormap [%0];" :: "l"(&map) : "memory");
    asm volatile("barrier.cluster.arrive.relaxed.aligned;" ::: "memory");

    if (warp >= 8) {
        asm volatile("setmaxnreg.dec.sync.aligned.u32 88;");
        int agent = -1;
        if (warp == 10 || warp >= 12) {
#pragma unroll 1
            for (int i = (0x032401 >> (4 * (warp - 10))) & 7; i < (helper ? 8 : 12 - CFG_NOC / 4); i += 5) {
                const int G = (helper ? 192 - 16 + i * 4 : CFG_NOC * 4 + i * 16) + blockIdx.x, u = G >> 2, f = bar_of(u);
                const int blk = u < 32 ? (f >> 4) * 2 + (G & 1) : u >> 3, step = u < 32 ? (f & 15) * 2 + (G >> 1 & 1) : G & 31;
                char* const tile = (char*)scr->b8 + (7 * 224 + G) * 2048;
                unsigned* const csp = scr->cs + (step * 7 + blk) * 32 + lane;
                uint2 v[32];
                unsigned o[16];
                wait_until(helper ? i * CFG_YH + CFG_YH0 : (G - CFG_NOC * 4) * (CFG_YP / 16) + CFG_Y0, t0);
                load_w(v, qw + step * (32 * N_ * 4) + (49 + blk) * 256 + lane * 8);
                store_w(v, o, tile + ((lane >> 3) * 32 + (lane & 7)) * 16);
                asm volatile("st.global.u32 [%0], %1;" :: "l"(csp), "r"(col_sums(o)) : "memory");
                asm volatile("fence.proxy.async.global;" ::: "memory");
                __syncwarp();
                publish(scr->flag + CS * FS + u, read_back(tile + lane * 64) | read_back(csp), blockIdx.y);
            }
        }
        if (warp == 8) {
            if (helper) load_x4(scr, sb, b, blockIdx.x - 16, lane);
            else load_x(scr, sb, b, lane);
            agent = 0;
        } else if (warp == 11) {
            const unsigned tgt = (*(volatile unsigned*)&scr->epoch[b] + 1) * 4;
            const unsigned* f = scr->flag + CS * FS + lane;
            unsigned todo0 = helper ? 0 : ~0u, todo1 = helper ? 0xFF0000 : 0xFFFF, v0 = ld_flag(f), v1 = ld_flag(f + 32);
            bool par = lane >= 2;
            asm volatile("barrier.cluster.wait.aligned;" ::: "memory");
#pragma unroll 1
            for (int it = 0; todo0 | todo1; it++) {
                const unsigned m0 = __ballot_sync(~0u, (int)(v0 - tgt) >= 0) & todo0, m1 = __ballot_sync(~0u, (int)(v1 - tgt) >= 0) & todo1;
                v0 = ld_flag(f); v1 = ld_flag(f + 32);
                todo0 &= ~m0; todo1 &= ~m1;
                if ((lane & 1) == rank) {
                    if (m0 >> lane & 1) mbar_arrive(bars + (B_GO + (lane >> 1)) * 8);
                    if (m1 >> lane & 1) mbar_arrive(bars + (B_GO + 16 + (lane >> 1)) * 8);
                }
                if (!par && !(lane ? todo1 : todo0)) { par = true; mbar_arrive(bars + (B_AFREE + lane) * 8); }
                if (it > (1 << 20)) __trap();
            }
        } else if (warp == 9) {
            asm volatile("barrier.cluster.wait.aligned;" ::: "memory");
            const char* src = (const char*)scr->b8 + (7 * NG + rank) * 8192;
#pragma unroll 1
            for (int i = helper ? 24 : 0, slot = rank; i < (helper ? 28 : 24); i++) {
                asm volatile("{\n.reg .pred p;\nWAIT_LOOP:\nmbarrier.try_wait.parity.shared::cta.b64 p, [%4], 0;\n@!p bra WAIT_LOOP;\n"
                             "elect.sync _|p, 0xffffffff;\n"
                             "@p cp.async.bulk.shared::cluster.global.mbarrier::complete_tx::bytes.multicast::cluster [%0], [%1], 8192, [%2], %3;\n}"
                             :: "r"(sb + SM_RING + slot * 8192), "l"(src + i * 16384),
                                "r"(bars + (B_FULL + bar_of(2 * i + rank)) * 8), "h"((uint16_t)3), "r"(bars + (B_GO + i) * 8) : "memory");
                slot += slot >= NR - 2 ? 2 - NR : 2;
            }
        } else if (warp == 12 || warp == 15) {
            const float zxf = __bfloat162float(__float2bfloat16_rn((float)__ldg(zero_x)));
            asm volatile("barrier.cluster.wait.aligned;" ::: "memory");
#pragma unroll 1
            for (int blk = helper ? 6 + (warp & 2) : warp & 2; blk < (helper ? 7 : 6); blk += 4) {
                const int w = min(blk * 32 + lane * 2, TN / 2 - 2);
                mbar_wait(bars + (B_AFREE + (blk >> 2)) * 8);
                uint2 v[32];
                unsigned s0[4], s1[4];
#pragma unroll
                for (int k = 0; k < 32; k++) v[k] = __ldcg((const uint2*)(scr->cs + k * (TN / 2) + w));
#pragma unroll
                for (int h = 0; h < 4; h++) {
                    s0[h] = s1[h] = 0;
#pragma unroll
                    for (int k = 0; k < 8; k++) { s0[h] += v[8 * h + k].x; s1[h] += v[8 * h + k].y; }
                }
                sts32(sb + SM_PAR + w * 4, zero_term(s0, zxf));
                sts32(sb + SM_PAR + w * 4 + 4, zero_term(s1, zxf));
                __syncwarp();
                if (lane < 2) mbar_arrive(bars + (B_PAR + blk + lane) * 8);
            }
        } else {
            asm volatile("barrier.cluster.wait.aligned;" ::: "memory");
            agent = warp == 10 ? 1 : warp - 11;
        }
        if (agent >= 0) {
            if (helper) store_out(&map, sb, b, agent, lane, 4, 0x3120, col_of(7, 6), 0, (blockIdx.x - 16) * 512, 128);
            else store_out(&map, sb, b, agent, lane, 6, agent < 2 ? 0x534120 : 0x541230, col_of(7, 0), 64, blockIdx.x * 128, 0);
        }
    } else {
        asm volatile("setmaxnreg.inc.sync.aligned.u32 168;");
        if (helper) consume<2>(scr, scale_w, bias, scale_x, sb, b, warp, lane);
        else consume<1>(scr, scale_w, bias, scale_x, sb, b, warp, lane);
    }
}

}

typedef CUresult (*EncodeFn)(CUtensorMap*, CUtensorMapDataType, cuuint32_t, void*, const cuuint64_t*, const cuuint64_t*,
                             const cuuint32_t*, const cuuint32_t*, CUtensorMapInterleave, CUtensorMapSwizzle,
                             CUtensorMapL2promotion, CUtensorMapFloatOOBfill);

namespace w8 {

constexpr int M_ = 2048, K_ = 1024, N_ = 3584;
constexpr int WA = 160, WB = 64;
constexpr int TN = 2 * WA + 2 * WB;
static_assert(TN == 448, "");
constexpr int X1 = 13;
constexpr int NSLOT = 7, SLOT = WA * 64;
constexpr int NSTG = 3, PFD = 700, NCONV = 5;
constexpr int NU = 48;
constexpr int UX = 32 + NSLOT;
constexpr int NJOB = 22;
constexpr int NCTA = 128;

constexpr int nA = 64, nWA = WA / 4, nWB = WB / 4;
constexpr int SEG1 = X1 * (nA + 2 * nWA);
constexpr int SEG2 = SEG1 + (16 - X1) * (nA + nWA);
constexpr int SEG3 = SEG2 + (16 - X1) * nWA;
constexpr int SEG4 = SEG3 + 16 * nWB;
constexpr int SEG5 = SEG4 + 16 * nWB;
static_assert(SEG5 == NJOB * NCTA, "");

constexpr int SM_A = 0;
constexpr int SM_RING = 131072;
constexpr int SM_STG = SM_RING + NSLOT * SLOT;
constexpr int SM_PAR = SM_STG + NSTG * 8192;
constexpr int SM_BAR = SM_PAR + 3 * TN * 2;
constexpr int B_FULLB = 0, B_FULLA = 48, B_GO = 64, B_PAR = 88, B_PSTEP = 92, B_AFREE = 100, B_NINIT = 102, B_FULLS = 102, B_END = 108;
constexpr int SM_TOTAL = SM_BAR + B_END * 8;
static_assert(SM_TOTAL <= 232448, "");

__device__ uint4 g_a8[M_ * K_ / 16];
__device__ uint4 g_b8[N_ * K_ / 16];
__device__ uint4 g_cs[16 * N_ * 2 / 16];
__device__ unsigned g_flag[16 * 16 + 8 * 64];
__device__ unsigned g_epoch[NCTA];
__device__ unsigned g_sink;
constexpr int SM_ALLOC = SM_TOTAL;

__device__ __forceinline__ void mbar_init(uint32_t bar, uint32_t cnt) {
    asm volatile("mbarrier.init.shared::cta.b64 [%0], %1;" :: "r"(bar), "r"(cnt) : "memory");
}
__device__ __forceinline__ void mbar_expect_tx(uint32_t bar, uint32_t bytes) {
    asm volatile("mbarrier.arrive.expect_tx.shared::cta.b64 _, [%0], %1;" :: "r"(bar), "r"(bytes) : "memory");
}
__device__ __forceinline__ void mbar_arrive(uint32_t bar) {
    asm volatile("mbarrier.arrive.shared::cta.b64 _, [%0];" :: "r"(bar) : "memory");
}
__device__ __forceinline__ void mbar_arrive_cluster(uint32_t bar) {
    asm volatile("mbarrier.arrive.shared::cluster.b64 _, [%0];" :: "r"(bar) : "memory");
}
__device__ __forceinline__ void mbar_wait(uint32_t bar, uint32_t parity = 0) {
    asm volatile("{\n.reg .pred p;\n.reg .u32 c;\n"
                 "mbarrier.try_wait.parity.shared::cta.b64 p, [%0], %1;\n"
                 "@p bra WAIT_DONE;\n"
                 "mov.u32 c, 0;\n"
                 "WAIT_LOOP:\n"
                 "mbarrier.try_wait.parity.shared::cta.b64 p, [%0], %1;\n"
                 "@p bra WAIT_DONE;\n"
                 "add.u32 c, c, 1;\nsetp.lt.u32 p, c, 0x100000;\n"
                 "@p bra WAIT_LOOP;\n"
                 "trap;\n"
                 "WAIT_DONE:\n}" :: "r"(bar), "r"(parity) : "memory");
}
__device__ __forceinline__ void mbar_wait2(uint32_t bar0, uint32_t bar1) {
    asm volatile("{\n.reg .pred p, q;\n.reg .u32 c;\nmov.u32 c, 0;\n"
                 "WAIT_LOOP:\n"
                 "mbarrier.try_wait.parity.shared::cta.b64 p, [%0], 0;\n"
                 "mbarrier.try_wait.parity.shared::cta.b64 q, [%1], 0;\n"
                 "and.pred p, p, q;\n"
                 "@p bra WAIT_DONE;\n"
                 "add.u32 c, c, 1;\nsetp.lt.u32 p, c, 0x100000;\n"
                 "@p bra WAIT_LOOP;\n"
                 "trap;\n"
                 "WAIT_DONE:\n}" :: "r"(bar0), "r"(bar1) : "memory");
}
__device__ __forceinline__ bool mbar_test(uint32_t bar) {
    uint32_t ok;
    asm volatile("{\n.reg .pred p;\nmbarrier.test_wait.parity.shared::cta.b64 p, [%1], 0;\nselp.u32 %0, 1, 0, p;\n}" : "=r"(ok) : "r"(bar) : "memory");
    return ok;
}
__device__ __forceinline__ bool mbar_test2(uint32_t bar0, uint32_t bar1) {
    uint32_t ok;
    asm volatile("{\n.reg .pred p, q;\nmbarrier.test_wait.parity.shared::cta.b64 p, [%1], 0;\n"
                 "mbarrier.test_wait.parity.shared::cta.b64 q, [%2], 0;\nand.pred p, p, q;\nselp.u32 %0, 1, 0, p;\n}"
                 : "=r"(ok) : "r"(bar0), "r"(bar1) : "memory");
    return ok;
}
__device__ __forceinline__ bool elect_one() {
    uint32_t ok;
    asm volatile("{\n.reg .pred p;\nelect.sync _|p, 0xffffffff;\nselp.u32 %0, 1, 0, p;\n}" : "=r"(ok));
    return ok;
}
__device__ __forceinline__ unsigned ld_acquire(const unsigned* p) {
    unsigned v;
    asm volatile("ld.acquire.gpu.global.u32 %0, [%1];" : "=r"(v) : "l"(p) : "memory");
    return v;
}
__device__ __forceinline__ unsigned ld_flag(const unsigned* p) {
    unsigned v;
    asm volatile("ld.relaxed.gpu.global.u32 %0, [%1];" : "=r"(v) : "l"(p) : "memory");
    return v;
}
__device__ __forceinline__ uint4 lds128(uint32_t a) {
    uint4 v;
    asm volatile("ld.shared.v4.b32 {%0,%1,%2,%3}, [%4];" : "=r"(v.x), "=r"(v.y), "=r"(v.z), "=r"(v.w) : "r"(a) : "memory");
    return v;
}
__device__ __forceinline__ void sts128(uint32_t a, uint4 v) {
    asm volatile("st.shared.v4.b32 [%0], {%1,%2,%3,%4};" :: "r"(a), "r"(v.x), "r"(v.y), "r"(v.z), "r"(v.w) : "memory");
}
__device__ __forceinline__ uint32_t lds32(uint32_t a) {
    uint32_t v;
    asm volatile("ld.shared.b32 %0, [%1];" : "=r"(v) : "r"(a) : "memory");
    return v;
}
__device__ __forceinline__ void sts32(uint32_t a, uint32_t v) {
    asm volatile("st.shared.b32 [%0], %1;" :: "r"(a), "r"(v) : "memory");
}
__device__ __forceinline__ void stg128(void* p, uint4 v) {
    asm volatile("st.global.v4.b32 [%0], {%1,%2,%3,%4};" :: "l"(p), "r"(v.x), "r"(v.y), "r"(v.z), "r"(v.w) : "memory");
}
__device__ __forceinline__ unsigned pack4(unsigned a, unsigned b, unsigned c, unsigned d) {
    unsigned lo, r;
    asm("cvt.pack.sat.s8.s32.b32 %0, %1, %2, 0;" : "=r"(lo) : "r"(d), "r"(c));
    asm("cvt.pack.sat.s8.s32.b32 %0, %1, %2, %3;" : "=r"(r) : "r"(b), "r"(a), "r"(lo));
    return r;
}
__device__ __forceinline__ void cpasync16(uint32_t dst, const void* src) {
    asm volatile("cp.async.cg.shared.global [%0], [%1], 16;" :: "r"(dst), "l"(src) : "memory");
}
__device__ __forceinline__ unsigned pf_l2(const void* p) {
    unsigned v;
    asm volatile("ld.global.cg.L2::128B.u32 %0, [%1];" : "=r"(v) : "l"(p) : "memory");
    return v;
}

constexpr uint32_t DESC_A_HI = 0x80000000u | (512 >> 4);
constexpr uint32_t DESC_B_HI = 128 >> 4;
template <int NR> __device__ __forceinline__ void wgmma_n160(int (&d)[NR], uint32_t alo, uint32_t blo, int scale_d) {
    asm volatile("{\n.reg .pred p;\n.reg .b64 da, db;\nsetp.ne.b32 p, %82, 0;\n"
        "mov.b64 da, {%80, %83};\nmov.b64 db, {%81, %84};\n"
        "wgmma.mma_async.sync.aligned.m64n160k32.s32.s8.s8 "
        "{%0, %1, %2, %3, %4, %5, %6, %7, %8, %9, %10, %11, %12, %13, %14, %15, "
        "%16, %17, %18, %19, %20, %21, %22, %23, %24, %25, %26, %27, %28, %29, %30, %31, "
        "%32, %33, %34, %35, %36, %37, %38, %39, %40, %41, %42, %43, %44, %45, %46, %47, "
        "%48, %49, %50, %51, %52, %53, %54, %55, %56, %57, %58, %59, %60, %61, %62, %63, "
        "%64, %65, %66, %67, %68, %69, %70, %71, %72, %73, %74, %75, %76, %77, %78, %79}, "
        "da, db, p;\n}\n"
        : "+r"(d[0]), "+r"(d[1]), "+r"(d[2]), "+r"(d[3]), "+r"(d[4]), "+r"(d[5]), "+r"(d[6]), "+r"(d[7]),
          "+r"(d[8]), "+r"(d[9]), "+r"(d[10]), "+r"(d[11]), "+r"(d[12]), "+r"(d[13]), "+r"(d[14]), "+r"(d[15]),
          "+r"(d[16]), "+r"(d[17]), "+r"(d[18]), "+r"(d[19]), "+r"(d[20]), "+r"(d[21]), "+r"(d[22]), "+r"(d[23]),
          "+r"(d[24]), "+r"(d[25]), "+r"(d[26]), "+r"(d[27]), "+r"(d[28]), "+r"(d[29]), "+r"(d[30]), "+r"(d[31]),
          "+r"(d[32]), "+r"(d[33]), "+r"(d[34]), "+r"(d[35]), "+r"(d[36]), "+r"(d[37]), "+r"(d[38]), "+r"(d[39]),
          "+r"(d[40]), "+r"(d[41]), "+r"(d[42]), "+r"(d[43]), "+r"(d[44]), "+r"(d[45]), "+r"(d[46]), "+r"(d[47]),
          "+r"(d[48]), "+r"(d[49]), "+r"(d[50]), "+r"(d[51]), "+r"(d[52]), "+r"(d[53]), "+r"(d[54]), "+r"(d[55]),
          "+r"(d[56]), "+r"(d[57]), "+r"(d[58]), "+r"(d[59]), "+r"(d[60]), "+r"(d[61]), "+r"(d[62]), "+r"(d[63]),
          "+r"(d[64]), "+r"(d[65]), "+r"(d[66]), "+r"(d[67]), "+r"(d[68]), "+r"(d[69]), "+r"(d[70]), "+r"(d[71]),
          "+r"(d[72]), "+r"(d[73]), "+r"(d[74]), "+r"(d[75]), "+r"(d[76]), "+r"(d[77]), "+r"(d[78]), "+r"(d[79])
        : "r"(alo), "r"(blo), "r"(scale_d), "r"(DESC_A_HI), "r"(DESC_B_HI));
}
template <int NR> __device__ __forceinline__ void wgmma_t128(int (&d)[NR], uint32_t alo, uint32_t blo, int scale_d) {
    asm volatile("{\n.reg .pred p;\n.reg .b64 da, db;\nsetp.ne.b32 p, %66, 0;\n"
        "mov.b64 da, {%64, %67};\nmov.b64 db, {%65, %68};\n"
        "wgmma.mma_async.sync.aligned.m64n128k32.s32.s8.s8 "
        "{%0, %1, %2, %3, %4, %5, %6, %7, %8, %9, %10, %11, %12, %13, %14, %15, "
        "%16, %17, %18, %19, %20, %21, %22, %23, %24, %25, %26, %27, %28, %29, %30, %31, "
        "%32, %33, %34, %35, %36, %37, %38, %39, %40, %41, %42, %43, %44, %45, %46, %47, "
        "%48, %49, %50, %51, %52, %53, %54, %55, %56, %57, %58, %59, %60, %61, %62, %63}, "
        "da, db, p;\n}\n"
        : "+r"(d[0]), "+r"(d[1]), "+r"(d[2]), "+r"(d[3]), "+r"(d[4]), "+r"(d[5]), "+r"(d[6]), "+r"(d[7]),
          "+r"(d[8]), "+r"(d[9]), "+r"(d[10]), "+r"(d[11]), "+r"(d[12]), "+r"(d[13]), "+r"(d[14]), "+r"(d[15]),
          "+r"(d[16]), "+r"(d[17]), "+r"(d[18]), "+r"(d[19]), "+r"(d[20]), "+r"(d[21]), "+r"(d[22]), "+r"(d[23]),
          "+r"(d[24]), "+r"(d[25]), "+r"(d[26]), "+r"(d[27]), "+r"(d[28]), "+r"(d[29]), "+r"(d[30]), "+r"(d[31]),
          "+r"(d[32]), "+r"(d[33]), "+r"(d[34]), "+r"(d[35]), "+r"(d[36]), "+r"(d[37]), "+r"(d[38]), "+r"(d[39]),
          "+r"(d[40]), "+r"(d[41]), "+r"(d[42]), "+r"(d[43]), "+r"(d[44]), "+r"(d[45]), "+r"(d[46]), "+r"(d[47]),
          "+r"(d[48]), "+r"(d[49]), "+r"(d[50]), "+r"(d[51]), "+r"(d[52]), "+r"(d[53]), "+r"(d[54]), "+r"(d[55]),
          "+r"(d[56]), "+r"(d[57]), "+r"(d[58]), "+r"(d[59]), "+r"(d[60]), "+r"(d[61]), "+r"(d[62]), "+r"(d[63])
        : "r"(alo), "r"(blo), "r"(scale_d), "r"(DESC_B_HI), "r"(DESC_A_HI));
}

__device__ __forceinline__ void wg_fence() { asm volatile("wgmma.fence.sync.aligned;" ::: "memory"); }
__device__ __forceinline__ void wg_commit() { asm volatile("wgmma.commit_group.sync.aligned;" ::: "memory"); }
template <int N> __device__ __forceinline__ void wg_wait() { asm volatile("wgmma.wait_group.sync.aligned %0;" :: "n"(N) : "memory"); }

struct Job { int src; int dst; };
__host__ __device__ constexpr int unit_of(int piece, int slab) {
    return piece < 2 ? (slab < X1 ? 2 * slab + piece : (piece ? 16 : X1) + slab) : 32 + (piece - 2) * 8 + (slab >> 1);
}
__device__ __forceinline__ Job decode_job(int g) {
    int slab, idx, piece;
    if (g < SEG2) {
        int r;
        if (g < SEG1) { slab = g / (nA + 2 * nWA); r = g - slab * (nA + 2 * nWA); }
        else { g -= SEG1; slab = g / (nA + nWA); r = g - slab * (nA + nWA); slab += X1; }
        piece = r < nA ? -1 : (r < nA + nWA ? 0 : 1);
        idx = r < nA ? r : r - nA - piece * nWA;
    } else if (g < SEG3) {
        g -= SEG2; slab = g / nWA; idx = g - slab * nWA; slab += X1; piece = 1;
    } else {
        g -= SEG3; piece = 2 + (g >> 8); slab = (g >> 4) & 15; idx = g & 15;
        static_assert(nWB == 16, "");
    }
    Job j;
    if (piece < 0) {
        const int flag = (idx >> 2) * 16 + slab;
        j.src = idx * 32 + (slab << 12);
        j.dst = (flag * 512 + (idx & 3) * 128) | (flag << 18);
    } else {
        const bool wide = piece < 2;
        const int w = wide ? WA : WB;
        const int nb = wide ? idx / (WA / 32) : idx / (WB / 32);
        const int J = idx - nb * (w / 32);
        const int cb = nb * TN + (wide ? piece * WA : 2 * WA - 2 * WB + piece * WB);
        j.src = cb + J * 32 + (slab << 12) + (wide ? 1 << 16 : 2 << 16);
        j.dst = (cb * (K_ / 16) + slab * w * 4 + J * 32) | ((256 + nb * 64 + unit_of(piece, slab)) << 18);
    }
    return j;
}
struct Coord { const CUtensorMap* m; int x, y, z; };
__device__ __forceinline__ Coord job_coord(const CUtensorMap* maps, int src) {
    const bool w = src >> 16;
    const int c0 = src & 0xFFF, slab = (src >> 12) & 15;
    return {maps + (w ? 1 : 0), w ? c0 : 0, w ? slab * 64 : slab * 2, w ? 0 : c0};
}
__device__ __forceinline__ void raw_load(const Coord& c, uint32_t dst, uint32_t bar) {
    mbar_expect_tx(bar, 8192);
    asm volatile("cp.async.bulk.tensor.3d.shared::cluster.global.tile.mbarrier::complete_tx::bytes [%0], [%1, {%2, %3, %4}], [%5];"
                 :: "r"(dst), "l"(c.m), "r"(c.x), "r"(c.y), "r"(c.z), "r"(bar) : "memory");
}
__device__ __forceinline__ void raw_prefetch(const Coord& c) {
    asm volatile("cp.async.bulk.prefetch.tensor.3d.L2.global.tile [%0, {%1, %2, %3}];"
                 :: "l"(c.m), "r"(c.x), "r"(c.y), "r"(c.z) : "memory");
}
__host__ __device__ constexpr unsigned unit_mask(int piece, int s0, int s1) {
    unsigned m = 0;
    for (int s = s0; s < s1; s++) m |= 1u << (unit_of(piece, s) & 31);
    return m;
}
__host__ __device__ constexpr int slot_of(int u) {
    return u < UX ? (u % NSLOT) * (SLOT / 2048) : u < UX + NSTG ? NSLOT * (SLOT / 2048) + (u - UX) * 4 : ((u - NSTG) % NSLOT) * (SLOT / 2048);
}
__host__ __device__ constexpr uint64_t slot_table(int piece) {
    uint64_t t = 0;
    if (piece < 2) for (int s = 0; s < 16; s++) t |= (uint64_t)(unit_of(piece, s) % NSLOT) << (4 * s);
    else for (int s = 0; s < 8; s++) t |= (uint64_t)slot_of(unit_of(piece, 2 * s)) << (8 * s);
    return t;
}
struct Maps { CUtensorMap m[3]; };

__device__ __forceinline__ uint32_t bf2_op_epi(int a, int b, uint32_t zc, uint32_t sx, uint32_t sw, uint32_t bi) {
    uint32_t v;
    float fa = __int2float_rn(a), fb = __int2float_rn(b);
    asm("cvt.rn.bf16x2.f32 %0, %1, %2;" : "=r"(v) : "f"(fb), "f"(fa));
    asm("sub.rn.bf16x2 %0, %0, %1;" : "+r"(v) : "r"(zc));
    asm("mul.rn.bf16x2 %0, %0, %1;" : "+r"(v) : "r"(sx));
    asm("mul.rn.bf16x2 %0, %0, %1;" : "+r"(v) : "r"(sw));
    asm("add.rn.bf16x2 %0, %0, %1;" : "+r"(v) : "r"(bi));
    return v;
}

struct Par { uint4 zc, sw, bi; };
__device__ __forceinline__ Par ld_par(uint32_t p) { return {lds128(p), lds128(p + TN * 2), lds128(p + TN * 4)}; }
__device__ __forceinline__ void epi_row(const int (&a)[WA / 2], int o, const Par& p, uint32_t sx2, char* out) {
    uint4 r;
    r.x = bf2_op_epi(a[o + 0], a[o + 4], p.zc.x, sx2, p.sw.x, p.bi.x);
    r.y = bf2_op_epi(a[o + 8], a[o + 12], p.zc.y, sx2, p.sw.y, p.bi.y);
    r.z = bf2_op_epi(a[o + 1], a[o + 5], p.zc.z, sx2, p.sw.z, p.bi.z);
    r.w = bf2_op_epi(a[o + 9], a[o + 13], p.zc.w, sx2, p.sw.w, p.bi.w);
    stg128(out, r);
}
template <int J, int JN>
__device__ __forceinline__ void epilogue(const int (&a)[WA / 2], Par& p, uint32_t par, uint32_t sx2, char* out) {
    epi_row(a, J * 16, p, sx2, out + J * 64);
    Par n = p;
    if (JN != J) n = ld_par(par + JN * 64);
    epi_row(a, J * 16 + 2, p, sx2, out + 8 * (N_ * 2) + J * 64);
    p = n;
}

__global__ void __cluster_dims__(2, 1, 1) __launch_bounds__(512, 1)
w8a8_kernel(const __grid_constant__ Maps maps, const char* __restrict__ qx, const char* __restrict__ qw, const __nv_bfloat16* __restrict__ scale_x, const int* __restrict__ zero_x,
            const __nv_bfloat16* __restrict__ scale_w, const __nv_bfloat16* __restrict__ bias,
            __nv_bfloat16* __restrict__ out) {
    extern __shared__ __align__(1024) unsigned char smem_raw[];
    const uint32_t sb = (uint32_t)__cvta_generic_to_shared(smem_raw);
    const uint32_t bars = sb + SM_BAR;
    const int warp = __shfl_sync(~0u, threadIdx.x >> 5, 0), lane = threadIdx.x & 31;
    const int b = blockIdx.x, rank = b & 1, nb = (b >> 1) & 7, mb = (b >> 4) * 2 + rank;

    if (warp >= 8) {
        asm volatile("setmaxnreg.dec.sync.aligned.u32 56;");
        if (warp >= 16 - NCONV) {
            const int cw = warp - (16 - NCONV);
            unsigned t0;
            asm volatile("mov.u32 %0, %clock;" : "=r"(t0));
            t0 += 100;
            asm volatile("barrier.cluster.arrive.relaxed.aligned;" ::: "memory");
            const Job mj = decode_job(min(lane, NJOB - 1) * NCTA + b);
            static_assert(NCONV == NSTG + 2 && NJOB == 22, "");
            const uint32_t s = sb + (cw < NSTG ? SM_STG + cw * 8192 : SM_A + (14 - NSTG + cw) * 8192);
            const uint32_t sbar = bars + (B_FULLS + cw) * 8;
            {
                const Coord c = job_coord(maps.m, __shfl_sync(~0u, mj.src, cw));
                if (elect_one()) {
                    mbar_init(sbar, 1);
                    asm volatile("fence.mbarrier_init.release.cluster;" ::: "memory");
                    unsigned t;
                    do { asm volatile("mov.u32 %0, %clock;" : "=r"(t)); } while ((int)(t - t0) < cw * PFD + (cw ? b * 88 : b * 0) / 16);
                    raw_load(c, s, sbar);
                }
                __syncwarp();
            }
            asm volatile("barrier.cluster.wait.aligned;" ::: "memory");
            t0 += b * 88 / 16;
            const int c4 = lane & 3, ln = (lane >> 2) * 2 + (c4 >> 1);
            const uint32_t rdA = ln * 128 + ((((c4 & 1) << 2) ^ (ln & 7)) << 4);
            const uint32_t rdB = (lane >> 3) * 2048 + (lane & 7) * 16;
            const int wrA = (lane >> 2) * 4 + (c4 ^ ((lane >> 3) & 3));
            uint32_t par = 0;
#pragma unroll 1
            for (int j = cw, jn; j < NJOB; j = jn, par ^= 1) {
                jn = j < 13 ? j + NCONV : (j < 15 ? 31 : j + NSTG);
                const int src = __shfl_sync(~0u, mj.src, j), dst = __shfl_sync(~0u, mj.dst, j);
                const int nsrc = __shfl_sync(~0u, mj.src, jn);
                const int kind = src >> 16;
                uint4 o[4];
                uint4* d;
                int dstep;
                mbar_wait(sbar, par);
                if (kind == 0) {
                    const uint32_t a0 = s + rdA;
                    d = g_a8 + (dst & 0x3FFFF) + wrA;
                    dstep = 32;
#pragma unroll
                    for (int i = 0; i < 4; i++) {
                        uint4 v0 = lds128(a0 + i * 2048), v1 = lds128((a0 ^ 16) + i * 2048);
                        uint4 v2 = lds128((a0 ^ 32) + i * 2048), v3 = lds128((a0 ^ 48) + i * 2048);
                        o[i].x = pack4(v0.x, v0.y, v0.z, v0.w); o[i].y = pack4(v1.x, v1.y, v1.z, v1.w);
                        o[i].z = pack4(v2.x, v2.y, v2.z, v2.w); o[i].w = pack4(v3.x, v3.y, v3.z, v3.w);
                    }
                } else {
                    const uint32_t a0 = s + rdB;
                    d = g_b8 + (dst & 0x3FFFF) + (lane >> 3) * (kind == 1 ? WA : WB) + (lane & 7);
                    dstep = 8;
#define CV_B(m, f)                                                                                    \
                    {                                                                                 \
                        uint4 v0 = lds128(a0 + m * 512), v1 = lds128(a0 + m * 512 + 128);             \
                        uint4 v2 = lds128(a0 + m * 512 + 256), v3 = lds128(a0 + m * 512 + 384);       \
                        o[0].f = pack4(v0.x, v1.x, v2.x, v3.x); o[1].f = pack4(v0.y, v1.y, v2.y, v3.y); \
                        o[2].f = pack4(v0.z, v1.z, v2.z, v3.z); o[3].f = pack4(v0.w, v1.w, v2.w, v3.w); \
                    }
                    CV_B(0, x) CV_B(1, y) CV_B(2, z) CV_B(3, w)
                }
#pragma unroll
                for (int i = 0; i < 4; i++) stg128(d + i * dstep, o[i]);
                unsigned tn;
                asm volatile("mov.u32 %0, %clock;" : "=r"(tn));
                const bool late = jn < NJOB && (int)(tn - t0) < jn * PFD;
                if (!late && elect_one()) {
                    if (jn < NJOB) { raw_load(job_coord(maps.m, nsrc), s, sbar); }
                    else if (jn == 31) mbar_arrive(bars + (B_AFREE - NSTG + cw) * 8);
                    else if (0 != 1) {
                        uint32_t ra;
                        asm("mapa.shared::cluster.u32 %0, %1, %2;" : "=r"(ra) : "r"(bars + (B_GO + ((UX + cw) >> 1)) * 8), "r"((UX + cw) & 1));
                        mbar_arrive_cluster(ra);
                    }
                }
                const int* csp = (const int*)d;
                unsigned csv = o[0].x;
                if (kind != 0) {
                    int cs[4];
#pragma unroll
                    for (int i = 0; i < 4; i++)
                        cs[i] = __dp4a((int)o[i].x, 0x01010101, __dp4a((int)o[i].y, 0x01010101,
                                __dp4a((int)o[i].z, 0x01010101, __dp4a((int)o[i].w, 0x01010101, 0))));
                    const int p01 = cs[0] + cs[1] * 65536, p23 = cs[2] + cs[3] * 65536;
                    const bool odd = lane & 8;
                    int v = (odd ? p23 : p01) + __shfl_xor_sync(~0u, odd ? p01 : p23, 8);
                    v += __shfl_xor_sync(~0u, v, 16);
                    int* p = (int*)g_cs + ((src >> 12) & 15) * (N_ / 2) + ((src & 0xFFF) >> 1) + (lane & 15);
                    if (lane < 16) *p = v;
                    csp = p; csv = v;
                }
#pragma unroll 1
                for (int it = 0; it < 1000; it++) {
                    bool ok = true;
                    if ((lane & 3) == 0) {
                        unsigned rb[5];
#pragma unroll
                        for (int i = 0; i < 4; i++)
                            asm volatile("ld.relaxed.gpu.global.u32 %0, [%1];" : "=r"(rb[i]) : "l"(d + i * dstep) : "memory");
                        asm volatile("ld.relaxed.gpu.global.u32 %0, [%1];" : "=r"(rb[4]) : "l"(csp) : "memory");
                        ok = rb[0] == o[0].x && rb[1] == o[1].x && rb[2] == o[2].x && rb[3] == o[3].x && rb[4] == csv;
                    }
                    if (__all_sync(~0u, ok)) break;
                }
                if (elect_one()) asm volatile("red.relaxed.gpu.global.add.u32 [%0], 1;" :: "l"(g_flag + ((unsigned)dst >> 18)) : "memory");
                __syncwarp();
                if (late && elect_one()) {
                    do { asm volatile("mov.u32 %0, %clock;" : "=r"(tn)); } while ((int)(tn - t0) < jn * PFD);
                    raw_load(job_coord(maps.m, nsrc), s, sbar);
                }
                __syncwarp();
            }
        } else if (warp == 8) {
            asm volatile("barrier.cluster.arrive.relaxed.aligned;" ::: "memory");
            const unsigned ep = *(volatile unsigned*)&g_epoch[b] + 1;
            const unsigned* f1 = g_flag + 256 + nb * 64 + lane;
            const unsigned* f2 = lane < 16 ? f1 + 32 : g_flag + mb * 16 + lane - 16;
            const unsigned t1 = ep * (WA / 32), t2 = ep * 4;
            static_assert(WB / 16 == 4, "");
            const unsigned n1 = lane == 0 ? unit_mask(0, 0, 8) : lane == 1 ? unit_mask(1, 0, 8) : lane == 2 ? unit_mask(0, 8, 16)
                              : lane == 3 ? unit_mask(1, 8, 16) : 0u;
            const unsigned n2 = lane < 4 ? 0u : 0xFFFFu;
            bool d1 = false, d2 = false, d3 = lane >= 5, fr = lane < 30;
            asm volatile("barrier.cluster.wait.aligned;" ::: "memory");
            for (int it = 0; 0 != 1; it++) {
                unsigned v1 = t1, v2 = t2;
                if (!d1) v1 = ld_flag(f1);
                if (!d2) v2 = ld_flag(f2);
                if (!fr) fr = mbar_test(bars + (B_AFREE - 30 + lane) * 8);
                if (!d2 && fr && (int)(v2 - t2) >= 0) {
                    d2 = true;
                    if (lane >= 16) {
                        asm volatile("fence.proxy.async.global;" ::: "memory");
                        asm volatile("cp.async.bulk.shared::cluster.global.mbarrier::complete_tx::bytes [%0], [%1], %2, [%3];"
                                     :: "r"(sb + SM_A + (lane - 16) * 8192), "l"((const char*)g_a8 + (mb * 16 + lane - 16) * 8192),
                                        "r"(8192), "r"(bars + (B_FULLA + lane - 16) * 8) : "memory");
                    } else if ((lane & 1) == rank) mbar_arrive(bars + (B_GO + 16 + (lane >> 1)) * 8);
                }
                if (!d1 && (int)(v1 - t1) >= 0) {
                    d1 = true;
                    if ((lane & 1) == rank) mbar_arrive(bars + (B_GO + (lane >> 1)) * 8);
                }
                const unsigned m1 = __ballot_sync(~0u, d1), m2 = __ballot_sync(~0u, d2);
                if (!d3 && (m1 & n1) == n1 && (m2 & n2) == n2) { d3 = true; mbar_arrive(bars + (B_PSTEP + lane) * 8); }
                if ((m1 & m2) == ~0u) break;
                if (it > (1 << 22)) __trap();
            }
        } else if (warp == 9) {
            asm volatile("barrier.cluster.arrive.relaxed.aligned;" ::: "memory");
            const int u = 2 * lane + rank;
            int so, fb;
            if (u < 2 * X1) { so = (u & 1) * (WA * K_) + (u >> 1) * (WA * 64); fb = (u & 1) * 24 + (u >> 1); }
            else if (u < X1 + 16) { so = (u - X1) * (WA * 64); fb = u - X1; }
            else if (u < 32) { so = WA * K_ + (u - 16) * (WA * 64); fb = 24 + u - 16; }
            else { so = 2 * WA * K_ + (u - 32) * (WB * 128); fb = u < 40 ? u - 16 : u; }
            const char* srcB = (const char*)g_b8 + nb * TN * K_ + so;
            const uint32_t dstB = sb + SM_RING + slot_of(u) * 2048;
            asm volatile("barrier.cluster.wait.aligned;" ::: "memory");
#pragma unroll 1
            for (int i = 0; i < NU / 2 && 0 != 1; i++) {
                mbar_wait(bars + (B_GO + i) * 8);
                if (lane == i) {
                    asm volatile("fence.proxy.async.global;" ::: "memory");
                    asm volatile("cp.async.bulk.shared::cluster.global.mbarrier::complete_tx::bytes.multicast::cluster [%0], [%1], %2, [%3], %4;"
                                 :: "r"(dstB), "l"(srcB), "r"(u < 32 ? WA * 64 : WB * 128), "r"(bars + (B_FULLB + fb) * 8), "h"((uint16_t)3) : "memory");
                }
                __syncwarp();
            }
        } else if (warp == 10) {
            unsigned pv, pv2;
            {
                static_assert(X1 > 0 && nA == 64 && nWA == 40, "");
                const int i = b - (b < 104 ? 64 : 104), q = i / 5;
                const char* p = b < 64 ? qx + (b * 32 + (lane >> 1)) * (K_ * 4) + (lane & 1) * 128
                                       : qw + lane * (N_ * 4) + (q * TN + (b < 104 ? 0 : WA) + (i - q * 5) * 32) * 4;
                pv = pf_l2(p);
                pv2 = pf_l2(p + (b < 64 ? 16 * K_ * 4 : 32 * N_ * 4));
                if (lane < 3) asm volatile("prefetch.tensormap [%0];" :: "l"(maps.m + lane) : "memory");
            }
            asm volatile("barrier.cluster.arrive.relaxed.aligned;" ::: "memory");
            if ((pv ^ pv2) == 0x40000000u) g_sink = pv;
            const float zxf = __bfloat162float(__float2bfloat16_rn((float)__ldg(zero_x)));
#pragma unroll 1
            for (int i = lane; i < TN / 4; i += 32) {
                const bool hi = i >= TN / 8;
                sts128(sb + SM_PAR + TN * 2 + i * 16, __ldg((const uint4*)((hi ? bias : scale_w) + nb * TN) + (hi ? i - TN / 8 : i)));
            }
            asm volatile("barrier.cluster.wait.aligned;" ::: "memory");
            int c[8], cs[8];
#pragma unroll
            for (int i = 0; i < 8; i++) { c[i] = 0; cs[i] = 0; }
#pragma unroll 1
            for (int st = 0; st < 5 && 0 != 1; st++) {
                const bool wide = st < 4;
                const int half = wide ? (st >> 1) : (lane >> 4);
                const int col = wide ? (st & 1) * WA + min(lane, WA / 8 - 1) * 8 : 2 * WA + (lane & 15) * 8;
                const uint4* src = g_cs + (half * 8 * N_ + nb * TN + col) / 8;
                mbar_wait(bars + (B_PSTEP + st) * 8);
                uint4 v[8];
#pragma unroll
                for (int i = 0; i < 8; i++) v[i] = __ldcg(src + i * (N_ / 8));
#pragma unroll
                for (int h = 0; h < 8; h += 4) {
                    const unsigned sv[4] = {v[h].x + v[h + 1].x + v[h + 2].x + v[h + 3].x, v[h].y + v[h + 1].y + v[h + 2].y + v[h + 3].y,
                                            v[h].z + v[h + 1].z + v[h + 2].z + v[h + 3].z, v[h].w + v[h + 1].w + v[h + 2].w + v[h + 3].w};
#pragma unroll
                    for (int i = 0; i < 4; i++) {
                        const int lo = (int)(short)(sv[i] & 0xFFFF);
                        c[2 * i] += lo; c[2 * i + 1] += ((int)(sv[i] - (unsigned)lo)) >> 16;
                    }
                }
                if (st >= 2) {
                    uint32_t z[4];
#pragma unroll
                    for (int i = 0; i < 8; i++) {
                        const int o = __shfl_xor_sync(~0u, c[i], 16);
                        if (!wide) c[i] += o;
                    }
#pragma unroll
                    for (int i = 0; i < 4; i++) {
                        const float lo = __bfloat162float(__float2bfloat16_rn((float)c[2 * i])) * zxf;
                        const float hi = __bfloat162float(__float2bfloat16_rn((float)c[2 * i + 1])) * zxf;
                        asm("cvt.rn.bf16x2.f32 %0, %1, %2;" : "=r"(z[i]) : "f"(hi), "f"(lo));
                    }
                    const uint32_t za = sb + SM_PAR + ((col & ~31) + (col & 8) * 2 + ((col >> 3) & 2)) * 2;
#pragma unroll
                    for (int i = 0; i < 4; i++) sts32(za + i * 8, z[i]);
                    __syncwarp();
                    if (lane == 0) { mbar_arrive(bars + (B_PAR + st - 2) * 8); }
#pragma unroll
                    for (int i = 0; i < 8; i++) c[i] = 0;
                }
#pragma unroll
                for (int i = 0; i < 8; i++) { const int t = c[i]; c[i] = cs[i]; cs[i] = t; }
            }
        } else {
            asm volatile("barrier.cluster.arrive.relaxed.aligned;" ::: "memory");
            asm volatile("barrier.cluster.wait.aligned;" ::: "memory");
        }
    } else {
        asm volatile("setmaxnreg.inc.sync.aligned.u32 200;");
        {
            constexpr int PER = (B_NINIT + 7) / 8;
            if (elect_one()) {
#pragma unroll 1
                for (int i = warp * PER; i < min(warp * PER + PER, B_NINIT); i++)
                    {
                    const int u = 2 * (i - B_GO) + rank;
                    mbar_init(bars + i * 8, (i < B_GO || i >= B_PAR || u < NSLOT) ? 1 : (u >= UX && u < UX + NSTG) ? 3 : 9);
                }
            }
            __syncwarp();
            const int i = warp * PER + lane;
            if (lane < PER && i < B_GO) mbar_expect_tx(bars + i * 8, (i < 16 || (i >= 24 && i < 40)) ? WA * 64 : 8192);
            static_assert(WB * 128 == 8192, "");
            asm volatile("fence.mbarrier_init.release.cluster;" ::: "memory");
        }
        asm volatile("barrier.cluster.arrive.relaxed.aligned;" ::: "memory");
        const int wg = warp >> 2;
        const uint32_t sd = (sb & 0x3FFFF) >> 4;
        const unsigned short sxr = __ldg((const unsigned short*)scale_x);
        const uint32_t sx2 = (uint32_t)sxr * 0x10001u;
        char* orow = (char*)out + (size_t)(mb * 128 + (warp & 3) * 16 + (lane >> 2)) * (N_ * 2) + (nb * TN + (lane & 3) * 8 + wg * WA) * 2;
        const uint32_t par = sb + SM_PAR + (lane & 3) * 16 + wg * WA * 2;
        uint32_t reladdr;
        int rell;
        {
            const int u = lane < 16 ? (lane < X1 ? 2 * lane + wg : (wg ? 16 : X1) + lane) : 16 + wg * 8 + lane;
            const int v = u + (u < 32 ? NSLOT : NSLOT + NSTG);
            rell = (lane < 24 && v < NU) ? lane : 99;
            asm("mapa.shared::cluster.u32 %0, %1, %2;" : "=r"(reladdr) : "r"(bars + (B_GO + (v >> 1)) * 8), "r"(v & 1));
        }
        asm volatile("barrier.cluster.wait.aligned;" ::: "memory");
        int a0[WA / 2], a1[WA / 2];
        uint32_t barB = bars + (B_FULLB + wg * 24) * 8;
        bool ready = false;
#define HAND_BACK(done) if (rell <= (done)) { mbar_arrive_cluster(reladdr); rell = 99; }
        if (0 != 1) {
            wg_fence();
            {
                uint64_t tbl = wg ? slot_table(1) : slot_table(0);
                uint32_t da = (sd + (SM_A >> 4)) | (1 << 16);
#pragma unroll 1
                for (int s = 0; s < 16; s++) {
                    const uint32_t db = ((sd + (SM_RING >> 4)) | (WA << 16)) + ((uint32_t)tbl & 15) * (SLOT >> 4);
                    const bool starved = !ready && !mbar_test2(bars + (B_FULLA + s) * 8, barB);
                    if (starved) {
                        wg_wait<0>();
                        HAND_BACK(s - 1)
                        mbar_wait2(bars + (B_FULLA + s) * 8, barB);
                    }
                    wgmma_n160(a0, da, db, s);
                    wgmma_n160(a1, da + 256, db, s);
                    wgmma_n160(a0, da + 2, db + 2 * WA, 1);
                    wgmma_n160(a1, da + 258, db + 2 * WA, 1);
                    wg_commit();
                    HAND_BACK(s - 2)
                    tbl >>= 4; da += 512; barB += 8;
                    ready = mbar_test2(bars + (B_FULLA + min(s + 1, 15)) * 8, barB);
                    wg_wait<1>();
                }
            }
            HAND_BACK(14)
            wg_wait<0>();
            HAND_BACK(15)
            mbar_wait(bars + (B_PAR + wg) * 8);
            Par P = ld_par(par);
            char* const orow1 = orow + 64 * (N_ * 2);
            epilogue<0, 1>(a0, P, par, sx2, orow); epilogue<1, 2>(a0, P, par, sx2, orow);
            epilogue<2, 3>(a0, P, par, sx2, orow); epilogue<3, 0>(a0, P, par, sx2, orow);
            int t[64];
            wg_fence();
            {
                uint64_t tbl = wg ? slot_table(3) : slot_table(2);
                uint32_t da = (sd + (SM_A >> 4)) | (1 << 16);
#pragma unroll
                for (int i = 16; i < 24; i++) {
                    const uint32_t db = ((sd + (SM_RING >> 4)) | (WB << 16)) + ((uint32_t)tbl & 255) * 128;
                    const bool starved = !ready && !mbar_test(barB);
                    if (starved) {
                        wg_wait<0>();
                        HAND_BACK(i - 1)
                        mbar_wait(barB);
                    }
#pragma unroll
                    for (int k = 0; k < 4; k++) wgmma_t128(t, db + k * 2 * WB, da + (k >> 1) * 512 + (k & 1) * 2, k ? 1 : i - 16);
                    wg_commit();
                    HAND_BACK(i - 2)
                    tbl >>= 8; da += 1024; barB += 8;
                    ready = mbar_test(barB);
                    switch (i) {
                        case 16: epilogue<0, 0>(a1, P, par, sx2, orow1); break;
                        case 17: epilogue<1, 1>(a1, P, par, sx2, orow1); break;
                        case 18: epilogue<2, 2>(a1, P, par, sx2, orow1); break;
                        case 19: epilogue<3, 3>(a1, P, par, sx2, orow1); break;
                        case 20: epilogue<4, 4>(a1, P, par, sx2, orow1); break;
                        case 21: epilogue<4, 4>(a0, P, par, sx2, orow); break;
                        default: break;
                    }
                    if (i < 20) P = ld_par(par + (i - 15) * 64);
                    wg_wait<1>();
                }
            }
            HAND_BACK(22)
            mbar_wait(bars + (B_PAR + 2) * 8);
            const int w = warp & 3, q = lane >> 2, c0 = (w >> 1) * 32 + q * 4 + (w & 1) * 2;
            const uint32_t pp = sb + SM_PAR + (2 * WA + wg * WB + c0) * 2;
            const uint32_t zc = lds32(pp), sw = lds32(pp + TN * 2), bi = lds32(pp + TN * 4);
            const int r0 = (lane & 3) * 2;
            const uint32_t st0 = r0 * 128 + (((c0 >> 3) ^ r0) << 4) + (c0 & 7) * 2, st1 = (st0 ^ 16) + 128;
            wg_wait<0>();
            asm volatile("bar.sync %0, 128;" :: "r"(3 + wg) : "memory");
#pragma unroll
            for (int h = 0; h < 2; h++) {
                const uint32_t buf = sb + SM_RING + (wg ? slot_of(UX + 1 + h) : slot_of(UX - 1 + h)) * 2048;
#pragma unroll
                for (int j = 0; j < 8; j++) {
                    const int o = h * 32 + j * 4;
                    sts32(buf + st0 + j * 1024, bf2_op_epi(t[o], t[o + 2], zc, sx2, sw, bi));
                    sts32(buf + st1 + j * 1024, bf2_op_epi(t[o + 1], t[o + 3], zc, sx2, sw, bi));
                }
                asm volatile("fence.proxy.async.shared::cta;" ::: "memory");
                asm volatile("bar.sync %0, 128;" :: "r"(3 + wg) : "memory");
                if (w == 0 && elect_one())
                    asm volatile("cp.async.bulk.tensor.2d.global.shared::cta.tile.bulk_group [%0, {%1, %2}], [%3];"
                                 :: "l"(maps.m + 2), "r"(nb * TN + 2 * WA + wg * WB), "r"(mb * 128 + h * 64), "r"(buf) : "memory");
            }
            if (w == 0) {
                asm volatile("cp.async.bulk.commit_group;" ::: "memory");
                asm volatile("cp.async.bulk.wait_group.read 0;" ::: "memory");
            }
        }
        if (threadIdx.x == 128) asm volatile("red.relaxed.gpu.global.add.u32 [%0], 1;" :: "l"(g_epoch + b) : "memory");
    }
}

static void launch(EncodeFn encode, void* const* d_in, void* d_out) {
    Maps maps;
    CUtensorMap &mx = maps.m[0], &mw = maps.m[1];
    {
        const cuuint64_t dim[3] = {32, K_ / 32, M_}, str[2] = {128, K_ * 4};
        const cuuint32_t box[3] = {32, 2, 32}, es[3] = {1, 1, 1};
        encode(&mx, CU_TENSOR_MAP_DATA_TYPE_INT32, 3, d_in[0], dim, str, box, es, CU_TENSOR_MAP_INTERLEAVE_NONE,
               CU_TENSOR_MAP_SWIZZLE_128B, CU_TENSOR_MAP_L2_PROMOTION_NONE, CU_TENSOR_MAP_FLOAT_OOB_FILL_NONE);
    }
    {
        const cuuint64_t dim[3] = {N_, K_, 1}, str[2] = {N_ * 4, (cuuint64_t)N_ * K_ * 4};
        const cuuint32_t box[3] = {32, 64, 1}, es[3] = {1, 1, 1};
        encode(&mw, CU_TENSOR_MAP_DATA_TYPE_INT32, 3, d_in[1], dim, str, box, es, CU_TENSOR_MAP_INTERLEAVE_NONE,
               CU_TENSOR_MAP_SWIZZLE_NONE, CU_TENSOR_MAP_L2_PROMOTION_NONE, CU_TENSOR_MAP_FLOAT_OOB_FILL_NONE);
    }
    {
        const cuuint64_t dim[2] = {N_, M_}, str[1] = {N_ * 2};
        const cuuint32_t box[2] = {WB, 64}, es[2] = {1, 1};
        encode(&maps.m[2], CU_TENSOR_MAP_DATA_TYPE_BFLOAT16, 2, d_out, dim, str, box, es, CU_TENSOR_MAP_INTERLEAVE_NONE,
               CU_TENSOR_MAP_SWIZZLE_128B, CU_TENSOR_MAP_L2_PROMOTION_NONE, CU_TENSOR_MAP_FLOAT_OOB_FILL_NONE);
    }
    w8a8_kernel<<<NCTA, 512, SM_ALLOC>>>(maps, (const char*)d_in[0], (const char*)d_in[1], (const __nv_bfloat16*)d_in[2], (const int*)d_in[3],
                                         (const __nv_bfloat16*)d_in[4], (const __nv_bfloat16*)d_in[5],
                                         (__nv_bfloat16*)d_out);
}

}

extern "C" void kernel_launch(void* const* d_in, const int* in_sizes, int n_in, void* d_out, int out_size) {
    using namespace ra;
    static EncodeFn encode = nullptr;
    static Scratch* scr = nullptr;
    static const JobTable* jobs = nullptr;
    static bool fits = false;
    if (!encode) {
        void* fn = nullptr;
        cudaDriverEntryPointQueryResult qr;
        cudaGetDriverEntryPoint("cuTensorMapEncodeTiled", &fn, cudaEnableDefault, &qr);
        encode = (EncodeFn)fn;
        cudaGetSymbolAddress((void**)&scr, g_scratch);
        cudaGetSymbolAddress((void**)&jobs, g_jobs);
        cudaFuncSetAttribute(w8a8_kernel, cudaFuncAttributeMaxDynamicSharedMemorySize, SM_ALLOC);
        cudaFuncSetAttribute(w8a8_kernel, cudaFuncAttributeNonPortableClusterSizeAllowed, 1);
        cudaFuncSetAttribute(w8a8_side, cudaFuncAttributeMaxDynamicSharedMemorySize, SM_ALLOC);
        cudaFuncSetAttribute(w8::w8a8_kernel, cudaFuncAttributeMaxDynamicSharedMemorySize, w8::SM_ALLOC);
        cudaLaunchConfig_t oc = {};
        oc.gridDim = dim3(NCTA); oc.blockDim = dim3(512); oc.dynamicSmemBytes = SM_ALLOC;
        cudaLaunchAttribute oa[1];
        oa[0].id = cudaLaunchAttributeClusterDimension; oa[0].val.clusterDim.x = CS; oa[0].val.clusterDim.y = 1; oa[0].val.clusterDim.z = 1;
        oc.attrs = oa; oc.numAttrs = 1;
        int nc = 0, dev = 0, sms = 0;
        cudaGetDevice(&dev);
        cudaDeviceGetAttribute(&sms, cudaDevAttrMultiProcessorCount, dev);
        fits = cudaOccupancyMaxActiveClusters(&nc, w8a8_kernel, &oc) == cudaSuccess && nc >= NCTA / CS && sms >= NCTA + NSIDE;
        cudaGetLastError();
    }
    if (!fits) { w8::launch(encode, d_in, d_out); return; }
    CUtensorMap map;
    {
        const cuuint64_t dim[2] = {N_, M_}, str[1] = {N_ * 2};
        const cuuint32_t box[2] = {64, 32}, es[2] = {1, 1};
        encode(&map, CU_TENSOR_MAP_DATA_TYPE_BFLOAT16, 2, d_out, dim, str, box, es, CU_TENSOR_MAP_INTERLEAVE_NONE,
               CU_TENSOR_MAP_SWIZZLE_128B, CU_TENSOR_MAP_L2_PROMOTION_NONE, CU_TENSOR_MAP_FLOAT_OOB_FILL_NONE);
    }
    w8a8_kernel<<<NCTA, 512, SM_ALLOC, cudaStreamPerThread>>>((const char*)d_in[0], (const char*)d_in[1], scr, jobs, (const __nv_bfloat16*)d_in[4],
                                                             (const __nv_bfloat16*)d_in[5], (const __nv_bfloat16*)d_in[2], (const int*)d_in[3], map);
    cudaLaunchConfig_t cfg = {};
    cfg.gridDim = dim3(NSIDE); cfg.blockDim = dim3(512); cfg.dynamicSmemBytes = SM_ALLOC; cfg.stream = cudaStreamPerThread;
    cudaLaunchAttribute at[1];
    at[0].id = cudaLaunchAttributeProgrammaticStreamSerialization; at[0].val.programmaticStreamSerializationAllowed = 1;
    cfg.attrs = at; cfg.numAttrs = 1;
    cudaLaunchKernelEx(&cfg, w8a8_side, (const char*)d_in[1], scr, (const __nv_bfloat16*)d_in[4], (const __nv_bfloat16*)d_in[5], (const __nv_bfloat16*)d_in[2],
                       (const int*)d_in[3], map);
}
```

```cpp
#include <cuda_runtime.h>
#include <cuda.h>
#include <cuda_bf16.h>
#include <stdint.h>

namespace ra {

constexpr int CFG_D = 2;
constexpr int CFG_P0 = 615;
constexpr int CFG_PF0 = 0;
constexpr int CFG_SLEEP = 400;
constexpr int CFG_NINIT = 2;
constexpr int CFG_NR = 10;
constexpr int CFG_PZ = 16;
constexpr int CFG_NOC = 12;
constexpr int CFG_YP = 1100;
constexpr int CFG_YH = 1000;
constexpr int CFG_YH0 = 2500;
constexpr int CFG_Y0 = 1400;

constexpr int M_ = 2048, K_ = 1024, N_ = 3584;
constexpr int CS = 16, NCTA = 112, NSIDE = 20, TN = 448;
constexpr int NRING = CFG_NR, NCONV = 6, NJOB = 26, NG = 56, NOUT = 4, D_ = CFG_D;

constexpr int SM_A = 0;
constexpr int SM_RING = 131072;
constexpr int SM_OUT = SM_RING + NRING * 8192;
constexpr int SM_PAR = SM_OUT + NOUT * 4096;
constexpr int SM_SUM = SM_PAR + 1024;
constexpr int SM_BAR = SM_SUM + 256;
constexpr int B_FULL = 0, B_PAR = 64, B_AFREE = 72, B_TURN = 74, B_OFREE = 76, B_SUM = 108, B_GO = 112, B_OFULL = 144, B_END = 148;
constexpr int SM_TOTAL = SM_BAR + B_END * 8;

constexpr int FS = 32;
struct __align__(2048) Scratch {
    uint4 a8[M_ * K_ / 16];
    uint4 b8[N_ * K_ / 16];
    unsigned cs[32 * TN / 2];
    unsigned flag[CS * FS + 64];
    unsigned epoch[NCTA + NSIDE];
};
__device__ Scratch g_scratch;
constexpr int SM_ALLOC = SM_TOTAL;
static_assert(SM_ALLOC <= 232448, "");

__device__ __forceinline__ void mbar_init(uint32_t bar, uint32_t cnt) {
    asm volatile("mbarrier.init.shared::cta.b64 [%0], %1;" :: "r"(bar), "r"(cnt) : "memory");
}
__device__ __forceinline__ void mbar_expect_tx(uint32_t bar, uint32_t bytes) {
    asm volatile("mbarrier.arrive.expect_tx.shared::cta.b64 _, [%0], %1;" :: "r"(bar), "r"(bytes) : "memory");
}
__device__ __forceinline__ void mbar_arrive(uint32_t bar) {
    asm volatile("mbarrier.arrive.shared::cta.b64 _, [%0];" :: "r"(bar) : "memory");
}
__device__ __forceinline__ void mbar_arrive_cluster(uint32_t bar) {
    asm volatile("mbarrier.arrive.shared::cluster.b64 _, [%0];" :: "r"(bar) : "memory");
}
__device__ __forceinline__ void mbar_wait(uint32_t bar) {
    asm volatile("{\n.reg .pred p;\nWAIT_LOOP:\nmbarrier.try_wait.parity.shared::cta.b64 p, [%0], 0;\n@!p bra WAIT_LOOP;\n}" :: "r"(bar) : "memory");
}
__device__ __forceinline__ void mbar_wait_cluster(uint32_t bar) {
    asm volatile("{\n.reg .pred p;\nWAIT_LOOP:\nmbarrier.try_wait.parity.relaxed.cluster.shared::cta.b64 p, [%0], 0;\n@!p bra WAIT_LOOP;\n"
                 "fence.acquire.sync_restrict::shared::cluster.cluster;\n}" :: "r"(bar) : "memory");
}
__device__ __forceinline__ void mbar_wait2(uint32_t bar0, uint32_t bar1) { mbar_wait(bar0); mbar_wait(bar1); }
__device__ __forceinline__ bool mbar_test(uint32_t bar) {
    uint32_t ok;
    asm volatile("{\n.reg .pred p;\nmbarrier.test_wait.parity.shared::cta.b64 p, [%1], 0;\nselp.u32 %0, 1, 0, p;\n}" : "=r"(ok) : "r"(bar) : "memory");
    return ok;
}
__device__ __forceinline__ bool mbar_test2(uint32_t bar0, uint32_t bar1) {
    uint32_t ok;
    asm volatile("{\n.reg .pred p, q;\nmbarrier.test_wait.parity.shared::cta.b64 p, [%1], 0;\n"
                 "mbarrier.test_wait.parity.shared::cta.b64 q, [%2], 0;\nand.pred p, p, q;\nselp.u32 %0, 1, 0, p;\n}"
                 : "=r"(ok) : "r"(bar0), "r"(bar1) : "memory");
    return ok;
}
__device__ __forceinline__ bool elect_one() {
    uint32_t ok;
    asm volatile("{\n.reg .pred p;\nelect.sync _|p, 0xffffffff;\nselp.u32 %0, 1, 0, p;\n}" : "=r"(ok));
    return ok;
}
__device__ __forceinline__ uint32_t mapa(uint32_t a, uint32_t cta) {
    uint32_t r;
    asm("mapa.shared::cluster.u32 %0, %1, %2;" : "=r"(r) : "r"(a), "r"(cta));
    return r;
}
__device__ __forceinline__ void st_async32(uint32_t a, uint32_t v, uint32_t bar) {
    asm volatile("st.async.shared::cluster.mbarrier::complete_tx::bytes.b32 [%0], %1, [%2];" :: "r"(a), "r"(v), "r"(bar) : "memory");
}
__device__ __forceinline__ unsigned ld_flag(const unsigned* p) {
    unsigned v;
    asm volatile("ld.relaxed.gpu.global.u32 %0, [%1];" : "=r"(v) : "l"(p) : "memory");
    return v;
}
__device__ __forceinline__ unsigned clk() { unsigned t; asm volatile("mov.u32 %0, %clock;" : "=r"(t)); return t; }
__device__ __forceinline__ uint32_t lds32(uint32_t a) {
    uint32_t v;
    asm volatile("ld.shared.b32 %0, [%1];" : "=r"(v) : "r"(a) : "memory");
    return v;
}
__device__ __forceinline__ void sts32(uint32_t a, uint32_t v) {
    asm volatile("st.shared.b32 [%0], %1;" :: "r"(a), "r"(v) : "memory");
}
__device__ __forceinline__ void stg128(void* p, uint4 v) {
    asm volatile("st.global.v4.b32 [%0], {%1,%2,%3,%4};" :: "l"(p), "r"(v.x), "r"(v.y), "r"(v.z), "r"(v.w) : "memory");
}
__device__ __forceinline__ unsigned pack4(unsigned a, unsigned b, unsigned c, unsigned d) {
    unsigned lo, r;
    asm("cvt.pack.sat.s8.s32.b32 %0, %1, %2, 0;" : "=r"(lo) : "r"(d), "r"(c));
    asm("cvt.pack.sat.s8.s32.b32 %0, %1, %2, %3;" : "=r"(r) : "r"(b), "r"(a), "r"(lo));
    return r;
}
constexpr uint32_t DESC_A_HI = 256 >> 4;
constexpr uint32_t DESC_B_HI = 0x80000000u | (512 >> 4);
__device__ __forceinline__ void mma_unit2(int (&d)[64], int (&e)[64], uint32_t alo, uint32_t blo, int scale_d) {
    asm volatile("{\n.reg .pred p;\n.reg .b64 da, db;\nsetp.ne.b32 p, %130, 0;\n"
        "mov.b64 da, {%128, %131};\nmov.b64 db, {%129, %132};\n"
        "wgmma.mma_async.sync.aligned.m64n128k32.s32.s8.s8 "
        "{%0, %1, %2, %3, %4, %5, %6, %7, %8, %9, %10, %11, %12, %13, %14, %15, "
        "%16, %17, %18, %19, %20, %21, %22, %23, %24, %25, %26, %27, %28, %29, %30, %31, "
        "%32, %33, %34, %35, %36, %37, %38, %39, %40, %41, %42, %43, %44, %45, %46, %47, "
        "%48, %49, %50, %51, %52, %53, %54, %55, %56, %57, %58, %59, %60, %61, %62, %63}, "
        "da, db, p;\n"
        "add.s64 da, da, 128;\n"
        "wgmma.mma_async.sync.aligned.m64n128k32.s32.s8.s8 "
        "{%64, %65, %66, %67, %68, %69, %70, %71, %72, %73, %74, %75, %76, %77, %78, %79, "
        "%80, %81, %82, %83, %84, %85, %86, %87, %88, %89, %90, %91, %92, %93, %94, %95, "
        "%96, %97, %98, %99, %100, %101, %102, %103, %104, %105, %106, %107, %108, %109, %110, %111, "
        "%112, %113, %114, %115, %116, %117, %118, %119, %120, %121, %122, %123, %124, %125, %126, %127}, "
        "da, db, p;\n"
        "add.s64 da, da, 128;\nadd.s64 db, db, 2;\n"
        "wgmma.mma_async.sync.aligned.m64n128k32.s32.s8.s8 "
        "{%0, %1, %2, %3, %4, %5, %6, %7, %8, %9, %10, %11, %12, %13, %14, %15, "
        "%16, %17, %18, %19, %20, %21, %22, %23, %24, %25, %26, %27, %28, %29, %30, %31, "
        "%32, %33, %34, %35, %36, %37, %38, %39, %40, %41, %42, %43, %44, %45, %46, %47, "
        "%48, %49, %50, %51, %52, %53, %54, %55, %56, %57, %58, %59, %60, %61, %62, %63}, "
        "da, db, 1;\n"
        "add.s64 da, da, 128;\n"
        "wgmma.mma_async.sync.aligned.m64n128k32.s32.s8.s8 "
        "{%64, %65, %66, %67, %68, %69, %70, %71, %72, %73, %74, %75, %76, %77, %78, %79, "
        "%80, %81, %82, %83, %84, %85, %86, %87, %88, %89, %90, %91, %92, %93, %94, %95, "
        "%96, %97, %98, %99, %100, %101, %102, %103, %104, %105, %106, %107, %108, %109, %110, %111, "
        "%112, %113, %114, %115, %116, %117, %118, %119, %120, %121, %122, %123, %124, %125, %126, %127}, "
        "da, db, 1;\n"
        "wgmma.commit_group.sync.aligned;\n}\n"
        : "+r"(d[0]), "+r"(d[1]), "+r"(d[2]), "+r"(d[3]), "+r"(d[4]), "+r"(d[5]), "+r"(d[6]), "+r"(d[7]),
          "+r"(d[8]), "+r"(d[9]), "+r"(d[10]), "+r"(d[11]), "+r"(d[12]), "+r"(d[13]), "+r"(d[14]), "+r"(d[15]),
          "+r"(d[16]), "+r"(d[17]), "+r"(d[18]), "+r"(d[19]), "+r"(d[20]), "+r"(d[21]), "+r"(d[22]), "+r"(d[23]),
          "+r"(d[24]), "+r"(d[25]), "+r"(d[26]), "+r"(d[27]), "+r"(d[28]), "+r"(d[29]), "+r"(d[30]), "+r"(d[31]),
          "+r"(d[32]), "+r"(d[33]), "+r"(d[34]), "+r"(d[35]), "+r"(d[36]), "+r"(d[37]), "+r"(d[38]), "+r"(d[39]),
          "+r"(d[40]), "+r"(d[41]), "+r"(d[42]), "+r"(d[43]), "+r"(d[44]), "+r"(d[45]), "+r"(d[46]), "+r"(d[47]),
          "+r"(d[48]), "+r"(d[49]), "+r"(d[50]), "+r"(d[51]), "+r"(d[52]), "+r"(d[53]), "+r"(d[54]), "+r"(d[55]),
          "+r"(d[56]), "+r"(d[57]), "+r"(d[58]), "+r"(d[59]), "+r"(d[60]), "+r"(d[61]), "+r"(d[62]), "+r"(d[63]),
          "+r"(e[0]), "+r"(e[1]), "+r"(e[2]), "+r"(e[3]), "+r"(e[4]), "+r"(e[5]), "+r"(e[6]), "+r"(e[7]),
          "+r"(e[8]), "+r"(e[9]), "+r"(e[10]), "+r"(e[11]), "+r"(e[12]), "+r"(e[13]), "+r"(e[14]), "+r"(e[15]),
          "+r"(e[16]), "+r"(e[17]), "+r"(e[18]), "+r"(e[19]), "+r"(e[20]), "+r"(e[21]), "+r"(e[22]), "+r"(e[23]),
          "+r"(e[24]), "+r"(e[25]), "+r"(e[26]), "+r"(e[27]), "+r"(e[28]), "+r"(e[29]), "+r"(e[30]), "+r"(e[31]),
          "+r"(e[32]), "+r"(e[33]), "+r"(e[34]), "+r"(e[35]), "+r"(e[36]), "+r"(e[37]), "+r"(e[38]), "+r"(e[39]),
          "+r"(e[40]), "+r"(e[41]), "+r"(e[42]), "+r"(e[43]), "+r"(e[44]), "+r"(e[45]), "+r"(e[46]), "+r"(e[47]),
          "+r"(e[48]), "+r"(e[49]), "+r"(e[50]), "+r"(e[51]), "+r"(e[52]), "+r"(e[53]), "+r"(e[54]), "+r"(e[55]),
          "+r"(e[56]), "+r"(e[57]), "+r"(e[58]), "+r"(e[59]), "+r"(e[60]), "+r"(e[61]), "+r"(e[62]), "+r"(e[63])
        : "r"(alo), "r"(blo), "r"(scale_d), "n"(DESC_A_HI), "n"(DESC_B_HI) : "memory");
}
__device__ __forceinline__ bool mma_pair(int (&d)[64], uint32_t alo, uint32_t blo, int scale_d, uint32_t bar) {
    uint32_t ok;
    asm volatile("{\n.reg .pred p, q;\n.reg .b64 da, db;\nsetp.ne.b32 p, %67, 0;\n"
        "mov.b64 da, {%65, %68};\nmov.b64 db, {%66, %69};\n"
        "wgmma.mma_async.sync.aligned.m64n128k32.s32.s8.s8 "
        "{%0, %1, %2, %3, %4, %5, %6, %7, %8, %9, %10, %11, %12, %13, %14, %15, "
        "%16, %17, %18, %19, %20, %21, %22, %23, %24, %25, %26, %27, %28, %29, %30, %31, "
        "%32, %33, %34, %35, %36, %37, %38, %39, %40, %41, %42, %43, %44, %45, %46, %47, "
        "%48, %49, %50, %51, %52, %53, %54, %55, %56, %57, %58, %59, %60, %61, %62, %63}, "
        "da, db, p;\n"
        "add.s64 da, da, 128;\nadd.s64 db, db, 2;\n"
        "wgmma.mma_async.sync.aligned.m64n128k32.s32.s8.s8 "
        "{%0, %1, %2, %3, %4, %5, %6, %7, %8, %9, %10, %11, %12, %13, %14, %15, "
        "%16, %17, %18, %19, %20, %21, %22, %23, %24, %25, %26, %27, %28, %29, %30, %31, "
        "%32, %33, %34, %35, %36, %37, %38, %39, %40, %41, %42, %43, %44, %45, %46, %47, "
        "%48, %49, %50, %51, %52, %53, %54, %55, %56, %57, %58, %59, %60, %61, %62, %63}, "
        "da, db, 1;\n"
        "add.s64 da, da, 128;\nadd.s64 db, db, 510;\n"
        "wgmma.mma_async.sync.aligned.m64n128k32.s32.s8.s8 "
        "{%0, %1, %2, %3, %4, %5, %6, %7, %8, %9, %10, %11, %12, %13, %14, %15, "
        "%16, %17, %18, %19, %20, %21, %22, %23, %24, %25, %26, %27, %28, %29, %30, %31, "
        "%32, %33, %34, %35, %36, %37, %38, %39, %40, %41, %42, %43, %44, %45, %46, %47, "
        "%48, %49, %50, %51, %52, %53, %54, %55, %56, %57, %58, %59, %60, %61, %62, %63}, "
        "da, db, 1;\n"
        "add.s64 da, da, 128;\nadd.s64 db, db, 2;\n"
        "wgmma.mma_async.sync.aligned.m64n128k32.s32.s8.s8 "
        "{%0, %1, %2, %3, %4, %5, %6, %7, %8, %9, %10, %11, %12, %13, %14, %15, "
        "%16, %17, %18, %19, %20, %21, %22, %23, %24, %25, %26, %27, %28, %29, %30, %31, "
        "%32, %33, %34, %35, %36, %37, %38, %39, %40, %41, %42, %43, %44, %45, %46, %47, "
        "%48, %49, %50, %51, %52, %53, %54, %55, %56, %57, %58, %59, %60, %61, %62, %63}, "
        "da, db, 1;\n"
        "add.s64 da, da, 128;\nadd.s64 db, db, 510;\n"
        "wgmma.mma_async.sync.aligned.m64n128k32.s32.s8.s8 "
        "{%0, %1, %2, %3, %4, %5, %6, %7, %8, %9, %10, %11, %12, %13, %14, %15, "
        "%16, %17, %18, %19, %20, %21, %22, %23, %24, %25, %26, %27, %28, %29, %30, %31, "
        "%32, %33, %34, %35, %36, %37, %38, %39, %40, %41, %42, %43, %44, %45, %46, %47, "
        "%48, %49, %50, %51, %52, %53, %54, %55, %56, %57, %58, %59, %60, %61, %62, %63}, "
        "da, db, 1;\n"
        "add.s64 da, da, 128;\nadd.s64 db, db, 2;\n"
        "mbarrier.test_wait.parity.shared::cta.b64 q, [%70], 0;\n"
        "wgmma.mma_async.sync.aligned.m64n128k32.s32.s8.s8 "
        "{%0, %1, %2, %3, %4, %5, %6, %7, %8, %9, %10, %11, %12, %13, %14, %15, "
        "%16, %17, %18, %19, %20, %21, %22, %23, %24, %25, %26, %27, %28, %29, %30, %31, "
        "%32, %33, %34, %35, %36, %37, %38, %39, %40, %41, %42, %43, %44, %45, %46, %47, "
        "%48, %49, %50, %51, %52, %53, %54, %55, %56, %57, %58, %59, %60, %61, %62, %63}, "
        "da, db, 1;\n"
        "add.s64 da, da, 128;\nadd.s64 db, db, 510;\n"
        "wgmma.mma_async.sync.aligned.m64n128k32.s32.s8.s8 "
        "{%0, %1, %2, %3, %4, %5, %6, %7, %8, %9, %10, %11, %12, %13, %14, %15, "
        "%16, %17, %18, %19, %20, %21, %22, %23, %24, %25, %26, %27, %28, %29, %30, %31, "
        "%32, %33, %34, %35, %36, %37, %38, %39, %40, %41, %42, %43, %44, %45, %46, %47, "
        "%48, %49, %50, %51, %52, %53, %54, %55, %56, %57, %58, %59, %60, %61, %62, %63}, "
        "da, db, 1;\n"
        "add.s64 da, da, 128;\nadd.s64 db, db, 2;\n"
        "wgmma.mma_async.sync.aligned.m64n128k32.s32.s8.s8 "
        "{%0, %1, %2, %3, %4, %5, %6, %7, %8, %9, %10, %11, %12, %13, %14, %15, "
        "%16, %17, %18, %19, %20, %21, %22, %23, %24, %25, %26, %27, %28, %29, %30, %31, "
        "%32, %33, %34, %35, %36, %37, %38, %39, %40, %41, %42, %43, %44, %45, %46, %47, "
        "%48, %49, %50, %51, %52, %53, %54, %55, %56, %57, %58, %59, %60, %61, %62, %63}, "
        "da, db, 1;\n"
        "wgmma.commit_group.sync.aligned;\nselp.u32 %64, 1, 0, q;\n}\n"
        : "+r"(d[0]), "+r"(d[1]), "+r"(d[2]), "+r"(d[3]), "+r"(d[4]), "+r"(d[5]), "+r"(d[6]), "+r"(d[7]),
          "+r"(d[8]), "+r"(d[9]), "+r"(d[10]), "+r"(d[11]), "+r"(d[12]), "+r"(d[13]), "+r"(d[14]), "+r"(d[15]),
          "+r"(d[16]), "+r"(d[17]), "+r"(d[18]), "+r"(d[19]), "+r"(d[20]), "+r"(d[21]), "+r"(d[22]), "+r"(d[23]),
          "+r"(d[24]), "+r"(d[25]), "+r"(d[26]), "+r"(d[27]), "+r"(d[28]), "+r"(d[29]), "+r"(d[30]), "+r"(d[31]),
          "+r"(d[32]), "+r"(d[33]), "+r"(d[34]), "+r"(d[35]), "+r"(d[36]), "+r"(d[37]), "+r"(d[38]), "+r"(d[39]),
          "+r"(d[40]), "+r"(d[41]), "+r"(d[42]), "+r"(d[43]), "+r"(d[44]), "+r"(d[45]), "+r"(d[46]), "+r"(d[47]),
          "+r"(d[48]), "+r"(d[49]), "+r"(d[50]), "+r"(d[51]), "+r"(d[52]), "+r"(d[53]), "+r"(d[54]), "+r"(d[55]),
          "+r"(d[56]), "+r"(d[57]), "+r"(d[58]), "+r"(d[59]), "+r"(d[60]), "+r"(d[61]), "+r"(d[62]), "+r"(d[63]), "=r"(ok)
        : "r"(alo), "r"(blo), "r"(scale_d), "n"(DESC_A_HI), "n"(DESC_B_HI), "r"(bar) : "memory");
    return ok;
}
__device__ __forceinline__ void mma_rows2(int (&d)[64], int (&e)[64], uint32_t alo, uint32_t blo, int scale_d) {
    asm volatile("{\n.reg .pred p;\n.reg .b64 da, db;\nsetp.ne.b32 p, %130, 0;\n"
        "mov.b64 da, {%128, %131};\nmov.b64 db, {%129, %132};\n"
        "wgmma.mma_async.sync.aligned.m64n128k32.s32.s8.s8 "
        "{%0, %1, %2, %3, %4, %5, %6, %7, %8, %9, %10, %11, %12, %13, %14, %15, "
        "%16, %17, %18, %19, %20, %21, %22, %23, %24, %25, %26, %27, %28, %29, %30, %31, "
        "%32, %33, %34, %35, %36, %37, %38, %39, %40, %41, %42, %43, %44, %45, %46, %47, "
        "%48, %49, %50, %51, %52, %53, %54, %55, %56, %57, %58, %59, %60, %61, %62, %63}, "
        "da, db, p;\n"
        "add.s64 db, db, 512;\n"
        "wgmma.mma_async.sync.aligned.m64n128k32.s32.s8.s8 "
        "{%64, %65, %66, %67, %68, %69, %70, %71, %72, %73, %74, %75, %76, %77, %78, %79, "
        "%80, %81, %82, %83, %84, %85, %86, %87, %88, %89, %90, %91, %92, %93, %94, %95, "
        "%96, %97, %98, %99, %100, %101, %102, %103, %104, %105, %106, %107, %108, %109, %110, %111, "
        "%112, %113, %114, %115, %116, %117, %118, %119, %120, %121, %122, %123, %124, %125, %126, %127}, "
        "da, db, p;\n"
        "add.s64 da, da, 128;\nadd.s64 db, db, -510;\n"
        "wgmma.mma_async.sync.aligned.m64n128k32.s32.s8.s8 "
        "{%0, %1, %2, %3, %4, %5, %6, %7, %8, %9, %10, %11, %12, %13, %14, %15, "
        "%16, %17, %18, %19, %20, %21, %22, %23, %24, %25, %26, %27, %28, %29, %30, %31, "
        "%32, %33, %34, %35, %36, %37, %38, %39, %40, %41, %42, %43, %44, %45, %46, %47, "
        "%48, %49, %50, %51, %52, %53, %54, %55, %56, %57, %58, %59, %60, %61, %62, %63}, "
        "da, db, 1;\n"
        "add.s64 db, db, 512;\n"
        "wgmma.mma_async.sync.aligned.m64n128k32.s32.s8.s8 "
        "{%64, %65, %66, %67, %68, %69, %70, %71, %72, %73, %74, %75, %76, %77, %78, %79, "
        "%80, %81, %82, %83, %84, %85, %86, %87, %88, %89, %90, %91, %92, %93, %94, %95, "
        "%96, %97, %98, %99, %100, %101, %102, %103, %104, %105, %106, %107, %108, %109, %110, %111, "
        "%112, %113, %114, %115, %116, %117, %118, %119, %120, %121, %122, %123, %124, %125, %126, %127}, "
        "da, db, 1;\n"
        "wgmma.commit_group.sync.aligned;\n}\n"
        : "+r"(d[0]), "+r"(d[1]), "+r"(d[2]), "+r"(d[3]), "+r"(d[4]), "+r"(d[5]), "+r"(d[6]), "+r"(d[7]),
          "+r"(d[8]), "+r"(d[9]), "+r"(d[10]), "+r"(d[11]), "+r"(d[12]), "+r"(d[13]), "+r"(d[14]), "+r"(d[15]),
          "+r"(d[16]), "+r"(d[17]), "+r"(d[18]), "+r"(d[19]), "+r"(d[20]), "+r"(d[21]), "+r"(d[22]), "+r"(d[23]),
          "+r"(d[24]), "+r"(d[25]), "+r"(d[26]), "+r"(d[27]), "+r"(d[28]), "+r"(d[29]), "+r"(d[30]), "+r"(d[31]),
          "+r"(d[32]), "+r"(d[33]), "+r"(d[34]), "+r"(d[35]), "+r"(d[36]), "+r"(d[37]), "+r"(d[38]), "+r"(d[39]),
          "+r"(d[40]), "+r"(d[41]), "+r"(d[42]), "+r"(d[43]), "+r"(d[44]), "+r"(d[45]), "+r"(d[46]), "+r"(d[47]),
          "+r"(d[48]), "+r"(d[49]), "+r"(d[50]), "+r"(d[51]), "+r"(d[52]), "+r"(d[53]), "+r"(d[54]), "+r"(d[55]),
          "+r"(d[56]), "+r"(d[57]), "+r"(d[58]), "+r"(d[59]), "+r"(d[60]), "+r"(d[61]), "+r"(d[62]), "+r"(d[63]),
          "+r"(e[0]), "+r"(e[1]), "+r"(e[2]), "+r"(e[3]), "+r"(e[4]), "+r"(e[5]), "+r"(e[6]), "+r"(e[7]),
          "+r"(e[8]), "+r"(e[9]), "+r"(e[10]), "+r"(e[11]), "+r"(e[12]), "+r"(e[13]), "+r"(e[14]), "+r"(e[15]),
          "+r"(e[16]), "+r"(e[17]), "+r"(e[18]), "+r"(e[19]), "+r"(e[20]), "+r"(e[21]), "+r"(e[22]), "+r"(e[23]),
          "+r"(e[24]), "+r"(e[25]), "+r"(e[26]), "+r"(e[27]), "+r"(e[28]), "+r"(e[29]), "+r"(e[30]), "+r"(e[31]),
          "+r"(e[32]), "+r"(e[33]), "+r"(e[34]), "+r"(e[35]), "+r"(e[36]), "+r"(e[37]), "+r"(e[38]), "+r"(e[39]),
          "+r"(e[40]), "+r"(e[41]), "+r"(e[42]), "+r"(e[43]), "+r"(e[44]), "+r"(e[45]), "+r"(e[46]), "+r"(e[47]),
          "+r"(e[48]), "+r"(e[49]), "+r"(e[50]), "+r"(e[51]), "+r"(e[52]), "+r"(e[53]), "+r"(e[54]), "+r"(e[55]),
          "+r"(e[56]), "+r"(e[57]), "+r"(e[58]), "+r"(e[59]), "+r"(e[60]), "+r"(e[61]), "+r"(e[62]), "+r"(e[63])
        : "r"(alo), "r"(blo), "r"(scale_d), "n"(DESC_A_HI), "n"(DESC_B_HI) : "memory");
}

__device__ __forceinline__ void wg_fence() { asm volatile("wgmma.fence.sync.aligned;" ::: "memory"); }
template <int N> __device__ __forceinline__ void wg_wait() { asm volatile("wgmma.wait_group.sync.aligned %0;" :: "n"(N) : "memory"); }

__host__ __device__ constexpr int unit_of(int wg, int s) { return wg ? (s < 16 - D_ ? D_ + 2 * s : s + 16) : (s < D_ ? s : 2 * s - D_ + 1); }

__host__ __device__ constexpr int bar_of(int u) { return u >= 32 ? u & ~1 : u < D_ || u >= 32 - D_ ? u : ((u - D_) & 1) ? D_ + ((u - D_) >> 1) : 16 + ((u - D_) >> 1); }
constexpr uint32_t step_table(int wg) {
    uint32_t t = 0;
    for (int s = 0; s < 15; s++) t |= (uint32_t)(unit_of(wg, s + 1) - unit_of(wg, s) - 1) << s;
    return t;
}
constexpr uint32_t STEPS0 = step_table(0), STEPS1 = step_table(1);
__host__ __device__ constexpr int sum_owner(int g) { return g < 8 ? (g & 4) | (g & 1) << 1 | (~g >> 1 & 1) : g; }
__device__ __forceinline__ int sum_group(int r) { return r < 8 ? (r & 4) | (~r & 1) << 1 | (r >> 1 & 1) : r; }
__device__ __forceinline__ int col_of(int c, int blk) { return (c < 7 ? blk * 7 + c : 49 + blk) * 64; }

struct JobTable { uint2 e[NCTA][NJOB + NCONV]; };
__device__ const JobTable g_jobs = {{
    {{0x0, 0x0}, {0x20400, 0x1000000}, {0x90202, 0x2008099}, {0x100004, 0x3010132}, {0x14000000, 0x310001ee}, {0x2a412a34, 0x2d82025a}, {0x14100e0e, 0x750042e1}, {0x5d0a07, 0x409c366}, {0x14202a0e, 0x75008440}, {0x650a09, 0x60a44c5}, {0x1430460e, 0x7504c59d}, {0x36c680b, 0x76ac612}, {0x1440620e, 0x750506ee}, {0x3f4780d, 0x87b4768}, {0x14507e0e, 0x75094840}, {0x33c600f, 0x963c8b2}, {0x14609a0e, 0x75098965}, {0x1470b60e, 0x750dca0e}, {0x1480001c, 0x98020ab6}, {0x1490701c, 0x980a4b97}, {0x14a00023, 0xba028c8a}, {0x14b07023, 0xba0acd7c}, {0x14c0002a, 0xdc030e6f}, {0x14d0702a, 0xdc0b4f53}, {0x30000000, 0x0}, {0x30000000, 0x0}, {0x30000000, 0x0}, {0x30000000, 0x0}, {0x30000000, 0x0}, {0x30000000, 0x0}, {0x30000000, 0x0}, {0x30000000, 0x0}},
    {{0x0, 0x0}, {0x420c00, 0x1080001}, {0x490a02, 0x208809a}, {0x500804, 0x3090133}, {0x14010007, 0x200001f9}, {0x1973605, 0x431426c}, {0x14110e15, 0x640042f7}, {0x2a4e5b31, 0x5b82c378}, {0x14212a15, 0x64008456}, {0x2654a09, 0x64a44db}, {0x14314615, 0x6404c5b2}, {0x16d2a0b, 0x72ac628}, {0x14416215, 0x64050703}, {0x1b5320d, 0x833477b}, {0x14517e15, 0x64094855}, {0xfd1a0f, 0x91bc8c5}, {0x14619a15, 0x64098970}, {0x1471b615, 0x640dca18}, {0x1481071c, 0x98020ac1}, {0x1491771c, 0x980a4ba6}, {0x14a10723, 0xba028c99}, {0x14b17723, 0xba0acd8c}, {0x14c1072a, 0xdc030e7e}, {0x14d1772a, 0xdc0b4f60}, {0x30000000, 0x0}, {0x30000000, 0x0}, {0x30000000, 0x0}, {0x30000000, 0x0}, {0x30000000, 0x0}, {0x30000000, 0x0}, {0x30000000, 0x0}, {0x30000000, 0x0}},
    {{0x0, 0x0}, {0x821400, 0x1100002}, {0x891202, 0x210809b}, {0x901004, 0x3110134}, {0x14020700, 0x31000204}, {0x3176605, 0x461427c}, {0x1412150e, 0x7500430d}, {0x39d7207, 0x471c38a}, {0x1422310e, 0x7500846c}, {0x660c09, 0x60a44f1}, {0x14324d0e, 0x7504c5c7}, {0x36d6a0b, 0x76ac63d}, {0x1442690e, 0x75050719}, {0x3756a0d, 0x86b478e}, {0x1b8300e, 0x83387fa}, {0x1452850e, 0x7509486a}, {0x3e040f, 0x903c8e7}, {0x1462a10e, 0x7509897a}, {0x1472bd0e, 0x750dca23}, {0x14820e1c, 0x98020acb}, {0x14927e1c, 0x980a4bb5}, {0x14a20e23, 0xba028ca8}, {0x14b27e23, 0xba0acd9b}, {0x14c20e2a, 0xdc030e8e}, {0x14d27e2a, 0xdc0b4f6d}, {0x30000000, 0x0}, {0x30000000, 0x0}, {0x30000000, 0x0}, {0x30000000, 0x0}, {0x30000000, 0x0}, {0x30000000, 0x0}, {0x30000000, 0x0}},
    {{0x0, 0x0}, {0xc21c00, 0x1180003}, {0xc91a02, 0x218809c}, {0xd01804, 0x3190135}, {0x14030707, 0x2000020f}, {0x981006, 0x411828d}, {0x14131515, 0x64004323}, {0x11e2407, 0x521c39a}, {0x14233115, 0x64008482}, {0x2264409, 0x6424504}, {0x14334d15, 0x6404c5dc}, {0x12e240b, 0x722c64f}, {0x14436915, 0x6405072e}, {0x136240d, 0x82347a0}, {0x3f8780e, 0x87b8810}, {0x14538515, 0x6409487f}, {0xfe1c0f, 0x91bc8ef}, {0x1463a115, 0x64098985}, {0x1473bd15, 0x640dca2d}, {0x1483151c, 0x98020ad6}, {0x1493851c, 0x980a4bc4}, {0x14a31523, 0xba028cb7}, {0x14b38523, 0xba0acdaa}, {0x14c3152a, 0xdc030e9d}, {0x14d3852a, 0xdc0b4f7b}, {0x30000000, 0x0}, {0x30000000, 0x0}, {0x30000000, 0x0}, {0x30000000, 0x0}, {0x30000000, 0x0}, {0x30000000, 0x0}, {0x30000000, 0x0}},
    {{0x0, 0x0}, {0x1022400, 0x1200005}, {0x1092202, 0x220809e}, {0x1102004, 0x3210137}, {0x14040e00, 0x3100021a}, {0x2184006, 0x441829d}, {0x14142a00, 0x31004339}, {0x31e6407, 0x561c3b0}, {0x14244600, 0x31048498}, {0x3e67c09, 0x67a4516}, {0x14346200, 0x3104c5f2}, {0x2ee5c0b, 0x75ac661}, {0x1b1320c, 0x73306d3}, {0x14447e00, 0x31090743}, {0x3b6740d, 0x87347bb}, {0x14549a00, 0x31094894}, {0x23e440f, 0x943c8fc}, {0x1464b600, 0x310d898f}, {0x1474d200, 0x310dca38}, {0x14841c1c, 0x98020ae1}, {0x14948c1c, 0x980a4bd3}, {0x14a41c23, 0xba028cc6}, {0x14b48c23, 0xba0acdb9}, {0x14c41c2a, 0xdc030eac}, {0x14d48c2a, 0xdc0b4f88}, {0x30000000, 0x0}, {0x30000000, 0x0}, {0x30000000, 0x0}, {0x30000000, 0x0}, {0x30000000, 0x0}, {0x30000000, 0x0}, {0x30000000, 0x0}},
    {{0x0, 0x0}, {0x1422c00, 0x1280006}, {0x1492a02, 0x228809f}, {0x1502804, 0x3290138}, {0x14050e07, 0x20000225}, {0x3d87806, 0x47982af}, {0x14152a07, 0x2000434e}, {0xdf1e07, 0x519c3c3}, {0x14254607, 0x200484ae}, {0x1672e09, 0x62a4528}, {0x3e97a0a, 0x67a8598}, {0x14356207, 0x2004c607}, {0x26f4e0b, 0x74ac686}, {0x14457e07, 0x20090758}, {0x1b7360d, 0x83347d0}, {0x14559a07, 0x200948a9}, {0x3fe7c0f, 0x97bc90d}, {0x1465b607, 0x200d899a}, {0x1475d207, 0x200dca42}, {0x1485231c, 0x98020af0}, {0x1495931c, 0x980a4be3}, {0x14a52323, 0xba028cd5}, {0x14b59323, 0xba0acdc8}, {0x14c5232a, 0xdc030ebb}, {0x14d5932a, 0xdc0b4f95}, {0x30000000, 0x0}, {0x30000000, 0x0}, {0x30000000, 0x0}, {0x30000000, 0x0}, {0x30000000, 0x0}, {0x30000000, 0x0}, {0x30000000, 0x0}},
    {{0x0, 0x0}, {0x1823400, 0x1300007}, {0x1893202, 0x23080a0}, {0x1903004, 0x3310139}, {0x14061500, 0x31000230}, {0x1592a06, 0x42982c1}, {0x14163100, 0x31004364}, {0x29f5607, 0x551c3d6}, {0x14264d00, 0x310484c4}, {0x2a75609, 0x6524536}, {0x14366900, 0x3104c61c}, {0x12f260b, 0x722c679}, {0xb2140c, 0x71306f2}, {0x14468500, 0x3109076d}, {0x3776e0d, 0x86b47e2}, {0x1456a100, 0x310948be}, {0x1bf360f, 0x933c921}, {0x1466bd00, 0x310d89a4}, {0x1476d900, 0x310dca4d}, {0x14862a1c, 0x98020aff}, {0x14969a1c, 0x980a4bf2}, {0x14a62a23, 0xba028ce5}, {0x14b69a23, 0xba0acdd7}, {0x14c62a2a, 0xdc030eca}, {0x14d69a2a, 0xdc0b4fa3}, {0x30000000, 0x0}, {0x30000000, 0x0}, {0x30000000, 0x0}, {0x30000000, 0x0}, {0x30000000, 0x0}, {0x30000000, 0x0}, {0x30000000, 0x0}},
    {{0x0, 0x0}, {0x1c23c00, 0x1380009}, {0x1c93a02, 0x23880a2}, {0x1d03804, 0x339013b}, {0x14071507, 0x2000023b}, {0x2d95a06, 0x45982d2}, {0x14173107, 0x2000437a}, {0x600808, 0x50a03ea}, {0x14274d07, 0x200484da}, {0x28000a, 0x6028546}, {0x2ea5c0a, 0x65a85b9}, {0x14376907, 0x2004c631}, {0x170280c, 0x72b06a6}, {0x14478507, 0x20090782}, {0xb8100e, 0x81387ef}, {0x1457a107, 0x200948d3}, {0x37f6e0f, 0x96bc933}, {0x1467bd07, 0x200d89af}, {0x1477d907, 0x200dca58}, {0x1487311c, 0x98020b0e}, {0x1497a11c, 0x980a4c01}, {0x14a73123, 0xba028cf4}, {0x14b7a123, 0xba0acde7}, {0x14c7312a, 0xdc030ed9}, {0x14d7a12a, 0xdc0b4fb0}, {0x30000000, 0x0}, {0x30000000, 0x0}, {0x30000000, 0x0}, {0x30000000, 0x0}, {0x30000000, 0x0}, {0x30000000, 0x0}, {0x30000000, 0x0}},
    {{0x0, 0x0}, {0x2024400, 0x140000a}, {0x2094202, 0x24080a3}, {0x2104004, 0x341013c}, {0x1408000e, 0x75000246}, {0x5a0c06, 0x40982e2}, {0x14181c0e, 0x75004390}, {0x2204008, 0x54203fd}, {0x1232608, 0x5220476}, {0x1428380e, 0x750484f0}, {0xe91a0a, 0x61a857a}, {0x1438540e, 0x7504c646}, {0x2f0580c, 0x75b06b6}, {0x1448700e, 0x75090797}, {0x2b8500e, 0x8538804}, {0x14588c0e, 0x750948e8}, {0x1468a80e, 0x750d89b9}, {0x1478c40e, 0x750dca62}, {0x1488381c, 0x98060b1d}, {0x1498a81c, 0x980e4c10}, {0x14a83823, 0xba068d03}, {0x14b8a823, 0xba0ecdf6}, {0x14c8382a, 0xdc070ee9}, {0x14d8a82a, 0xdc0f4fbd}, {0x30000000, 0x0}, {0x30000000, 0x0}, {0x30000000, 0x0}, {0x30000000, 0x0}, {0x30000000, 0x0}, {0x30000000, 0x0}, {0x30000000, 0x0}, {0x30000000, 0x0}},
    {{0x0, 0x0}, {0x2424c00, 0x148000b}, {0x2494a02, 0x24880a4}, {0x2504804, 0x349013d}, {0x14090015, 0x64000251}, {0x2a483833, 0x3a8282f4}, {0x14191c15, 0x640043a6}, {0x3e07808, 0x57a040f}, {0x2e35e08, 0x55a0489}, {0x14293815, 0x64048506}, {0x1a9320a, 0x6328582}, {0x14395415, 0x6404c65b}, {0xf11a0c, 0x71b06cb}, {0x14497015, 0x640907ac}, {0x1792a0e, 0x82b8821}, {0x14598c15, 0x640948fd}, {0x1469a815, 0x640d89c4}, {0x1479c415, 0x640dca6d}, {0x14893f1c, 0x98060b2c}, {0x1499af1c, 0x980e4c1f}, {0x14a93f23, 0xba068d12}, {0x14b9af23, 0xba0ece05}, {0x14c93f2a, 0xdc070ef6}, {0x14d9af2a, 0xdc0f4fca}, {0x30000000, 0x0}, {0x30000000, 0x0}, {0x30000000, 0x0}, {0x30000000, 0x0}, {0x30000000, 0x0}, {0x30000000, 0x0}, {0x30000000, 0x0}, {0x30000000, 0x0}},
    {{0x0, 0x0}, {0x2825400, 0x150000d}, {0x2895202, 0x25080a6}, {0x2905004, 0x351013f}, {0x2a200031, 0x8001cd}, {0x140a070e, 0x7500025d}, {0x1b0606, 0x401830b}, {0x141a230e, 0x750043bc}, {0x3216208, 0x5620434}, {0x142a3f0e, 0x7504851c}, {0x2694a0a, 0x64a8589}, {0x143a5b0e, 0x7504c670}, {0x331620c, 0x76306e3}, {0x144a770e, 0x750907c1}, {0x3b9720e, 0x8738839}, {0x145a930e, 0x75094912}, {0x146aaf0e, 0x750d89cf}, {0x147acb0e, 0x750dca77}, {0x148a461c, 0x98060b3c}, {0x149ab61c, 0x980e4c2e}, {0x14aa4623, 0xba068d21}, {0x14bab623, 0xba0ece14}, {0x14ca462a, 0xdc070f03}, {0x14dab62a, 0xdc0f4fd8}, {0x30000000, 0x0}, {0x30000000, 0x0}, {0x30000000, 0x0}, {0x30000000, 0x0}, {0x30000000, 0x0}, {0x30000000, 0x0}, {0x30000000, 0x0}, {0x30000000, 0x0}},
    {{0x0, 0x0}, {0x2c25c00, 0x158000e}, {0x2c95a02, 0x25880a7}, {0x2d05804, 0x3590140}, {0x2a210032, 0x18001ce}, {0x140b0715, 0x64000273}, {0x19b3606, 0x431831c}, {0x141b2315, 0x640043d2}, {0x1222408, 0x522044a}, {0x142b3f15, 0x64048532}, {0xaa140a, 0x61285a1}, {0x143b5b15, 0x6404c685}, {0x1b2340c, 0x73306fd}, {0x144b7715, 0x640907d6}, {0x1fa3c0e, 0x93b884f}, {0x145b9315, 0x64094927}, {0x146baf15, 0x640d89d9}, {0x147bcb15, 0x640dca82}, {0x148b4d1c, 0x98060b4b}, {0x149bbd1c, 0x980e4c3e}, {0x14ab4d23, 0xba068d30}, {0x14bbbd23, 0xba0ece23}, {0x14cb4d2a, 0xdc070f10}, {0x14dbbd2a, 0xdc0f4fe5}, {0x30000000, 0x0}, {0x30000000, 0x0}, {0x30000000, 0x0}, {0x30000000, 0x0}, {0x30000000, 0x0}, {0x30000000, 0x0}, {0x30000000, 0x0}, {0x30000000, 0x0}},
    {{0x0, 0x0}, {0x3026400, 0x160000f}, {0x3096202, 0x26080a8}, {0x3106004, 0x3610141}, {0x2a220731, 0x78001cf}, {0x140c1c00, 0x31000289}, {0x2db5e06, 0x4598329}, {0x141c3800, 0x310443e8}, {0x3226408, 0x5620460}, {0x142c5400, 0x31048548}, {0x32a640a, 0x66285bc}, {0x143c7000, 0x3108c69a}, {0x3f27c0c, 0x77b0713}, {0x144c8c00, 0x310907eb}, {0x3fa7c0e, 0x97b8864}, {0x145ca800, 0x310d493b}, {0x146cc400, 0x310d89e4}, {0x147cd20e, 0x750dca8c}, {0x148c541c, 0x98060b5a}, {0x149cc41c, 0x980e4c4d}, {0x14ac5423, 0xba068d40}, {0x14bcc423, 0xba0ece33}, {0x14cc542a, 0xdc070f1e}, {0x14dcc42a, 0xdc0f4ff2}, {0x30000000, 0x0}, {0x30000000, 0x0}, {0x30000000, 0x0}, {0x30000000, 0x0}, {0x30000000, 0x0}, {0x30000000, 0x0}, {0x30000000, 0x0}, {0x30000000, 0x0}},
    {{0x0, 0x0}, {0x3426c00, 0x1680011}, {0x3496a02, 0x26880aa}, {0x3506804, 0x3690143}, {0x2a230732, 0x88001d1}, {0x140d1c07, 0x2000029f}, {0x5c0807, 0x409c33a}, {0x141d3807, 0x200443fe}, {0x1632e08, 0x52a0478}, {0x142d5407, 0x2004855e}, {0x16b2e0a, 0x62a85d3}, {0x143d7007, 0x2008c6af}, {0x2734e0c, 0x84b072f}, {0x144d8c07, 0x20090800}, {0x1bb360e, 0x9338878}, {0x145da807, 0x200d4946}, {0x146dc407, 0x200d89ee}, {0x147dd215, 0x640dca97}, {0x148d5b1c, 0x98060b69}, {0x149dcb1c, 0x980e4c5c}, {0x14ad5b23, 0xba068d4f}, {0x14bdcb23, 0xba0ece42}, {0x14cd5b2a, 0xdc070f2b}, {0x14ddcb2a, 0xdc0f5000}, {0x30000000, 0x0}, {0x30000000, 0x0}, {0x30000000, 0x0}, {0x30000000, 0x0}, {0x30000000, 0x0}, {0x30000000, 0x0}, {0x30000000, 0x0}, {0x30000000, 0x0}},
    {{0x0, 0x0}, {0x3827400, 0x1700012}, {0x3897202, 0x27080ab}, {0x3907004, 0x3710144}, {0x2a240e31, 0xe8041d2}, {0x140e2300, 0x310002b5}, {0x19c3007, 0x431c348}, {0x141e3f00, 0x31044414}, {0x3636e08, 0x56a048e}, {0x142e5b00, 0x31048573}, {0x3ab760a, 0x67285eb}, {0x143e7700, 0x3108c6c4}, {0x74080d, 0x80b4744}, {0x144e9300, 0x31090815}, {0x3bb760e, 0x973888d}, {0x145eaf00, 0x310d4950}, {0x146ecb00, 0x310d89f9}, {0x147ed90e, 0x750dcaa1}, {0x148e621c, 0x98060b78}, {0x149ed21c, 0x980e4c6b}, {0x14ae6223, 0xba068d5e}, {0x14bed223, 0xba0ece51}, {0x14ce622a, 0xdc070f38}, {0x14ded22a, 0xdc0f500d}, {0x30000000, 0x0}, {0x30000000, 0x0}, {0x30000000, 0x0}, {0x30000000, 0x0}, {0x30000000, 0x0}, {0x30000000, 0x0}, {0x30000000, 0x0}, {0x30000000, 0x0}},
    {{0x0, 0x0}, {0x3c27c00, 0x1780013}, {0x3c97a02, 0x27880ac}, {0x3d07804, 0x3790145}, {0x2a250e32, 0xf8041d4}, {0x140f2307, 0x200002cb}, {0x2dc5807, 0x459c355}, {0x141f3f07, 0x2004442a}, {0x2244009, 0x54244ad}, {0x142f5b07, 0x20048588}, {0x16c280b, 0x72ac5fd}, {0x143f7707, 0x2008c6d9}, {0x234400d, 0x8434756}, {0x144f9307, 0x2009082a}, {0x17c280f, 0x92bc8a0}, {0x145faf07, 0x200d495b}, {0x146fcb07, 0x200d8a03}, {0x147fd915, 0x640dcaac}, {0x148f691c, 0x98060b87}, {0x149fd91c, 0x980e4c7a}, {0x14af6923, 0xba068d6d}, {0x14bfd923, 0xba0ece60}, {0x14cf692a, 0xdc070f46}, {0x14dfd92a, 0xdc0f501a}, {0x30000000, 0x0}, {0x30000000, 0x0}, {0x30000000, 0x0}, {0x30000000, 0x0}, {0x30000000, 0x0}, {0x30000000, 0x0}, {0x30000000, 0x0}, {0x30000000, 0x0}},
    {{0x0, 0x0}, {0x30600, 0x1000015}, {0xa0402, 0x20080ae}, {0x110204, 0x3010147}, {0x14e00001, 0x310001ef}, {0x170605, 0x401425c}, {0x14f00e0f, 0x750042e3}, {0x9d1207, 0x411c369}, {0x15002a0f, 0x75008443}, {0xa51209, 0x61244c8}, {0x1510460f, 0x7504c5a0}, {0x3ac700b, 0x772c615}, {0x1520620f, 0x750506f1}, {0x35020d, 0x803476b}, {0x15307e0f, 0x75094842}, {0x37c680f, 0x96bc8b5}, {0x15409a0f, 0x75098967}, {0x1550b60f, 0x750dca0f}, {0x1560001d, 0x98020ab8}, {0x1570701d, 0x980a4b99}, {0x15800024, 0xba028c8b}, {0x15907024, 0xba0acd7e}, {0x15a0002b, 0xdc030e71}, {0x15b0702b, 0xdc0b4f55}, {0x30000000, 0x0}, {0x30000000, 0x0}, {0x30000000, 0x0}, {0x30000000, 0x0}, {0x30000000, 0x0}, {0x30000000, 0x0}, {0x30000000, 0x0}, {0x30000000, 0x0}},
    {{0x0, 0x0}, {0x430e00, 0x1080016}, {0x4a0c02, 0x20880af}, {0x510a04, 0x3090148}, {0x14e10008, 0x200001fa}, {0x1d73e05, 0x439426d}, {0x14f10e16, 0x640042f9}, {0x21d4207, 0x441c379}, {0x15012a16, 0x64008459}, {0x2a55209, 0x65244de}, {0x15114616, 0x6404c5b5}, {0x1ad320b, 0x732c62a}, {0x15216216, 0x64050706}, {0x1f53a0d, 0x83b477d}, {0x38000e, 0x80387ea}, {0x15317e16, 0x64094857}, {0x3bd720f, 0x973c8e2}, {0x15419a16, 0x64098971}, {0x1551b616, 0x640dca1a}, {0x1561071d, 0x98020ac2}, {0x1571771d, 0x980a4ba8}, {0x15810724, 0xba028c9b}, {0x15917724, 0xba0acd8d}, {0x15a1072b, 0xdc030e80}, {0x15b1772b, 0xdc0b4f62}, {0x30000000, 0x0}, {0x30000000, 0x0}, {0x30000000, 0x0}, {0x30000000, 0x0}, {0x30000000, 0x0}, {0x30000000, 0x0}, {0x30000000, 0x0}},
    {{0x0, 0x0}, {0x831600, 0x1100017}, {0x8a1402, 0x21080b0}, {0x911204, 0x3110149}, {0x14e20701, 0x31000205}, {0x3576e05, 0x469427f}, {0x14f2150f, 0x7500430f}, {0x3dd7a07, 0x479c38b}, {0x1502310f, 0x7500846f}, {0xa61409, 0x61244f4}, {0x15124d0f, 0x7504c5ca}, {0x3ad720b, 0x772c63f}, {0x1522690f, 0x7505071b}, {0x3b5720d, 0x8734790}, {0x238400e, 0x84387ff}, {0x1532850f, 0x7509486c}, {0xbe140f, 0x913c8ec}, {0x1542a10f, 0x7509897c}, {0x1552bd0f, 0x750dca24}, {0x15620e1d, 0x98020acd}, {0x15727e1d, 0x980a4bb7}, {0x15820e24, 0xba028caa}, {0x15927e24, 0xba0acd9d}, {0x15a20e2b, 0xdc030e8f}, {0x15b27e2b, 0xdc0b4f6f}, {0x30000000, 0x0}, {0x30000000, 0x0}, {0x30000000, 0x0}, {0x30000000, 0x0}, {0x30000000, 0x0}, {0x30000000, 0x0}, {0x30000000, 0x0}},
    {{0x0, 0x0}, {0xc31e00, 0x1180018}, {0xca1c02, 0x21880b1}, {0xd11a04, 0x319014a}, {0x14e30708, 0x20000210}, {0xd81806, 0x4198290}, {0x14f31516, 0x64004325}, {0x15e2c07, 0x529c39d}, {0x15033116, 0x64008485}, {0x2664c09, 0x64a4507}, {0x15134d16, 0x6404c5df}, {0x16e2c0b, 0x72ac652}, {0x15236916, 0x64050730}, {0x1762c0d, 0x82b47a3}, {0x15338516, 0x64094881}, {0x3fd7a0f, 0x97bc8e3}, {0x1543a116, 0x64098986}, {0x1553bd16, 0x640dca2f}, {0x1563151d, 0x98020ad7}, {0x1573851d, 0x980a4bc6}, {0x15831524, 0xba028cb9}, {0x15938524, 0xba0acdac}, {0x15a3152b, 0xdc030e9f}, {0x15b3852b, 0xdc0b4f7d}, {0x30000000, 0x0}, {0x30000000, 0x0}, {0x30000000, 0x0}, {0x30000000, 0x0}, {0x30000000, 0x0}, {0x30000000, 0x0}, {0x30000000, 0x0}, {0x30000000, 0x0}},
    {{0x0, 0x0}, {0x1032600, 0x120001a}, {0x10a2402, 0x22080b3}, {0x1112204, 0x321014c}, {0x14e40e01, 0x3100021b}, {0x2584806, 0x44982a0}, {0x14f42a01, 0x3100433b}, {0x35e6c07, 0x569c3b3}, {0x15044601, 0x3104849b}, {0x270609, 0x602451a}, {0x15146201, 0x3104c5f4}, {0x32e640b, 0x762c664}, {0x15247e01, 0x31090745}, {0x236440d, 0x84347ab}, {0x139220e, 0x823881f}, {0x15349a01, 0x31094896}, {0x27e4c0f, 0x94bc8fe}, {0x1544b601, 0x310d8991}, {0x1554d201, 0x310dca39}, {0x15641c1d, 0x98020ae2}, {0x15748c1d, 0x980a4bd5}, {0x15841c24, 0xba028cc8}, {0x15948c24, 0xba0acdbb}, {0x15a41c2b, 0xdc030eae}, {0x15b48c2b, 0xdc0b4f8a}, {0x30000000, 0x0}, {0x30000000, 0x0}, {0x30000000, 0x0}, {0x30000000, 0x0}, {0x30000000, 0x0}, {0x30000000, 0x0}, {0x30000000, 0x0}},
    {{0x0, 0x0}, {0x1432e00, 0x128001b}, {0x14a2c02, 0x22880b4}, {0x1512a04, 0x329014d}, {0x14e50e08, 0x20000226}, {0x2a454632, 0x478242b2}, {0x14f52a08, 0x20004351}, {0x11f2607, 0x521c3c6}, {0x15054608, 0x200484b1}, {0x1a73609, 0x632452b}, {0x15156208, 0x2004c609}, {0x6f0e0b, 0x70ac671}, {0x3716a0c, 0x76b06e5}, {0x15257e08, 0x2009075a}, {0x1f73e0d, 0x83b47d1}, {0x15359a08, 0x200948ac}, {0x3f060f, 0x903c911}, {0x1545b608, 0x200d899b}, {0x1555d208, 0x200dca44}, {0x1565231d, 0x98020af2}, {0x1575931d, 0x980a4be4}, {0x15852324, 0xba028cd7}, {0x15959324, 0xba0acdca}, {0x15a5232b, 0xdc030ebd}, {0x15b5932b, 0xdc0b4f97}, {0x30000000, 0x0}, {0x30000000, 0x0}, {0x30000000, 0x0}, {0x30000000, 0x0}, {0x30000000, 0x0}, {0x30000000, 0x0}, {0x30000000, 0x0}},
    {{0x0, 0x0}, {0x1833600, 0x130001c}, {0x18a3402, 0x23080b5}, {0x1913204, 0x331014e}, {0x14e61501, 0x31000231}, {0x1993206, 0x43182c4}, {0x14f63101, 0x31004367}, {0x2df5e07, 0x559c3d9}, {0x15064d01, 0x310484c7}, {0x3276609, 0x662453b}, {0x15166901, 0x3104c61e}, {0x16f2e0b, 0x72ac67c}, {0x15268501, 0x3109076f}, {0x3f67c0d, 0x87b47bc}, {0x3796a0e, 0x86b8836}, {0x1536a101, 0x310948c1}, {0x1ff3e0f, 0x93bc922}, {0x1546bd01, 0x310d89a6}, {0x1556d901, 0x310dca4e}, {0x15662a1d, 0x98020b01}, {0x15769a1d, 0x980a4bf4}, {0x15862a24, 0xba028ce6}, {0x15969a24, 0xba0acdd9}, {0x15a62a2b, 0xdc030ecc}, {0x15b69a2b, 0xdc0b4fa4}, {0x30000000, 0x0}, {0x30000000, 0x0}, {0x30000000, 0x0}, {0x30000000, 0x0}, {0x30000000, 0x0}, {0x30000000, 0x0}, {0x30000000, 0x0}},
    {{0x0, 0x0}, {0x1c33e00, 0x138001e}, {0x1ca3c02, 0x23880b7}, {0x1d13a04, 0x3390150}, {0x14e71508, 0x2000023c}, {0x3196206, 0x46182d4}, {0x14f73108, 0x2000437d}, {0xa01008, 0x51203ec}, {0x15074d08, 0x200484dd}, {0x68080a, 0x60a8549}, {0x36a6c0a, 0x66a85be}, {0x15176908, 0x2004c633}, {0x1f0380c, 0x73b06aa}, {0x15278508, 0x20090785}, {0xf8180e, 0x81b87f2}, {0x1537a108, 0x200948d6}, {0x3bf760f, 0x973c936}, {0x1547bd08, 0x200d89b0}, {0x1557d908, 0x200dca59}, {0x1567311d, 0x98020b10}, {0x1577a11d, 0x980a4c03}, {0x15873124, 0xba028cf6}, {0x1597a124, 0xba0acde9}, {0x15a7312b, 0xdc030edb}, {0x15b7a12b, 0xdc0b4fb2}, {0x30000000, 0x0}, {0x30000000, 0x0}, {0x30000000, 0x0}, {0x30000000, 0x0}, {0x30000000, 0x0}, {0x30000000, 0x0}, {0x30000000, 0x0}},
    {{0x0, 0x0}, {0x2034600, 0x140001f}, {0x20a4402, 0x24080b8}, {0x2114204, 0x3410151}, {0x14e8000f, 0x75000247}, {0x9a1406, 0x41182e5}, {0x14f81c0f, 0x75004393}, {0x2604808, 0x54a0400}, {0x1508380f, 0x750484f3}, {0x1e8380a, 0x63a8558}, {0x12b260a, 0x62285d1}, {0x1518540f, 0x7504c648}, {0x370680c, 0x76b06bb}, {0x1528700f, 0x7509079a}, {0x338600e, 0x863880a}, {0x15388c0f, 0x750948eb}, {0x1548a80f, 0x750d89bb}, {0x1558c40f, 0x750dca63}, {0x1568381d, 0x98060b1f}, {0x1578a81d, 0x980e4c12}, {0x15883824, 0xba068d05}, {0x1598a824, 0xba0ecdf8}, {0x15a8382b, 0xdc070eeb}, {0x15b8a82b, 0xdc0f4fbf}, {0x30000000, 0x0}, {0x30000000, 0x0}, {0x30000000, 0x0}, {0x30000000, 0x0}, {0x30000000, 0x0}, {0x30000000, 0x0}, {0x30000000, 0x0}, {0x30000000, 0x0}},
    {{0x0, 0x0}, {0x2434e00, 0x1480020}, {0x24a4c02, 0x24880b9}, {0x2514a04, 0x3490152}, {0x14e90016, 0x64000252}, {0x21a4406, 0x44182f5}, {0x14f91c16, 0x640043a9}, {0x210208, 0x5020413}, {0x3236608, 0x562048c}, {0x15093816, 0x64048509}, {0x1e93a0a, 0x63a8583}, {0x15195416, 0x6404c65e}, {0x131220c, 0x72306cd}, {0x15297016, 0x640907af}, {0x1f93a0e, 0x83b8825}, {0x15398c16, 0x64094900}, {0x1549a816, 0x640d89c5}, {0x1559c416, 0x640dca6e}, {0x15693f1d, 0x98060b2e}, {0x1579af1d, 0x980e4c21}, {0x15893f24, 0xba068d14}, {0x1599af24, 0xba0ece07}, {0x15a93f2b, 0xdc070ef8}, {0x15b9af2b, 0xdc0f4fcc}, {0x30000000, 0x0}, {0x30000000, 0x0}, {0x30000000, 0x0}, {0x30000000, 0x0}, {0x30000000, 0x0}, {0x30000000, 0x0}, {0x30000000, 0x0}, {0x30000000, 0x0}},
    {{0x0, 0x0}, {0x2835600, 0x1500022}, {0x28a5402, 0x25080bb}, {0x2915204, 0x3510154}, {0x2a261531, 0x158041d5}, {0x14ea070f, 0x75000260}, {0x11b2606, 0x4218316}, {0x14fa230f, 0x750043bf}, {0x3a17208, 0x5720439}, {0x150a3f0f, 0x7504851e}, {0x2e95a0a, 0x65a858f}, {0x151a5b0f, 0x7504c673}, {0x3b1720c, 0x77306e8}, {0x152a770f, 0x750907c4}, {0x3a040e, 0x903883e}, {0x153a930f, 0x75094915}, {0x154aaf0f, 0x750d89d0}, {0x155acb0f, 0x750dca78}, {0x156a461d, 0x98060b3d}, {0x157ab61d, 0x980e4c30}, {0x158a4624, 0xba068d23}, {0x159ab624, 0xba0ece16}, {0x15aa462b, 0xdc070f05}, {0x15bab62b, 0xdc0f4fda}, {0x30000000, 0x0}, {0x30000000, 0x0}, {0x30000000, 0x0}, {0x30000000, 0x0}, {0x30000000, 0x0}, {0x30000000, 0x0}, {0x30000000, 0x0}, {0x30000000, 0x0}},
    {{0x0, 0x0}, {0x2c35e00, 0x1580023}, {0x2ca5c02, 0x25880bc}, {0x2d15a04, 0x3590155}, {0x2a271532, 0x168041d6}, {0x14eb0716, 0x64000276}, {0x2a4a3f33, 0x41828320}, {0x14fb2316, 0x640043d5}, {0x1a23408, 0x532044f}, {0x150b3f16, 0x64048534}, {0x16a2c0a, 0x62a85a9}, {0x151b5b16, 0x6404c688}, {0x1f23c0c, 0x73b06fe}, {0x152b7716, 0x640907d9}, {0x23a440e, 0x9438853}, {0x153b9316, 0x6409492a}, {0x154baf16, 0x640d89da}, {0x155bcb16, 0x640dca83}, {0x156b4d1d, 0x98060b4d}, {0x157bbd1d, 0x980e4c40}, {0x158b4d24, 0xba068d32}, {0x159bbd24, 0xba0ece25}, {0x15ab4d2b, 0xdc070f12}, {0x15bbbd2b, 0xdc0f4fe7}, {0x30000000, 0x0}, {0x30000000, 0x0}, {0x30000000, 0x0}, {0x30000000, 0x0}, {0x30000000, 0x0}, {0x30000000, 0x0}, {0x30000000, 0x0}, {0x30000000, 0x0}},
    {{0x0, 0x0}, {0x3036600, 0x1600024}, {0x30a6402, 0x26080bd}, {0x3116204, 0x3610156}, {0x2a280033, 0x28081d8}, {0x14ec1c01, 0x3100028c}, {0x35b6e06, 0x469832f}, {0x14fc3801, 0x310443eb}, {0x3a27408, 0x5720465}, {0x150c5401, 0x3104854a}, {0x3ea7c0a, 0x67a85c2}, {0x151c7001, 0x3108c69d}, {0x33060c, 0x8030717}, {0x152c8c01, 0x310907ee}, {0x3b060e, 0x9038868}, {0x153ca801, 0x310d493c}, {0x154cc401, 0x310d89e5}, {0x155cd20f, 0x750dca8e}, {0x156c541d, 0x98060b5c}, {0x157cc41d, 0x980e4c4f}, {0x158c5424, 0xba068d42}, {0x159cc424, 0xba0ece34}, {0x15ac542b, 0xdc070f20}, {0x15bcc42b, 0xdc0f4ff4}, {0x30000000, 0x0}, {0x30000000, 0x0}, {0x30000000, 0x0}, {0x30000000, 0x0}, {0x30000000, 0x0}, {0x30000000, 0x0}, {0x30000000, 0x0}, {0x30000000, 0x0}},
    {{0x0, 0x0}, {0x3436e00, 0x1680026}, {0x34a6c02, 0x26880bf}, {0x3516a04, 0x3690158}, {0x2a290034, 0x38081d9}, {0x14ed1c08, 0x200002a2}, {0x9c1007, 0x411c33d}, {0x14fd3808, 0x20044401}, {0x1a33608, 0x532047b}, {0x150d5408, 0x20048560}, {0x1ab360a, 0x63285d6}, {0x151d7008, 0x2008c6b2}, {0x2b3560c, 0x8530732}, {0x152d8c08, 0x20090803}, {0x1fb3e0e, 0x93b8879}, {0x153da808, 0x200d4947}, {0x154dc408, 0x200d89ef}, {0x155dd216, 0x640dca98}, {0x156d5b1d, 0x98060b6b}, {0x157dcb1d, 0x980e4c5e}, {0x158d5b24, 0xba068d51}, {0x159dcb24, 0xba0ece44}, {0x15ad5b2b, 0xdc070f2d}, {0x15bdcb2b, 0xdc0f5001}, {0x30000000, 0x0}, {0x30000000, 0x0}, {0x30000000, 0x0}, {0x30000000, 0x0}, {0x30000000, 0x0}, {0x30000000, 0x0}, {0x30000000, 0x0}, {0x30000000, 0x0}},
    {{0x0, 0x0}, {0x3837600, 0x1700027}, {0x38a7402, 0x27080c0}, {0x3917204, 0x3710159}, {0x2a2a0733, 0x98081da}, {0x14ee2301, 0x310002b7}, {0x1dc3807, 0x439c349}, {0x14fe3f01, 0x31044417}, {0x3a37608, 0x5720491}, {0x150e5b01, 0x31048576}, {0x3eb7e0a, 0x67a85ec}, {0x151e7701, 0x3108c6c7}, {0xb4100d, 0x8134747}, {0x152e9301, 0x31090818}, {0x3fb7e0e, 0x97b888f}, {0x153eaf01, 0x310d4951}, {0x154ecb01, 0x310d89fa}, {0x155ed90f, 0x750dcaa3}, {0x156e621d, 0x98060b7a}, {0x157ed21d, 0x980e4c6d}, {0x158e6224, 0xba068d60}, {0x159ed224, 0xba0ece53}, {0x15ae622b, 0xdc070f3a}, {0x15bed22b, 0xdc0f500f}, {0x30000000, 0x0}, {0x30000000, 0x0}, {0x30000000, 0x0}, {0x30000000, 0x0}, {0x30000000, 0x0}, {0x30000000, 0x0}, {0x30000000, 0x0}, {0x30000000, 0x0}},
    {{0x0, 0x0}, {0x3c37e00, 0x1780028}, {0x3ca7c02, 0x27880c1}, {0x3d17a04, 0x379015a}, {0x2a2b0734, 0xa8081dc}, {0x14ef2308, 0x200002cd}, {0x31c6007, 0x461c358}, {0x14ff3f08, 0x2004442d}, {0x2644809, 0x54a44af}, {0x150f5b08, 0x2004858b}, {0x1ac300b, 0x732c600}, {0x151f7708, 0x2008c6dc}, {0x274480d, 0x84b4759}, {0x152f9308, 0x2009082d}, {0x1bc300f, 0x933c8a2}, {0x153faf08, 0x200d495c}, {0x154fcb08, 0x200d8a05}, {0x155fd916, 0x640dcaad}, {0x156f691d, 0x98060b89}, {0x157fd91d, 0x980e4c7c}, {0x158f6924, 0xba068d6f}, {0x159fd924, 0xba0ece62}, {0x15af692b, 0xdc070f48}, {0x15bfd92b, 0xdc0f501c}, {0x30000000, 0x0}, {0x30000000, 0x0}, {0x30000000, 0x0}, {0x30000000, 0x0}, {0x30000000, 0x0}, {0x30000000, 0x0}, {0x30000000, 0x0}, {0x30000000, 0x0}},
    {{0x0, 0x0}, {0x40001, 0x100402a}, {0xb0602, 0x20080c3}, {0x120404, 0x301015c}, {0x15c00002, 0x310001f0}, {0x570e05, 0x409425e}, {0x15d00e10, 0x750042e6}, {0xdd1a07, 0x419c36b}, {0x15e02a10, 0x75008446}, {0x1252209, 0x62244cd}, {0x15f04610, 0x7504c5a3}, {0x3ec780b, 0x77ac616}, {0x16006210, 0x750506f4}, {0x750a0d, 0x80b476e}, {0x16107e10, 0x75094845}, {0x3bc700f, 0x973c8b7}, {0x16209a10, 0x75098968}, {0x1630b610, 0x750dca10}, {0x1640001e, 0x98020ab9}, {0x1650701e, 0x980a4b9a}, {0x16600025, 0xba028c8d}, {0x16707025, 0xba0acd80}, {0x1680002c, 0xdc030e73}, {0x1690702c, 0xdc0b4f57}, {0x30000000, 0x0}, {0x30000000, 0x0}, {0x30000000, 0x0}, {0x30000000, 0x0}, {0x30000000, 0x0}, {0x30000000, 0x0}, {0x30000000, 0x0}, {0x30000000, 0x0}},
    {{0x0, 0x0}, {0x440801, 0x108402b}, {0x4b0e02, 0x20880c4}, {0x520c04, 0x309015d}, {0x15c10009, 0x200001fb}, {0x2a423133, 0x33820270}, {0x15d10e17, 0x640042fc}, {0x25d4a07, 0x449c37c}, {0x15e12a17, 0x6400845c}, {0x2e55a09, 0x65a44e1}, {0x15f14617, 0x6404c5b8}, {0x1ed3a0b, 0x73ac62b}, {0x16016217, 0x64050709}, {0x235420d, 0x8434781}, {0x16117e17, 0x6409485a}, {0x13d220f, 0x923c8c7}, {0x16219a17, 0x64098972}, {0x1631b617, 0x640dca1b}, {0x1641071e, 0x98020ac4}, {0x1651771e, 0x980a4baa}, {0x16610725, 0xba028c9c}, {0x16717725, 0xba0acd8f}, {0x1681072c, 0xdc030e82}, {0x1691772c, 0xdc0b4f64}, {0x30000000, 0x0}, {0x30000000, 0x0}, {0x30000000, 0x0}, {0x30000000, 0x0}, {0x30000000, 0x0}, {0x30000000, 0x0}, {0x30000000, 0x0}, {0x30000000, 0x0}},
    {{0x0, 0x0}, {0x841001, 0x110402c}, {0x8b1602, 0x21080c5}, {0x921404, 0x311015e}, {0x15c20702, 0x31000206}, {0x3977605, 0x4714282}, {0x15d21510, 0x75004312}, {0x2a4f5b32, 0x5c82c38e}, {0x15e23110, 0x75008472}, {0xe61c09, 0x61a44f7}, {0x15f24d10, 0x7504c5cd}, {0x3ed7a0b, 0x77ac641}, {0x16026910, 0x7505071e}, {0x3f57a0d, 0x87b4792}, {0x16128510, 0x7509486f}, {0x27d4a0f, 0x94bc8d4}, {0x1622a110, 0x7509897d}, {0x1632bd10, 0x750dca25}, {0x16420e1e, 0x98020ace}, {0x16527e1e, 0x980a4bb9}, {0x16620e25, 0xba028cac}, {0x16727e25, 0xba0acd9f}, {0x16820e2c, 0xdc030e91}, {0x16927e2c, 0xdc0b4f71}, {0x30000000, 0x0}, {0x30000000, 0x0}, {0x30000000, 0x0}, {0x30000000, 0x0}, {0x30000000, 0x0}, {0x30000000, 0x0}, {0x30000000, 0x0}, {0x30000000, 0x0}},
    {{0x0, 0x0}, {0xc41801, 0x118402d}, {0xcb1e02, 0x21880c6}, {0xd21c04, 0x319015f}, {0x15c30709, 0x20000211}, {0x1182006, 0x4218292}, {0x15d31517, 0x64004328}, {0x19e3407, 0x531c39f}, {0x15e33117, 0x64008487}, {0x2a65409, 0x652450a}, {0x15f34d17, 0x6404c5e2}, {0x1ae340b, 0x732c654}, {0x31020c, 0x70306c3}, {0x16036917, 0x64050733}, {0x2b6540d, 0x85347b0}, {0x16138517, 0x64094884}, {0x13e240f, 0x923c8f1}, {0x1623a117, 0x64098987}, {0x1633bd17, 0x640dca30}, {0x1643151e, 0x98020ad9}, {0x1653851e, 0x980a4bc8}, {0x16631525, 0xba028cbb}, {0x16738525, 0xba0acdae}, {0x1683152c, 0xdc030ea1}, {0x1693852c, 0xdc0b4f7f}, {0x30000000, 0x0}, {0x30000000, 0x0}, {0x30000000, 0x0}, {0x30000000, 0x0}, {0x30000000, 0x0}, {0x30000000, 0x0}, {0x30000000, 0x0}},
    {{0x0, 0x0}, {0x1042001, 0x120402f}, {0x10b2602, 0x22080c8}, {0x1122404, 0x3210161}, {0x15c40e02, 0x3100021c}, {0x2985006, 0x45182a3}, {0x15d42a02, 0x3100433e}, {0x39e7407, 0x571c3b5}, {0x15e44602, 0x3104849d}, {0x670e09, 0x60a451d}, {0x15f46202, 0x3104c5f7}, {0x36e6c0b, 0x76ac667}, {0x16047e02, 0x31090748}, {0x2764c0d, 0x84b47ad}, {0x1b9320e, 0x8338824}, {0x16149a02, 0x31094899}, {0x2be540f, 0x953c901}, {0x1624b602, 0x310d8992}, {0x1634d202, 0x310dca3b}, {0x16441c1e, 0x98020ae4}, {0x16548c1e, 0x980a4bd7}, {0x16641c25, 0xba028cca}, {0x16748c25, 0xba0acdbd}, {0x16841c2c, 0xdc030eb0}, {0x16948c2c, 0xdc0b4f8c}, {0x30000000, 0x0}, {0x30000000, 0x0}, {0x30000000, 0x0}, {0x30000000, 0x0}, {0x30000000, 0x0}, {0x30000000, 0x0}, {0x30000000, 0x0}},
    {{0x0, 0x0}, {0x1442801, 0x1284030}, {0x14b2e02, 0x22880c9}, {0x1522c04, 0x3290162}, {0x15c50e09, 0x20000227}, {0x190206, 0x40182b3}, {0x15d52a09, 0x20004354}, {0x15f2e07, 0x529c3c9}, {0x15e54609, 0x200484b3}, {0x1e73e09, 0x63a452c}, {0x15f56209, 0x2004c60c}, {0xaf160b, 0x712c674}, {0x3f17a0c, 0x77b06e9}, {0x16057e09, 0x2009075d}, {0x237460d, 0x84347d5}, {0x16159a09, 0x200948ae}, {0x7f0e0f, 0x90bc914}, {0x1625b609, 0x200d899d}, {0x1635d209, 0x200dca45}, {0x1645231e, 0x98020af3}, {0x1655931e, 0x980a4be6}, {0x16652325, 0xba028cd9}, {0x16759325, 0xba0acdcc}, {0x1685232c, 0xdc030ebf}, {0x1695932c, 0xdc0b4f99}, {0x30000000, 0x0}, {0x30000000, 0x0}, {0x30000000, 0x0}, {0x30000000, 0x0}, {0x30000000, 0x0}, {0x30000000, 0x0}, {0x30000000, 0x0}},
    {{0x0, 0x0}, {0x1843001, 0x1304031}, {0x18b3602, 0x23080ca}, {0x1923404, 0x3310163}, {0x15c61502, 0x31000232}, {0x1d93a06, 0x43982c5}, {0x15d63102, 0x3100436a}, {0x31f6607, 0x561c3dc}, {0x15e64d02, 0x310484c9}, {0x3676e09, 0x66a453e}, {0x15f66902, 0x3104c621}, {0x1ef3e0b, 0x73ac680}, {0x16068502, 0x31090772}, {0x770e0d, 0x80b47c2}, {0x3f97a0e, 0x87b883a}, {0x1616a102, 0x310948c3}, {0x23f460f, 0x943c926}, {0x1626bd02, 0x310d89a7}, {0x1636d902, 0x310dca50}, {0x16462a1e, 0x98020b03}, {0x16569a1e, 0x980a4bf6}, {0x16662a25, 0xba028ce8}, {0x16769a25, 0xba0acddb}, {0x16862a2c, 0xdc030ece}, {0x16969a2c, 0xdc0b4fa6}, {0x30000000, 0x0}, {0x30000000, 0x0}, {0x30000000, 0x0}, {0x30000000, 0x0}, {0x30000000, 0x0}, {0x30000000, 0x0}, {0x30000000, 0x0}},
    {{0x0, 0x0}, {0x1c43801, 0x1384033}, {0x1cb3e02, 0x23880cc}, {0x1d23c04, 0x3390165}, {0x15c71509, 0x2000023d}, {0x3596a06, 0x46982d7}, {0x15d73109, 0x20004380}, {0xe01808, 0x51a03ef}, {0x15e74d09, 0x200484df}, {0xe8180a, 0x61a854f}, {0x15f76909, 0x2004c636}, {0x2af560b, 0x752c689}, {0x232440c, 0x7430702}, {0x16078509, 0x20090787}, {0x138200e, 0x82387f4}, {0x1617a109, 0x200948d8}, {0x3ff7e0f, 0x97bc937}, {0x1627bd09, 0x200d89b2}, {0x1637d909, 0x200dca5a}, {0x1647311e, 0x98020b12}, {0x1657a11e, 0x980a4c05}, {0x16673125, 0xba028cf8}, {0x1677a125, 0xba0acdea}, {0x1687312c, 0xdc030edd}, {0x1697a12c, 0xdc0b4fb4}, {0x30000000, 0x0}, {0x30000000, 0x0}, {0x30000000, 0x0}, {0x30000000, 0x0}, {0x30000000, 0x0}, {0x30000000, 0x0}, {0x30000000, 0x0}},
    {{0x0, 0x0}, {0x2044001, 0x1404034}, {0x20b4602, 0x24080cd}, {0x2124404, 0x3410166}, {0x15c80010, 0x75000248}, {0xda1c06, 0x41982e8}, {0x15d81c10, 0x75004396}, {0x2a05008, 0x5520402}, {0x1e33e08, 0x53a047d}, {0x15e83810, 0x750484f5}, {0x1692a0a, 0x62a857f}, {0x15f85410, 0x7504c64b}, {0x3b0700c, 0x77306be}, {0x16087010, 0x7509079c}, {0x378680e, 0x86b880c}, {0x16188c10, 0x750948ed}, {0x1628a810, 0x750d89bc}, {0x1638c410, 0x750dca65}, {0x1648381e, 0x98060b21}, {0x1658a81e, 0x980e4c14}, {0x16683825, 0xba068d07}, {0x1678a825, 0xba0ecdfa}, {0x1688382c, 0xdc070eec}, {0x1698a82c, 0xdc0f4fc1}, {0x30000000, 0x0}, {0x30000000, 0x0}, {0x30000000, 0x0}, {0x30000000, 0x0}, {0x30000000, 0x0}, {0x30000000, 0x0}, {0x30000000, 0x0}, {0x30000000, 0x0}},
    {{0x0, 0x0}, {0x2444801, 0x1484035}, {0x24b4e02, 0x24880ce}, {0x2524c04, 0x3490167}, {0x2a2c1c31, 0x1c80c1dd}, {0x15c90017, 0x64000253}, {0x15d91c17, 0x640043ac}, {0x610a08, 0x50a0416}, {0x15e93817, 0x6404850b}, {0x3a8700a, 0x672856d}, {0x32b660a, 0x66285e6}, {0x15f95417, 0x6404c660}, {0x1712a0c, 0x72b06d0}, {0x16097017, 0x640907b1}, {0x239420e, 0x8438829}, {0x16198c17, 0x64094902}, {0x1629a817, 0x640d89c7}, {0x1639c417, 0x640dca6f}, {0x16493f1e, 0x98060b30}, {0x1659af1e, 0x980e4c23}, {0x16693f25, 0xba068d16}, {0x1679af25, 0xba0ece09}, {0x16893f2c, 0xdc070efa}, {0x1699af2c, 0xdc0f4fce}, {0x30000000, 0x0}, {0x30000000, 0x0}, {0x30000000, 0x0}, {0x30000000, 0x0}, {0x30000000, 0x0}, {0x30000000, 0x0}, {0x30000000, 0x0}, {0x30000000, 0x0}},
    {{0x0, 0x0}, {0x2845001, 0x1504037}, {0x28b5602, 0x25080d0}, {0x2925404, 0x3510169}, {0x2a2d1c32, 0x1d80c1df}, {0x15ca0710, 0x75000262}, {0x9b1606, 0x4118311}, {0x15da2310, 0x750043c2}, {0x3e17a08, 0x57a043b}, {0x15ea3f10, 0x75048521}, {0x329620a, 0x6628591}, {0x15fa5b10, 0x7504c675}, {0x32040c, 0x70306ed}, {0x160a7710, 0x750907c6}, {0x7a0c0e, 0x90b8841}, {0x161a9310, 0x75094918}, {0x162aaf10, 0x750d89d1}, {0x163acb10, 0x750dca7a}, {0x164a461e, 0x98060b3f}, {0x165ab61e, 0x980e4c32}, {0x166a4625, 0xba068d25}, {0x167ab625, 0xba0ece18}, {0x168a462c, 0xdc070f07}, {0x169ab62c, 0xdc0f4fdc}, {0x30000000, 0x0}, {0x30000000, 0x0}, {0x30000000, 0x0}, {0x30000000, 0x0}, {0x30000000, 0x0}, {0x30000000, 0x0}, {0x30000000, 0x0}, {0x30000000, 0x0}},
    {{0x0, 0x0}, {0x2c45801, 0x1584038}, {0x2cb5e02, 0x25880d1}, {0x2d25c04, 0x359016a}, {0x2a2e2331, 0x2380c1e0}, {0x15cb0717, 0x64000278}, {0x21b4606, 0x4418321}, {0x15db2317, 0x640043d8}, {0x1e23c08, 0x53a0451}, {0x15eb3f17, 0x64048537}, {0x1aa340a, 0x63285ac}, {0x15fb5b17, 0x6404c68a}, {0x2724c0c, 0x74b0705}, {0x160b7717, 0x640907db}, {0x27a4c0e, 0x94b8856}, {0x161b9317, 0x6409492d}, {0x162baf17, 0x640d89dc}, {0x163bcb17, 0x640dca84}, {0x164b4d1e, 0x98060b4f}, {0x165bbd1e, 0x980e4c41}, {0x166b4d25, 0xba068d34}, {0x167bbd25, 0xba0ece27}, {0x168b4d2c, 0xdc070f14}, {0x169bbd2c, 0xdc0f4fe9}, {0x30000000, 0x0}, {0x30000000, 0x0}, {0x30000000, 0x0}, {0x30000000, 0x0}, {0x30000000, 0x0}, {0x30000000, 0x0}, {0x30000000, 0x0}, {0x30000000, 0x0}},
    {{0x0, 0x0}, {0x3046001, 0x1604039}, {0x30b6602, 0x26080d2}, {0x3126404, 0x361016b}, {0x2a2f2332, 0x2480c1e1}, {0x15cc1c02, 0x3100028e}, {0x39b7606, 0x4718332}, {0x15dc3802, 0x310443ee}, {0x3e27c08, 0x57a0467}, {0x15ec5402, 0x3104854d}, {0x2b060a, 0x60285c6}, {0x15fc7002, 0x3108c69f}, {0xb3160c, 0x813071c}, {0x160c8c02, 0x310907f1}, {0x7b0e0e, 0x90b886b}, {0x161ca802, 0x310d493e}, {0x162cc402, 0x310d89e6}, {0x163cd210, 0x750dca8f}, {0x164c541e, 0x98060b5e}, {0x165cc41e, 0x980e4c51}, {0x166c5425, 0xba068d43}, {0x167cc425, 0xba0ece36}, {0x168c542c, 0xdc070f22}, {0x169cc42c, 0xdc0f4ff6}, {0x30000000, 0x0}, {0x30000000, 0x0}, {0x30000000, 0x0}, {0x30000000, 0x0}, {0x30000000, 0x0}, {0x30000000, 0x0}, {0x30000000, 0x0}, {0x30000000, 0x0}},
    {{0x0, 0x0}, {0x3446801, 0x168403b}, {0x34b6e02, 0x26880d4}, {0x3526c04, 0x369016d}, {0x2a300e33, 0x108101e3}, {0x15cd1c09, 0x200002a4}, {0xdc1807, 0x419c33f}, {0x15dd3809, 0x20044404}, {0x2234608, 0x5420481}, {0x15ed5409, 0x20048563}, {0x22b460a, 0x64285db}, {0x15fd7009, 0x2008c6b4}, {0x333660c, 0x8630737}, {0x160d8c09, 0x20090806}, {0x23b460e, 0x943887d}, {0x161da809, 0x200d4948}, {0x162dc409, 0x200d89f1}, {0x163dd217, 0x640dca99}, {0x164d5b1e, 0x98060b6d}, {0x165dcb1e, 0x980e4c60}, {0x166d5b25, 0xba068d53}, {0x167dcb25, 0xba0ece45}, {0x168d5b2c, 0xdc070f2f}, {0x169dcb2c, 0xdc0f5003}, {0x30000000, 0x0}, {0x30000000, 0x0}, {0x30000000, 0x0}, {0x30000000, 0x0}, {0x30000000, 0x0}, {0x30000000, 0x0}, {0x30000000, 0x0}, {0x30000000, 0x0}},
    {{0x0, 0x0}, {0x3847001, 0x170403c}, {0x38b7602, 0x27080d5}, {0x3927404, 0x371016e}, {0x2a310e34, 0x118101e4}, {0x15ce2302, 0x310002ba}, {0x2a4c5431, 0x5482c34c}, {0x15de3f02, 0x3104441a}, {0x240009, 0x5024497}, {0x15ee5b02, 0x31048578}, {0x2c000b, 0x702c5f0}, {0x15fe7702, 0x3108c6ca}, {0xf4180d, 0x81b4749}, {0x160e9302, 0x3109081b}, {0x3c000f, 0x903c892}, {0x161eaf02, 0x310d4953}, {0x162ecb02, 0x310d89fb}, {0x163ed910, 0x750dcaa4}, {0x164e621e, 0x98060b7c}, {0x165ed21e, 0x980e4c6f}, {0x166e6225, 0xba068d62}, {0x167ed225, 0xba0ece55}, {0x168e622c, 0xdc070f3c}, {0x169ed22c, 0xdc0f5011}, {0x30000000, 0x0}, {0x30000000, 0x0}, {0x30000000, 0x0}, {0x30000000, 0x0}, {0x30000000, 0x0}, {0x30000000, 0x0}, {0x30000000, 0x0}, {0x30000000, 0x0}},
    {{0x0, 0x0}, {0x3c47801, 0x178403d}, {0x3cb7e02, 0x27880d6}, {0x3d27c04, 0x379016f}, {0x2a321533, 0x178101e5}, {0x15cf2309, 0x200002d0}, {0x35c6807, 0x469c35b}, {0x15df3f09, 0x20044430}, {0x2e45809, 0x55a44b5}, {0x15ef5b09, 0x2004858d}, {0x22c400b, 0x742c605}, {0x15ff7709, 0x2008c6df}, {0x2b4500d, 0x853475c}, {0x160f9309, 0x20090830}, {0x1fc380f, 0x93bc8a4}, {0x161faf09, 0x200d495d}, {0x162fcb09, 0x200d8a06}, {0x163fd917, 0x640dcaae}, {0x164f691e, 0x98060b8b}, {0x165fd91e, 0x980e4c7e}, {0x166f6925, 0xba068d71}, {0x167fd925, 0xba0ece64}, {0x168f692c, 0xdc070f49}, {0x169fd92c, 0xdc0f501e}, {0x30000000, 0x0}, {0x30000000, 0x0}, {0x30000000, 0x0}, {0x30000000, 0x0}, {0x30000000, 0x0}, {0x30000000, 0x0}, {0x30000000, 0x0}, {0x30000000, 0x0}},
    {{0x0, 0x0}, {0x50201, 0x100403f}, {0xc0003, 0x200c0d8}, {0x130604, 0x3010171}, {0x16a00003, 0x310001f2}, {0x971605, 0x4114261}, {0x16b00e11, 0x750042e9}, {0x11d2207, 0x421c36e}, {0x16c02a11, 0x75008448}, {0x1652a09, 0x62a44d0}, {0x16d04611, 0x7504c5a5}, {0x2d020b, 0x702c61a}, {0x16e06211, 0x750506f6}, {0xb5120d, 0x8134771}, {0x16f07e11, 0x75094847}, {0x3fc780f, 0x97bc8b9}, {0x17009a11, 0x75098969}, {0x1710b611, 0x750dca12}, {0x1720001f, 0x98020aba}, {0x1730701f, 0x980a4b9c}, {0x17400026, 0xba028c8f}, {0x17507026, 0xba0acd82}, {0x1760002d, 0xdc030e75}, {0x1770702d, 0xdc0b4f59}, {0x30000000, 0x0}, {0x30000000, 0x0}, {0x30000000, 0x0}, {0x30000000, 0x0}, {0x30000000, 0x0}, {0x30000000, 0x0}, {0x30000000, 0x0}, {0x30000000, 0x0}},
    {{0x0, 0x0}, {0x450a01, 0x1084040}, {0x4c0803, 0x208c0d9}, {0x530e04, 0x3090172}, {0x16a1000a, 0x200001fd}, {0x2174605, 0x4414271}, {0x16b10e18, 0x640042ff}, {0x29d5207, 0x451c37f}, {0x16c12a18, 0x6400845e}, {0x3656a09, 0x66a44e6}, {0x16d14618, 0x6404c5ba}, {0x22d420b, 0x742c62f}, {0x16e16218, 0x6405070b}, {0x2754a0d, 0x84b4783}, {0x16f17e18, 0x6409485d}, {0x17d2a0f, 0x92bc8ca}, {0x17019a18, 0x64098974}, {0x1711b618, 0x640dca1c}, {0x1721071f, 0x98020ac5}, {0x1731771f, 0x980a4bac}, {0x17410726, 0xba028c9e}, {0x17517726, 0xba0acd91}, {0x1761072d, 0xdc030e84}, {0x1771772d, 0xdc0b4f66}, {0x30000000, 0x0}, {0x30000000, 0x0}, {0x30000000, 0x0}, {0x30000000, 0x0}, {0x30000000, 0x0}, {0x30000000, 0x0}, {0x30000000, 0x0}, {0x30000000, 0x0}},
    {{0x0, 0x0}, {0x851201, 0x1104041}, {0x8c1003, 0x210c0da}, {0x931604, 0x3110173}, {0x16a20703, 0x31000208}, {0x3d77e05, 0x4794283}, {0x16b21511, 0x75004315}, {0x1e0407, 0x501c38f}, {0x16c23111, 0x75008474}, {0x1262409, 0x62244f9}, {0x16d24d11, 0x7504c5cf}, {0x2e040b, 0x702c644}, {0x16e26911, 0x75050720}, {0x36040d, 0x8034796}, {0x16f28511, 0x75094872}, {0x2bd520f, 0x953c8d7}, {0x1702a111, 0x7509897e}, {0x1712bd11, 0x750dca27}, {0x17220e1f, 0x98020acf}, {0x17327e1f, 0x980a4bbb}, {0x17420e26, 0xba028cae}, {0x17527e26, 0xba0acda0}, {0x17620e2d, 0xdc030e93}, {0x17727e2d, 0xdc0b4f73}, {0x30000000, 0x0}, {0x30000000, 0x0}, {0x30000000, 0x0}, {0x30000000, 0x0}, {0x30000000, 0x0}, {0x30000000, 0x0}, {0x30000000, 0x0}, {0x30000000, 0x0}},
    {{0x0, 0x0}, {0xc51a01, 0x1184042}, {0xcc1803, 0x218c0db}, {0xd31e04, 0x3190174}, {0x16a3070a, 0x20000213}, {0x1582806, 0x4298295}, {0x16b31518, 0x6400432b}, {0x1de3c07, 0x539c3a1}, {0x16c33118, 0x6400848a}, {0x2e65c09, 0x65a450d}, {0x16d34d18, 0x6404c5e4}, {0x1ee3c0b, 0x73ac656}, {0x710a0c, 0x70b06c6}, {0x16e36918, 0x64050736}, {0x2f65c0d, 0x85b47b3}, {0x16f38518, 0x64094887}, {0x17e2c0f, 0x92bc8f4}, {0x1703a118, 0x64098989}, {0x1713bd18, 0x640dca31}, {0x1723151f, 0x98020ada}, {0x1733851f, 0x980a4bca}, {0x17431526, 0xba028cbd}, {0x17538526, 0xba0acdb0}, {0x1763152d, 0xdc030ea2}, {0x1773852d, 0xdc0b4f80}, {0x30000000, 0x0}, {0x30000000, 0x0}, {0x30000000, 0x0}, {0x30000000, 0x0}, {0x30000000, 0x0}, {0x30000000, 0x0}, {0x30000000, 0x0}},
    {{0x0, 0x0}, {0x1052201, 0x1204044}, {0x10c2003, 0x220c0dd}, {0x1132604, 0x3210176}, {0x16a40e03, 0x3100021e}, {0x2d85806, 0x45982a6}, {0x16b42a03, 0x31004341}, {0x3de7c07, 0x579c3b7}, {0x2614a08, 0x54a042c}, {0x16c44603, 0x310484a0}, {0x2e75e09, 0x65a4539}, {0x16d46203, 0x3104c5f9}, {0x1af360b, 0x732c67e}, {0x16e47e03, 0x3109074b}, {0x37060d, 0x80347c0}, {0x16f49a03, 0x3109489c}, {0x2fe5c0f, 0x95bc904}, {0x1704b603, 0x310d8993}, {0x1714d203, 0x310dca3c}, {0x17241c1f, 0x98020ae6}, {0x17348c1f, 0x980a4bd9}, {0x17441c26, 0xba028ccc}, {0x17548c26, 0xba0acdbf}, {0x17641c2d, 0xdc030eb2}, {0x17748c2d, 0xdc0b4f8e}, {0x30000000, 0x0}, {0x30000000, 0x0}, {0x30000000, 0x0}, {0x30000000, 0x0}, {0x30000000, 0x0}, {0x30000000, 0x0}, {0x30000000, 0x0}},
    {{0x0, 0x0}, {0x1452a01, 0x1284045}, {0x14c2803, 0x228c0de}, {0x1532e04, 0x3290177}, {0x16a50e0a, 0x20000229}, {0x590a06, 0x40982b6}, {0x16b52a0a, 0x20004357}, {0x19f3607, 0x531c3cb}, {0x16c5460a, 0x200484b6}, {0x2274609, 0x6424530}, {0x16d5620a, 0x2004c60f}, {0xef1e0b, 0x71ac677}, {0x16e57e0a, 0x20090760}, {0x3766c0d, 0x86b47b8}, {0x2f95a0e, 0x85b8831}, {0x16f59a0a, 0x200948b1}, {0xbf160f, 0x913c916}, {0x1705b60a, 0x200d899e}, {0x1715d20a, 0x200dca46}, {0x1725231f, 0x98020af5}, {0x1735931f, 0x980a4be8}, {0x17452326, 0xba028cdb}, {0x17559326, 0xba0acdce}, {0x1765232d, 0xdc030ec1}, {0x1775932d, 0xdc0b4f9b}, {0x30000000, 0x0}, {0x30000000, 0x0}, {0x30000000, 0x0}, {0x30000000, 0x0}, {0x30000000, 0x0}, {0x30000000, 0x0}, {0x30000000, 0x0}},
    {{0x0, 0x0}, {0x1853201, 0x1304046}, {0x18c3003, 0x230c0df}, {0x1933604, 0x3310178}, {0x16a61503, 0x31000234}, {0x2a464d31, 0x4d8242c8}, {0x16b63103, 0x3100436d}, {0x35f6e07, 0x569c3df}, {0x16c64d03, 0x310484cc}, {0x3a77609, 0x6724541}, {0x16d66903, 0x3104c624}, {0x22f460b, 0x742c684}, {0x16e68503, 0x31090775}, {0xf71e0d, 0x81b47c8}, {0xba140e, 0x9138843}, {0x16f6a103, 0x310948c6}, {0x27f4e0f, 0x94bc929}, {0x1706bd03, 0x310d89a8}, {0x1716d903, 0x310dca51}, {0x17262a1f, 0x98020b05}, {0x17369a1f, 0x980a4bf7}, {0x17462a26, 0xba028cea}, {0x17569a26, 0xba0acddd}, {0x17662a2d, 0xdc030ed0}, {0x17769a2d, 0xdc0b4fa8}, {0x30000000, 0x0}, {0x30000000, 0x0}, {0x30000000, 0x0}, {0x30000000, 0x0}, {0x30000000, 0x0}, {0x30000000, 0x0}, {0x30000000, 0x0}},
    {{0x0, 0x0}, {0x1c53a01, 0x1384048}, {0x1cc3803, 0x238c0e1}, {0x1d33e04, 0x339017a}, {0x16a7150a, 0x2000023f}, {0x3997206, 0x47182da}, {0x16b7310a, 0x20004383}, {0x1202008, 0x52203f2}, {0x16c74d0a, 0x200484e2}, {0x168280a, 0x62a8554}, {0x16d7690a, 0x2004c639}, {0x32f660b, 0x762c68e}, {0x2f25c0c, 0x75b070a}, {0x16e7850a, 0x2009078a}, {0x178280e, 0x82b87f7}, {0x16f7a10a, 0x200948db}, {0x1707bd0a, 0x200d89b3}, {0x1717d90a, 0x200dca5b}, {0x1727311f, 0x98020b14}, {0x1737a11f, 0x980a4c07}, {0x17473126, 0xba028cf9}, {0x1757a126, 0xba0acdec}, {0x1767312d, 0xdc030edf}, {0x1777a12d, 0xdc0b4fb6}, {0x30000000, 0x0}, {0x30000000, 0x0}, {0x30000000, 0x0}, {0x30000000, 0x0}, {0x30000000, 0x0}, {0x30000000, 0x0}, {0x30000000, 0x0}, {0x30000000, 0x0}},
    {{0x0, 0x0}, {0x2054201, 0x1404049}, {0x20c4003, 0x240c0e2}, {0x2134604, 0x341017b}, {0x16a80011, 0x7500024a}, {0x11a2406, 0x42182ea}, {0x16b81c11, 0x75004399}, {0x2e05808, 0x55a0405}, {0x16c83811, 0x750484f8}, {0x2a8500a, 0x6528562}, {0x1eb3e0a, 0x63a85d7}, {0x16d85411, 0x7504c64e}, {0x3f0780c, 0x77b06bf}, {0x16e87011, 0x7509079f}, {0x3b8700e, 0x873880f}, {0x16f88c11, 0x750948f0}, {0x1708a811, 0x750d89bd}, {0x1718c411, 0x750dca66}, {0x1728381f, 0x98060b23}, {0x1738a81f, 0x980e4c16}, {0x17483826, 0xba068d09}, {0x1758a826, 0xba0ecdfb}, {0x1768382d, 0xdc070eee}, {0x1778a82d, 0xdc0f4fc3}, {0x30000000, 0x0}, {0x30000000, 0x0}, {0x30000000, 0x0}, {0x30000000, 0x0}, {0x30000000, 0x0}, {0x30000000, 0x0}, {0x30000000, 0x0}, {0x30000000, 0x0}},
    {{0x0, 0x0}, {0x2454a01, 0x148404a}, {0x24c4803, 0x248c0e3}, {0x2534e04, 0x349017c}, {0x2a331534, 0x188101e7}, {0x16a90018, 0x64000255}, {0x16b91c18, 0x640043af}, {0xa11208, 0x5120418}, {0x3e37e08, 0x57a0492}, {0x16c93818, 0x6404850e}, {0x229420a, 0x6428587}, {0x16d95418, 0x6404c663}, {0x1f13a0c, 0x73b06d4}, {0x16e97018, 0x640907b4}, {0x2794a0e, 0x84b882c}, {0x16f98c18, 0x64094905}, {0x1709a818, 0x640d89c8}, {0x1719c418, 0x640dca71}, {0x17293f1f, 0x98060b32}, {0x1739af1f, 0x980e4c25}, {0x17493f26, 0xba068d18}, {0x1759af26, 0xba0ece0b}, {0x17693f2d, 0xdc070efc}, {0x1779af2d, 0xdc0f4fd0}, {0x30000000, 0x0}, {0x30000000, 0x0}, {0x30000000, 0x0}, {0x30000000, 0x0}, {0x30000000, 0x0}, {0x30000000, 0x0}, {0x30000000, 0x0}, {0x30000000, 0x0}},
    {{0x0, 0x0}, {0x2855201, 0x150404c}, {0x28c5003, 0x250c0e5}, {0x2935604, 0x351017e}, {0x2a342a31, 0x2a8141e8}, {0x16aa0711, 0x75000265}, {0xdb1e06, 0x4198313}, {0x16ba2311, 0x750043c5}, {0x220408, 0x502043f}, {0x16ca3f11, 0x75048524}, {0x3696a0a, 0x66a8594}, {0x16da5b11, 0x7504c678}, {0x720c0c, 0x70b06f0}, {0x16ea7711, 0x750907c9}, {0xfa1c0e, 0x91b8846}, {0x16fa9311, 0x7509491a}, {0x170aaf11, 0x750d89d3}, {0x171acb11, 0x750dca7b}, {0x172a461f, 0x98060b41}, {0x173ab61f, 0x980e4c34}, {0x174a4626, 0xba068d27}, {0x175ab626, 0xba0ece1a}, {0x176a462d, 0xdc070f09}, {0x177ab62d, 0xdc0f4fdd}, {0x30000000, 0x0}, {0x30000000, 0x0}, {0x30000000, 0x0}, {0x30000000, 0x0}, {0x30000000, 0x0}, {0x30000000, 0x0}, {0x30000000, 0x0}, {0x30000000, 0x0}},
    {{0x0, 0x0}, {0x2c55a01, 0x158404d}, {0x2cc5803, 0x258c0e6}, {0x2d35e04, 0x359017f}, {0x2a352a32, 0x2b8141ea}, {0x16ab0718, 0x6400027b}, {0x25b4e06, 0x4498324}, {0x16bb2318, 0x640043db}, {0x2224408, 0x5420455}, {0x16cb3f18, 0x6404853a}, {0x1ea3c0a, 0x63a85ad}, {0x16db5b18, 0x6404c68d}, {0x2b2540c, 0x7530707}, {0x16eb7718, 0x640907de}, {0x2fa5c0e, 0x95b885b}, {0x16fb9318, 0x6409492f}, {0x170baf18, 0x640d89dd}, {0x171bcb18, 0x640dca86}, {0x172b4d1f, 0x98060b50}, {0x173bbd1f, 0x980e4c43}, {0x174b4d26, 0xba068d36}, {0x175bbd26, 0xba0ece29}, {0x176b4d2d, 0xdc070f16}, {0x177bbd2d, 0xdc0f4feb}, {0x30000000, 0x0}, {0x30000000, 0x0}, {0x30000000, 0x0}, {0x30000000, 0x0}, {0x30000000, 0x0}, {0x30000000, 0x0}, {0x30000000, 0x0}, {0x30000000, 0x0}},
    {{0x0, 0x0}, {0x3056201, 0x160404e}, {0x30c6003, 0x260c0e7}, {0x3136604, 0x3610180}, {0x2a363131, 0x318141eb}, {0x16ac1c03, 0x31000291}, {0x3db7e06, 0x4798333}, {0x16bc3803, 0x310443f0}, {0x230608, 0x502046b}, {0x16cc5403, 0x31048550}, {0x6b0e0a, 0x60a85c9}, {0x16dc7003, 0x3108c6a2}, {0xf31e0c, 0x81b071f}, {0x16ec8c03, 0x310907f3}, {0xbb160e, 0x913886e}, {0x16fca803, 0x310d493f}, {0x170cc403, 0x310d89e8}, {0x171cd211, 0x750dca90}, {0x172c541f, 0x98060b60}, {0x173cc41f, 0x980e4c52}, {0x174c5426, 0xba068d45}, {0x175cc426, 0xba0ece38}, {0x176c542d, 0xdc070f23}, {0x177cc42d, 0xdc0f4ff8}, {0x30000000, 0x0}, {0x30000000, 0x0}, {0x30000000, 0x0}, {0x30000000, 0x0}, {0x30000000, 0x0}, {0x30000000, 0x0}, {0x30000000, 0x0}, {0x30000000, 0x0}},
    {{0x0, 0x0}, {0x3456a01, 0x1684050}, {0x34c6803, 0x268c0e9}, {0x3536e04, 0x3690182}, {0x2a373132, 0x328141ec}, {0x16ad1c0a, 0x200002a7}, {0x11c2007, 0x421c342}, {0x16bd380a, 0x20044406}, {0x2634e08, 0x54a0483}, {0x16cd540a, 0x20048566}, {0x26b4e0a, 0x64a85de}, {0x16dd700a, 0x2008c6b7}, {0x3736e0c, 0x86b0739}, {0x16ed8c0a, 0x20090808}, {0x2bb560e, 0x9538883}, {0x16fda80a, 0x200d494a}, {0x170dc40a, 0x200d89f2}, {0x171dd218, 0x640dca9b}, {0x172d5b1f, 0x98060b6f}, {0x173dcb1f, 0x980e4c62}, {0x174d5b26, 0xba068d55}, {0x175dcb26, 0xba0ece47}, {0x176d5b2d, 0xdc070f31}, {0x177dcb2d, 0xdc0f5005}, {0x30000000, 0x0}, {0x30000000, 0x0}, {0x30000000, 0x0}, {0x30000000, 0x0}, {0x30000000, 0x0}, {0x30000000, 0x0}, {0x30000000, 0x0}, {0x30000000, 0x0}},
    {{0x0, 0x0}, {0x3857201, 0x1704051}, {0x38c7003, 0x270c0ea}, {0x3937604, 0x3710183}, {0x2a381c33, 0x1e8181f7}, {0x16ae2303, 0x310002bd}, {0x21c4007, 0x441c34d}, {0x16be3f03, 0x3104441c}, {0x640809, 0x50a4499}, {0x16ce5b03, 0x3104857b}, {0x6c080b, 0x70ac5f3}, {0x16de7703, 0x3108c6cc}, {0x134200d, 0x823474c}, {0x16ee9303, 0x3109081d}, {0x7c080f, 0x90bc895}, {0x16feaf03, 0x310d4954}, {0x170ecb03, 0x310d89fd}, {0x171ed911, 0x750dcaa5}, {0x172e621f, 0x98060b7e}, {0x173ed21f, 0x980e4c71}, {0x174e6226, 0xba068d64}, {0x175ed226, 0xba0ece57}, {0x176e622d, 0xdc070f3e}, {0x177ed22d, 0xdc0f5013}, {0x30000000, 0x0}, {0x30000000, 0x0}, {0x30000000, 0x0}, {0x30000000, 0x0}, {0x30000000, 0x0}, {0x30000000, 0x0}, {0x30000000, 0x0}, {0x30000000, 0x0}},
    {{0x0, 0x0}, {0x3c57a01, 0x1784052}, {0x3cc7803, 0x278c0eb}, {0x3d37e04, 0x3790184}, {0x2a391c34, 0x1f818202}, {0x16af230a, 0x200002d3}, {0x39c7007, 0x471c35e}, {0x16bf3f0a, 0x20044432}, {0x3646809, 0x56a44ba}, {0x16cf5b0a, 0x20048590}, {0x26c480b, 0x74ac608}, {0x16df770a, 0x2008c6e1}, {0x2f4580d, 0x85b475e}, {0x16ef930a, 0x20090832}, {0x23c400f, 0x943c8a8}, {0x16ffaf0a, 0x200d495f}, {0x170fcb0a, 0x200d8a07}, {0x171fd918, 0x640dcab0}, {0x172f691f, 0x98060b8d}, {0x173fd91f, 0x980e4c80}, {0x174f6926, 0xba068d73}, {0x175fd926, 0xba0ece66}, {0x176f692d, 0xdc070f4b}, {0x177fd92d, 0xdc0f5020}, {0x30000000, 0x0}, {0x30000000, 0x0}, {0x30000000, 0x0}, {0x30000000, 0x0}, {0x30000000, 0x0}, {0x30000000, 0x0}, {0x30000000, 0x0}, {0x30000000, 0x0}},
    {{0x0, 0x0}, {0x60401, 0x1004054}, {0xd0203, 0x200c0ed}, {0x140005, 0x3014186}, {0x17800004, 0x310001f3}, {0xd71e05, 0x4194264}, {0x17900e12, 0x750042ec}, {0x15d2a07, 0x429c371}, {0x17a02a12, 0x7500844b}, {0x1a53209, 0x63244d3}, {0x17b04612, 0x7504c5a8}, {0xad120b, 0x712c620}, {0x17c06212, 0x750506f9}, {0xf51a0d, 0x81b4773}, {0x17d07e12, 0x7509484a}, {0x3d020f, 0x903c8bd}, {0x17e09a12, 0x7509896a}, {0x17f0b612, 0x750dca13}, {0x18000020, 0x98020abc}, {0x18107020, 0x980a4b9e}, {0x18200027, 0xba028c91}, {0x18307027, 0xba0acd84}, {0x1840002e, 0xdc030e77}, {0x1850702e, 0xdc0b4f5a}, {0x30000000, 0x0}, {0x30000000, 0x0}, {0x30000000, 0x0}, {0x30000000, 0x0}, {0x30000000, 0x0}, {0x30000000, 0x0}, {0x30000000, 0x0}, {0x30000000, 0x0}},
    {{0x0, 0x0}, {0x460c01, 0x1084055}, {0x4d0a03, 0x208c0ee}, {0x540805, 0x3094187}, {0x1781000b, 0x200001fe}, {0x2574e05, 0x4494274}, {0x17910e19, 0x64004302}, {0x2dd5a07, 0x459c381}, {0x17a12a19, 0x64008461}, {0x3a57209, 0x67244e9}, {0x17b14619, 0x6404c5bd}, {0x26d4a0b, 0x74ac632}, {0x17c16219, 0x6405070e}, {0x2b5520d, 0x8534786}, {0x17d17e19, 0x6409485f}, {0x1bd320f, 0x933c8cc}, {0x17e19a19, 0x64098975}, {0x17f1b619, 0x640dca1e}, {0x18010720, 0x98020ac6}, {0x18117720, 0x980a4bad}, {0x18210727, 0xba028ca0}, {0x18317727, 0xba0acd93}, {0x1841072e, 0xdc030e86}, {0x1851772e, 0xdc0b4f68}, {0x30000000, 0x0}, {0x30000000, 0x0}, {0x30000000, 0x0}, {0x30000000, 0x0}, {0x30000000, 0x0}, {0x30000000, 0x0}, {0x30000000, 0x0}, {0x30000000, 0x0}},
    {{0x0, 0x0}, {0x861401, 0x1104056}, {0x8d1203, 0x210c0ef}, {0x941005, 0x3114188}, {0x17820704, 0x31000209}, {0x2a433134, 0x34820286}, {0x17921512, 0x75004318}, {0x5e0c07, 0x509c392}, {0x17a23112, 0x75008477}, {0x1662c09, 0x62a44fc}, {0x17b24d12, 0x7504c5d2}, {0x6e0c0b, 0x70ac647}, {0x17c26912, 0x75050723}, {0x760c0d, 0x80b4798}, {0x17d28512, 0x75094874}, {0x2fd5a0f, 0x95bc8da}, {0x17e2a112, 0x75098980}, {0x17f2bd12, 0x750dca28}, {0x18020e20, 0x98020ad1}, {0x18127e20, 0x980a4bbd}, {0x18220e27, 0xba028caf}, {0x18327e27, 0xba0acda2}, {0x18420e2e, 0xdc030e95}, {0x18527e2e, 0xdc0b4f75}, {0x30000000, 0x0}, {0x30000000, 0x0}, {0x30000000, 0x0}, {0x30000000, 0x0}, {0x30000000, 0x0}, {0x30000000, 0x0}, {0x30000000, 0x0}, {0x30000000, 0x0}},
    {{0x0, 0x0}, {0xc61c01, 0x1184057}, {0xcd1a03, 0x218c0f0}, {0xd41805, 0x3194189}, {0x1783070b, 0x20000214}, {0x1983006, 0x4318298}, {0x17931519, 0x6400432e}, {0x21e4407, 0x541c3a5}, {0x17a33119, 0x6400848d}, {0x3266409, 0x662450f}, {0x17b34d19, 0x6404c5e7}, {0x22e440b, 0x742c65a}, {0xb1120c, 0x71306c8}, {0x17c36919, 0x64050738}, {0x336640d, 0x86347b5}, {0x17d38519, 0x64094889}, {0x1be340f, 0x933c8f7}, {0x17e3a119, 0x6409898a}, {0x17f3bd19, 0x640dca33}, {0x18031520, 0x98020adb}, {0x18138520, 0x980a4bcc}, {0x18231527, 0xba028cbf}, {0x18338527, 0xba0acdb1}, {0x1843152e, 0xdc030ea4}, {0x1853852e, 0xdc0b4f82}, {0x30000000, 0x0}, {0x30000000, 0x0}, {0x30000000, 0x0}, {0x30000000, 0x0}, {0x30000000, 0x0}, {0x30000000, 0x0}, {0x30000000, 0x0}},
    {{0x0, 0x0}, {0x1062401, 0x1204059}, {0x10d2203, 0x220c0f2}, {0x1142005, 0x321418b}, {0x17840e04, 0x3100021f}, {0x3186006, 0x46182a8}, {0x17942a04, 0x31004344}, {0x1f0607, 0x501c3bb}, {0x17a44604, 0x310484a3}, {0xa71609, 0x6124520}, {0x17b46204, 0x3104c5fc}, {0x3ae740b, 0x772c669}, {0x2714a0c, 0x74b06db}, {0x17c47e04, 0x3109074d}, {0xb7160d, 0x81347c5}, {0x17d49a04, 0x3109489e}, {0x33e640f, 0x963c906}, {0x17e4b604, 0x310d8995}, {0x17f4d204, 0x310dca3d}, {0x18041c20, 0x98020ae8}, {0x18148c20, 0x980a4bdb}, {0x18241c27, 0xba028cce}, {0x18348c27, 0xba0acdc1}, {0x18441c2e, 0xdc030eb4}, {0x18548c2e, 0xdc0b4f90}, {0x30000000, 0x0}, {0x30000000, 0x0}, {0x30000000, 0x0}, {0x30000000, 0x0}, {0x30000000, 0x0}, {0x30000000, 0x0}, {0x30000000, 0x0}},
    {{0x0, 0x0}, {0x1462c01, 0x128405a}, {0x14d2a03, 0x228c0f3}, {0x1542805, 0x329418c}, {0x17850e0b, 0x2000022a}, {0x991206, 0x41182b9}, {0x17952a0b, 0x20004359}, {0x1df3e07, 0x539c3cd}, {0x620c08, 0x50a0441}, {0x17a5460b, 0x200484b9}, {0xa8100a, 0x612854c}, {0x17b5620b, 0x2004c611}, {0x2ef5e0b, 0x75ac68c}, {0x17c57e0b, 0x20090762}, {0x2774e0d, 0x84b47d7}, {0x17d59a0b, 0x200948b3}, {0xff1e0f, 0x91bc919}, {0x17e5b60b, 0x200d899f}, {0x17f5d20b, 0x200dca48}, {0x18052320, 0x98020af7}, {0x18159320, 0x980a4bea}, {0x18252327, 0xba028cdd}, {0x18359327, 0xba0acdd0}, {0x1845232e, 0xdc030ec3}, {0x1855932e, 0xdc0b4f9d}, {0x30000000, 0x0}, {0x30000000, 0x0}, {0x30000000, 0x0}, {0x30000000, 0x0}, {0x30000000, 0x0}, {0x30000000, 0x0}, {0x30000000, 0x0}},
    {{0x0, 0x0}, {0x1863401, 0x130405b}, {0x18d3203, 0x230c0f4}, {0x1943005, 0x331418d}, {0x17861504, 0x31000235}, {0x2194206, 0x44182c9}, {0x17963104, 0x3100436f}, {0x39f7607, 0x571c3e1}, {0x2624c08, 0x54a0457}, {0x17a64d04, 0x310484cf}, {0x228400a, 0x642855c}, {0x17b66904, 0x3104c626}, {0x30000c, 0x7030699}, {0x17c68504, 0x31090777}, {0x3b7760d, 0x87347e5}, {0x17d6a104, 0x310948c8}, {0x2bf560f, 0x953c92b}, {0x17e6bd04, 0x310d89aa}, {0x17f6d904, 0x310dca52}, {0x18062a20, 0x98020b06}, {0x18169a20, 0x980a4bf9}, {0x18262a27, 0xba028cec}, {0x18369a27, 0xba0acddf}, {0x18462a2e, 0xdc030ed2}, {0x18569a2e, 0xdc0b4faa}, {0x30000000, 0x0}, {0x30000000, 0x0}, {0x30000000, 0x0}, {0x30000000, 0x0}, {0x30000000, 0x0}, {0x30000000, 0x0}, {0x30000000, 0x0}},
    {{0x0, 0x0}, {0x1c63c01, 0x138405d}, {0x1cd3a03, 0x238c0f6}, {0x1d43805, 0x339418f}, {0x1787150b, 0x20000240}, {0x3d97a06, 0x47982db}, {0x1797310b, 0x20004385}, {0x1602808, 0x52a03f5}, {0x17a74d0b, 0x200484e5}, {0x1a8300a, 0x6328557}, {0x17b7690b, 0x2004c63b}, {0x3af760b, 0x772c694}, {0x17c7850b, 0x2009078c}, {0x2f75e0d, 0x85b47dd}, {0x2ba540e, 0x9538859}, {0x17d7a10b, 0x200948de}, {0x17e7bd0b, 0x200d89b4}, {0x17f7d90b, 0x200dca5d}, {0x18073120, 0x98020b16}, {0x1817a120, 0x980a4c08}, {0x18273127, 0xba028cfb}, {0x1837a127, 0xba0acdee}, {0x1847312e, 0xdc030ee1}, {0x1857a12e, 0xdc0b4fb7}, {0x30000000, 0x0}, {0x30000000, 0x0}, {0x30000000, 0x0}, {0x30000000, 0x0}, {0x30000000, 0x0}, {0x30000000, 0x0}, {0x30000000, 0x0}, {0x30000000, 0x0}},
    {{0x0, 0x0}, {0x2064401, 0x140405e}, {0x20d4203, 0x240c0f7}, {0x2144005, 0x3414190}, {0x17880012, 0x7500024b}, {0x15a2c06, 0x42982ed}, {0x17981c12, 0x7500439b}, {0x3206008, 0x5620408}, {0x17a83812, 0x750484fb}, {0x2e8580a, 0x65a8565}, {0x17b85412, 0x7504c650}, {0xb0100c, 0x713069e}, {0x730e0c, 0x80b071a}, {0x17c87012, 0x750907a1}, {0x39020e, 0x8038814}, {0x17d88c12, 0x750948f3}, {0x17e8a812, 0x750d89bf}, {0x17f8c412, 0x750dca67}, {0x18083820, 0x98060b25}, {0x1818a820, 0x980e4c18}, {0x18283827, 0xba068d0b}, {0x1838a827, 0xba0ecdfd}, {0x1848382e, 0xdc070ef0}, {0x1858a82e, 0xdc0f4fc5}, {0x30000000, 0x0}, {0x30000000, 0x0}, {0x30000000, 0x0}, {0x30000000, 0x0}, {0x30000000, 0x0}, {0x30000000, 0x0}, {0x30000000, 0x0}, {0x30000000, 0x0}},
    {{0x0, 0x0}, {0x2464c01, 0x148405f}, {0x24d4a03, 0x248c0f8}, {0x2544805, 0x3494191}, {0x17890019, 0x64000256}, {0x25a4c06, 0x44982f8}, {0x17991c19, 0x640043b1}, {0xe11a08, 0x51a041b}, {0x17a93819, 0x64048511}, {0x29020a, 0x6028572}, {0x36b6e0a, 0x66a85e8}, {0x17b95419, 0x6404c665}, {0x231420c, 0x74306d8}, {0x17c97019, 0x640907b7}, {0x2b9520e, 0x853882e}, {0x17d98c19, 0x64094908}, {0x17e9a819, 0x640d89c9}, {0x17f9c419, 0x640dca72}, {0x18093f20, 0x98060b34}, {0x1819af20, 0x980e4c27}, {0x18293f27, 0xba068d1a}, {0x1839af27, 0xba0ece0d}, {0x18493f2e, 0xdc070efe}, {0x1859af2e, 0xdc0f4fd2}, {0x30000000, 0x0}, {0x30000000, 0x0}, {0x30000000, 0x0}, {0x30000000, 0x0}, {0x30000000, 0x0}, {0x30000000, 0x0}, {0x30000000, 0x0}, {0x30000000, 0x0}},
    {{0x0, 0x0}, {0x2865401, 0x1504061}, {0x28d5203, 0x250c0fa}, {0x2945005, 0x3514193}, {0x178a0712, 0x75000268}, {0x31a6406, 0x4618300}, {0x179a2312, 0x750043c7}, {0x1a13208, 0x5320423}, {0x1242009, 0x52244a2}, {0x17aa3f12, 0x75048527}, {0x3a9720a, 0x6728597}, {0x17ba5b12, 0x7504c67a}, {0xf21c0c, 0x71b06f5}, {0x17ca7712, 0x750907cc}, {0x13a240e, 0x9238849}, {0x17da9312, 0x7509491d}, {0x17eaaf12, 0x750d89d4}, {0x17facb12, 0x750dca7c}, {0x180a4620, 0x98060b43}, {0x181ab620, 0x980e4c36}, {0x182a4627, 0xba068d29}, {0x183ab627, 0xba0ece1c}, {0x184a462e, 0xdc070f0b}, {0x185ab62e, 0xdc0f4fdf}, {0x30000000, 0x0}, {0x30000000, 0x0}, {0x30000000, 0x0}, {0x30000000, 0x0}, {0x30000000, 0x0}, {0x30000000, 0x0}, {0x30000000, 0x0}, {0x30000000, 0x0}},
    {{0x0, 0x0}, {0x2c65c01, 0x1584062}, {0x2cd5a03, 0x258c0fb}, {0x2d45805, 0x3594194}, {0x178b0719, 0x6400027e}, {0x3da7c06, 0x4798307}, {0x179b2319, 0x640043dd}, {0x2a15208, 0x552042e}, {0x2a45009, 0x55244b2}, {0x17ab3f19, 0x6404853d}, {0x22a440a, 0x64285b1}, {0x17bb5b19, 0x6404c690}, {0x332640c, 0x763070d}, {0x17cb7719, 0x640907e1}, {0x33a640e, 0x963885e}, {0x17db9319, 0x64094932}, {0x17ebaf19, 0x640d89de}, {0x17fbcb19, 0x640dca87}, {0x180b4d20, 0x98060b52}, {0x181bbd20, 0x980e4c45}, {0x182b4d27, 0xba068d38}, {0x183bbd27, 0xba0ece2b}, {0x184b4d2e, 0xdc070f18}, {0x185bbd2e, 0xdc0f4fed}, {0x30000000, 0x0}, {0x30000000, 0x0}, {0x30000000, 0x0}, {0x30000000, 0x0}, {0x30000000, 0x0}, {0x30000000, 0x0}, {0x30000000, 0x0}, {0x30000000, 0x0}},
    {{0x0, 0x0}, {0x3066401, 0x1604063}, {0x30d6203, 0x260c0fc}, {0x3146005, 0x3614195}, {0x2a3a2333, 0x2581820d}, {0x178c1c04, 0x31000294}, {0x2a4b3f34, 0x42828336}, {0x179c3804, 0x310443f3}, {0x630e08, 0x50a046d}, {0x17ac5404, 0x31048553}, {0xab160a, 0x61285cb}, {0x17bc7004, 0x3108c6a5}, {0x1732e0c, 0x82b0724}, {0x17cc8c04, 0x310907f6}, {0xfb1e0e, 0x91b8870}, {0x17dca804, 0x310d4940}, {0x17ecc404, 0x310d89e9}, {0x17fcd212, 0x750dca91}, {0x180c5420, 0x98060b62}, {0x181cc420, 0x980e4c54}, {0x182c5427, 0xba068d47}, {0x183cc427, 0xba0ece3a}, {0x184c542e, 0xdc070f25}, {0x185cc42e, 0xdc0f4ffa}, {0x30000000, 0x0}, {0x30000000, 0x0}, {0x30000000, 0x0}, {0x30000000, 0x0}, {0x30000000, 0x0}, {0x30000000, 0x0}, {0x30000000, 0x0}, {0x30000000, 0x0}},
    {{0x0, 0x0}, {0x3466c01, 0x1684065}, {0x34d6a03, 0x268c0fe}, {0x3546805, 0x3694197}, {0x2a3b2334, 0x26818218}, {0x178d1c0b, 0x200002aa}, {0x15c2807, 0x429c345}, {0x179d380b, 0x20044409}, {0x2a35608, 0x5520486}, {0x17ad540b, 0x20048569}, {0x2ab560a, 0x65285e0}, {0x17bd700b, 0x2008c6ba}, {0x3b3760c, 0x873073c}, {0x17cd8c0b, 0x2009080b}, {0x2fb5e0e, 0x95b8885}, {0x17dda80b, 0x200d494b}, {0x17edc40b, 0x200d89f3}, {0x17fdd219, 0x640dca9c}, {0x180d5b20, 0x98060b71}, {0x181dcb20, 0x980e4c64}, {0x182d5b27, 0xba068d56}, {0x183dcb27, 0xba0ece49}, {0x184d5b2e, 0xdc070f33}, {0x185dcb2e, 0xdc0f5007}, {0x30000000, 0x0}, {0x30000000, 0x0}, {0x30000000, 0x0}, {0x30000000, 0x0}, {0x30000000, 0x0}, {0x30000000, 0x0}, {0x30000000, 0x0}, {0x30000000, 0x0}},
    {{0x0, 0x0}, {0x3867401, 0x1704066}, {0x38d7203, 0x270c0ff}, {0x3947005, 0x3714198}, {0x2a3c3831, 0x3881c223}, {0x178e2304, 0x310002c0}, {0x25c4807, 0x449c350}, {0x179e3f04, 0x3104441f}, {0xa41009, 0x512449c}, {0x17ae5b04, 0x3104857e}, {0xac100b, 0x712c5f5}, {0x17be7704, 0x3108c6cf}, {0x174280d, 0x82b474f}, {0x17ce9304, 0x31090820}, {0xbc100f, 0x913c898}, {0x17deaf04, 0x310d4955}, {0x17eecb04, 0x310d89fe}, {0x17fed912, 0x750dcaa7}, {0x180e6220, 0x98060b80}, {0x181ed220, 0x980e4c73}, {0x182e6227, 0xba068d66}, {0x183ed227, 0xba0ece58}, {0x184e622e, 0xdc070f40}, {0x185ed22e, 0xdc0f5014}, {0x30000000, 0x0}, {0x30000000, 0x0}, {0x30000000, 0x0}, {0x30000000, 0x0}, {0x30000000, 0x0}, {0x30000000, 0x0}, {0x30000000, 0x0}, {0x30000000, 0x0}},
    {{0x0, 0x0}, {0x3c67c01, 0x1784067}, {0x3cd7a03, 0x278c100}, {0x3d47805, 0x3794199}, {0x2a3d3832, 0x3981c22e}, {0x178f230b, 0x200002d6}, {0x3dc7807, 0x479c35f}, {0x179f3f0b, 0x20044435}, {0x3a47009, 0x57244bd}, {0x17af5b0b, 0x20048593}, {0x2ac500b, 0x752c60b}, {0x17bf770b, 0x2008c6e4}, {0x334600d, 0x8634761}, {0x17cf930b, 0x20090835}, {0x27c480f, 0x94bc8aa}, {0x17dfaf0b, 0x200d4960}, {0x17efcb0b, 0x200d8a09}, {0x17ffd919, 0x640dcab1}, {0x180f6920, 0x98060b8f}, {0x181fd920, 0x980e4c82}, {0x182f6927, 0xba068d75}, {0x183fd927, 0xba0ece68}, {0x184f692e, 0xdc070f4d}, {0x185fd92e, 0xdc0f5022}, {0x30000000, 0x0}, {0x30000000, 0x0}, {0x30000000, 0x0}, {0x30000000, 0x0}, {0x30000000, 0x0}, {0x30000000, 0x0}, {0x30000000, 0x0}, {0x30000000, 0x0}},
    {{0x0, 0x0}, {0x70601, 0x1004069}, {0xe0403, 0x200c102}, {0x150205, 0x301419b}, {0x18600005, 0x310001f5}, {0x1172605, 0x4214267}, {0x18700e13, 0x750042ee}, {0x19d3207, 0x431c374}, {0x18802a13, 0x7500844e}, {0x1e53a09, 0x63a44d4}, {0x18904613, 0x7504c5aa}, {0xed1a0b, 0x71ac622}, {0x18a06213, 0x750506fc}, {0x135220d, 0x8234776}, {0x18b07e13, 0x7509484d}, {0x7d0a0f, 0x90bc8bf}, {0x18c09a13, 0x7509896c}, {0x18d0b613, 0x750dca14}, {0x18e00021, 0x98020abd}, {0x18f07021, 0x980a4ba0}, {0x19000028, 0xba028c93}, {0x19107028, 0xba0acd86}, {0x1920002f, 0xdc030e79}, {0x1930702f, 0xdc0b4f5c}, {0x30000000, 0x0}, {0x30000000, 0x0}, {0x30000000, 0x0}, {0x30000000, 0x0}, {0x30000000, 0x0}, {0x30000000, 0x0}, {0x30000000, 0x0}, {0x30000000, 0x0}},
    {{0x400800, 0x80000}, {0x470e01, 0x108406a}, {0x4e0c03, 0x208c103}, {0x550a05, 0x309419c}, {0x1861000c, 0x20000200}, {0x2975605, 0x4514277}, {0x18710e1a, 0x64004304}, {0x31d6207, 0x461c384}, {0x18812a1a, 0x64008464}, {0x3e57a09, 0x67a44ea}, {0x1891461a, 0x6404c5bf}, {0x2ad520b, 0x752c635}, {0x18a1621a, 0x64050711}, {0x2f55a0d, 0x85b4788}, {0x18b17e1a, 0x64094862}, {0x1fd3a0f, 0x93bc8ce}, {0x18c19a1a, 0x64098976}, {0x18d1b61a, 0x640dca1f}, {0x18e10721, 0x98020ac7}, {0x18f17721, 0x980a4baf}, {0x19010728, 0xba028ca2}, {0x19117728, 0xba0acd95}, {0x1921072f, 0xdc030e88}, {0x1931772f, 0xdc0b4f6a}, {0x30000000, 0x0}, {0x30000000, 0x0}, {0x30000000, 0x0}, {0x30000000, 0x0}, {0x30000000, 0x0}, {0x30000000, 0x0}, {0x30000000, 0x0}, {0x30000000, 0x0}},
    {{0x801000, 0x100000}, {0x871601, 0x110406b}, {0x8e1403, 0x210c104}, {0x951205, 0x311419d}, {0x18620705, 0x3100020b}, {0x180006, 0x4018287}, {0x18721513, 0x7500431a}, {0x9e1407, 0x511c395}, {0x18823113, 0x7500847a}, {0x1a63409, 0x63244ff}, {0x18924d13, 0x7504c5d5}, {0xae140b, 0x712c64a}, {0x18a26913, 0x75050726}, {0xb6140d, 0x813479b}, {0x18b28513, 0x75094877}, {0x33d620f, 0x963c8dc}, {0x18c2a113, 0x75098981}, {0x18d2bd13, 0x750dca29}, {0x18e20e21, 0x98020ad2}, {0x18f27e21, 0x980a4bbe}, {0x19020e28, 0xba028cb1}, {0x19127e28, 0xba0acda4}, {0x19220e2f, 0xdc030e97}, {0x19327e2f, 0xdc0b4f77}, {0x30000000, 0x0}, {0x30000000, 0x0}, {0x30000000, 0x0}, {0x30000000, 0x0}, {0x30000000, 0x0}, {0x30000000, 0x0}, {0x30000000, 0x0}, {0x30000000, 0x0}},
    {{0xc01800, 0x180000}, {0xc71e01, 0x118406c}, {0xce1c03, 0x218c105}, {0xd51a05, 0x319419e}, {0x1863070c, 0x20000216}, {0x1d83806, 0x4398299}, {0x1873151a, 0x64004330}, {0x25e4c07, 0x549c3a8}, {0x1883311a, 0x64008490}, {0x3666c09, 0x66a4512}, {0x18934d1a, 0x6404c5ea}, {0x26e4c0b, 0x74ac65c}, {0x18a3691a, 0x6405073b}, {0x1b6340d, 0x83347a5}, {0xb9120e, 0x8138819}, {0x18b3851a, 0x6409488c}, {0x1fe3c0f, 0x93bc8f8}, {0x18c3a11a, 0x6409898b}, {0x18d3bd1a, 0x640dca34}, {0x18e31521, 0x98020add}, {0x18f38521, 0x980a4bce}, {0x19031528, 0xba028cc1}, {0x19138528, 0xba0acdb3}, {0x1923152f, 0xdc030ea6}, {0x1933852f, 0xdc0b4f84}, {0x30000000, 0x0}, {0x30000000, 0x0}, {0x30000000, 0x0}, {0x30000000, 0x0}, {0x30000000, 0x0}, {0x30000000, 0x0}, {0x30000000, 0x0}},
    {{0x1002000, 0x200000}, {0x1072601, 0x120406e}, {0x10e2403, 0x220c107}, {0x1152205, 0x32141a0}, {0x18640e05, 0x31000220}, {0x3586806, 0x46982ab}, {0x18742a05, 0x31004346}, {0x5f0e07, 0x509c3be}, {0x18844605, 0x310484a6}, {0xe71e09, 0x61a4523}, {0x18946205, 0x3104c5ff}, {0x3ee7c0b, 0x77ac66b}, {0x2b1520c, 0x75306dd}, {0x18a47e05, 0x31090750}, {0x137260d, 0x82347ca}, {0x18b49a05, 0x310948a1}, {0x37e6c0f, 0x96bc909}, {0x18c4b605, 0x310d8996}, {0x18d4d205, 0x310dca3f}, {0x18e41c21, 0x98020aea}, {0x18f48c21, 0x980a4bdd}, {0x19041c28, 0xba028cd0}, {0x19148c28, 0xba0acdc3}, {0x19241c2f, 0xdc030eb5}, {0x19348c2f, 0xdc0b4f92}, {0x30000000, 0x0}, {0x30000000, 0x0}, {0x30000000, 0x0}, {0x30000000, 0x0}, {0x30000000, 0x0}, {0x30000000, 0x0}, {0x30000000, 0x0}},
    {{0x1402800, 0x280000}, {0x1472e01, 0x128406f}, {0x14e2c03, 0x228c108}, {0x1552a05, 0x32941a1}, {0x18650e0c, 0x2000022b}, {0xd91a06, 0x41982bc}, {0x18752a0c, 0x2000435c}, {0x21f4607, 0x541c3d1}, {0xe21c08, 0x51a0447}, {0x1885460c, 0x200484bc}, {0x128200a, 0x6228551}, {0x1895620c, 0x2004c614}, {0x36f6e0b, 0x76ac691}, {0x18a57e0c, 0x20090765}, {0x2b7560d, 0x85347da}, {0x18b59a0c, 0x200948b6}, {0x13f260f, 0x923c91b}, {0x18c5b60c, 0x200d89a0}, {0x18d5d20c, 0x200dca49}, {0x18e52321, 0x98020af9}, {0x18f59321, 0x980a4bec}, {0x19052328, 0xba028cdf}, {0x19159328, 0xba0acdd2}, {0x1925232f, 0xdc030ec5}, {0x1935932f, 0xdc0b4f9f}, {0x30000000, 0x0}, {0x30000000, 0x0}, {0x30000000, 0x0}, {0x30000000, 0x0}, {0x30000000, 0x0}, {0x30000000, 0x0}, {0x30000000, 0x0}},
    {{0x1803000, 0x300000}, {0x1873601, 0x1304070}, {0x18e3403, 0x230c109}, {0x1953205, 0x33141a2}, {0x18661505, 0x31000236}, {0x2594a06, 0x44982cc}, {0x18763105, 0x31004372}, {0x3df7e07, 0x579c3e3}, {0x2a25408, 0x552045a}, {0x18864d05, 0x310484d2}, {0x268480a, 0x64a855f}, {0x18966905, 0x3104c629}, {0x70080c, 0x70b069b}, {0x18a68505, 0x3109077a}, {0x3f77e0d, 0x87b47e6}, {0x18b6a105, 0x310948cb}, {0x2ff5e0f, 0x95bc92e}, {0x18c6bd05, 0x310d89ab}, {0x18d6d905, 0x310dca54}, {0x18e62a21, 0x98020b08}, {0x18f69a21, 0x980a4bfb}, {0x19062a28, 0xba028cee}, {0x19169a28, 0xba0acde1}, {0x19262a2f, 0xdc030ed4}, {0x19369a2f, 0xdc0b4fac}, {0x30000000, 0x0}, {0x30000000, 0x0}, {0x30000000, 0x0}, {0x30000000, 0x0}, {0x30000000, 0x0}, {0x30000000, 0x0}, {0x30000000, 0x0}},
    {{0x1c03800, 0x380000}, {0x1c73e01, 0x1384072}, {0x1ce3c03, 0x238c10b}, {0x1d53a05, 0x33941a4}, {0x1867150c, 0x20000241}, {0x2a474d32, 0x4e8242de}, {0x1877310c, 0x20004388}, {0x1a03008, 0x53203f7}, {0xa31608, 0x5120470}, {0x18874d0c, 0x200484e8}, {0x3e8780a, 0x67a856e}, {0x1897690c, 0x2004c63e}, {0x230400c, 0x74306ae}, {0x18a7850c, 0x2009078f}, {0x1f8380e, 0x83b87fb}, {0x18b7a10c, 0x200948e0}, {0x18c7bd0c, 0x200d89b6}, {0x18d7d90c, 0x200dca5e}, {0x18e73121, 0x98020b18}, {0x18f7a121, 0x980a4c0a}, {0x19073128, 0xba028cfd}, {0x1917a128, 0xba0acdf0}, {0x1927312f, 0xdc030ee3}, {0x1937a12f, 0xdc0b4fb9}, {0x30000000, 0x0}, {0x30000000, 0x0}, {0x30000000, 0x0}, {0x30000000, 0x0}, {0x30000000, 0x0}, {0x30000000, 0x0}, {0x30000000, 0x0}, {0x30000000, 0x0}},
    {{0x2004000, 0x400000}, {0x2074601, 0x1404073}, {0x20e4403, 0x240c10c}, {0x2154205, 0x34141a5}, {0x18680013, 0x7500024c}, {0x19a3406, 0x43182f0}, {0x18781c13, 0x7500439e}, {0x3606808, 0x56a040b}, {0x18883813, 0x750484fe}, {0x328600a, 0x6628567}, {0x18985413, 0x7504c653}, {0x130200c, 0x72306a3}, {0x133260c, 0x8230722}, {0x18a87013, 0x750907a4}, {0x790a0e, 0x80b8817}, {0x18b88c13, 0x750948f5}, {0x18c8a813, 0x750d89c0}, {0x18d8c413, 0x750dca69}, {0x18e83821, 0x98060b27}, {0x18f8a821, 0x980e4c1a}, {0x19083828, 0xba068d0c}, {0x1918a828, 0xba0ecdff}, {0x1928382f, 0xdc070ef2}, {0x1938a82f, 0xdc0f4fc7}, {0x30000000, 0x0}, {0x30000000, 0x0}, {0x30000000, 0x0}, {0x30000000, 0x0}, {0x30000000, 0x0}, {0x30000000, 0x0}, {0x30000000, 0x0}, {0x30000000, 0x0}},
    {{0x2404800, 0x480000}, {0x2474e01, 0x1484074}, {0x24e4c03, 0x248c10d}, {0x2554a05, 0x34941a6}, {0x1869001a, 0x64000257}, {0x29a5406, 0x45182fb}, {0x18791c1a, 0x640043b4}, {0x1212208, 0x522041e}, {0x1889381a, 0x64048514}, {0xa9120a, 0x6128577}, {0x1899541a, 0x6404c668}, {0x2b0500c, 0x75306b3}, {0x2f35e0c, 0x85b0734}, {0x18a9701a, 0x640907b9}, {0x339620e, 0x8638834}, {0x18b98c1a, 0x6409490a}, {0x18c9a81a, 0x640d89cb}, {0x18d9c41a, 0x640dca73}, {0x18e93f21, 0x98060b36}, {0x18f9af21, 0x980e4c29}, {0x19093f28, 0xba068d1c}, {0x1919af28, 0xba0ece0e}, {0x19293f2f, 0xdc070eff}, {0x1939af2f, 0xdc0f4fd4}, {0x30000000, 0x0}, {0x30000000, 0x0}, {0x30000000, 0x0}, {0x30000000, 0x0}, {0x30000000, 0x0}, {0x30000000, 0x0}, {0x30000000, 0x0}, {0x30000000, 0x0}},
    {{0x2805000, 0x500000}, {0x2875601, 0x1504076}, {0x28e5403, 0x250c10f}, {0x2955205, 0x35141a8}, {0x186a0713, 0x7500026b}, {0x35a6c06, 0x4698303}, {0x187a2313, 0x750043ca}, {0x1e13a08, 0x53a0425}, {0x1642809, 0x52a44a4}, {0x188a3f13, 0x75048529}, {0x2a040a, 0x602859c}, {0x189a5b13, 0x7504c67d}, {0x132240c, 0x72306f8}, {0x18aa7713, 0x750907ce}, {0x17a2c0e, 0x92b884b}, {0x18ba9313, 0x7509491f}, {0x18caaf13, 0x750d89d5}, {0x18dacb13, 0x750dca7e}, {0x18ea4621, 0x98060b45}, {0x18fab621, 0x980e4c38}, {0x190a4628, 0xba068d2b}, {0x191ab628, 0xba0ece1e}, {0x192a462f, 0xdc070f0d}, {0x193ab62f, 0xdc0f4fe1}, {0x30000000, 0x0}, {0x30000000, 0x0}, {0x30000000, 0x0}, {0x30000000, 0x0}, {0x30000000, 0x0}, {0x30000000, 0x0}, {0x30000000, 0x0}, {0x30000000, 0x0}},
    {{0x2c05800, 0x580000}, {0x2c75e01, 0x1584077}, {0x2ce5c03, 0x258c110}, {0x2d55a05, 0x35941a9}, {0x186b071a, 0x64000281}, {0x2a493834, 0x3b82830a}, {0x187b231a, 0x640043e0}, {0x2e15a08, 0x55a0431}, {0x3246009, 0x56244b8}, {0x188b3f1a, 0x6404853f}, {0x26a4c0a, 0x64a85b4}, {0x189b5b1a, 0x6404c692}, {0x3726c0c, 0x76b070f}, {0x18ab771a, 0x640907e3}, {0x37a6c0e, 0x96b8860}, {0x18bb931a, 0x64094934}, {0x18cbaf1a, 0x640d89e0}, {0x18dbcb1a, 0x640dca88}, {0x18eb4d21, 0x98060b54}, {0x18fbbd21, 0x980e4c47}, {0x190b4d28, 0xba068d3a}, {0x191bbd28, 0xba0ece2d}, {0x192b4d2f, 0xdc070f1a}, {0x193bbd2f, 0xdc0f4fee}, {0x30000000, 0x0}, {0x30000000, 0x0}, {0x30000000, 0x0}, {0x30000000, 0x0}, {0x30000000, 0x0}, {0x30000000, 0x0}, {0x30000000, 0x0}, {0x30000000, 0x0}},
    {{0x3006000, 0x600000}, {0x3076601, 0x1604078}, {0x30e6403, 0x260c111}, {0x3156205, 0x36141aa}, {0x186c1c05, 0x31000297}, {0x15b2e06, 0x4298319}, {0x187c3805, 0x310443f6}, {0xa21408, 0x5120444}, {0xe51a09, 0x61a44cb}, {0x188c5405, 0x31048555}, {0xeb1e0a, 0x61a85ce}, {0x189c7005, 0x3108c6a7}, {0x1b3360c, 0x8330727}, {0x18ac8c05, 0x310907f8}, {0x13b260e, 0x9238873}, {0x18bca805, 0x310d4942}, {0x18ccc405, 0x310d89ea}, {0x18dcd213, 0x750dca93}, {0x18ec5421, 0x98060b63}, {0x18fcc421, 0x980e4c56}, {0x190c5428, 0xba068d49}, {0x191cc428, 0xba0ece3c}, {0x192c542f, 0xdc070f27}, {0x193cc42f, 0xdc0f4ffc}, {0x30000000, 0x0}, {0x30000000, 0x0}, {0x30000000, 0x0}, {0x30000000, 0x0}, {0x30000000, 0x0}, {0x30000000, 0x0}, {0x30000000, 0x0}, {0x30000000, 0x0}},
    {{0x3406800, 0x680000}, {0x3476e01, 0x168407a}, {0x34e6c03, 0x268c113}, {0x3556a05, 0x36941ac}, {0x186d1c0c, 0x200002ad}, {0x29b5606, 0x4518327}, {0x187d380c, 0x2004440c}, {0x2e25c08, 0x55a045d}, {0x3256209, 0x66244e3}, {0x188d540c, 0x2004856b}, {0x2eb5e0a, 0x65a85e3}, {0x189d700c, 0x2008c6bc}, {0x3f37e0c, 0x87b073d}, {0x18ad8c0c, 0x2009080d}, {0x33b660e, 0x9638888}, {0x18bda80c, 0x200d494c}, {0x18cdc40c, 0x200d89f5}, {0x18ddd21a, 0x640dca9d}, {0x18ed5b21, 0x98060b73}, {0x18fdcb21, 0x980e4c65}, {0x190d5b28, 0xba068d58}, {0x191dcb28, 0xba0ece4b}, {0x192d5b2f, 0xdc070f35}, {0x193dcb2f, 0xdc0f5009}, {0x30000000, 0x0}, {0x30000000, 0x0}, {0x30000000, 0x0}, {0x30000000, 0x0}, {0x30000000, 0x0}, {0x30000000, 0x0}, {0x30000000, 0x0}, {0x30000000, 0x0}},
    {{0x3807000, 0x700000}, {0x3877601, 0x170407b}, {0x38e7403, 0x270c114}, {0x3957205, 0x37141ad}, {0x186e2305, 0x310002c2}, {0x1c0007, 0x401c337}, {0x2de5c07, 0x559c3ad}, {0x187e3f05, 0x31044422}, {0xe41809, 0x51a449f}, {0x188e5b05, 0x31048580}, {0xec180b, 0x71ac5f8}, {0x189e7705, 0x3108c6d1}, {0x1b4300d, 0x8334751}, {0x18ae9305, 0x31090823}, {0xfc180f, 0x91bc89a}, {0x18beaf05, 0x310d4957}, {0x18cecb05, 0x310d89ff}, {0x18ded913, 0x750dcaa8}, {0x18ee6221, 0x98060b82}, {0x18fed221, 0x980e4c75}, {0x190e6228, 0xba068d67}, {0x191ed228, 0xba0ece5a}, {0x192e622f, 0xdc070f42}, {0x193ed22f, 0xdc0f5016}, {0x30000000, 0x0}, {0x30000000, 0x0}, {0x30000000, 0x0}, {0x30000000, 0x0}, {0x30000000, 0x0}, {0x30000000, 0x0}, {0x30000000, 0x0}, {0x30000000, 0x0}},
    {{0x3c07800, 0x780000}, {0x3c77e01, 0x178407c}, {0x3ce7c03, 0x278c115}, {0x3d57a05, 0x37941ae}, {0x2a3e3f31, 0x3f81c239}, {0x186f230c, 0x200002d8}, {0x2a4d5432, 0x5582c362}, {0x187f3f0c, 0x20044438}, {0x3e47809, 0x57a44be}, {0x188f5b0c, 0x20048595}, {0x2ec580b, 0x75ac60d}, {0x189f770c, 0x2008c6e6}, {0x374680d, 0x86b4764}, {0x18af930c, 0x20090838}, {0x2bc500f, 0x953c8ad}, {0x18bfaf0c, 0x200d4961}, {0x18cfcb0c, 0x200d8a0a}, {0x18dfd91a, 0x640dcab2}, {0x18ef6921, 0x98060b91}, {0x18ffd921, 0x980e4c84}, {0x190f6928, 0xba068d77}, {0x191fd928, 0xba0ece6a}, {0x192f692f, 0xdc070f4f}, {0x193fd92f, 0xdc0f5024}, {0x30000000, 0x0}, {0x30000000, 0x0}, {0x30000000, 0x0}, {0x30000000, 0x0}, {0x30000000, 0x0}, {0x30000000, 0x0}, {0x30000000, 0x0}, {0x30000000, 0x0}},
    {{0x10200, 0x0}, {0x80002, 0x100807e}, {0xf0603, 0x200c117}, {0x160405, 0x30141b0}, {0x19400006, 0x310001f6}, {0x1572e05, 0x4294269}, {0x19500e14, 0x750042f3}, {0x1dd3a07, 0x439c375}, {0x19602a14, 0x75008452}, {0x2254209, 0x64244d8}, {0x19704614, 0x7504c5ae}, {0x12d220b, 0x722c625}, {0x19806214, 0x75050700}, {0x1752a0d, 0x82b4779}, {0x19907e14, 0x75094851}, {0xbd120f, 0x913c8c2}, {0x19a09a14, 0x7509896d}, {0x19b0b614, 0x750dca16}, {0x19c00022, 0x98020abe}, {0x19d07022, 0x980a4ba2}, {0x19e00029, 0xba028c95}, {0x19f07029, 0xba0acd88}, {0x1a000030, 0xdc030e7b}, {0x1a107030, 0xdc0b4f5e}, {0x30000000, 0x0}, {0x30000000, 0x0}, {0x30000000, 0x0}, {0x30000000, 0x0}, {0x30000000, 0x0}, {0x30000000, 0x0}, {0x30000000, 0x0}, {0x30000000, 0x0}},
    {{0x410a00, 0x80000}, {0x480802, 0x108807f}, {0x4f0e03, 0x208c118}, {0x560c05, 0x30941b1}, {0x1941000d, 0x20000201}, {0x2d75e05, 0x459427a}, {0x19510e1b, 0x64004308}, {0x35d6a07, 0x469c387}, {0x19612a1b, 0x64008468}, {0x260409, 0x60244ee}, {0x1971461b, 0x6404c5c3}, {0x32d620b, 0x762c63a}, {0x1981621b, 0x64050715}, {0x335620d, 0x863478b}, {0x19917e1b, 0x64094866}, {0x23d420f, 0x943c8d2}, {0x19a19a1b, 0x64098978}, {0x19b1b61b, 0x640dca20}, {0x19c10722, 0x98020ac9}, {0x19d17722, 0x980a4bb1}, {0x19e10729, 0xba028ca4}, {0x19f17729, 0xba0acd97}, {0x1a010730, 0xdc030e8a}, {0x1a117730, 0xdc0b4f6c}, {0x30000000, 0x0}, {0x30000000, 0x0}, {0x30000000, 0x0}, {0x30000000, 0x0}, {0x30000000, 0x0}, {0x30000000, 0x0}, {0x30000000, 0x0}, {0x30000000, 0x0}},
    {{0x811200, 0x100000}, {0x881002, 0x1108080}, {0x8f1603, 0x210c119}, {0x961405, 0x31141b2}, {0x19420706, 0x3100020c}, {0x580806, 0x409828a}, {0x19521514, 0x7500431e}, {0xde1c07, 0x519c397}, {0x19623114, 0x7500847e}, {0x1e63c09, 0x63a4500}, {0x19724d14, 0x7504c5d9}, {0xee1c0b, 0x71ac64c}, {0x19826914, 0x7505072a}, {0xf61c0d, 0x81b479e}, {0x19928514, 0x7509487b}, {0x37d6a0f, 0x96bc8df}, {0x19a2a114, 0x75098982}, {0x19b2bd14, 0x750dca2b}, {0x19c20e22, 0x98020ad3}, {0x19d27e22, 0x980a4bc0}, {0x19e20e29, 0xba028cb3}, {0x19f27e29, 0xba0acda6}, {0x1a020e30, 0xdc030e99}, {0x1a127e30, 0xdc0b4f79}, {0x30000000, 0x0}, {0x30000000, 0x0}, {0x30000000, 0x0}, {0x30000000, 0x0}, {0x30000000, 0x0}, {0x30000000, 0x0}, {0x30000000, 0x0}, {0x30000000, 0x0}},
    {{0xc11a00, 0x180000}, {0xc81802, 0x1188081}, {0xcf1e03, 0x218c11a}, {0xd61c05, 0x31941b3}, {0x1943070d, 0x20000217}, {0x2a444631, 0x4682429c}, {0x1953151b, 0x64004334}, {0x29e5407, 0x551c3aa}, {0x1963311b, 0x64008494}, {0x3a67409, 0x6724515}, {0x19734d1b, 0x6404c5ee}, {0x2ae540b, 0x752c65f}, {0x1983691b, 0x6405073f}, {0x1f63c0d, 0x83b47a7}, {0x1993851b, 0x64094890}, {0x7e0c0f, 0x90bc8e9}, {0x19a3a11b, 0x6409898d}, {0x19b3bd1b, 0x640dca35}, {0x19c31522, 0x98020ade}, {0x19d38522, 0x980a4bd0}, {0x19e31529, 0xba028cc2}, {0x19f38529, 0xba0acdb5}, {0x1a031530, 0xdc030ea8}, {0x1a138530, 0xdc0b4f86}, {0x30000000, 0x0}, {0x30000000, 0x0}, {0x30000000, 0x0}, {0x30000000, 0x0}, {0x30000000, 0x0}, {0x30000000, 0x0}, {0x30000000, 0x0}, {0x30000000, 0x0}},
    {{0x1012200, 0x200000}, {0x1082002, 0x1208083}, {0x10f2603, 0x220c11c}, {0x1162405, 0x32141b5}, {0x19440e06, 0x31000222}, {0x3987006, 0x47182ae}, {0x19542a06, 0x3100434a}, {0x9f1607, 0x511c3c0}, {0x19644606, 0x310484aa}, {0x1272609, 0x6224525}, {0x19746206, 0x3104c603}, {0x2f060b, 0x702c66f}, {0x2f15a0c, 0x75b06e0}, {0x19847e06, 0x31090754}, {0x1772e0d, 0x82b47cd}, {0x19949a06, 0x310948a5}, {0x3be740f, 0x973c90c}, {0x19a4b606, 0x310d8997}, {0x19b4d206, 0x310dca40}, {0x19c41c22, 0x98020aec}, {0x19d48c22, 0x980a4bdf}, {0x19e41c29, 0xba028cd2}, {0x19f48c29, 0xba0acdc4}, {0x1a041c30, 0xdc030eb7}, {0x1a148c30, 0xdc0b4f93}, {0x30000000, 0x0}, {0x30000000, 0x0}, {0x30000000, 0x0}, {0x30000000, 0x0}, {0x30000000, 0x0}, {0x30000000, 0x0}, {0x30000000, 0x0}},
    {{0x1412a00, 0x280000}, {0x1482802, 0x1288084}, {0x14f2e03, 0x228c11d}, {0x1562c05, 0x32941b6}, {0x19450e0d, 0x2000022d}, {0x1192206, 0x42182be}, {0x19552a0d, 0x20004360}, {0x25f4e07, 0x549c3d4}, {0x1965460d, 0x200484c0}, {0x2674e09, 0x64a4533}, {0xea1c0a, 0x61a85a4}, {0x1975620d, 0x2004c618}, {0x3ef7e0b, 0x77ac695}, {0x19857e0d, 0x20090769}, {0x337660d, 0x86347df}, {0x19959a0d, 0x200948ba}, {0x17f2e0f, 0x92bc91e}, {0x19a5b60d, 0x200d89a2}, {0x19b5d20d, 0x200dca4a}, {0x19c52322, 0x98020afb}, {0x19d59322, 0x980a4bee}, {0x19e52329, 0xba028ce1}, {0x19f59329, 0xba0acdd4}, {0x1a052330, 0xdc030ec6}, {0x1a159330, 0xdc0b4fa1}, {0x30000000, 0x0}, {0x30000000, 0x0}, {0x30000000, 0x0}, {0x30000000, 0x0}, {0x30000000, 0x0}, {0x30000000, 0x0}, {0x30000000, 0x0}},
    {{0x1813200, 0x300000}, {0x1883002, 0x1308085}, {0x18f3603, 0x230c11e}, {0x1963405, 0x33141b7}, {0x19461506, 0x31000238}, {0x2995206, 0x45182cf}, {0x19563106, 0x31004376}, {0x200008, 0x50203e7}, {0x19664d06, 0x310484d6}, {0x3e77e09, 0x67a4542}, {0x2aa540a, 0x65285b6}, {0x19766906, 0x3104c62d}, {0xf0180c, 0x71b06a1}, {0x19868506, 0x3109077e}, {0x78080e, 0x80b87ed}, {0x1996a106, 0x310948cf}, {0x33f660f, 0x963c931}, {0x19a6bd06, 0x310d89ac}, {0x19b6d906, 0x310dca55}, {0x19c62a22, 0x98020b0a}, {0x19d69a22, 0x980a4bfd}, {0x19e62a29, 0xba028cf0}, {0x19f69a29, 0xba0acde3}, {0x1a062a30, 0xdc030ed6}, {0x1a169a30, 0xdc0b4fae}, {0x30000000, 0x0}, {0x30000000, 0x0}, {0x30000000, 0x0}, {0x30000000, 0x0}, {0x30000000, 0x0}, {0x30000000, 0x0}, {0x30000000, 0x0}},
    {{0x1c13a00, 0x380000}, {0x1c83802, 0x1388087}, {0x1cf3e03, 0x238c120}, {0x1d63c05, 0x33941b9}, {0x1947150d, 0x20000243}, {0x1a0406, 0x40182df}, {0x1957310d, 0x2000438c}, {0x1e03808, 0x53a03f9}, {0xe31e08, 0x51a0473}, {0x19674d0d, 0x200484ec}, {0x690a0a, 0x60a8574}, {0x1977690d, 0x2004c642}, {0x270480c, 0x74b06b0}, {0x1987850d, 0x20090793}, {0x278480e, 0x84b8802}, {0x1997a10d, 0x200948e4}, {0x19a7bd0d, 0x200d89b7}, {0x19b7d90d, 0x200dca5f}, {0x19c73122, 0x98020b19}, {0x19d7a122, 0x980a4c0c}, {0x19e73129, 0xba028cff}, {0x19f7a129, 0xba0acdf2}, {0x1a073130, 0xdc030ee5}, {0x1a17a130, 0xdc0b4fbb}, {0x30000000, 0x0}, {0x30000000, 0x0}, {0x30000000, 0x0}, {0x30000000, 0x0}, {0x30000000, 0x0}, {0x30000000, 0x0}, {0x30000000, 0x0}, {0x30000000, 0x0}},
    {{0x2014200, 0x400000}, {0x2084002, 0x1408088}, {0x20f4603, 0x240c121}, {0x2164405, 0x34141ba}, {0x19480014, 0x7500024e}, {0x1da3c06, 0x43982f1}, {0x19581c14, 0x750043a2}, {0x3a07008, 0x572040d}, {0x19683814, 0x75048502}, {0x368680a, 0x66a856a}, {0x19785414, 0x7504c657}, {0x1b0300c, 0x73306a9}, {0x1f33e0c, 0x83b0728}, {0x19887014, 0x750907a8}, {0xf91a0e, 0x81b881c}, {0x19988c14, 0x750948f9}, {0x19a8a814, 0x750d89c1}, {0x19b8c414, 0x750dca6a}, {0x19c83822, 0x98060b29}, {0x19d8a822, 0x980e4c1b}, {0x19e83829, 0xba068d0e}, {0x19f8a829, 0xba0ece01}, {0x1a083830, 0xdc070ef4}, {0x1a18a830, 0xdc0f4fc9}, {0x30000000, 0x0}, {0x30000000, 0x0}, {0x30000000, 0x0}, {0x30000000, 0x0}, {0x30000000, 0x0}, {0x30000000, 0x0}, {0x30000000, 0x0}, {0x30000000, 0x0}},
    {{0x2414a00, 0x480000}, {0x2484802, 0x1488089}, {0x24f4e03, 0x248c122}, {0x2564c05, 0x34941bb}, {0x1949001b, 0x64000259}, {0x2da5c06, 0x45982fe}, {0x19591c1b, 0x640043b8}, {0x1612a08, 0x52a0421}, {0x1969381b, 0x64048518}, {0x129220a, 0x622857c}, {0x1979541b, 0x6404c66c}, {0x330600c, 0x76306b8}, {0x1989701b, 0x640907bd}, {0x2f8580e, 0x85b8807}, {0x27b4e0e, 0x94b8880}, {0x19998c1b, 0x6409490e}, {0x19a9a81b, 0x640d89cc}, {0x19b9c41b, 0x640dca75}, {0x19c93f22, 0x98060b38}, {0x19d9af22, 0x980e4c2b}, {0x19e93f29, 0xba068d1d}, {0x19f9af29, 0xba0ece10}, {0x1a093f30, 0xdc070f01}, {0x1a19af30, 0xdc0f4fd6}, {0x30000000, 0x0}, {0x30000000, 0x0}, {0x30000000, 0x0}, {0x30000000, 0x0}, {0x30000000, 0x0}, {0x30000000, 0x0}, {0x30000000, 0x0}, {0x30000000, 0x0}},
    {{0x2815200, 0x500000}, {0x2885002, 0x150808b}, {0x28f5603, 0x250c124}, {0x2965405, 0x35141bd}, {0x194a0714, 0x7500026f}, {0x39a7406, 0x4718306}, {0x195a2314, 0x750043ce}, {0x2214208, 0x5420429}, {0x1e43809, 0x53a44a8}, {0x196a3f14, 0x7504852e}, {0x6a0c0a, 0x60a859f}, {0x197a5b14, 0x7504c681}, {0x1722c0c, 0x72b06fa}, {0x198a7714, 0x750907d2}, {0x1ba340e, 0x933884e}, {0x199a9314, 0x75094923}, {0x19aaaf14, 0x750d89d6}, {0x19bacb14, 0x750dca7f}, {0x19ca4622, 0x98060b47}, {0x19dab622, 0x980e4c3a}, {0x19ea4629, 0xba068d2d}, {0x19fab629, 0xba0ece20}, {0x1a0a4630, 0xdc070f0f}, {0x1a1ab630, 0xdc0f4fe3}, {0x30000000, 0x0}, {0x30000000, 0x0}, {0x30000000, 0x0}, {0x30000000, 0x0}, {0x30000000, 0x0}, {0x30000000, 0x0}, {0x30000000, 0x0}, {0x30000000, 0x0}},
    {{0x2c15a00, 0x580000}, {0x2c85802, 0x158808c}, {0x2cf5e03, 0x258c125}, {0x2d65c05, 0x35941be}, {0x194b071b, 0x64000285}, {0x5b0e06, 0x409830e}, {0x195b231b, 0x640043e4}, {0x3616a08, 0x56a0436}, {0x196b3f1b, 0x64048544}, {0x2a9520a, 0x652858c}, {0x1ec380b, 0x73ac601}, {0x197b5b1b, 0x6404c696}, {0x3b2740c, 0x7730712}, {0x198b771b, 0x640907e7}, {0x3ba740e, 0x9738863}, {0x199b931b, 0x64094938}, {0x19abaf1b, 0x640d89e1}, {0x19bbcb1b, 0x640dca8a}, {0x19cb4d22, 0x98060b56}, {0x19dbbd22, 0x980e4c49}, {0x19eb4d29, 0xba068d3c}, {0x19fbbd29, 0xba0ece2f}, {0x1a0b4d30, 0xdc070f1c}, {0x1a1bbd30, 0xdc0f4ff0}, {0x30000000, 0x0}, {0x30000000, 0x0}, {0x30000000, 0x0}, {0x30000000, 0x0}, {0x30000000, 0x0}, {0x30000000, 0x0}, {0x30000000, 0x0}, {0x30000000, 0x0}},
    {{0x3016200, 0x600000}, {0x3086002, 0x160808d}, {0x30f6603, 0x260c126}, {0x3166405, 0x36141bf}, {0x194c1c06, 0x3100029b}, {0x1db3e06, 0x439831d}, {0x195c3806, 0x310443fa}, {0x1622c08, 0x52a044c}, {0x196c5406, 0x3104855a}, {0x12a240a, 0x62285a6}, {0x6d0a0b, 0x70ac61d}, {0x197c7006, 0x3108c6ab}, {0x233460c, 0x843072c}, {0x198c8c06, 0x310907fc}, {0x17b2e0e, 0x92b8876}, {0x199ca806, 0x310d4943}, {0x19acc406, 0x310d89ec}, {0x19bcd214, 0x750dca94}, {0x19cc5422, 0x98060b65}, {0x19dcc422, 0x980e4c58}, {0x19ec5429, 0xba068d4b}, {0x19fcc429, 0xba0ece3e}, {0x1a0c5430, 0xdc070f29}, {0x1a1cc430, 0xdc0f4ffe}, {0x30000000, 0x0}, {0x30000000, 0x0}, {0x30000000, 0x0}, {0x30000000, 0x0}, {0x30000000, 0x0}, {0x30000000, 0x0}, {0x30000000, 0x0}, {0x30000000, 0x0}},
    {{0x3416a00, 0x680000}, {0x3486802, 0x168808f}, {0x34f6e03, 0x268c128}, {0x3566c05, 0x36941c1}, {0x194d1c0d, 0x200002b1}, {0x31b6606, 0x461832c}, {0x195d380d, 0x20044410}, {0x3626c08, 0x56a0462}, {0x196d540d, 0x2004856f}, {0x3aa740a, 0x67285c1}, {0x2ed5a0b, 0x75ac637}, {0x197d700d, 0x2008c6c0}, {0x34000d, 0x8034741}, {0x198d8c0d, 0x20090811}, {0x37b6e0e, 0x96b888b}, {0x199da80d, 0x200d494e}, {0x19adc40d, 0x200d89f6}, {0x19bdd21b, 0x640dca9f}, {0x19cd5b22, 0x98060b74}, {0x19ddcb22, 0x980e4c67}, {0x19ed5b29, 0xba068d5a}, {0x19fdcb29, 0xba0ece4d}, {0x1a0d5b30, 0xdc070f36}, {0x1a1dcb30, 0xdc0f500b}, {0x30000000, 0x0}, {0x30000000, 0x0}, {0x30000000, 0x0}, {0x30000000, 0x0}, {0x30000000, 0x0}, {0x30000000, 0x0}, {0x30000000, 0x0}, {0x30000000, 0x0}},
    {{0x3817200, 0x700000}, {0x3887002, 0x1708090}, {0x38f7603, 0x270c129}, {0x3967405, 0x37141c2}, {0x2a3f3f32, 0x4081c244}, {0x194e2306, 0x310002c7}, {0x29c5007, 0x451c353}, {0x195e3f06, 0x31044426}, {0x1a43009, 0x53244a7}, {0x196e5b06, 0x31048584}, {0x12c200b, 0x722c5fb}, {0x197e7706, 0x3108c6d5}, {0x1f4380d, 0x83b4752}, {0x198e9306, 0x31090827}, {0x13c200f, 0x923c89d}, {0x199eaf06, 0x310d4958}, {0x19aecb06, 0x310d8a01}, {0x19bed914, 0x750dcaa9}, {0x19ce6222, 0x98060b84}, {0x19ded222, 0x980e4c77}, {0x19ee6229, 0xba068d69}, {0x19fed229, 0xba0ece5c}, {0x1a0e6230, 0xdc070f44}, {0x1a1ed230, 0xdc0f5018}, {0x30000000, 0x0}, {0x30000000, 0x0}, {0x30000000, 0x0}, {0x30000000, 0x0}, {0x30000000, 0x0}, {0x30000000, 0x0}, {0x30000000, 0x0}, {0x30000000, 0x0}},
    {{0x3c17a00, 0x780000}, {0x3c87802, 0x1788091}, {0x3cf7e03, 0x278c12a}, {0x3d67c05, 0x37941c3}, {0x2a402a33, 0x2c82024f}, {0x194f230d, 0x200002dd}, {0x1d0207, 0x401c363}, {0x195f3f0d, 0x2004443c}, {0x250209, 0x60244c3}, {0x196f5b0d, 0x20048599}, {0x32c600b, 0x762c610}, {0x197f770d, 0x2008c6ea}, {0x3b4700d, 0x8734766}, {0x198f930d, 0x2009083c}, {0x2fc580f, 0x95bc8af}, {0x199faf0d, 0x200d4963}, {0x19afcb0d, 0x200d8a0b}, {0x19bfd91b, 0x640dcab4}, {0x19cf6922, 0x98060b93}, {0x19dfd922, 0x980e4c86}, {0x19ef6929, 0xba068d79}, {0x19ffd929, 0xba0ece6b}, {0x1a0f6930, 0xdc070f51}, {0x1a1fd930, 0xdc0f5025}, {0x30000000, 0x0}, {0x30000000, 0x0}, {0x30000000, 0x0}, {0x30000000, 0x0}, {0x30000000, 0x0}, {0x30000000, 0x0}, {0x30000000, 0x0}, {0x30000000, 0x0}}
}};
static_assert(NJOB + NCONV == 32, "");

__device__ __forceinline__ unsigned read_back(const void* p) {
    unsigned v = 0;
    asm volatile("ld.relaxed.gpu.global.u32 %0, [%1];" : "=r"(v) : "l"(p) : "memory");
    return v;
}
__device__ __forceinline__ void publish(unsigned* flag, unsigned seen, unsigned zero) {
    asm volatile("{\n.reg .pred p;\n.reg .u32 t;\nredux.sync.or.b32 t, %1, 0xffffffff;\nand.b32 t, t, %2;\nadd.u32 t, t, 1;\n"
                 "elect.sync _|p, 0xffffffff;\n@p red.relaxed.gpu.global.add.u32 [%0], t;\n}" :: "l"(flag), "r"(seen), "r"(zero) : "memory");
}

__device__ __forceinline__ void load_w(uint2 (&v)[32], const char* g) {
#pragma unroll
    for (int k = 0; k < 32; k++)
        asm volatile("ld.global.nc.L1::no_allocate.v2.b32 {%0,%1}, [%2];" : "=r"(v[k].x), "=r"(v[k].y) : "l"(g + k * (N_ * 4)));
}
__device__ __forceinline__ void store_w(const uint2 (&v)[32], unsigned (&o)[16], char* d) {
#pragma unroll
    for (int i = 0; i < 8; i++) {
        o[i] = pack4(v[4 * i].x, v[4 * i + 1].x, v[4 * i + 2].x, v[4 * i + 3].x);
        o[8 + i] = pack4(v[4 * i].y, v[4 * i + 1].y, v[4 * i + 2].y, v[4 * i + 3].y);
        if ((i & 3) == 3) {
            stg128(d + (i >> 2) * 128, make_uint4(o[i - 3], o[i - 2], o[i - 1], o[i]));
            stg128(d + (i >> 2) * 128 + 256, make_uint4(o[i + 5], o[i + 6], o[i + 7], o[i + 8]));
        }
    }
}
__device__ __forceinline__ unsigned col_sums(const unsigned (&o)[16]) {
    int cs[4];
#pragma unroll
    for (int i = 0; i < 4; i++)
        cs[i] = __dp4a((int)o[4 * i], 0x01010101, __dp4a((int)o[4 * i + 1], 0x01010101,
                __dp4a((int)o[4 * i + 2], 0x01010101, __dp4a((int)o[4 * i + 3], 0x01010101, 0))));
    return cs[0] + cs[1] + (cs[2] + cs[3]) * 65536;
}
__device__ __forceinline__ void wait_until(int due, unsigned t0) {
    for (int rem; (rem = due - (int)(clk() - t0)) > 0;) if (rem > CFG_SLEEP) __nanosleep(CFG_SLEEP / 4);
}

__device__ __forceinline__ uint32_t zero_term(const unsigned (&sv)[4], float zxf) {
    int lo = 0, hi = 0;
#pragma unroll
    for (int h = 0; h < 4; h++) {
        const int l = (int)(short)(sv[h] & 0xFFFF);
        lo += l; hi += ((int)(sv[h] - (unsigned)l)) >> 16;
    }
    const float fl = __bfloat162float(__float2bfloat16_rn((float)lo)) * zxf, fh = __bfloat162float(__float2bfloat16_rn((float)hi)) * zxf;
    uint32_t z;
    asm("cvt.rn.bf16x2.f32 %0, %1, %2;" : "=r"(z) : "f"(fh), "f"(fl));
    return z;
}

__device__ __forceinline__ void load_x(Scratch* scr, uint32_t sb, int b, int lane) {
    const int r = b & 15;
    const unsigned tgt = (*(volatile unsigned*)&scr->epoch[b] + 1) * 4;
    const unsigned* f = scr->flag + r * FS + (lane & 15);
    const uint32_t sa = __shfl_sync(~0u, sb, 0);
    const char* const ga = (const char*)scr->a8 + __shfl_sync(~0u, r * 16 * 8192, 0);
    unsigned todo = 0xFFFF, v = ld_flag(f);
    asm volatile("barrier.cluster.wait.aligned;" ::: "memory");
#pragma unroll 1
    for (int it = 0; todo; it++) {
        unsigned m = __ballot_sync(~0u, (int)(v - tgt) >= 0) & todo;
        v = ld_flag(f);
        todo &= ~m;
        while (m) {
            const int sl = __ffs(m) - 1;
            m &= m - 1;
            asm volatile("{\n.reg .pred p;\nelect.sync _|p, 0xffffffff;\n"
                         "@p cp.async.bulk.shared::cluster.global.mbarrier::complete_tx::bytes [%0], [%1], 8192, [%2];\n}"
                         :: "r"(sa + sl * 8192), "l"(ga + (unsigned)sl * 8192), "r"(sa + SM_BAR + (B_FULL + sl) * 8) : "memory");
        }
        if (it > (1 << 20)) __trap();
    }
}

__device__ __forceinline__ void load_x4(Scratch* scr, uint32_t sb, int b, int h, int lane) {
    const uint32_t bars = sb + SM_BAR;
    const unsigned tgt = (*(volatile unsigned*)&scr->epoch[b] + 1) * 4;
    const unsigned* f = scr->flag + (4 * h + (lane >> 4)) * FS + (lane & 15);
    asm volatile("barrier.cluster.wait.aligned;" ::: "memory");
#pragma unroll 1
    for (int it = 0, sl = 0; sl < 16; it++) {
        const unsigned v0 = ld_flag(f), v1 = ld_flag(f + 2 * FS);
        unsigned m = __ballot_sync(~0u, (int)(v0 - tgt) >= 0 && (int)(v1 - tgt) >= 0);
        m &= m >> 16;
#pragma unroll 1
        for (; m >> sl & 1; sl++) {
            if (sl >= 4) mbar_wait(bars + (B_GO + sl - 4) * 8);
            if (elect_one()) {
#pragma unroll
                for (int k = 0; k < 4; k++)
                    asm volatile("cp.async.bulk.shared::cluster.global.mbarrier::complete_tx::bytes [%0], [%1], %2, [%3];"
                                 :: "r"(sb + SM_A + ((sl & 3) * 4 + k) * 8192), "l"((const char*)scr->a8 + ((4 * h + k) * 16 + sl) * 8192),
                                    "r"(8192), "r"(bars + (B_FULL + (k >> 1) * 16 + sl) * 8) : "memory");
            }
        }
        if (it > (1 << 20)) __trap();
    }
}

__device__ __forceinline__ void store_out(const CUtensorMap* map, uint32_t sb, int b, int agent, int lane, int n, unsigned seq, int col, int dcol, int row, int drow) {
    const uint32_t bars = sb + SM_BAR;
    const uint32_t buf = sb + SM_OUT + agent * 4096, full = bars + (B_OFULL + agent) * 8;
#pragma unroll 1
    for (int t = 0; t < n; t++, seq >>= 4) {
        asm volatile("{\n.reg .pred p;\n.reg .u32 c;\nmov.u32 c, 0;\n"
                     "WAIT_LOOP:\n"
                     "mbarrier.try_wait.parity.shared::cta.b64 p, [%4], %5;\n"
                     "@p bra WAIT_DONE;\n"
                     "add.u32 c, c, 1;\nsetp.lt.u32 p, c, 0x100000;\n"
                     "@p bra WAIT_LOOP;\n"
                     "trap;\n"
                     "WAIT_DONE:\n"
                     "fence.proxy.async.shared::cta;\n"
                     "elect.sync _|p, 0xffffffff;\n"
                     "@p cp.async.bulk.tensor.2d.global.shared::cta.tile.bulk_group [%0, {%1, %2}], [%3];\n"
                     "cp.async.bulk.commit_group;\n}"
                     :: "l"(map), "r"(col + (seq & 7) * dcol), "r"(row + agent * 32 + (seq & 7) * drow), "r"(buf), "r"(full), "r"(t & 1) : "memory");
        asm volatile("cp.async.bulk.wait_group.read 0;" ::: "memory");
        if (elect_one()) mbar_arrive(bars + (B_OFREE + t * 4 + 4 + agent) * 8);
    }
}

template <int V> struct I { static constexpr int v = V; };
template <int MODE>
__device__ __forceinline__ void consume(Scratch* scr, const __nv_bfloat16* __restrict__ scale_w, const __nv_bfloat16* __restrict__ bias,
                                        const __nv_bfloat16* __restrict__ scale_x, uint32_t sb, int b, int warp, int lane) {
    constexpr bool SIDE = MODE != 0;
    constexpr int NR = NRING, NG = SIDE ? 48 : 56;
    const uint32_t bars = sb + SM_BAR;
    const int c = SIDE ? 7 : b >> 4;
    constexpr uint32_t SD = 0x400 >> 4;
    if ((sb & 0xFFFFFF) != 0x400) __trap();
    const int wg = warp >> 2;
    const unsigned short sxr = __ldg((const unsigned short*)scale_x);
    const uint32_t sx2 = (uint32_t)sxr * 0x10001u;
    const int c0 = (warp & 3) * 16 + (lane >> 2) * 2;
    uint32_t sw[4], bi[4];
#pragma unroll
    for (int i = 0; i < 4; i++) {
        const int col = col_of(c, i < 2 ? wg * 2 + i : i == 2 ? 4 + wg : 6) + c0;
        sw[i] = __ldg((const uint32_t*)(scale_w + col));
        bi[i] = __ldg((const uint32_t*)(bias + col));
    }
    const uint32_t st0 = sb + SM_OUT + (lane & 3) * 256 + (((c0 >> 3) ^ ((lane & 3) * 2)) << 4) + (c0 & 7) * 2;
    constexpr uint32_t DX0 = (SD + (SM_A >> 4)) | (1 << 16), DW0 = (SD + (SM_RING >> 4)) | (8 << 16);
    asm volatile("barrier.cluster.wait.aligned;" ::: "memory");
    int a0[64], a1[64];
    constexpr int MUL = SIDE ? 4 : 2, NONE = 64 * MUL, BIAS = NR + 64 - NG;
    const uint32_t go = mapa(bars + B_GO * 8, lane & (SIDE ? 1 : 15)) - (64 - NG) * MUL;
    const int key = SIDE ? (lane < 2 ? lane * 4 : 1) : (lane < 16 ? (lane >> 2) * 2 : 1);
    int pend = NONE;
    uint32_t bb = bars + (B_FULL + wg * 16) * 8;
#define RELEASE() { if ((pend & (NONE + 8 - MUL)) == key) mbar_arrive_cluster(go + (pend & ~7)); }
    struct Par { uint32_t a, b, c, d; };
    auto load_par = [&](int blk, uint32_t swv, uint32_t biv) {
        mbar_wait_cluster(bars + (B_PAR + blk) * 8);
        const uint32_t zc = lds32(sb + SM_PAR + (blk * 64 + c0) * 2);
        const float sxf = __uint_as_float(sx2 << 16);
        const float s0 = sxf * __uint_as_float(swv << 16), s1 = sxf * __uint_as_float(swv & 0xFFFF0000u);
        Par P = {__float_as_uint(s0), __float_as_uint(s1), __float_as_uint(fmaf(-__uint_as_float(zc << 16), s0, __uint_as_float(biv << 16))),
                 __float_as_uint(fmaf(-__uint_as_float(zc & 0xFFFF0000u), s1, __uint_as_float(biv & 0xFFFF0000u)))};
        asm volatile("{\n.reg .pred p;\nsetp.ne.u32 p, %3, 0;\n@p st.shared.v2.b32 [%0], {%1, %2};\n}" :: "r"(st0), "r"(P.c), "r"(P.d), "r"(blockIdx.y) : "memory");
        return P;
    };
    auto drain = [&](int (&a)[64], auto Q, int t, const Par& P) {
#pragma unroll
        for (int q = Q.v; q < Q.v + 2; q++) {
#pragma unroll
            for (int j = 0; j < 8; j++) {
                const int o = q * 16 + (j >> 1) * 4 + (j & 1);
                asm("cvt.rn.f32.s32 %0, %0;\n\tcvt.rn.f32.s32 %1, %1;\n\tfma.rn.f32 %0, %0, %2, %4;\n\tfma.rn.f32 %1, %1, %3, %5;\n\t"
                    "cvt.rn.bf16x2.f32 %0, %1, %0;" : "+r"(a[o]), "+r"(a[o + 2]) : "r"(P.a), "r"(P.b), "r"(P.c), "r"(P.d));
            }
            mbar_wait(bars + (B_OFREE + t * 4 + q) * 8);
#pragma unroll
            for (int j = 0; j < 8; j++) sts32((st0 ^ ((j & 1) * 16)) + q * 4096 + (j >> 1) * 1024 + (j & 1) * 128, a[q * 16 + (j >> 1) * 4 + (j & 1)]);
            __syncwarp();
            if (lane == 0) mbar_arrive(bars + (B_OFULL + q) * 8);
        }
    };
    wg_fence();
    if (MODE == 2) {
#pragma unroll 1
        for (int s = 0; s < 16; s++) {
            mbar_wait2(bars + (B_FULL + 48 + (s >> 2) * 2) * 8, bb + s * 8);
            mma_rows2(a0, a1, DW0 + s * 256, DX0 + ((s & 3) * 4 + 2 * wg) * 512, s);
            wg_wait<1>();
            if (s && lane == 0) mbar_arrive(bars + (B_GO + s - 1) * 8);
        }
        const Par P = load_par(6, sw[3], bi[3]);
        wg_wait<0>();
        drain(a0, I<0>(), wg, P); drain(a0, I<2>(), wg, P);
        drain(a1, I<0>(), 2 + wg, P); drain(a1, I<2>(), 2 + wg, P);
    } else {
    {
        uint32_t tbl = wg ? STEPS1 : STEPS0;
        uint32_t ba = bars + B_FULL * 8;
        int u = MUL * (wg * D_ + BIAS);
        uint32_t dw = DW0 + wg * D_ * 512;
        static_assert(D_ < NR, "");
        mbar_wait2(ba, bb);
#pragma unroll 1
        for (uint32_t dx = DX0;;) {
            mma_unit2(a0, a1, dw, dx, dx - DX0);
            dx += 512; ba += 8; bb += 8;
            const bool ready = mbar_test2(ba, bb);
            wg_wait<1>();
            RELEASE()
            pend = u;
            if (dx == DX0 + 16 * 512) break;
            u += MUL + (tbl & 1) * MUL;
            dw += 512 + (tbl & 1) * 512;
            if (dw >= DW0 + NR * 512) dw -= NR * 512;
            tbl >>= 1;
            if (!ready && !mbar_test2(ba, bb)) {
                wg_wait<0>();
                RELEASE()
                pend = NONE;
                mbar_wait(ba);
                if (wg) mbar_wait(bb);
            }
        }
    }
    Par P0 = load_par(2 * wg, sw[0], bi[0]);
    const Par P1 = load_par(2 * wg + 1, sw[1], bi[1]);
#define RELEASE2() { if ((pend & (NONE + 8 - 2 * MUL)) == (key & ~MUL)) mbar_arrive_cluster(go + (pend & ~7)); }
    static_assert(NR % 2 == 0, "");
    wg_wait<0>();
#pragma unroll 1
    for (int ph = 0;; ph++) {
        const int m = ph ? MUL : 0;
        const int u0 = 32 + ph * 16 + wg * 8;
        uint32_t dw = DW0 + (ph ? 48 % NR : wg ? 40 % NR : 32 % NR) * 512;
        bb = bars + (B_FULL + u0) * 8;
        if ((pend & (NONE + 8 - MUL - m)) == (key & ~m)) mbar_arrive_cluster(go + (pend & ~7));
        drain(a0, I<0>(), ph ? (ph + wg) * 2 + (ph & 2) : wg, P0);
        const bool first = mbar_test(bb);
        drain(a0, I<2>(), wg ? 4 * ph + 1 : 3 * ph, P0);
        if (ph == 1) drain(a1, I<0>(), 3 + 2 * wg, P1);
        if (SIDE ? ph == 1 : ph + wg == 2) break;
        pend = NONE;
        if (!first) mbar_wait(bb);
        if (ph + wg) mbar_wait(bars + (B_TURN + ph) * 8);
        wg_fence();
#pragma unroll 1
        for (int n = 0;; n += 2) {
            RELEASE2()
            const bool ready = mma_pair(a0, dw, DX0 + n * 1024, n, bb + n * 8 + 16);
            wg_wait<1>();
            pend = n ? MUL * (u0 + BIAS + n - 2) : NONE;
            if (n == 6) break;
            dw += 1024;
            if (dw == DW0 + NR * 512) dw = DW0;
            if (!ready) {
                RELEASE2()
                pend = NONE;
                mbar_wait(bb + n * 8 + 16);
            }
        }
        if (ph == 0 && (threadIdx.x & 127) == 0) mbar_arrive(bars + (B_TURN + wg) * 8);
        RELEASE2()
        pend = MUL * (u0 + BIAS + 6);
        if (ph == 0) drain(a1, I<2>(), 2 + 2 * wg, P1);
        P0 = load_par(4 + 2 * ph + wg, ph ? sw[3] : sw[2], ph ? bi[3] : bi[2]);
        wg_wait<0>();
    }
    }
    if (threadIdx.x == 128) asm volatile("red.relaxed.gpu.global.add.u32 [%0], 1;" :: "l"(scr->epoch + b) : "memory");
}

__global__ void __cluster_dims__(CS, 1, 1) __launch_bounds__(512, 1)
w8a8_kernel(const char* __restrict__ qx, const char* __restrict__ qw, Scratch* scr, const JobTable* __restrict__ jobs, const __nv_bfloat16* __restrict__ scale_w,
            const __nv_bfloat16* __restrict__ bias, const __nv_bfloat16* __restrict__ scale_x, const int* __restrict__ zero_x,
            const __grid_constant__ CUtensorMap map) {
    extern __shared__ __align__(1024) unsigned char smem_raw[];
    const uint32_t sb = (uint32_t)__cvta_generic_to_shared(smem_raw);
    const uint32_t bars = sb + SM_BAR;
    const int warp = __shfl_sync(~0u, threadIdx.x >> 5, 0), lane = threadIdx.x & 31;
    const int b = blockIdx.x, r = b & 15, c = b >> 4;
    const unsigned t0 = clk() + CFG_PF0;
    if (warp < CFG_NINIT) {
#pragma unroll 1
        for (int w = warp; w < 8; w += CFG_NINIT) {
            if (elect_one()) {
                const uint32_t cnt = w < B_GO / 16 ? 1 : 4 * CS + 1;
#pragma unroll
                for (int i = 0; i < 16; i++) mbar_init(bars + (w * 16 + i) * 8, cnt);
            }
            __syncwarp();
            const int i = w * 16 + lane;
            if (lane < 16 && i < B_OFREE + NOUT && (i >> 1) != B_TURN / 2) mbar_expect_tx(bars + i * 8, i >= B_AFREE ? 0 : i >= B_PAR ? 128 : w == 1 ? 8192 : 16384);
            if (w == B_GO / 16 && 4 * lane + (r >> 2) < NRING)
                asm volatile("mbarrier.arrive.shared::cta.b64 _, [%0], %1;" :: "r"(bars + i * 8), "r"(4 * CS) : "memory");
        }
        if (warp == (B_SUM / 16) % CFG_NINIT) {
            if (elect_one()) {
#pragma unroll
                for (int k = 0; k < NOUT; k++) mbar_init(bars + (B_OFULL + k) * 8, 4);
                mbar_init(bars + B_SUM * 8, r < 8 ? 1 : 3);
                mbar_expect_tx(bars + B_SUM * 8, r < 8 ? 32 * 64 : 30 * 64);
            }
        }
        asm volatile("fence.mbarrier_init.release.cluster;" ::: "memory");
    } else if (warp == 7) {
        asm volatile("st.shared.v2.b32 [%0], {%1, %1};" :: "r"(sb + SM_SUM + lane * 8), "r"(0) : "memory");
        asm volatile("fence.release.sync_restrict::shared::cta.cluster;" ::: "memory");
    } else if (warp == 9) {
        asm volatile("griddepcontrol.launch_dependents;");
        if (elect_one()) asm volatile("prefetch.tensormap [%0];" :: "l"(&map) : "memory");
    } else if (warp >= 14) {
        const char* pf = qx + (r * 128 + ((threadIdx.x >> 1) & 31)) * (K_ * 4) + (lane & 1) * 128;
        if (c >= 5) asm volatile("prefetch.global.L2 [%0];" :: "l"(pf + (c - 5) * (32 * K_ * 4)) : "memory");
        asm volatile("prefetch.global.L2 [%0];" :: "l"(pf + ((c + 2) & 3) * (32 * K_ * 4) + ((c + 2) >> 2) * 256) : "memory");
    }
    asm volatile("barrier.cluster.arrive.relaxed.aligned;" ::: "memory");

    if (warp >= 8) {
        asm volatile("setmaxnreg.dec.sync.aligned.u32 88;");
        int agent = -1;
        if (warp >= 16 - NCONV) {
            const int cw = warp - (16 - NCONV);
            const unsigned zero = blockIdx.y;
            const char* const gx = qx + (lane >> 4) * (K_ * 4) + (lane & 15) * 16;
            const char* const gw = qw + lane * 8;
            const int wrB = ((lane >> 3) * 32 + (lane & 7)) * 16;
            uint2 tab;
            asm volatile("ld.global.nc.v2.u32 {%0, %1}, [%2];" : "=r"(tab.x), "=r"(tab.y) : "l"(&jobs->e[b][lane]));
            bool synced = false;
#pragma unroll 1
            for (int p = cw || c >= 5 ? cw : NCONV;; p = p < CFG_PZ ? p + NCONV : p < CFG_PZ + 3 ? 31 : p + 3) {
                uint2 j;
                if (p < 4) {
                    const int g = 7 * p + c - 5;
                    j.x = ((r * 128 + (g & 3) * 32) * 16 + (g >> 2)) | (r * 64 + g) << 16;
                    j.y = max((p - 1) * (CFG_P0 / 4) + b * (CFG_P0 * 4 / NCTA) / 16, 0) | (r * FS + (g >> 2)) << 14 | p << 24;
                } else { j.x = __shfl_sync(~0u, tab.x, p); j.y = __shfl_sync(~0u, tab.y, p); }
                if (j.x >= 3u << 28) break;
                const int kind = j.x >> 28, sig = (j.y >> 14) & 0x3FF;
                char* tile = (char*)scr + ((j.x >> 16) & 0xFFF) * 2048;
                const char* g = (kind ? gw : gx) + (j.x & 0xFFFF) * 256;
                wait_until((j.y & 0x3FFF) * 4, t0);
                if (kind == 0) {
                    uint4 v[16];
#pragma unroll
                    for (int i = 0; i < 16; i++)
                        asm volatile("ld.global.nc.L1::no_allocate.v4.b32 {%0,%1,%2,%3}, [%4];"
                                     : "=r"(v[i].x), "=r"(v[i].y), "=r"(v[i].z), "=r"(v[i].w) : "l"(g + i * (2 * K_ * 4)));
#pragma unroll
                    for (int i = 0; i < 16; i++)
                        asm volatile("st.global.b32 [%0], %1;" :: "l"(tile + ((lane * 4) ^ ((i & 3) * 16)) + i * 128),
                                     "r"(pack4(v[i].x, v[i].y, v[i].z, v[i].w)) : "memory");
                    asm volatile("fence.proxy.async.global;" ::: "memory");
                    __syncwarp();
                    publish(scr->flag + sig, read_back(tile + lane * 64), zero);
                } else {
                    uint2 v[32];
                    unsigned o[16];
                    load_w(v, g);
                    if (!synced) asm volatile("barrier.cluster.wait.aligned;" ::: "memory");
                    synced = true;
                    store_w(v, o, tile + wrB);
                    asm volatile("{\n.reg .pred p;\nsetp.eq.u32 p, %1, 0;\nfence.proxy.async.global;\nbar.warp.sync 0xffffffff;\n"
                                 "@p mbarrier.arrive.shared::cta.b64 _, [%0];\n}" :: "r"(bars + (B_GO + (sig & 15)) * 8), "r"(lane | (kind & 2)) : "memory");
                    const unsigned csv = col_sums(o);
                    if (kind == 1) {
                        const int own = (j.y >> (24 + (lane >> 4) * 4)) & 15;
                        const uint32_t so = SM_SUM + (sig & 48) * 4 + (lane & 15) * 4;
                        if (own != r) {
                            const uint32_t ro = mapa(sb, own);
                            asm volatile("red.async.relaxed.cluster.shared::cluster.mbarrier::complete_tx::bytes.add.u32 [%0], %1, [%2];"
                                         :: "r"(ro + so), "r"(csv), "r"(ro + SM_BAR + B_SUM * 8) : "memory");
                        } else asm volatile("red.relaxed.cluster.shared::cta.add.u32 [%0], %1;" :: "r"(sb + so), "r"(csv) : "memory");
                        __syncwarp();
                        if (own == r && (lane & 15) == 0) mbar_arrive(bars + B_SUM * 8);
                    } else {
                        unsigned* csp = scr->cs + (j.y >> 24) * 32 + lane;
                        asm volatile("st.global.u32 [%0], %1;" :: "l"(csp), "r"(csv) : "memory");
                        publish(scr->flag + sig, read_back(tile + lane * 64) | read_back(csp), zero);
                    }
                }
                __syncwarp();
            }
            if (!synced) asm volatile("barrier.cluster.wait.aligned;" ::: "memory");
            agent = (cw + 6 * NCONV - CFG_PZ) % NCONV + 1;
            if (agent > 3) agent = -1;
        } else if (warp == 9) {
            asm volatile("barrier.cluster.wait.aligned;" ::: "memory");
        } else {
            load_x(scr, sb, b, lane);
            agent = 0;
        }
        const char* src = (const char*)scr->b8 + (c * 224 + r) * 2048;
        const int zxi = __ldg(zero_x);
#pragma unroll 1
        for (int i = 0, slot = r >> 2, end = 8;; end = NG / 4) {
#pragma unroll 1
            for (; warp == 9 && i < end; i++) {
                asm volatile("{\n.reg .pred p;\nWAIT_LOOP:\nmbarrier.try_wait.parity.shared::cta.b64 p, [%4], 0;\n@!p bra WAIT_LOOP;\n"
                             "elect.sync _|p, 0xffffffff;\n"
                             "@p cp.async.bulk.shared::cluster.global.mbarrier::complete_tx::bytes.multicast::cluster [%0], [%1], 2048, [%2], %3;\n}"
                             :: "r"(sb + SM_RING + slot * 8192 + (r & 3) * 2048), "l"(src + i * 32768),
                                "r"(bars + (B_FULL + bar_of(4 * i + (r >> 2))) * 8), "h"((uint16_t)0xFFFF), "r"(bars + (B_GO + i) * 8) : "memory");
                slot += slot >= NRING - 4 ? 4 - NRING : 4;
            }
            if (end != 8) break;
            if (warp == (r < 8 ? 9 : r < 10 ? 8 : r < 14 ? 16 - NCONV + (CFG_PZ + 3) % NCONV : 0)) {
                const float zxf = __bfloat162float(__float2bfloat16_rn((float)zxi));
                const int grp = sum_group(r);
                mbar_wait_cluster(bars + B_SUM * 8);
                unsigned sv[4];
#pragma unroll
                for (int h = 0; h < 4; h++) sv[h] = lds32(sb + SM_SUM + h * 64 + (lane & 15) * 4);
                const uint32_t z = zero_term(sv, zxf);
#pragma unroll 2
                for (int k = 0; k < 8; k++) {
                    const uint32_t rb = mapa(sb, k * 2 + (lane >> 4));
                    st_async32(rb + SM_PAR + grp * 64 + (lane & 15) * 4, z, rb + SM_BAR + (B_PAR + (grp >> 1)) * 8);
                }
            }
        }
        __syncwarp();
        if (agent >= 0) store_out(&map, sb, b, agent, lane, 7, agent < 2 ? 0x6351420 : 0x6534120, c * 64, 7 * 64, r * 128, 0);
    } else {
        asm volatile("setmaxnreg.inc.sync.aligned.u32 168;");
        consume<0>(scr, scale_w, bias, scale_x, sb, b, warp, lane);
    }
}

__global__ void __cluster_dims__(2, 1, 1) __launch_bounds__(512, 1)
w8a8_side(const char* __restrict__ qw, Scratch* scr, const __nv_bfloat16* __restrict__ scale_w, const __nv_bfloat16* __restrict__ bias,
          const __nv_bfloat16* __restrict__ scale_x, const int* __restrict__ zero_x, const __grid_constant__ CUtensorMap map) {
    extern __shared__ __align__(1024) unsigned char smem_raw[];
    const uint32_t sb = (uint32_t)__cvta_generic_to_shared(smem_raw);
    const uint32_t bars = sb + SM_BAR;
    const int warp = __shfl_sync(~0u, threadIdx.x >> 5, 0), lane = threadIdx.x & 31;
    const int b = NCTA + blockIdx.x, rank = b & 1;
    const bool helper = blockIdx.x >= 16;
    constexpr int NR = NRING;
    const unsigned t0 = clk();
    if (warp < 3) {
#pragma unroll 1
        for (int w = warp; w < B_OFULL / 16; w += 3) {
            if (elect_one()) {
                const uint32_t cnt = w < B_GO / 16 ? 1 : !helper ? 9 : w == B_GO / 16 ? 8 : 1;
#pragma unroll
                for (int i = 0; i < 16; i++) mbar_init(bars + (w * 16 + i) * 8, cnt);
            }
            __syncwarp();
            const int i = w * 16 + lane;
            if (lane < 16 && i < B_PAR) mbar_expect_tx(bars + i * 8, w == 1 && !helper ? 8192 : 16384);
            if (lane < 16 && i >= B_OFREE && i < B_OFREE + NOUT) mbar_arrive(bars + i * 8);
            if (w == B_GO / 16 && 2 * lane + rank < NR && !helper)
                asm volatile("mbarrier.arrive.shared::cta.b64 _, [%0], %1;" :: "r"(bars + i * 8), "r"(8) : "memory");
        }
        asm volatile("fence.mbarrier_init.release.cluster;" ::: "memory");
    } else if (warp == 3) {
        if (elect_one()) {
#pragma unroll
            for (int i = 0; i < NOUT; i++) mbar_init(bars + (B_OFULL + i) * 8, 4);
            asm volatile("fence.mbarrier_init.release.cluster;" ::: "memory");
        }
        __syncwarp();
    } else if (warp == 11 && elect_one()) asm volatile("prefetch.tensormap [%0];" :: "l"(&map) : "memory");
    asm volatile("barrier.cluster.arrive.relaxed.aligned;" ::: "memory");

    if (warp >= 8) {
        asm volatile("setmaxnreg.dec.sync.aligned.u32 88;");
        int agent = -1;
        if (warp == 10 || warp >= 12) {
#pragma unroll 1
            for (int i = (0x032401 >> (4 * (warp - 10))) & 7; i < (helper ? 8 : 12 - CFG_NOC / 4); i += 5) {
                const int G = (helper ? 192 - 16 + i * 4 : CFG_NOC * 4 + i * 16) + blockIdx.x, u = G >> 2, f = bar_of(u);
                const int blk = u < 32 ? (f >> 4) * 2 + (G & 1) : u >> 3, step = u < 32 ? (f & 15) * 2 + (G >> 1 & 1) : G & 31;
                char* const tile = (char*)scr->b8 + (7 * 224 + G) * 2048;
                unsigned* const csp = scr->cs + (step * 7 + blk) * 32 + lane;
                uint2 v[32];
                unsigned o[16];
                wait_until(helper ? i * CFG_YH + CFG_YH0 : (G - CFG_NOC * 4) * (CFG_YP / 16) + CFG_Y0, t0);
                load_w(v, qw + step * (32 * N_ * 4) + (49 + blk) * 256 + lane * 8);
                store_w(v, o, tile + ((lane >> 3) * 32 + (lane & 7)) * 16);
                asm volatile("st.global.u32 [%0], %1;" :: "l"(csp), "r"(col_sums(o)) : "memory");
                asm volatile("fence.proxy.async.global;" ::: "memory");
                __syncwarp();
                publish(scr->flag + CS * FS + u, read_back(tile + lane * 64) | read_back(csp), blockIdx.y);
            }
        }
        if (warp == 8) {
            if (helper) load_x4(scr, sb, b, blockIdx.x - 16, lane);
            else load_x(scr, sb, b, lane);
            agent = 0;
        } else if (warp == 11) {
            const unsigned tgt = (*(volatile unsigned*)&scr->epoch[b] + 1) * 4;
            const unsigned* f = scr->flag + CS * FS + lane;
            unsigned todo0 = helper ? 0 : ~0u, todo1 = helper ? 0xFF0000 : 0xFFFF, v0 = ld_flag(f), v1 = ld_flag(f + 32);
            bool par = lane >= 2;
            asm volatile("barrier.cluster.wait.aligned;" ::: "memory");
#pragma unroll 1
            for (int it = 0; todo0 | todo1; it++) {
                const unsigned m0 = __ballot_sync(~0u, (int)(v0 - tgt) >= 0) & todo0, m1 = __ballot_sync(~0u, (int)(v1 - tgt) >= 0) & todo1;
                v0 = ld_flag(f); v1 = ld_flag(f + 32);
                todo0 &= ~m0; todo1 &= ~m1;
                if ((lane & 1) == rank) {
                    if (m0 >> lane & 1) mbar_arrive(bars + (B_GO + (lane >> 1)) * 8);
                    if (m1 >> lane & 1) mbar_arrive(bars + (B_GO + 16 + (lane >> 1)) * 8);
                }
                if (!par && !(lane ? todo1 : todo0)) { par = true; mbar_arrive(bars + (B_AFREE + lane) * 8); }
                if (it > (1 << 20)) __trap();
            }
        } else if (warp == 9) {
            asm volatile("barrier.cluster.wait.aligned;" ::: "memory");
            const char* src = (const char*)scr->b8 + (7 * NG + rank) * 8192;
#pragma unroll 1
            for (int i = helper ? 24 : 0, slot = rank; i < (helper ? 28 : 24); i++) {
                asm volatile("{\n.reg .pred p;\nWAIT_LOOP:\nmbarrier.try_wait.parity.shared::cta.b64 p, [%4], 0;\n@!p bra WAIT_LOOP;\n"
                             "elect.sync _|p, 0xffffffff;\n"
                             "@p cp.async.bulk.shared::cluster.global.mbarrier::complete_tx::bytes.multicast::cluster [%0], [%1], 8192, [%2], %3;\n}"
                             :: "r"(sb + SM_RING + slot * 8192), "l"(src + i * 16384),
                                "r"(bars + (B_FULL + bar_of(2 * i + rank)) * 8), "h"((uint16_t)3), "r"(bars + (B_GO + i) * 8) : "memory");
                slot += slot >= NR - 2 ? 2 - NR : 2;
            }
        } else if (warp == 12 || warp == 15) {
            const float zxf = __bfloat162float(__float2bfloat16_rn((float)__ldg(zero_x)));
            asm volatile("barrier.cluster.wait.aligned;" ::: "memory");
#pragma unroll 1
            for (int blk = helper ? 6 + (warp & 2) : warp & 2; blk < (helper ? 7 : 6); blk += 4) {
                const int w = min(blk * 32 + lane * 2, TN / 2 - 2);
                mbar_wait(bars + (B_AFREE + (blk >> 2)) * 8);
                uint2 v[32];
                unsigned s0[4], s1[4];
#pragma unroll
                for (int k = 0; k < 32; k++) v[k] = __ldcg((const uint2*)(scr->cs + k * (TN / 2) + w));
#pragma unroll
                for (int h = 0; h < 4; h++) {
                    s0[h] = s1[h] = 0;
#pragma unroll
                    for (int k = 0; k < 8; k++) { s0[h] += v[8 * h + k].x; s1[h] += v[8 * h + k].y; }
                }
                sts32(sb + SM_PAR + w * 4, zero_term(s0, zxf));
                sts32(sb + SM_PAR + w * 4 + 4, zero_term(s1, zxf));
                __syncwarp();
                if (lane < 2) mbar_arrive(bars + (B_PAR + blk + lane) * 8);
            }
        } else {
            asm volatile("barrier.cluster.wait.aligned;" ::: "memory");
            agent = warp == 10 ? 1 : warp - 11;
        }
        if (agent >= 0) {
            if (helper) store_out(&map, sb, b, agent, lane, 4, 0x3120, col_of(7, 6), 0, (blockIdx.x - 16) * 512, 128);
            else store_out(&map, sb, b, agent, lane, 6, agent < 2 ? 0x351420 : 0x534120, col_of(7, 0), 64, blockIdx.x * 128, 0);
        }
    } else {
        asm volatile("setmaxnreg.inc.sync.aligned.u32 168;");
        if (helper) consume<2>(scr, scale_w, bias, scale_x, sb, b, warp, lane);
        else consume<1>(scr, scale_w, bias, scale_x, sb, b, warp, lane);
    }
}

}

typedef CUresult (*EncodeFn)(CUtensorMap*, CUtensorMapDataType, cuuint32_t, void*, const cuuint64_t*, const cuuint64_t*,
                             const cuuint32_t*, const cuuint32_t*, CUtensorMapInterleave, CUtensorMapSwizzle,
                             CUtensorMapL2promotion, CUtensorMapFloatOOBfill);

namespace w8 {

constexpr int M_ = 2048, K_ = 1024, N_ = 3584;
constexpr int WA = 160, WB = 64;
constexpr int TN = 2 * WA + 2 * WB;
static_assert(TN == 448, "");
constexpr int X1 = 13;
constexpr int NSLOT = 7, SLOT = WA * 64;
constexpr int NSTG = 3, PFD = 700, NCONV = 5;
constexpr int NU = 48;
constexpr int UX = 32 + NSLOT;
constexpr int NJOB = 22;
constexpr int NCTA = 128;

constexpr int nA = 64, nWA = WA / 4, nWB = WB / 4;
constexpr int SEG1 = X1 * (nA + 2 * nWA);
constexpr int SEG2 = SEG1 + (16 - X1) * (nA + nWA);
constexpr int SEG3 = SEG2 + (16 - X1) * nWA;
constexpr int SEG4 = SEG3 + 16 * nWB;
constexpr int SEG5 = SEG4 + 16 * nWB;
static_assert(SEG5 == NJOB * NCTA, "");

constexpr int SM_A = 0;
constexpr int SM_RING = 131072;
constexpr int SM_STG = SM_RING + NSLOT * SLOT;
constexpr int SM_PAR = SM_STG + NSTG * 8192;
constexpr int SM_BAR = SM_PAR + 3 * TN * 2;
constexpr int B_FULLB = 0, B_FULLA = 48, B_GO = 64, B_PAR = 88, B_PSTEP = 92, B_AFREE = 100, B_NINIT = 102, B_FULLS = 102, B_END = 108;
constexpr int SM_TOTAL = SM_BAR + B_END * 8;
static_assert(SM_TOTAL <= 232448, "");

__device__ uint4 g_a8[M_ * K_ / 16];
__device__ uint4 g_b8[N_ * K_ / 16];
__device__ uint4 g_cs[16 * N_ * 2 / 16];
__device__ unsigned g_flag[16 * 16 + 8 * 64];
__device__ unsigned g_epoch[NCTA];
__device__ unsigned g_sink;
constexpr int SM_ALLOC = SM_TOTAL;

__device__ __forceinline__ void mbar_init(uint32_t bar, uint32_t cnt) {
    asm volatile("mbarrier.init.shared::cta.b64 [%0], %1;" :: "r"(bar), "r"(cnt) : "memory");
}
__device__ __forceinline__ void mbar_expect_tx(uint32_t bar, uint32_t bytes) {
    asm volatile("mbarrier.arrive.expect_tx.shared::cta.b64 _, [%0], %1;" :: "r"(bar), "r"(bytes) : "memory");
}
__device__ __forceinline__ void mbar_arrive(uint32_t bar) {
    asm volatile("mbarrier.arrive.shared::cta.b64 _, [%0];" :: "r"(bar) : "memory");
}
__device__ __forceinline__ void mbar_arrive_cluster(uint32_t bar) {
    asm volatile("mbarrier.arrive.shared::cluster.b64 _, [%0];" :: "r"(bar) : "memory");
}
__device__ __forceinline__ void mbar_wait(uint32_t bar, uint32_t parity = 0) {
    asm volatile("{\n.reg .pred p;\n.reg .u32 c;\n"
                 "mbarrier.try_wait.parity.shared::cta.b64 p, [%0], %1;\n"
                 "@p bra WAIT_DONE;\n"
                 "mov.u32 c, 0;\n"
                 "WAIT_LOOP:\n"
                 "mbarrier.try_wait.parity.shared::cta.b64 p, [%0], %1;\n"
                 "@p bra WAIT_DONE;\n"
                 "add.u32 c, c, 1;\nsetp.lt.u32 p, c, 0x100000;\n"
                 "@p bra WAIT_LOOP;\n"
                 "trap;\n"
                 "WAIT_DONE:\n}" :: "r"(bar), "r"(parity) : "memory");
}
__device__ __forceinline__ void mbar_wait2(uint32_t bar0, uint32_t bar1) {
    asm volatile("{\n.reg .pred p, q;\n.reg .u32 c;\nmov.u32 c, 0;\n"
                 "WAIT_LOOP:\n"
                 "mbarrier.try_wait.parity.shared::cta.b64 p, [%0], 0;\n"
                 "mbarrier.try_wait.parity.shared::cta.b64 q, [%1], 0;\n"
                 "and.pred p, p, q;\n"
                 "@p bra WAIT_DONE;\n"
                 "add.u32 c, c, 1;\nsetp.lt.u32 p, c, 0x100000;\n"
                 "@p bra WAIT_LOOP;\n"
                 "trap;\n"
                 "WAIT_DONE:\n}" :: "r"(bar0), "r"(bar1) : "memory");
}
__device__ __forceinline__ bool mbar_test(uint32_t bar) {
    uint32_t ok;
    asm volatile("{\n.reg .pred p;\nmbarrier.test_wait.parity.shared::cta.b64 p, [%1], 0;\nselp.u32 %0, 1, 0, p;\n}" : "=r"(ok) : "r"(bar) : "memory");
    return ok;
}
__device__ __forceinline__ bool mbar_test2(uint32_t bar0, uint32_t bar1) {
    uint32_t ok;
    asm volatile("{\n.reg .pred p, q;\nmbarrier.test_wait.parity.shared::cta.b64 p, [%1], 0;\n"
                 "mbarrier.test_wait.parity.shared::cta.b64 q, [%2], 0;\nand.pred p, p, q;\nselp.u32 %0, 1, 0, p;\n}"
                 : "=r"(ok) : "r"(bar0), "r"(bar1) : "memory");
    return ok;
}
__device__ __forceinline__ bool elect_one() {
    uint32_t ok;
    asm volatile("{\n.reg .pred p;\nelect.sync _|p, 0xffffffff;\nselp.u32 %0, 1, 0, p;\n}" : "=r"(ok));
    return ok;
}
__device__ __forceinline__ unsigned ld_acquire(const unsigned* p) {
    unsigned v;
    asm volatile("ld.acquire.gpu.global.u32 %0, [%1];" : "=r"(v) : "l"(p) : "memory");
    return v;
}
__device__ __forceinline__ unsigned ld_flag(const unsigned* p) {
    unsigned v;
    asm volatile("ld.relaxed.gpu.global.u32 %0, [%1];" : "=r"(v) : "l"(p) : "memory");
    return v;
}
__device__ __forceinline__ uint4 lds128(uint32_t a) {
    uint4 v;
    asm volatile("ld.shared.v4.b32 {%0,%1,%2,%3}, [%4];" : "=r"(v.x), "=r"(v.y), "=r"(v.z), "=r"(v.w) : "r"(a) : "memory");
    return v;
}
__device__ __forceinline__ void sts128(uint32_t a, uint4 v) {
    asm volatile("st.shared.v4.b32 [%0], {%1,%2,%3,%4};" :: "r"(a), "r"(v.x), "r"(v.y), "r"(v.z), "r"(v.w) : "memory");
}
__device__ __forceinline__ uint32_t lds32(uint32_t a) {
    uint32_t v;
    asm volatile("ld.shared.b32 %0, [%1];" : "=r"(v) : "r"(a) : "memory");
    return v;
}
__device__ __forceinline__ void sts32(uint32_t a, uint32_t v) {
    asm volatile("st.shared.b32 [%0], %1;" :: "r"(a), "r"(v) : "memory");
}
__device__ __forceinline__ void stg128(void* p, uint4 v) {
    asm volatile("st.global.v4.b32 [%0], {%1,%2,%3,%4};" :: "l"(p), "r"(v.x), "r"(v.y), "r"(v.z), "r"(v.w) : "memory");
}
__device__ __forceinline__ unsigned pack4(unsigned a, unsigned b, unsigned c, unsigned d) {
    unsigned lo, r;
    asm("cvt.pack.sat.s8.s32.b32 %0, %1, %2, 0;" : "=r"(lo) : "r"(d), "r"(c));
    asm("cvt.pack.sat.s8.s32.b32 %0, %1, %2, %3;" : "=r"(r) : "r"(b), "r"(a), "r"(lo));
    return r;
}
__device__ __forceinline__ void cpasync16(uint32_t dst, const void* src) {
    asm volatile("cp.async.cg.shared.global [%0], [%1], 16;" :: "r"(dst), "l"(src) : "memory");
}
__device__ __forceinline__ unsigned pf_l2(const void* p) {
    unsigned v;
    asm volatile("ld.global.cg.L2::128B.u32 %0, [%1];" : "=r"(v) : "l"(p) : "memory");
    return v;
}

constexpr uint32_t DESC_A_HI = 0x80000000u | (512 >> 4);
constexpr uint32_t DESC_B_HI = 128 >> 4;
template <int NR> __device__ __forceinline__ void wgmma_n160(int (&d)[NR], uint32_t alo, uint32_t blo, int scale_d) {
    asm volatile("{\n.reg .pred p;\n.reg .b64 da, db;\nsetp.ne.b32 p, %82, 0;\n"
        "mov.b64 da, {%80, %83};\nmov.b64 db, {%81, %84};\n"
        "wgmma.mma_async.sync.aligned.m64n160k32.s32.s8.s8 "
        "{%0, %1, %2, %3, %4, %5, %6, %7, %8, %9, %10, %11, %12, %13, %14, %15, "
        "%16, %17, %18, %19, %20, %21, %22, %23, %24, %25, %26, %27, %28, %29, %30, %31, "
        "%32, %33, %34, %35, %36, %37, %38, %39, %40, %41, %42, %43, %44, %45, %46, %47, "
        "%48, %49, %50, %51, %52, %53, %54, %55, %56, %57, %58, %59, %60, %61, %62, %63, "
        "%64, %65, %66, %67, %68, %69, %70, %71, %72, %73, %74, %75, %76, %77, %78, %79}, "
        "da, db, p;\n}\n"
        : "+r"(d[0]), "+r"(d[1]), "+r"(d[2]), "+r"(d[3]), "+r"(d[4]), "+r"(d[5]), "+r"(d[6]), "+r"(d[7]),
          "+r"(d[8]), "+r"(d[9]), "+r"(d[10]), "+r"(d[11]), "+r"(d[12]), "+r"(d[13]), "+r"(d[14]), "+r"(d[15]),
          "+r"(d[16]), "+r"(d[17]), "+r"(d[18]), "+r"(d[19]), "+r"(d[20]), "+r"(d[21]), "+r"(d[22]), "+r"(d[23]),
          "+r"(d[24]), "+r"(d[25]), "+r"(d[26]), "+r"(d[27]), "+r"(d[28]), "+r"(d[29]), "+r"(d[30]), "+r"(d[31]),
          "+r"(d[32]), "+r"(d[33]), "+r"(d[34]), "+r"(d[35]), "+r"(d[36]), "+r"(d[37]), "+r"(d[38]), "+r"(d[39]),
          "+r"(d[40]), "+r"(d[41]), "+r"(d[42]), "+r"(d[43]), "+r"(d[44]), "+r"(d[45]), "+r"(d[46]), "+r"(d[47]),
          "+r"(d[48]), "+r"(d[49]), "+r"(d[50]), "+r"(d[51]), "+r"(d[52]), "+r"(d[53]), "+r"(d[54]), "+r"(d[55]),
          "+r"(d[56]), "+r"(d[57]), "+r"(d[58]), "+r"(d[59]), "+r"(d[60]), "+r"(d[61]), "+r"(d[62]), "+r"(d[63]),
          "+r"(d[64]), "+r"(d[65]), "+r"(d[66]), "+r"(d[67]), "+r"(d[68]), "+r"(d[69]), "+r"(d[70]), "+r"(d[71]),
          "+r"(d[72]), "+r"(d[73]), "+r"(d[74]), "+r"(d[75]), "+r"(d[76]), "+r"(d[77]), "+r"(d[78]), "+r"(d[79])
        : "r"(alo), "r"(blo), "r"(scale_d), "r"(DESC_A_HI), "r"(DESC_B_HI));
}
template <int NR> __device__ __forceinline__ void wgmma_t128(int (&d)[NR], uint32_t alo, uint32_t blo, int scale_d) {
    asm volatile("{\n.reg .pred p;\n.reg .b64 da, db;\nsetp.ne.b32 p, %66, 0;\n"
        "mov.b64 da, {%64, %67};\nmov.b64 db, {%65, %68};\n"
        "wgmma.mma_async.sync.aligned.m64n128k32.s32.s8.s8 "
        "{%0, %1, %2, %3, %4, %5, %6, %7, %8, %9, %10, %11, %12, %13, %14, %15, "
        "%16, %17, %18, %19, %20, %21, %22, %23, %24, %25, %26, %27, %28, %29, %30, %31, "
        "%32, %33, %34, %35, %36, %37, %38, %39, %40, %41, %42, %43, %44, %45, %46, %47, "
        "%48, %49, %50, %51, %52, %53, %54, %55, %56, %57, %58, %59, %60, %61, %62, %63}, "
        "da, db, p;\n}\n"
        : "+r"(d[0]), "+r"(d[1]), "+r"(d[2]), "+r"(d[3]), "+r"(d[4]), "+r"(d[5]), "+r"(d[6]), "+r"(d[7]),
          "+r"(d[8]), "+r"(d[9]), "+r"(d[10]), "+r"(d[11]), "+r"(d[12]), "+r"(d[13]), "+r"(d[14]), "+r"(d[15]),
          "+r"(d[16]), "+r"(d[17]), "+r"(d[18]), "+r"(d[19]), "+r"(d[20]), "+r"(d[21]), "+r"(d[22]), "+r"(d[23]),
          "+r"(d[24]), "+r"(d[25]), "+r"(d[26]), "+r"(d[27]), "+r"(d[28]), "+r"(d[29]), "+r"(d[30]), "+r"(d[31]),
          "+r"(d[32]), "+r"(d[33]), "+r"(d[34]), "+r"(d[35]), "+r"(d[36]), "+r"(d[37]), "+r"(d[38]), "+r"(d[39]),
          "+r"(d[40]), "+r"(d[41]), "+r"(d[42]), "+r"(d[43]), "+r"(d[44]), "+r"(d[45]), "+r"(d[46]), "+r"(d[47]),
          "+r"(d[48]), "+r"(d[49]), "+r"(d[50]), "+r"(d[51]), "+r"(d[52]), "+r"(d[53]), "+r"(d[54]), "+r"(d[55]),
          "+r"(d[56]), "+r"(d[57]), "+r"(d[58]), "+r"(d[59]), "+r"(d[60]), "+r"(d[61]), "+r"(d[62]), "+r"(d[63])
        : "r"(alo), "r"(blo), "r"(scale_d), "r"(DESC_B_HI), "r"(DESC_A_HI));
}

__device__ __forceinline__ void wg_fence() { asm volatile("wgmma.fence.sync.aligned;" ::: "memory"); }
__device__ __forceinline__ void wg_commit() { asm volatile("wgmma.commit_group.sync.aligned;" ::: "memory"); }
template <int N> __device__ __forceinline__ void wg_wait() { asm volatile("wgmma.wait_group.sync.aligned %0;" :: "n"(N) : "memory"); }

struct Job { int src; int dst; };
__host__ __device__ constexpr int unit_of(int piece, int slab) {
    return piece < 2 ? (slab < X1 ? 2 * slab + piece : (piece ? 16 : X1) + slab) : 32 + (piece - 2) * 8 + (slab >> 1);
}
__device__ __forceinline__ Job decode_job(int g) {
    int slab, idx, piece;
    if (g < SEG2) {
        int r;
        if (g < SEG1) { slab = g / (nA + 2 * nWA); r = g - slab * (nA + 2 * nWA); }
        else { g -= SEG1; slab = g / (nA + nWA); r = g - slab * (nA + nWA); slab += X1; }
        piece = r < nA ? -1 : (r < nA + nWA ? 0 : 1);
        idx = r < nA ? r : r - nA - piece * nWA;
    } else if (g < SEG3) {
        g -= SEG2; slab = g / nWA; idx = g - slab * nWA; slab += X1; piece = 1;
    } else {
        g -= SEG3; piece = 2 + (g >> 8); slab = (g >> 4) & 15; idx = g & 15;
        static_assert(nWB == 16, "");
    }
    Job j;
    if (piece < 0) {
        const int flag = (idx >> 2) * 16 + slab;
        j.src = idx * 32 + (slab << 12);
        j.dst = (flag * 512 + (idx & 3) * 128) | (flag << 18);
    } else {
        const bool wide = piece < 2;
        const int w = wide ? WA : WB;
        const int nb = wide ? idx / (WA / 32) : idx / (WB / 32);
        const int J = idx - nb * (w / 32);
        const int cb = nb * TN + (wide ? piece * WA : 2 * WA - 2 * WB + piece * WB);
        j.src = cb + J * 32 + (slab << 12) + (wide ? 1 << 16 : 2 << 16);
        j.dst = (cb * (K_ / 16) + slab * w * 4 + J * 32) | ((256 + nb * 64 + unit_of(piece, slab)) << 18);
    }
    return j;
}
struct Coord { const CUtensorMap* m; int x, y, z; };
__device__ __forceinline__ Coord job_coord(const CUtensorMap* maps, int src) {
    const bool w = src >> 16;
    const int c0 = src & 0xFFF, slab = (src >> 12) & 15;
    return {maps + (w ? 1 : 0), w ? c0 : 0, w ? slab * 64 : slab * 2, w ? 0 : c0};
}
__device__ __forceinline__ void raw_load(const Coord& c, uint32_t dst, uint32_t bar) {
    mbar_expect_tx(bar, 8192);
    asm volatile("cp.async.bulk.tensor.3d.shared::cluster.global.tile.mbarrier::complete_tx::bytes [%0], [%1, {%2, %3, %4}], [%5];"
                 :: "r"(dst), "l"(c.m), "r"(c.x), "r"(c.y), "r"(c.z), "r"(bar) : "memory");
}
__device__ __forceinline__ void raw_prefetch(const Coord& c) {
    asm volatile("cp.async.bulk.prefetch.tensor.3d.L2.global.tile [%0, {%1, %2, %3}];"
                 :: "l"(c.m), "r"(c.x), "r"(c.y), "r"(c.z) : "memory");
}
__host__ __device__ constexpr unsigned unit_mask(int piece, int s0, int s1) {
    unsigned m = 0;
    for (int s = s0; s < s1; s++) m |= 1u << (unit_of(piece, s) & 31);
    return m;
}
__host__ __device__ constexpr int slot_of(int u) {
    return u < UX ? (u % NSLOT) * (SLOT / 2048) : u < UX + NSTG ? NSLOT * (SLOT / 2048) + (u - UX) * 4 : ((u - NSTG) % NSLOT) * (SLOT / 2048);
}
__host__ __device__ constexpr uint64_t slot_table(int piece) {
    uint64_t t = 0;
    if (piece < 2) for (int s = 0; s < 16; s++) t |= (uint64_t)(unit_of(piece, s) % NSLOT) << (4 * s);
    else for (int s = 0; s < 8; s++) t |= (uint64_t)slot_of(unit_of(piece, 2 * s)) << (8 * s);
    return t;
}
struct Maps { CUtensorMap m[3]; };

__device__ __forceinline__ uint32_t bf2_op_epi(int a, int b, uint32_t zc, uint32_t sx, uint32_t sw, uint32_t bi) {
    uint32_t v;
    float fa = __int2float_rn(a), fb = __int2float_rn(b);
    asm("cvt.rn.bf16x2.f32 %0, %1, %2;" : "=r"(v) : "f"(fb), "f"(fa));
    asm("sub.rn.bf16x2 %0, %0, %1;" : "+r"(v) : "r"(zc));
    asm("mul.rn.bf16x2 %0, %0, %1;" : "+r"(v) : "r"(sx));
    asm("mul.rn.bf16x2 %0, %0, %1;" : "+r"(v) : "r"(sw));
    asm("add.rn.bf16x2 %0, %0, %1;" : "+r"(v) : "r"(bi));
    return v;
}

struct Par { uint4 zc, sw, bi; };
__device__ __forceinline__ Par ld_par(uint32_t p) { return {lds128(p), lds128(p + TN * 2), lds128(p + TN * 4)}; }
__device__ __forceinline__ void epi_row(const int (&a)[WA / 2], int o, const Par& p, uint32_t sx2, char* out) {
    uint4 r;
    r.x = bf2_op_epi(a[o + 0], a[o + 4], p.zc.x, sx2, p.sw.x, p.bi.x);
    r.y = bf2_op_epi(a[o + 8], a[o + 12], p.zc.y, sx2, p.sw.y, p.bi.y);
    r.z = bf2_op_epi(a[o + 1], a[o + 5], p.zc.z, sx2, p.sw.z, p.bi.z);
    r.w = bf2_op_epi(a[o + 9], a[o + 13], p.zc.w, sx2, p.sw.w, p.bi.w);
    stg128(out, r);
}
template <int J, int JN>
__device__ __forceinline__ void epilogue(const int (&a)[WA / 2], Par& p, uint32_t par, uint32_t sx2, char* out) {
    epi_row(a, J * 16, p, sx2, out + J * 64);
    Par n = p;
    if (JN != J) n = ld_par(par + JN * 64);
    epi_row(a, J * 16 + 2, p, sx2, out + 8 * (N_ * 2) + J * 64);
    p = n;
}

__global__ void __cluster_dims__(2, 1, 1) __launch_bounds__(512, 1)
w8a8_kernel(const __grid_constant__ Maps maps, const char* __restrict__ qx, const char* __restrict__ qw, const __nv_bfloat16* __restrict__ scale_x, const int* __restrict__ zero_x,
            const __nv_bfloat16* __restrict__ scale_w, const __nv_bfloat16* __restrict__ bias,
            __nv_bfloat16* __restrict__ out) {
    extern __shared__ __align__(1024) unsigned char smem_raw[];
    const uint32_t sb = (uint32_t)__cvta_generic_to_shared(smem_raw);
    const uint32_t bars = sb + SM_BAR;
    const int warp = __shfl_sync(~0u, threadIdx.x >> 5, 0), lane = threadIdx.x & 31;
    const int b = blockIdx.x, rank = b & 1, nb = (b >> 1) & 7, mb = (b >> 4) * 2 + rank;

    if (warp >= 8) {
        asm volatile("setmaxnreg.dec.sync.aligned.u32 56;");
        if (warp >= 16 - NCONV) {
            const int cw = warp - (16 - NCONV);
            unsigned t0;
            asm volatile("mov.u32 %0, %clock;" : "=r"(t0));
            t0 += 100;
            asm volatile("barrier.cluster.arrive.relaxed.aligned;" ::: "memory");
            const Job mj = decode_job(min(lane, NJOB - 1) * NCTA + b);
            static_assert(NCONV == NSTG + 2 && NJOB == 22, "");
            const uint32_t s = sb + (cw < NSTG ? SM_STG + cw * 8192 : SM_A + (14 - NSTG + cw) * 8192);
            const uint32_t sbar = bars + (B_FULLS + cw) * 8;
            {
                const Coord c = job_coord(maps.m, __shfl_sync(~0u, mj.src, cw));
                if (elect_one()) {
                    mbar_init(sbar, 1);
                    asm volatile("fence.mbarrier_init.release.cluster;" ::: "memory");
                    unsigned t;
                    do { asm volatile("mov.u32 %0, %clock;" : "=r"(t)); } while ((int)(t - t0) < cw * PFD + (cw ? b * 88 : b * 0) / 16);
                    raw_load(c, s, sbar);
                }
                __syncwarp();
            }
            asm volatile("barrier.cluster.wait.aligned;" ::: "memory");
            t0 += b * 88 / 16;
            const int c4 = lane & 3, ln = (lane >> 2) * 2 + (c4 >> 1);
            const uint32_t rdA = ln * 128 + ((((c4 & 1) << 2) ^ (ln & 7)) << 4);
            const uint32_t rdB = (lane >> 3) * 2048 + (lane & 7) * 16;
            const int wrA = (lane >> 2) * 4 + (c4 ^ ((lane >> 3) & 3));
            uint32_t par = 0;
#pragma unroll 1
            for (int j = cw, jn; j < NJOB; j = jn, par ^= 1) {
                jn = j < 13 ? j + NCONV : (j < 15 ? 31 : j + NSTG);
                const int src = __shfl_sync(~0u, mj.src, j), dst = __shfl_sync(~0u, mj.dst, j);
                const int nsrc = __shfl_sync(~0u, mj.src, jn);
                const int kind = src >> 16;
                uint4 o[4];
                uint4* d;
                int dstep;
                mbar_wait(sbar, par);
                if (kind == 0) {
                    const uint32_t a0 = s + rdA;
                    d = g_a8 + (dst & 0x3FFFF) + wrA;
                    dstep = 32;
#pragma unroll
                    for (int i = 0; i < 4; i++) {
                        uint4 v0 = lds128(a0 + i * 2048), v1 = lds128((a0 ^ 16) + i * 2048);
                        uint4 v2 = lds128((a0 ^ 32) + i * 2048), v3 = lds128((a0 ^ 48) + i * 2048);
                        o[i].x = pack4(v0.x, v0.y, v0.z, v0.w); o[i].y = pack4(v1.x, v1.y, v1.z, v1.w);
                        o[i].z = pack4(v2.x, v2.y, v2.z, v2.w); o[i].w = pack4(v3.x, v3.y, v3.z, v3.w);
                    }
                } else {
                    const uint32_t a0 = s + rdB;
                    d = g_b8 + (dst & 0x3FFFF) + (lane >> 3) * (kind == 1 ? WA : WB) + (lane & 7);
                    dstep = 8;
#define CV_B(m, f)                                                                                    \
                    {                                                                                 \
                        uint4 v0 = lds128(a0 + m * 512), v1 = lds128(a0 + m * 512 + 128);             \
                        uint4 v2 = lds128(a0 + m * 512 + 256), v3 = lds128(a0 + m * 512 + 384);       \
                        o[0].f = pack4(v0.x, v1.x, v2.x, v3.x); o[1].f = pack4(v0.y, v1.y, v2.y, v3.y); \
                        o[2].f = pack4(v0.z, v1.z, v2.z, v3.z); o[3].f = pack4(v0.w, v1.w, v2.w, v3.w); \
                    }
                    CV_B(0, x) CV_B(1, y) CV_B(2, z) CV_B(3, w)
                }
#pragma unroll
                for (int i = 0; i < 4; i++) stg128(d + i * dstep, o[i]);
                unsigned tn;
                asm volatile("mov.u32 %0, %clock;" : "=r"(tn));
                const bool late = jn < NJOB && (int)(tn - t0) < jn * PFD;
                if (!late && elect_one()) {
                    if (jn < NJOB) { raw_load(job_coord(maps.m, nsrc), s, sbar); }
                    else if (jn == 31) mbar_arrive(bars + (B_AFREE - NSTG + cw) * 8);
                    else if (0 != 1) {
                        uint32_t ra;
                        asm("mapa.shared::cluster.u32 %0, %1, %2;" : "=r"(ra) : "r"(bars + (B_GO + ((UX + cw) >> 1)) * 8), "r"((UX + cw) & 1));
                        mbar_arrive_cluster(ra);
                    }
                }
                const int* csp = (const int*)d;
                unsigned csv = o[0].x;
                if (kind != 0) {
                    int cs[4];
#pragma unroll
                    for (int i = 0; i < 4; i++)
                        cs[i] = __dp4a((int)o[i].x, 0x01010101, __dp4a((int)o[i].y, 0x01010101,
                                __dp4a((int)o[i].z, 0x01010101, __dp4a((int)o[i].w, 0x01010101, 0))));
                    const int p01 = cs[0] + cs[1] * 65536, p23 = cs[2] + cs[3] * 65536;
                    const bool odd = lane & 8;
                    int v = (odd ? p23 : p01) + __shfl_xor_sync(~0u, odd ? p01 : p23, 8);
                    v += __shfl_xor_sync(~0u, v, 16);
                    int* p = (int*)g_cs + ((src >> 12) & 15) * (N_ / 2) + ((src & 0xFFF) >> 1) + (lane & 15);
                    if (lane < 16) *p = v;
                    csp = p; csv = v;
                }
#pragma unroll 1
                for (int it = 0; it < 1000; it++) {
                    bool ok = true;
                    if ((lane & 3) == 0) {
                        unsigned rb[5];
#pragma unroll
                        for (int i = 0; i < 4; i++)
                            asm volatile("ld.relaxed.gpu.global.u32 %0, [%1];" : "=r"(rb[i]) : "l"(d + i * dstep) : "memory");
                        asm volatile("ld.relaxed.gpu.global.u32 %0, [%1];" : "=r"(rb[4]) : "l"(csp) : "memory");
                        ok = rb[0] == o[0].x && rb[1] == o[1].x && rb[2] == o[2].x && rb[3] == o[3].x && rb[4] == csv;
                    }
                    if (__all_sync(~0u, ok)) break;
                }
                if (elect_one()) asm volatile("red.relaxed.gpu.global.add.u32 [%0], 1;" :: "l"(g_flag + ((unsigned)dst >> 18)) : "memory");
                __syncwarp();
                if (late && elect_one()) {
                    do { asm volatile("mov.u32 %0, %clock;" : "=r"(tn)); } while ((int)(tn - t0) < jn * PFD);
                    raw_load(job_coord(maps.m, nsrc), s, sbar);
                }
                __syncwarp();
            }
        } else if (warp == 8) {
            asm volatile("barrier.cluster.arrive.relaxed.aligned;" ::: "memory");
            const unsigned ep = *(volatile unsigned*)&g_epoch[b] + 1;
            const unsigned* f1 = g_flag + 256 + nb * 64 + lane;
            const unsigned* f2 = lane < 16 ? f1 + 32 : g_flag + mb * 16 + lane - 16;
            const unsigned t1 = ep * (WA / 32), t2 = ep * 4;
            static_assert(WB / 16 == 4, "");
            const unsigned n1 = lane == 0 ? unit_mask(0, 0, 8) : lane == 1 ? unit_mask(1, 0, 8) : lane == 2 ? unit_mask(0, 8, 16)
                              : lane == 3 ? unit_mask(1, 8, 16) : 0u;
            const unsigned n2 = lane < 4 ? 0u : 0xFFFFu;
            bool d1 = false, d2 = false, d3 = lane >= 5, fr = lane < 30;
            asm volatile("barrier.cluster.wait.aligned;" ::: "memory");
            for (int it = 0; 0 != 1; it++) {
                unsigned v1 = t1, v2 = t2;
                if (!d1) v1 = ld_flag(f1);
                if (!d2) v2 = ld_flag(f2);
                if (!fr) fr = mbar_test(bars + (B_AFREE - 30 + lane) * 8);
                if (!d2 && fr && (int)(v2 - t2) >= 0) {
                    d2 = true;
                    if (lane >= 16) {
                        asm volatile("fence.proxy.async.global;" ::: "memory");
                        asm volatile("cp.async.bulk.shared::cluster.global.mbarrier::complete_tx::bytes [%0], [%1], %2, [%3];"
                                     :: "r"(sb + SM_A + (lane - 16) * 8192), "l"((const char*)g_a8 + (mb * 16 + lane - 16) * 8192),
                                        "r"(8192), "r"(bars + (B_FULLA + lane - 16) * 8) : "memory");
                    } else if ((lane & 1) == rank) mbar_arrive(bars + (B_GO + 16 + (lane >> 1)) * 8);
                }
                if (!d1 && (int)(v1 - t1) >= 0) {
                    d1 = true;
                    if ((lane & 1) == rank) mbar_arrive(bars + (B_GO + (lane >> 1)) * 8);
                }
                const unsigned m1 = __ballot_sync(~0u, d1), m2 = __ballot_sync(~0u, d2);
                if (!d3 && (m1 & n1) == n1 && (m2 & n2) == n2) { d3 = true; mbar_arrive(bars + (B_PSTEP + lane) * 8); }
                if ((m1 & m2) == ~0u) break;
                if (it > (1 << 22)) __trap();
            }
        } else if (warp == 9) {
            asm volatile("barrier.cluster.arrive.relaxed.aligned;" ::: "memory");
            const int u = 2 * lane + rank;
            int so, fb;
            if (u < 2 * X1) { so = (u & 1) * (WA * K_) + (u >> 1) * (WA * 64); fb = (u & 1) * 24 + (u >> 1); }
            else if (u < X1 + 16) { so = (u - X1) * (WA * 64); fb = u - X1; }
            else if (u < 32) { so = WA * K_ + (u - 16) * (WA * 64); fb = 24 + u - 16; }
            else { so = 2 * WA * K_ + (u - 32) * (WB * 128); fb = u < 40 ? u - 16 : u; }
            const char* srcB = (const char*)g_b8 + nb * TN * K_ + so;
            const uint32_t dstB = sb + SM_RING + slot_of(u) * 2048;
            asm volatile("barrier.cluster.wait.aligned;" ::: "memory");
#pragma unroll 1
            for (int i = 0; i < NU / 2 && 0 != 1; i++) {
                mbar_wait(bars + (B_GO + i) * 8);
                if (lane == i) {
                    asm volatile("fence.proxy.async.global;" ::: "memory");
                    asm volatile("cp.async.bulk.shared::cluster.global.mbarrier::complete_tx::bytes.multicast::cluster [%0], [%1], %2, [%3], %4;"
                                 :: "r"(dstB), "l"(srcB), "r"(u < 32 ? WA * 64 : WB * 128), "r"(bars + (B_FULLB + fb) * 8), "h"((uint16_t)3) : "memory");
                }
                __syncwarp();
            }
        } else if (warp == 10) {
            unsigned pv, pv2;
            {
                static_assert(X1 > 0 && nA == 64 && nWA == 40, "");
                const int i = b - (b < 104 ? 64 : 104), q = i / 5;
                const char* p = b < 64 ? qx + (b * 32 + (lane >> 1)) * (K_ * 4) + (lane & 1) * 128
                                       : qw + lane * (N_ * 4) + (q * TN + (b < 104 ? 0 : WA) + (i - q * 5) * 32) * 4;
                pv = pf_l2(p);
                pv2 = pf_l2(p + (b < 64 ? 16 * K_ * 4 : 32 * N_ * 4));
                if (lane < 3) asm volatile("prefetch.tensormap [%0];" :: "l"(maps.m + lane) : "memory");
            }
            asm volatile("barrier.cluster.arrive.relaxed.aligned;" ::: "memory");
            if ((pv ^ pv2) == 0x40000000u) g_sink = pv;
            const float zxf = __bfloat162float(__float2bfloat16_rn((float)__ldg(zero_x)));
#pragma unroll 1
            for (int i = lane; i < TN / 4; i += 32) {
                const bool hi = i >= TN / 8;
                sts128(sb + SM_PAR + TN * 2 + i * 16, __ldg((const uint4*)((hi ? bias : scale_w) + nb * TN) + (hi ? i - TN / 8 : i)));
            }
            asm volatile("barrier.cluster.wait.aligned;" ::: "memory");
            int c[8], cs[8];
#pragma unroll
            for (int i = 0; i < 8; i++) { c[i] = 0; cs[i] = 0; }
#pragma unroll 1
            for (int st = 0; st < 5 && 0 != 1; st++) {
                const bool wide = st < 4;
                const int half = wide ? (st >> 1) : (lane >> 4);
                const int col = wide ? (st & 1) * WA + min(lane, WA / 8 - 1) * 8 : 2 * WA + (lane & 15) * 8;
                const uint4* src = g_cs + (half * 8 * N_ + nb * TN + col) / 8;
                mbar_wait(bars + (B_PSTEP + st) * 8);
                uint4 v[8];
#pragma unroll
                for (int i = 0; i < 8; i++) v[i] = __ldcg(src + i * (N_ / 8));
#pragma unroll
                for (int h = 0; h < 8; h += 4) {
                    const unsigned sv[4] = {v[h].x + v[h + 1].x + v[h + 2].x + v[h + 3].x, v[h].y + v[h + 1].y + v[h + 2].y + v[h + 3].y,
                                            v[h].z + v[h + 1].z + v[h + 2].z + v[h + 3].z, v[h].w + v[h + 1].w + v[h + 2].w + v[h + 3].w};
#pragma unroll
                    for (int i = 0; i < 4; i++) {
                        const int lo = (int)(short)(sv[i] & 0xFFFF);
                        c[2 * i] += lo; c[2 * i + 1] += ((int)(sv[i] - (unsigned)lo)) >> 16;
                    }
                }
                if (st >= 2) {
                    uint32_t z[4];
#pragma unroll
                    for (int i = 0; i < 8; i++) {
                        const int o = __shfl_xor_sync(~0u, c[i], 16);
                        if (!wide) c[i] += o;
                    }
#pragma unroll
                    for (int i = 0; i < 4; i++) {
                        const float lo = __bfloat162float(__float2bfloat16_rn((float)c[2 * i])) * zxf;
                        const float hi = __bfloat162float(__float2bfloat16_rn((float)c[2 * i + 1])) * zxf;
                        asm("cvt.rn.bf16x2.f32 %0, %1, %2;" : "=r"(z[i]) : "f"(hi), "f"(lo));
                    }
                    const uint32_t za = sb + SM_PAR + ((col & ~31) + (col & 8) * 2 + ((col >> 3) & 2)) * 2;
#pragma unroll
                    for (int i = 0; i < 4; i++) sts32(za + i * 8, z[i]);
                    __syncwarp();
                    if (lane == 0) { mbar_arrive(bars + (B_PAR + st - 2) * 8); }
#pragma unroll
                    for (int i = 0; i < 8; i++) c[i] = 0;
                }
#pragma unroll
                for (int i = 0; i < 8; i++) { const int t = c[i]; c[i] = cs[i]; cs[i] = t; }
            }
        } else {
            asm volatile("barrier.cluster.arrive.relaxed.aligned;" ::: "memory");
            asm volatile("barrier.cluster.wait.aligned;" ::: "memory");
        }
    } else {
        asm volatile("setmaxnreg.inc.sync.aligned.u32 200;");
        {
            constexpr int PER = (B_NINIT + 7) / 8;
            if (elect_one()) {
#pragma unroll 1
                for (int i = warp * PER; i < min(warp * PER + PER, B_NINIT); i++)
                    {
                    const int u = 2 * (i - B_GO) + rank;
                    mbar_init(bars + i * 8, (i < B_GO || i >= B_PAR || u < NSLOT) ? 1 : (u >= UX && u < UX + NSTG) ? 3 : 9);
                }
            }
            __syncwarp();
            const int i = warp * PER + lane;
            if (lane < PER && i < B_GO) mbar_expect_tx(bars + i * 8, (i < 16 || (i >= 24 && i < 40)) ? WA * 64 : 8192);
            static_assert(WB * 128 == 8192, "");
            asm volatile("fence.mbarrier_init.release.cluster;" ::: "memory");
        }
        asm volatile("barrier.cluster.arrive.relaxed.aligned;" ::: "memory");
        const int wg = warp >> 2;
        const uint32_t sd = (sb & 0x3FFFF) >> 4;
        const unsigned short sxr = __ldg((const unsigned short*)scale_x);
        const uint32_t sx2 = (uint32_t)sxr * 0x10001u;
        char* orow = (char*)out + (size_t)(mb * 128 + (warp & 3) * 16 + (lane >> 2)) * (N_ * 2) + (nb * TN + (lane & 3) * 8 + wg * WA) * 2;
        const uint32_t par = sb + SM_PAR + (lane & 3) * 16 + wg * WA * 2;
        uint32_t reladdr;
        int rell;
        {
            const int u = lane < 16 ? (lane < X1 ? 2 * lane + wg : (wg ? 16 : X1) + lane) : 16 + wg * 8 + lane;
            const int v = u + (u < 32 ? NSLOT : NSLOT + NSTG);
            rell = (lane < 24 && v < NU) ? lane : 99;
            asm("mapa.shared::cluster.u32 %0, %1, %2;" : "=r"(reladdr) : "r"(bars + (B_GO + (v >> 1)) * 8), "r"(v & 1));
        }
        asm volatile("barrier.cluster.wait.aligned;" ::: "memory");
        int a0[WA / 2], a1[WA / 2];
        uint32_t barB = bars + (B_FULLB + wg * 24) * 8;
        bool ready = false;
#define HAND_BACK(done) if (rell <= (done)) { mbar_arrive_cluster(reladdr); rell = 99; }
        if (0 != 1) {
            wg_fence();
            {
                uint64_t tbl = wg ? slot_table(1) : slot_table(0);
                uint32_t da = (sd + (SM_A >> 4)) | (1 << 16);
#pragma unroll 1
                for (int s = 0; s < 16; s++) {
                    const uint32_t db = ((sd + (SM_RING >> 4)) | (WA << 16)) + ((uint32_t)tbl & 15) * (SLOT >> 4);
                    const bool starved = !ready && !mbar_test2(bars + (B_FULLA + s) * 8, barB);
                    if (starved) {
                        wg_wait<0>();
                        HAND_BACK(s - 1)
                        mbar_wait2(bars + (B_FULLA + s) * 8, barB);
                    }
                    wgmma_n160(a0, da, db, s);
                    wgmma_n160(a1, da + 256, db, s);
                    wgmma_n160(a0, da + 2, db + 2 * WA, 1);
                    wgmma_n160(a1, da + 258, db + 2 * WA, 1);
                    wg_commit();
                    HAND_BACK(s - 2)
                    tbl >>= 4; da += 512; barB += 8;
                    ready = mbar_test2(bars + (B_FULLA + min(s + 1, 15)) * 8, barB);
                    wg_wait<1>();
                }
            }
            HAND_BACK(14)
            wg_wait<0>();
            HAND_BACK(15)
            mbar_wait(bars + (B_PAR + wg) * 8);
            Par P = ld_par(par);
            char* const orow1 = orow + 64 * (N_ * 2);
            epilogue<0, 1>(a0, P, par, sx2, orow); epilogue<1, 2>(a0, P, par, sx2, orow);
            epilogue<2, 3>(a0, P, par, sx2, orow); epilogue<3, 0>(a0, P, par, sx2, orow);
            int t[64];
            wg_fence();
            {
                uint64_t tbl = wg ? slot_table(3) : slot_table(2);
                uint32_t da = (sd + (SM_A >> 4)) | (1 << 16);
#pragma unroll
                for (int i = 16; i < 24; i++) {
                    const uint32_t db = ((sd + (SM_RING >> 4)) | (WB << 16)) + ((uint32_t)tbl & 255) * 128;
                    const bool starved = !ready && !mbar_test(barB);
                    if (starved) {
                        wg_wait<0>();
                        HAND_BACK(i - 1)
                        mbar_wait(barB);
                    }
#pragma unroll
                    for (int k = 0; k < 4; k++) wgmma_t128(t, db + k * 2 * WB, da + (k >> 1) * 512 + (k & 1) * 2, k ? 1 : i - 16);
                    wg_commit();
                    HAND_BACK(i - 2)
                    tbl >>= 8; da += 1024; barB += 8;
                    ready = mbar_test(barB);
                    switch (i) {
                        case 16: epilogue<0, 0>(a1, P, par, sx2, orow1); break;
                        case 17: epilogue<1, 1>(a1, P, par, sx2, orow1); break;
                        case 18: epilogue<2, 2>(a1, P, par, sx2, orow1); break;
                        case 19: epilogue<3, 3>(a1, P, par, sx2, orow1); break;
                        case 20: epilogue<4, 4>(a1, P, par, sx2, orow1); break;
                        case 21: epilogue<4, 4>(a0, P, par, sx2, orow); break;
                        default: break;
                    }
                    if (i < 20) P = ld_par(par + (i - 15) * 64);
                    wg_wait<1>();
                }
            }
            HAND_BACK(22)
            mbar_wait(bars + (B_PAR + 2) * 8);
            const int w = warp & 3, q = lane >> 2, c0 = (w >> 1) * 32 + q * 4 + (w & 1) * 2;
            const uint32_t pp = sb + SM_PAR + (2 * WA + wg * WB + c0) * 2;
            const uint32_t zc = lds32(pp), sw = lds32(pp + TN * 2), bi = lds32(pp + TN * 4);
            const int r0 = (lane & 3) * 2;
            const uint32_t st0 = r0 * 128 + (((c0 >> 3) ^ r0) << 4) + (c0 & 7) * 2, st1 = (st0 ^ 16) + 128;
            wg_wait<0>();
            asm volatile("bar.sync %0, 128;" :: "r"(3 + wg) : "memory");
#pragma unroll
            for (int h = 0; h < 2; h++) {
                const uint32_t buf = sb + SM_RING + (wg ? slot_of(UX + 1 + h) : slot_of(UX - 1 + h)) * 2048;
#pragma unroll
                for (int j = 0; j < 8; j++) {
                    const int o = h * 32 + j * 4;
                    sts32(buf + st0 + j * 1024, bf2_op_epi(t[o], t[o + 2], zc, sx2, sw, bi));
                    sts32(buf + st1 + j * 1024, bf2_op_epi(t[o + 1], t[o + 3], zc, sx2, sw, bi));
                }
                asm volatile("fence.proxy.async.shared::cta;" ::: "memory");
                asm volatile("bar.sync %0, 128;" :: "r"(3 + wg) : "memory");
                if (w == 0 && elect_one())
                    asm volatile("cp.async.bulk.tensor.2d.global.shared::cta.tile.bulk_group [%0, {%1, %2}], [%3];"
                                 :: "l"(maps.m + 2), "r"(nb * TN + 2 * WA + wg * WB), "r"(mb * 128 + h * 64), "r"(buf) : "memory");
            }
            if (w == 0) {
                asm volatile("cp.async.bulk.commit_group;" ::: "memory");
                asm volatile("cp.async.bulk.wait_group.read 0;" ::: "memory");
            }
        }
        if (threadIdx.x == 128) asm volatile("red.relaxed.gpu.global.add.u32 [%0], 1;" :: "l"(g_epoch + b) : "memory");
    }
}

static void launch(EncodeFn encode, void* const* d_in, void* d_out) {
    Maps maps;
    CUtensorMap &mx = maps.m[0], &mw = maps.m[1];
    {
        const cuuint64_t dim[3] = {32, K_ / 32, M_}, str[2] = {128, K_ * 4};
        const cuuint32_t box[3] = {32, 2, 32}, es[3] = {1, 1, 1};
        encode(&mx, CU_TENSOR_MAP_DATA_TYPE_INT32, 3, d_in[0], dim, str, box, es, CU_TENSOR_MAP_INTERLEAVE_NONE,
               CU_TENSOR_MAP_SWIZZLE_128B, CU_TENSOR_MAP_L2_PROMOTION_NONE, CU_TENSOR_MAP_FLOAT_OOB_FILL_NONE);
    }
    {
        const cuuint64_t dim[3] = {N_, K_, 1}, str[2] = {N_ * 4, (cuuint64_t)N_ * K_ * 4};
        const cuuint32_t box[3] = {32, 64, 1}, es[3] = {1, 1, 1};
        encode(&mw, CU_TENSOR_MAP_DATA_TYPE_INT32, 3, d_in[1], dim, str, box, es, CU_TENSOR_MAP_INTERLEAVE_NONE,
               CU_TENSOR_MAP_SWIZZLE_NONE, CU_TENSOR_MAP_L2_PROMOTION_NONE, CU_TENSOR_MAP_FLOAT_OOB_FILL_NONE);
    }
    {
        const cuuint64_t dim[2] = {N_, M_}, str[1] = {N_ * 2};
        const cuuint32_t box[2] = {WB, 64}, es[2] = {1, 1};
        encode(&maps.m[2], CU_TENSOR_MAP_DATA_TYPE_BFLOAT16, 2, d_out, dim, str, box, es, CU_TENSOR_MAP_INTERLEAVE_NONE,
               CU_TENSOR_MAP_SWIZZLE_128B, CU_TENSOR_MAP_L2_PROMOTION_NONE, CU_TENSOR_MAP_FLOAT_OOB_FILL_NONE);
    }
    w8a8_kernel<<<NCTA, 512, SM_ALLOC>>>(maps, (const char*)d_in[0], (const char*)d_in[1], (const __nv_bfloat16*)d_in[2], (const int*)d_in[3],
                                         (const __nv_bfloat16*)d_in[4], (const __nv_bfloat16*)d_in[5],
                                         (__nv_bfloat16*)d_out);
}

}

extern "C" void kernel_launch(void* const* d_in, const int* in_sizes, int n_in, void* d_out, int out_size) {
    using namespace ra;
    static EncodeFn encode = nullptr;
    static Scratch* scr = nullptr;
    static const JobTable* jobs = nullptr;
    static bool fits = false;
    if (!encode) {
        void* fn = nullptr;
        cudaDriverEntryPointQueryResult qr;
        cudaGetDriverEntryPoint("cuTensorMapEncodeTiled", &fn, cudaEnableDefault, &qr);
        encode = (EncodeFn)fn;
        cudaGetSymbolAddress((void**)&scr, g_scratch);
        cudaGetSymbolAddress((void**)&jobs, g_jobs);
        cudaFuncSetAttribute(w8a8_kernel, cudaFuncAttributeMaxDynamicSharedMemorySize, SM_ALLOC);
        cudaFuncSetAttribute(w8a8_kernel, cudaFuncAttributeNonPortableClusterSizeAllowed, 1);
        cudaFuncSetAttribute(w8a8_side, cudaFuncAttributeMaxDynamicSharedMemorySize, SM_ALLOC);
        cudaFuncSetAttribute(w8::w8a8_kernel, cudaFuncAttributeMaxDynamicSharedMemorySize, w8::SM_ALLOC);
        cudaLaunchConfig_t oc = {};
        oc.gridDim = dim3(NCTA); oc.blockDim = dim3(512); oc.dynamicSmemBytes = SM_ALLOC;
        cudaLaunchAttribute oa[1];
        oa[0].id = cudaLaunchAttributeClusterDimension; oa[0].val.clusterDim.x = CS; oa[0].val.clusterDim.y = 1; oa[0].val.clusterDim.z = 1;
        oc.attrs = oa; oc.numAttrs = 1;
        int nc = 0, dev = 0, sms = 0;
        cudaGetDevice(&dev);
        cudaDeviceGetAttribute(&sms, cudaDevAttrMultiProcessorCount, dev);
        fits = cudaOccupancyMaxActiveClusters(&nc, w8a8_kernel, &oc) == cudaSuccess && nc >= NCTA / CS && sms >= NCTA + NSIDE;
        cudaGetLastError();
    }
    if (!fits) { w8::launch(encode, d_in, d_out); return; }
    CUtensorMap map;
    {
        const cuuint64_t dim[2] = {N_, M_}, str[1] = {N_ * 2};
        const cuuint32_t box[2] = {64, 32}, es[2] = {1, 1};
        encode(&map, CU_TENSOR_MAP_DATA_TYPE_BFLOAT16, 2, d_out, dim, str, box, es, CU_TENSOR_MAP_INTERLEAVE_NONE,
               CU_TENSOR_MAP_SWIZZLE_128B, CU_TENSOR_MAP_L2_PROMOTION_NONE, CU_TENSOR_MAP_FLOAT_OOB_FILL_NONE);
    }
    w8a8_kernel<<<NCTA, 512, SM_ALLOC, cudaStreamPerThread>>>((const char*)d_in[0], (const char*)d_in[1], scr, jobs, (const __nv_bfloat16*)d_in[4],
                                                             (const __nv_bfloat16*)d_in[5], (const __nv_bfloat16*)d_in[2], (const int*)d_in[3], map);
    cudaLaunchConfig_t cfg = {};
    cfg.gridDim = dim3(NSIDE); cfg.blockDim = dim3(512); cfg.dynamicSmemBytes = SM_ALLOC; cfg.stream = cudaStreamPerThread;
    cudaLaunchAttribute at[1];
    at[0].id = cudaLaunchAttributeProgrammaticStreamSerialization; at[0].val.programmaticStreamSerializationAllowed = 1;
    cfg.attrs = at; cfg.numAttrs = 1;
    cudaLaunchKernelEx(&cfg, w8a8_side, (const char*)d_in[1], scr, (const __nv_bfloat16*)d_in[4], (const __nv_bfloat16*)d_in[5], (const __nv_bfloat16*)d_in[2],
                       (const int*)d_in[3], map);
}
```

```cpp
#include <cuda_runtime.h>
#include <cuda.h>
#include <cuda_bf16.h>
#include <stdint.h>

namespace ra {

constexpr int CFG_D = 2;
constexpr int CFG_P0 = 615;
constexpr int CFG_PF0 = 0;
constexpr int CFG_SLEEP = 400;
constexpr int CFG_NINIT = 2;
constexpr int CFG_NR = 10;
constexpr int CFG_PZ = 16;
constexpr int CFG_NOC = 12;
constexpr int CFG_YP = 1100;
constexpr int CFG_YH = 1000;
constexpr int CFG_YH0 = 1700;
constexpr int CFG_Y0 = 1000;

constexpr int M_ = 2048, K_ = 1024, N_ = 3584;
constexpr int CS = 16, NCTA = 112, NSIDE = 20, TN = 448;
constexpr int NRING = CFG_NR, NCONV = 6, NJOB = 26, NG = 56, NOUT = 4, D_ = CFG_D;

constexpr int SM_A = 0;
constexpr int SM_RING = 131072;
constexpr int SM_OUT = SM_RING + NRING * 8192;
constexpr int SM_PAR = SM_OUT + NOUT * 4096;
constexpr int SM_SUM = SM_PAR + 1024;
constexpr int SM_BAR = SM_SUM + 256;
constexpr int B_FULL = 0, B_PAR = 64, B_AFREE = 72, B_TURN = 74, B_OFREE = 76, B_SUM = 108, B_GO = 112, B_OFULL = 144, B_END = 148;
constexpr int SM_TOTAL = SM_BAR + B_END * 8;

constexpr int FS = 32;
struct __align__(2048) Scratch {
    uint4 a8[M_ * K_ / 16];
    uint4 b8[N_ * K_ / 16];
    unsigned cs[32 * TN / 2];
    unsigned flag[CS * FS + 64];
    unsigned epoch[NCTA + NSIDE];
};
__device__ Scratch g_scratch;
constexpr int SM_ALLOC = SM_TOTAL;
static_assert(SM_ALLOC <= 232448, "");

__device__ __forceinline__ void mbar_init(uint32_t bar, uint32_t cnt) {
    asm volatile("mbarrier.init.shared::cta.b64 [%0], %1;" :: "r"(bar), "r"(cnt) : "memory");
}
__device__ __forceinline__ void mbar_expect_tx(uint32_t bar, uint32_t bytes) {
    asm volatile("mbarrier.arrive.expect_tx.shared::cta.b64 _, [%0], %1;" :: "r"(bar), "r"(bytes) : "memory");
}
__device__ __forceinline__ void mbar_arrive(uint32_t bar) {
    asm volatile("mbarrier.arrive.shared::cta.b64 _, [%0];" :: "r"(bar) : "memory");
}
__device__ __forceinline__ void mbar_arrive_cluster(uint32_t bar) {
    asm volatile("mbarrier.arrive.shared::cluster.b64 _, [%0];" :: "r"(bar) : "memory");
}
__device__ __forceinline__ void mbar_wait(uint32_t bar) {
    asm volatile("{\n.reg .pred p;\nWAIT_LOOP:\nmbarrier.try_wait.parity.shared::cta.b64 p, [%0], 0;\n@!p bra WAIT_LOOP;\n}" :: "r"(bar) : "memory");
}
__device__ __forceinline__ void mbar_wait_cluster(uint32_t bar) {
    asm volatile("{\n.reg .pred p;\nWAIT_LOOP:\nmbarrier.try_wait.parity.relaxed.cluster.shared::cta.b64 p, [%0], 0;\n@!p bra WAIT_LOOP;\n"
                 "fence.acquire.sync_restrict::shared::cluster.cluster;\n}" :: "r"(bar) : "memory");
}
__device__ __forceinline__ void mbar_wait2(uint32_t bar0, uint32_t bar1) { mbar_wait(bar0); mbar_wait(bar1); }
__device__ __forceinline__ bool mbar_test(uint32_t bar) {
    uint32_t ok;
    asm volatile("{\n.reg .pred p;\nmbarrier.test_wait.parity.shared::cta.b64 p, [%1], 0;\nselp.u32 %0, 1, 0, p;\n}" : "=r"(ok) : "r"(bar) : "memory");
    return ok;
}
__device__ __forceinline__ bool mbar_test2(uint32_t bar0, uint32_t bar1) {
    uint32_t ok;
    asm volatile("{\n.reg .pred p, q;\nmbarrier.test_wait.parity.shared::cta.b64 p, [%1], 0;\n"
                 "mbarrier.test_wait.parity.shared::cta.b64 q, [%2], 0;\nand.pred p, p, q;\nselp.u32 %0, 1, 0, p;\n}"
                 : "=r"(ok) : "r"(bar0), "r"(bar1) : "memory");
    return ok;
}
__device__ __forceinline__ bool elect_one() {
    uint32_t ok;
    asm volatile("{\n.reg .pred p;\nelect.sync _|p, 0xffffffff;\nselp.u32 %0, 1, 0, p;\n}" : "=r"(ok));
    return ok;
}
__device__ __forceinline__ uint32_t mapa(uint32_t a, uint32_t cta) {
    uint32_t r;
    asm("mapa.shared::cluster.u32 %0, %1, %2;" : "=r"(r) : "r"(a), "r"(cta));
    return r;
}
__device__ __forceinline__ void st_async32(uint32_t a, uint32_t v, uint32_t bar) {
    asm volatile("st.async.shared::cluster.mbarrier::complete_tx::bytes.b32 [%0], %1, [%2];" :: "r"(a), "r"(v), "r"(bar) : "memory");
}
__device__ __forceinline__ unsigned ld_flag(const unsigned* p) {
    unsigned v;
    asm volatile("ld.relaxed.gpu.global.u32 %0, [%1];" : "=r"(v) : "l"(p) : "memory");
    return v;
}
__device__ __forceinline__ unsigned clk() { unsigned t; asm volatile("mov.u32 %0, %clock;" : "=r"(t)); return t; }
__device__ __forceinline__ uint32_t lds32(uint32_t a) {
    uint32_t v;
    asm volatile("ld.shared.b32 %0, [%1];" : "=r"(v) : "r"(a) : "memory");
    return v;
}
__device__ __forceinline__ void sts32(uint32_t a, uint32_t v) {
    asm volatile("st.shared.b32 [%0], %1;" :: "r"(a), "r"(v) : "memory");
}
__device__ __forceinline__ void stg128(void* p, uint4 v) {
    asm volatile("st.global.v4.b32 [%0], {%1,%2,%3,%4};" :: "l"(p), "r"(v.x), "r"(v.y), "r"(v.z), "r"(v.w) : "memory");
}
__device__ __forceinline__ unsigned pack4(unsigned a, unsigned b, unsigned c, unsigned d) {
    unsigned lo, r;
    asm("cvt.pack.sat.s8.s32.b32 %0, %1, %2, 0;" : "=r"(lo) : "r"(d), "r"(c));
    asm("cvt.pack.sat.s8.s32.b32 %0, %1, %2, %3;" : "=r"(r) : "r"(b), "r"(a), "r"(lo));
    return r;
}
constexpr uint32_t DESC_A_HI = 256 >> 4;
constexpr uint32_t DESC_B_HI = 0x80000000u | (512 >> 4);
__device__ __forceinline__ void mma_unit2(int (&d)[64], int (&e)[64], uint32_t alo, uint32_t blo, int scale_d) {
    asm volatile("{\n.reg .pred p;\n.reg .b64 da, db;\nsetp.ne.b32 p, %130, 0;\n"
        "mov.b64 da, {%128, %131};\nmov.b64 db, {%129, %132};\n"
        "wgmma.mma_async.sync.aligned.m64n128k32.s32.s8.s8 "
        "{%0, %1, %2, %3, %4, %5, %6, %7, %8, %9, %10, %11, %12, %13, %14, %15, "
        "%16, %17, %18, %19, %20, %21, %22, %23, %24, %25, %26, %27, %28, %29, %30, %31, "
        "%32, %33, %34, %35, %36, %37, %38, %39, %40, %41, %42, %43, %44, %45, %46, %47, "
        "%48, %49, %50, %51, %52, %53, %54, %55, %56, %57, %58, %59, %60, %61, %62, %63}, "
        "da, db, p;\n"
        "add.s64 da, da, 128;\n"
        "wgmma.mma_async.sync.aligned.m64n128k32.s32.s8.s8 "
        "{%64, %65, %66, %67, %68, %69, %70, %71, %72, %73, %74, %75, %76, %77, %78, %79, "
        "%80, %81, %82, %83, %84, %85, %86, %87, %88, %89, %90, %91, %92, %93, %94, %95, "
        "%96, %97, %98, %99, %100, %101, %102, %103, %104, %105, %106, %107, %108, %109, %110, %111, "
        "%112, %113, %114, %115, %116, %117, %118, %119, %120, %121, %122, %123, %124, %125, %126, %127}, "
        "da, db, p;\n"
        "add.s64 da, da, 128;\nadd.s64 db, db, 2;\n"
        "wgmma.mma_async.sync.aligned.m64n128k32.s32.s8.s8 "
        "{%0, %1, %2, %3, %4, %5, %6, %7, %8, %9, %10, %11, %12, %13, %14, %15, "
        "%16, %17, %18, %19, %20, %21, %22, %23, %24, %25, %26, %27, %28, %29, %30, %31, "
        "%32, %33, %34, %35, %36, %37, %38, %39, %40, %41, %42, %43, %44, %45, %46, %47, "
        "%48, %49, %50, %51, %52, %53, %54, %55, %56, %57, %58, %59, %60, %61, %62, %63}, "
        "da, db, 1;\n"
        "add.s64 da, da, 128;\n"
        "wgmma.mma_async.sync.aligned.m64n128k32.s32.s8.s8 "
        "{%64, %65, %66, %67, %68, %69, %70, %71, %72, %73, %74, %75, %76, %77, %78, %79, "
        "%80, %81, %82, %83, %84, %85, %86, %87, %88, %89, %90, %91, %92, %93, %94, %95, "
        "%96, %97, %98, %99, %100, %101, %102, %103, %104, %105, %106, %107, %108, %109, %110, %111, "
        "%112, %113, %114, %115, %116, %117, %118, %119, %120, %121, %122, %123, %124, %125, %126, %127}, "
        "da, db, 1;\n"
        "wgmma.commit_group.sync.aligned;\n}\n"
        : "+r"(d[0]), "+r"(d[1]), "+r"(d[2]), "+r"(d[3]), "+r"(d[4]), "+r"(d[5]), "+r"(d[6]), "+r"(d[7]),
          "+r"(d[8]), "+r"(d[9]), "+r"(d[10]), "+r"(d[11]), "+r"(d[12]), "+r"(d[13]), "+r"(d[14]), "+r"(d[15]),
          "+r"(d[16]), "+r"(d[17]), "+r"(d[18]), "+r"(d[19]), "+r"(d[20]), "+r"(d[21]), "+r"(d[22]), "+r"(d[23]),
          "+r"(d[24]), "+r"(d[25]), "+r"(d[26]), "+r"(d[27]), "+r"(d[28]), "+r"(d[29]), "+r"(d[30]), "+r"(d[31]),
          "+r"(d[32]), "+r"(d[33]), "+r"(d[34]), "+r"(d[35]), "+r"(d[36]), "+r"(d[37]), "+r"(d[38]), "+r"(d[39]),
          "+r"(d[40]), "+r"(d[41]), "+r"(d[42]), "+r"(d[43]), "+r"(d[44]), "+r"(d[45]), "+r"(d[46]), "+r"(d[47]),
          "+r"(d[48]), "+r"(d[49]), "+r"(d[50]), "+r"(d[51]), "+r"(d[52]), "+r"(d[53]), "+r"(d[54]), "+r"(d[55]),
          "+r"(d[56]), "+r"(d[57]), "+r"(d[58]), "+r"(d[59]), "+r"(d[60]), "+r"(d[61]), "+r"(d[62]), "+r"(d[63]),
          "+r"(e[0]), "+r"(e[1]), "+r"(e[2]), "+r"(e[3]), "+r"(e[4]), "+r"(e[5]), "+r"(e[6]), "+r"(e[7]),
          "+r"(e[8]), "+r"(e[9]), "+r"(e[10]), "+r"(e[11]), "+r"(e[12]), "+r"(e[13]), "+r"(e[14]), "+r"(e[15]),
          "+r"(e[16]), "+r"(e[17]), "+r"(e[18]), "+r"(e[19]), "+r"(e[20]), "+r"(e[21]), "+r"(e[22]), "+r"(e[23]),
          "+r"(e[24]), "+r"(e[25]), "+r"(e[26]), "+r"(e[27]), "+r"(e[28]), "+r"(e[29]), "+r"(e[30]), "+r"(e[31]),
          "+r"(e[32]), "+r"(e[33]), "+r"(e[34]), "+r"(e[35]), "+r"(e[36]), "+r"(e[37]), "+r"(e[38]), "+r"(e[39]),
          "+r"(e[40]), "+r"(e[41]), "+r"(e[42]), "+r"(e[43]), "+r"(e[44]), "+r"(e[45]), "+r"(e[46]), "+r"(e[47]),
          "+r"(e[48]), "+r"(e[49]), "+r"(e[50]), "+r"(e[51]), "+r"(e[52]), "+r"(e[53]), "+r"(e[54]), "+r"(e[55]),
          "+r"(e[56]), "+r"(e[57]), "+r"(e[58]), "+r"(e[59]), "+r"(e[60]), "+r"(e[61]), "+r"(e[62]), "+r"(e[63])
        : "r"(alo), "r"(blo), "r"(scale_d), "n"(DESC_A_HI), "n"(DESC_B_HI) : "memory");
}
__device__ __forceinline__ bool mma_pair(int (&d)[64], uint32_t alo, uint32_t blo, int scale_d, uint32_t bar) {
    uint32_t ok;
    asm volatile("{\n.reg .pred p, q;\n.reg .b64 da, db;\nsetp.ne.b32 p, %67, 0;\n"
        "mov.b64 da, {%65, %68};\nmov.b64 db, {%66, %69};\n"
        "wgmma.mma_async.sync.aligned.m64n128k32.s32.s8.s8 "
        "{%0, %1, %2, %3, %4, %5, %6, %7, %8, %9, %10, %11, %12, %13, %14, %15, "
        "%16, %17, %18, %19, %20, %21, %22, %23, %24, %25, %26, %27, %28, %29, %30, %31, "
        "%32, %33, %34, %35, %36, %37, %38, %39, %40, %41, %42, %43, %44, %45, %46, %47, "
        "%48, %49, %50, %51, %52, %53, %54, %55, %56, %57, %58, %59, %60, %61, %62, %63}, "
        "da, db, p;\n"
        "add.s64 da, da, 128;\nadd.s64 db, db, 2;\n"
        "wgmma.mma_async.sync.aligned.m64n128k32.s32.s8.s8 "
        "{%0, %1, %2, %3, %4, %5, %6, %7, %8, %9, %10, %11, %12, %13, %14, %15, "
        "%16, %17, %18, %19, %20, %21, %22, %23, %24, %25, %26, %27, %28, %29, %30, %31, "
        "%32, %33, %34, %35, %36, %37, %38, %39, %40, %41, %42, %43, %44, %45, %46, %47, "
        "%48, %49, %50, %51, %52, %53, %54, %55, %56, %57, %58, %59, %60, %61, %62, %63}, "
        "da, db, 1;\n"
        "add.s64 da, da, 128;\nadd.s64 db, db, 510;\n"
        "wgmma.mma_async.sync.aligned.m64n128k32.s32.s8.s8 "
        "{%0, %1, %2, %3, %4, %5, %6, %7, %8, %9, %10, %11, %12, %13, %14, %15, "
        "%16, %17, %18, %19, %20, %21, %22, %23, %24, %25, %26, %27, %28, %29, %30, %31, "
        "%32, %33, %34, %35, %36, %37, %38, %39, %40, %41, %42, %43, %44, %45, %46, %47, "
        "%48, %49, %50, %51, %52, %53, %54, %55, %56, %57, %58, %59, %60, %61, %62, %63}, "
        "da, db, 1;\n"
        "add.s64 da, da, 128;\nadd.s64 db, db, 2;\n"
        "wgmma.mma_async.sync.aligned.m64n128k32.s32.s8.s8 "
        "{%0, %1, %2, %3, %4, %5, %6, %7, %8, %9, %10, %11, %12, %13, %14, %15, "
        "%16, %17, %18, %19, %20, %21, %22, %23, %24, %25, %26, %27, %28, %29, %30, %31, "
        "%32, %33, %34, %35, %36, %37, %38, %39, %40, %41, %42, %43, %44, %45, %46, %47, "
        "%48, %49, %50, %51, %52, %53, %54, %55, %56, %57, %58, %59, %60, %61, %62, %63}, "
        "da, db, 1;\n"
        "add.s64 da, da, 128;\nadd.s64 db, db, 510;\n"
        "wgmma.mma_async.sync.aligned.m64n128k32.s32.s8.s8 "
        "{%0, %1, %2, %3, %4, %5, %6, %7, %8, %9, %10, %11, %12, %13, %14, %15, "
        "%16, %17, %18, %19, %20, %21, %22, %23, %24, %25, %26, %27, %28, %29, %30, %31, "
        "%32, %33, %34, %35, %36, %37, %38, %39, %40, %41, %42, %43, %44, %45, %46, %47, "
        "%48, %49, %50, %51, %52, %53, %54, %55, %56, %57, %58, %59, %60, %61, %62, %63}, "
        "da, db, 1;\n"
        "add.s64 da, da, 128;\nadd.s64 db, db, 2;\n"
        "mbarrier.test_wait.parity.shared::cta.b64 q, [%70], 0;\n"
        "wgmma.mma_async.sync.aligned.m64n128k32.s32.s8.s8 "
        "{%0, %1, %2, %3, %4, %5, %6, %7, %8, %9, %10, %11, %12, %13, %14, %15, "
        "%16, %17, %18, %19, %20, %21, %22, %23, %24, %25, %26, %27, %28, %29, %30, %31, "
        "%32, %33, %34, %35, %36, %37, %38, %39, %40, %41, %42, %43, %44, %45, %46, %47, "
        "%48, %49, %50, %51, %52, %53, %54, %55, %56, %57, %58, %59, %60, %61, %62, %63}, "
        "da, db, 1;\n"
        "add.s64 da, da, 128;\nadd.s64 db, db, 510;\n"
        "wgmma.mma_async.sync.aligned.m64n128k32.s32.s8.s8 "
        "{%0, %1, %2, %3, %4, %5, %6, %7, %8, %9, %10, %11, %12, %13, %14, %15, "
        "%16, %17, %18, %19, %20, %21, %22, %23, %24, %25, %26, %27, %28, %29, %30, %31, "
        "%32, %33, %34, %35, %36, %37, %38, %39, %40, %41, %42, %43, %44, %45, %46, %47, "
        "%48, %49, %50, %51, %52, %53, %54, %55, %56, %57, %58, %59, %60, %61, %62, %63}, "
        "da, db, 1;\n"
        "add.s64 da, da, 128;\nadd.s64 db, db, 2;\n"
        "wgmma.mma_async.sync.aligned.m64n128k32.s32.s8.s8 "
        "{%0, %1, %2, %3, %4, %5, %6, %7, %8, %9, %10, %11, %12, %13, %14, %15, "
        "%16, %17, %18, %19, %20, %21, %22, %23, %24, %25, %26, %27, %28, %29, %30, %31, "
        "%32, %33, %34, %35, %36, %37, %38, %39, %40, %41, %42, %43, %44, %45, %46, %47, "
        "%48, %49, %50, %51, %52, %53, %54, %55, %56, %57, %58, %59, %60, %61, %62, %63}, "
        "da, db, 1;\n"
        "wgmma.commit_group.sync.aligned;\nselp.u32 %64, 1, 0, q;\n}\n"
        : "+r"(d[0]), "+r"(d[1]), "+r"(d[2]), "+r"(d[3]), "+r"(d[4]), "+r"(d[5]), "+r"(d[6]), "+r"(d[7]),
          "+r"(d[8]), "+r"(d[9]), "+r"(d[10]), "+r"(d[11]), "+r"(d[12]), "+r"(d[13]), "+r"(d[14]), "+r"(d[15]),
          "+r"(d[16]), "+r"(d[17]), "+r"(d[18]), "+r"(d[19]), "+r"(d[20]), "+r"(d[21]), "+r"(d[22]), "+r"(d[23]),
          "+r"(d[24]), "+r"(d[25]), "+r"(d[26]), "+r"(d[27]), "+r"(d[28]), "+r"(d[29]), "+r"(d[30]), "+r"(d[31]),
          "+r"(d[32]), "+r"(d[33]), "+r"(d[34]), "+r"(d[35]), "+r"(d[36]), "+r"(d[37]), "+r"(d[38]), "+r"(d[39]),
          "+r"(d[40]), "+r"(d[41]), "+r"(d[42]), "+r"(d[43]), "+r"(d[44]), "+r"(d[45]), "+r"(d[46]), "+r"(d[47]),
          "+r"(d[48]), "+r"(d[49]), "+r"(d[50]), "+r"(d[51]), "+r"(d[52]), "+r"(d[53]), "+r"(d[54]), "+r"(d[55]),
          "+r"(d[56]), "+r"(d[57]), "+r"(d[58]), "+r"(d[59]), "+r"(d[60]), "+r"(d[61]), "+r"(d[62]), "+r"(d[63]), "=r"(ok)
        : "r"(alo), "r"(blo), "r"(scale_d), "n"(DESC_A_HI), "n"(DESC_B_HI), "r"(bar) : "memory");
    return ok;
}
__device__ __forceinline__ void mma_rows2(int (&d)[64], int (&e)[64], uint32_t alo, uint32_t blo, int scale_d) {
    asm volatile("{\n.reg .pred p;\n.reg .b64 da, db;\nsetp.ne.b32 p, %130, 0;\n"
        "mov.b64 da, {%128, %131};\nmov.b64 db, {%129, %132};\n"
        "wgmma.mma_async.sync.aligned.m64n128k32.s32.s8.s8 "
        "{%0, %1, %2, %3, %4, %5, %6, %7, %8, %9, %10, %11, %12, %13, %14, %15, "
        "%16, %17, %18, %19, %20, %21, %22, %23, %24, %25, %26, %27, %28, %29, %30, %31, "
        "%32, %33, %34, %35, %36, %37, %38, %39, %40, %41, %42, %43, %44, %45, %46, %47, "
        "%48, %49, %50, %51, %52, %53, %54, %55, %56, %57, %58, %59, %60, %61, %62, %63}, "
        "da, db, p;\n"
        "add.s64 db, db, 512;\n"
        "wgmma.mma_async.sync.aligned.m64n128k32.s32.s8.s8 "
        "{%64, %65, %66, %67, %68, %69, %70, %71, %72, %73, %74, %75, %76, %77, %78, %79, "
        "%80, %81, %82, %83, %84, %85, %86, %87, %88, %89, %90, %91, %92, %93, %94, %95, "
        "%96, %97, %98, %99, %100, %101, %102, %103, %104, %105, %106, %107, %108, %109, %110, %111, "
        "%112, %113, %114, %115, %116, %117, %118, %119, %120, %121, %122, %123, %124, %125, %126, %127}, "
        "da, db, p;\n"
        "add.s64 da, da, 128;\nadd.s64 db, db, -510;\n"
        "wgmma.mma_async.sync.aligned.m64n128k32.s32.s8.s8 "
        "{%0, %1, %2, %3, %4, %5, %6, %7, %8, %9, %10, %11, %12, %13, %14, %15, "
        "%16, %17, %18, %19, %20, %21, %22, %23, %24, %25, %26, %27, %28, %29, %30, %31, "
        "%32, %33, %34, %35, %36, %37, %38, %39, %40, %41, %42, %43, %44, %45, %46, %47, "
        "%48, %49, %50, %51, %52, %53, %54, %55, %56, %57, %58, %59, %60, %61, %62, %63}, "
        "da, db, 1;\n"
        "add.s64 db, db, 512;\n"
        "wgmma.mma_async.sync.aligned.m64n128k32.s32.s8.s8 "
        "{%64, %65, %66, %67, %68, %69, %70, %71, %72, %73, %74, %75, %76, %77, %78, %79, "
        "%80, %81, %82, %83, %84, %85, %86, %87, %88, %89, %90, %91, %92, %93, %94, %95, "
        "%96, %97, %98, %99, %100, %101, %102, %103, %104, %105, %106, %107, %108, %109, %110, %111, "
        "%112, %113, %114, %115, %116, %117, %118, %119, %120, %121, %122, %123, %124, %125, %126, %127}, "
        "da, db, 1;\n"
        "wgmma.commit_group.sync.aligned;\n}\n"
        : "+r"(d[0]), "+r"(d[1]), "+r"(d[2]), "+r"(d[3]), "+r"(d[4]), "+r"(d[5]), "+r"(d[6]), "+r"(d[7]),
          "+r"(d[8]), "+r"(d[9]), "+r"(d[10]), "+r"(d[11]), "+r"(d[12]), "+r"(d[13]), "+r"(d[14]), "+r"(d[15]),
          "+r"(d[16]), "+r"(d[17]), "+r"(d[18]), "+r"(d[19]), "+r"(d[20]), "+r"(d[21]), "+r"(d[22]), "+r"(d[23]),
          "+r"(d[24]), "+r"(d[25]), "+r"(d[26]), "+r"(d[27]), "+r"(d[28]), "+r"(d[29]), "+r"(d[30]), "+r"(d[31]),
          "+r"(d[32]), "+r"(d[33]), "+r"(d[34]), "+r"(d[35]), "+r"(d[36]), "+r"(d[37]), "+r"(d[38]), "+r"(d[39]),
          "+r"(d[40]), "+r"(d[41]), "+r"(d[42]), "+r"(d[43]), "+r"(d[44]), "+r"(d[45]), "+r"(d[46]), "+r"(d[47]),
          "+r"(d[48]), "+r"(d[49]), "+r"(d[50]), "+r"(d[51]), "+r"(d[52]), "+r"(d[53]), "+r"(d[54]), "+r"(d[55]),
          "+r"(d[56]), "+r"(d[57]), "+r"(d[58]), "+r"(d[59]), "+r"(d[60]), "+r"(d[61]), "+r"(d[62]), "+r"(d[63]),
          "+r"(e[0]), "+r"(e[1]), "+r"(e[2]), "+r"(e[3]), "+r"(e[4]), "+r"(e[5]), "+r"(e[6]), "+r"(e[7]),
          "+r"(e[8]), "+r"(e[9]), "+r"(e[10]), "+r"(e[11]), "+r"(e[12]), "+r"(e[13]), "+r"(e[14]), "+r"(e[15]),
          "+r"(e[16]), "+r"(e[17]), "+r"(e[18]), "+r"(e[19]), "+r"(e[20]), "+r"(e[21]), "+r"(e[22]), "+r"(e[23]),
          "+r"(e[24]), "+r"(e[25]), "+r"(e[26]), "+r"(e[27]), "+r"(e[28]), "+r"(e[29]), "+r"(e[30]), "+r"(e[31]),
          "+r"(e[32]), "+r"(e[33]), "+r"(e[34]), "+r"(e[35]), "+r"(e[36]), "+r"(e[37]), "+r"(e[38]), "+r"(e[39]),
          "+r"(e[40]), "+r"(e[41]), "+r"(e[42]), "+r"(e[43]), "+r"(e[44]), "+r"(e[45]), "+r"(e[46]), "+r"(e[47]),
          "+r"(e[48]), "+r"(e[49]), "+r"(e[50]), "+r"(e[51]), "+r"(e[52]), "+r"(e[53]), "+r"(e[54]), "+r"(e[55]),
          "+r"(e[56]), "+r"(e[57]), "+r"(e[58]), "+r"(e[59]), "+r"(e[60]), "+r"(e[61]), "+r"(e[62]), "+r"(e[63])
        : "r"(alo), "r"(blo), "r"(scale_d), "n"(DESC_A_HI), "n"(DESC_B_HI) : "memory");
}

__device__ __forceinline__ void wg_fence() { asm volatile("wgmma.fence.sync.aligned;" ::: "memory"); }
template <int N> __device__ __forceinline__ void wg_wait() { asm volatile("wgmma.wait_group.sync.aligned %0;" :: "n"(N) : "memory"); }

__host__ __device__ constexpr int unit_of(int wg, int s) { return wg ? (s < 16 - D_ ? D_ + 2 * s : s + 16) : (s < D_ ? s : 2 * s - D_ + 1); }

__host__ __device__ constexpr int bar_of(int u) { return u >= 32 ? u & ~1 : u < D_ || u >= 32 - D_ ? u : ((u - D_) & 1) ? D_ + ((u - D_) >> 1) : 16 + ((u - D_) >> 1); }
constexpr uint32_t step_table(int wg) {
    uint32_t t = 0;
    for (int s = 0; s < 15; s++) t |= (uint32_t)(unit_of(wg, s + 1) - unit_of(wg, s) - 1) << s;
    return t;
}
constexpr uint32_t STEPS0 = step_table(0), STEPS1 = step_table(1);
__host__ __device__ constexpr int sum_owner(int g) { return g < 8 ? (g & 4) | (g & 1) << 1 | (~g >> 1 & 1) : g; }
__device__ __forceinline__ int sum_group(int r) { return r < 8 ? (r & 4) | (~r & 1) << 1 | (r >> 1 & 1) : r; }
__device__ __forceinline__ int col_of(int c, int blk) { return (c < 7 ? blk * 7 + c : 49 + blk) * 64; }

struct JobTable { uint2 e[NCTA][NJOB + NCONV]; };
__device__ const JobTable g_jobs = {{
    {{0x0, 0x0}, {0x20400, 0x1000000}, {0x90202, 0x2008099}, {0x100004, 0x3010132}, {0x14000000, 0x310001ee}, {0x2a412a34, 0x2d82025a}, {0x14100e0e, 0x750042e1}, {0x5d0a07, 0x409c366}, {0x14202a0e, 0x75008440}, {0x650a09, 0x60a44c5}, {0x1430460e, 0x7504c59d}, {0x36c680b, 0x76ac612}, {0x1440620e, 0x750506ee}, {0x3f4780d, 0x87b4768}, {0x14507e0e, 0x75094840}, {0x33c600f, 0x963c8b2}, {0x14609a0e, 0x75098965}, {0x1470b60e, 0x750dca0e}, {0x1480001c, 0x98020ab6}, {0x1490701c, 0x980a4b97}, {0x14a00023, 0xba028c8a}, {0x14b07023, 0xba0acd7c}, {0x14c0002a, 0xdc030e6f}, {0x14d0702a, 0xdc0b4f53}, {0x30000000, 0x0}, {0x30000000, 0x0}, {0x30000000, 0x0}, {0x30000000, 0x0}, {0x30000000, 0x0}, {0x30000000, 0x0}, {0x30000000, 0x0}, {0x30000000, 0x0}},
    {{0x0, 0x0}, {0x420c00, 0x1080001}, {0x490a02, 0x208809a}, {0x500804, 0x3090133}, {0x14010007, 0x200001f9}, {0x1973605, 0x431426c}, {0x14110e15, 0x640042f7}, {0x2a4e5b31, 0x5b82c378}, {0x14212a15, 0x64008456}, {0x2654a09, 0x64a44db}, {0x14314615, 0x6404c5b2}, {0x16d2a0b, 0x72ac628}, {0x14416215, 0x64050703}, {0x1b5320d, 0x833477b}, {0x14517e15, 0x64094855}, {0xfd1a0f, 0x91bc8c5}, {0x14619a15, 0x64098970}, {0x1471b615, 0x640dca18}, {0x1481071c, 0x98020ac1}, {0x1491771c, 0x980a4ba6}, {0x14a10723, 0xba028c99}, {0x14b17723, 0xba0acd8c}, {0x14c1072a, 0xdc030e7e}, {0x14d1772a, 0xdc0b4f60}, {0x30000000, 0x0}, {0x30000000, 0x0}, {0x30000000, 0x0}, {0x30000000, 0x0}, {0x30000000, 0x0}, {0x30000000, 0x0}, {0x30000000, 0x0}, {0x30000000, 0x0}},
    {{0x0, 0x0}, {0x821400, 0x1100002}, {0x891202, 0x210809b}, {0x901004, 0x3110134}, {0x14020700, 0x31000204}, {0x3176605, 0x461427c}, {0x1412150e, 0x7500430d}, {0x39d7207, 0x471c38a}, {0x1422310e, 0x7500846c}, {0x660c09, 0x60a44f1}, {0x14324d0e, 0x7504c5c7}, {0x36d6a0b, 0x76ac63d}, {0x1442690e, 0x75050719}, {0x3756a0d, 0x86b478e}, {0x1b8300e, 0x83387fa}, {0x1452850e, 0x7509486a}, {0x3e040f, 0x903c8e7}, {0x1462a10e, 0x7509897a}, {0x1472bd0e, 0x750dca23}, {0x14820e1c, 0x98020acb}, {0x14927e1c, 0x980a4bb5}, {0x14a20e23, 0xba028ca8}, {0x14b27e23, 0xba0acd9b}, {0x14c20e2a, 0xdc030e8e}, {0x14d27e2a, 0xdc0b4f6d}, {0x30000000, 0x0}, {0x30000000, 0x0}, {0x30000000, 0x0}, {0x30000000, 0x0}, {0x30000000, 0x0}, {0x30000000, 0x0}, {0x30000000, 0x0}},
    {{0x0, 0x0}, {0xc21c00, 0x1180003}, {0xc91a02, 0x218809c}, {0xd01804, 0x3190135}, {0x14030707, 0x2000020f}, {0x981006, 0x411828d}, {0x14131515, 0x64004323}, {0x11e2407, 0x521c39a}, {0x14233115, 0x64008482}, {0x2264409, 0x6424504}, {0x14334d15, 0x6404c5dc}, {0x12e240b, 0x722c64f}, {0x14436915, 0x6405072e}, {0x136240d, 0x82347a0}, {0x3f8780e, 0x87b8810}, {0x14538515, 0x6409487f}, {0xfe1c0f, 0x91bc8ef}, {0x1463a115, 0x64098985}, {0x1473bd15, 0x640dca2d}, {0x1483151c, 0x98020ad6}, {0x1493851c, 0x980a4bc4}, {0x14a31523, 0xba028cb7}, {0x14b38523, 0xba0acdaa}, {0x14c3152a, 0xdc030e9d}, {0x14d3852a, 0xdc0b4f7b}, {0x30000000, 0x0}, {0x30000000, 0x0}, {0x30000000, 0x0}, {0x30000000, 0x0}, {0x30000000, 0x0}, {0x30000000, 0x0}, {0x30000000, 0x0}},
    {{0x0, 0x0}, {0x1022400, 0x1200005}, {0x1092202, 0x220809e}, {0x1102004, 0x3210137}, {0x14040e00, 0x3100021a}, {0x2184006, 0x441829d}, {0x14142a00, 0x31004339}, {0x31e6407, 0x561c3b0}, {0x14244600, 0x31048498}, {0x3e67c09, 0x67a4516}, {0x14346200, 0x3104c5f2}, {0x2ee5c0b, 0x75ac661}, {0x1b1320c, 0x73306d3}, {0x14447e00, 0x31090743}, {0x3b6740d, 0x87347bb}, {0x14549a00, 0x31094894}, {0x23e440f, 0x943c8fc}, {0x1464b600, 0x310d898f}, {0x1474d200, 0x310dca38}, {0x14841c1c, 0x98020ae1}, {0x14948c1c, 0x980a4bd3}, {0x14a41c23, 0xba028cc6}, {0x14b48c23, 0xba0acdb9}, {0x14c41c2a, 0xdc030eac}, {0x14d48c2a, 0xdc0b4f88}, {0x30000000, 0x0}, {0x30000000, 0x0}, {0x30000000, 0x0}, {0x30000000, 0x0}, {0x30000000, 0x0}, {0x30000000, 0x0}, {0x30000000, 0x0}},
    {{0x0, 0x0}, {0x1422c00, 0x1280006}, {0x1492a02, 0x228809f}, {0x1502804, 0x3290138}, {0x14050e07, 0x20000225}, {0x3d87806, 0x47982af}, {0x14152a07, 0x2000434e}, {0xdf1e07, 0x519c3c3}, {0x14254607, 0x200484ae}, {0x1672e09, 0x62a4528}, {0x3e97a0a, 0x67a8598}, {0x14356207, 0x2004c607}, {0x26f4e0b, 0x74ac686}, {0x14457e07, 0x20090758}, {0x1b7360d, 0x83347d0}, {0x14559a07, 0x200948a9}, {0x3fe7c0f, 0x97bc90d}, {0x1465b607, 0x200d899a}, {0x1475d207, 0x200dca42}, {0x1485231c, 0x98020af0}, {0x1495931c, 0x980a4be3}, {0x14a52323, 0xba028cd5}, {0x14b59323, 0xba0acdc8}, {0x14c5232a, 0xdc030ebb}, {0x14d5932a, 0xdc0b4f95}, {0x30000000, 0x0}, {0x30000000, 0x0}, {0x30000000, 0x0}, {0x30000000, 0x0}, {0x30000000, 0x0}, {0x30000000, 0x0}, {0x30000000, 0x0}},
    {{0x0, 0x0}, {0x1823400, 0x1300007}, {0x1893202, 0x23080a0}, {0x1903004, 0x3310139}, {0x14061500, 0x31000230}, {0x1592a06, 0x42982c1}, {0x14163100, 0x31004364}, {0x29f5607, 0x551c3d6}, {0x14264d00, 0x310484c4}, {0x2a75609, 0x6524536}, {0x14366900, 0x3104c61c}, {0x12f260b, 0x722c679}, {0xb2140c, 0x71306f2}, {0x14468500, 0x3109076d}, {0x3776e0d, 0x86b47e2}, {0x1456a100, 0x310948be}, {0x1bf360f, 0x933c921}, {0x1466bd00, 0x310d89a4}, {0x1476d900, 0x310dca4d}, {0x14862a1c, 0x98020aff}, {0x14969a1c, 0x980a4bf2}, {0x14a62a23, 0xba028ce5}, {0x14b69a23, 0xba0acdd7}, {0x14c62a2a, 0xdc030eca}, {0x14d69a2a, 0xdc0b4fa3}, {0x30000000, 0x0}, {0x30000000, 0x0}, {0x30000000, 0x0}, {0x30000000, 0x0}, {0x30000000, 0x0}, {0x30000000, 0x0}, {0x30000000, 0x0}},
    {{0x0, 0x0}, {0x1c23c00, 0x1380009}, {0x1c93a02, 0x23880a2}, {0x1d03804, 0x339013b}, {0x14071507, 0x2000023b}, {0x2d95a06, 0x45982d2}, {0x14173107, 0x2000437a}, {0x600808, 0x50a03ea}, {0x14274d07, 0x200484da}, {0x28000a, 0x6028546}, {0x2ea5c0a, 0x65a85b9}, {0x14376907, 0x2004c631}, {0x170280c, 0x72b06a6}, {0x14478507, 0x20090782}, {0xb8100e, 0x81387ef}, {0x1457a107, 0x200948d3}, {0x37f6e0f, 0x96bc933}, {0x1467bd07, 0x200d89af}, {0x1477d907, 0x200dca58}, {0x1487311c, 0x98020b0e}, {0x1497a11c, 0x980a4c01}, {0x14a73123, 0xba028cf4}, {0x14b7a123, 0xba0acde7}, {0x14c7312a, 0xdc030ed9}, {0x14d7a12a, 0xdc0b4fb0}, {0x30000000, 0x0}, {0x30000000, 0x0}, {0x30000000, 0x0}, {0x30000000, 0x0}, {0x30000000, 0x0}, {0x30000000, 0x0}, {0x30000000, 0x0}},
    {{0x0, 0x0}, {0x2024400, 0x140000a}, {0x2094202, 0x24080a3}, {0x2104004, 0x341013c}, {0x1408000e, 0x75000246}, {0x5a0c06, 0x40982e2}, {0x14181c0e, 0x75004390}, {0x2204008, 0x54203fd}, {0x1232608, 0x5220476}, {0x1428380e, 0x750484f0}, {0xe91a0a, 0x61a857a}, {0x1438540e, 0x7504c646}, {0x2f0580c, 0x75b06b6}, {0x1448700e, 0x75090797}, {0x2b8500e, 0x8538804}, {0x14588c0e, 0x750948e8}, {0x1468a80e, 0x750d89b9}, {0x1478c40e, 0x750dca62}, {0x1488381c, 0x98060b1d}, {0x1498a81c, 0x980e4c10}, {0x14a83823, 0xba068d03}, {0x14b8a823, 0xba0ecdf6}, {0x14c8382a, 0xdc070ee9}, {0x14d8a82a, 0xdc0f4fbd}, {0x30000000, 0x0}, {0x30000000, 0x0}, {0x30000000, 0x0}, {0x30000000, 0x0}, {0x30000000, 0x0}, {0x30000000, 0x0}, {0x30000000, 0x0}, {0x30000000, 0x0}},
    {{0x0, 0x0}, {0x2424c00, 0x148000b}, {0x2494a02, 0x24880a4}, {0x2504804, 0x349013d}, {0x14090015, 0x64000251}, {0x2a483833, 0x3a8282f4}, {0x14191c15, 0x640043a6}, {0x3e07808, 0x57a040f}, {0x2e35e08, 0x55a0489}, {0x14293815, 0x64048506}, {0x1a9320a, 0x6328582}, {0x14395415, 0x6404c65b}, {0xf11a0c, 0x71b06cb}, {0x14497015, 0x640907ac}, {0x1792a0e, 0x82b8821}, {0x14598c15, 0x640948fd}, {0x1469a815, 0x640d89c4}, {0x1479c415, 0x640dca6d}, {0x14893f1c, 0x98060b2c}, {0x1499af1c, 0x980e4c1f}, {0x14a93f23, 0xba068d12}, {0x14b9af23, 0xba0ece05}, {0x14c93f2a, 0xdc070ef6}, {0x14d9af2a, 0xdc0f4fca}, {0x30000000, 0x0}, {0x30000000, 0x0}, {0x30000000, 0x0}, {0x30000000, 0x0}, {0x30000000, 0x0}, {0x30000000, 0x0}, {0x30000000, 0x0}, {0x30000000, 0x0}},
    {{0x0, 0x0}, {0x2825400, 0x150000d}, {0x2895202, 0x25080a6}, {0x2905004, 0x351013f}, {0x2a200031, 0x8001cd}, {0x140a070e, 0x7500025d}, {0x1b0606, 0x401830b}, {0x141a230e, 0x750043bc}, {0x3216208, 0x5620434}, {0x142a3f0e, 0x7504851c}, {0x2694a0a, 0x64a8589}, {0x143a5b0e, 0x7504c670}, {0x331620c, 0x76306e3}, {0x144a770e, 0x750907c1}, {0x3b9720e, 0x8738839}, {0x145a930e, 0x75094912}, {0x146aaf0e, 0x750d89cf}, {0x147acb0e, 0x750dca77}, {0x148a461c, 0x98060b3c}, {0x149ab61c, 0x980e4c2e}, {0x14aa4623, 0xba068d21}, {0x14bab623, 0xba0ece14}, {0x14ca462a, 0xdc070f03}, {0x14dab62a, 0xdc0f4fd8}, {0x30000000, 0x0}, {0x30000000, 0x0}, {0x30000000, 0x0}, {0x30000000, 0x0}, {0x30000000, 0x0}, {0x30000000, 0x0}, {0x30000000, 0x0}, {0x30000000, 0x0}},
    {{0x0, 0x0}, {0x2c25c00, 0x158000e}, {0x2c95a02, 0x25880a7}, {0x2d05804, 0x3590140}, {0x2a210032, 0x18001ce}, {0x140b0715, 0x64000273}, {0x19b3606, 0x431831c}, {0x141b2315, 0x640043d2}, {0x1222408, 0x522044a}, {0x142b3f15, 0x64048532}, {0xaa140a, 0x61285a1}, {0x143b5b15, 0x6404c685}, {0x1b2340c, 0x73306fd}, {0x144b7715, 0x640907d6}, {0x1fa3c0e, 0x93b884f}, {0x145b9315, 0x64094927}, {0x146baf15, 0x640d89d9}, {0x147bcb15, 0x640dca82}, {0x148b4d1c, 0x98060b4b}, {0x149bbd1c, 0x980e4c3e}, {0x14ab4d23, 0xba068d30}, {0x14bbbd23, 0xba0ece23}, {0x14cb4d2a, 0xdc070f10}, {0x14dbbd2a, 0xdc0f4fe5}, {0x30000000, 0x0}, {0x30000000, 0x0}, {0x30000000, 0x0}, {0x30000000, 0x0}, {0x30000000, 0x0}, {0x30000000, 0x0}, {0x30000000, 0x0}, {0x30000000, 0x0}},
    {{0x0, 0x0}, {0x3026400, 0x160000f}, {0x3096202, 0x26080a8}, {0x3106004, 0x3610141}, {0x2a220731, 0x78001cf}, {0x140c1c00, 0x31000289}, {0x2db5e06, 0x4598329}, {0x141c3800, 0x310443e8}, {0x3226408, 0x5620460}, {0x142c5400, 0x31048548}, {0x32a640a, 0x66285bc}, {0x143c7000, 0x3108c69a}, {0x3f27c0c, 0x77b0713}, {0x144c8c00, 0x310907eb}, {0x3fa7c0e, 0x97b8864}, {0x145ca800, 0x310d493b}, {0x146cc400, 0x310d89e4}, {0x147cd20e, 0x750dca8c}, {0x148c541c, 0x98060b5a}, {0x149cc41c, 0x980e4c4d}, {0x14ac5423, 0xba068d40}, {0x14bcc423, 0xba0ece33}, {0x14cc542a, 0xdc070f1e}, {0x14dcc42a, 0xdc0f4ff2}, {0x30000000, 0x0}, {0x30000000, 0x0}, {0x30000000, 0x0}, {0x30000000, 0x0}, {0x30000000, 0x0}, {0x30000000, 0x0}, {0x30000000, 0x0}, {0x30000000, 0x0}},
    {{0x0, 0x0}, {0x3426c00, 0x1680011}, {0x3496a02, 0x26880aa}, {0x3506804, 0x3690143}, {0x2a230732, 0x88001d1}, {0x140d1c07, 0x2000029f}, {0x5c0807, 0x409c33a}, {0x141d3807, 0x200443fe}, {0x1632e08, 0x52a0478}, {0x142d5407, 0x2004855e}, {0x16b2e0a, 0x62a85d3}, {0x143d7007, 0x2008c6af}, {0x2734e0c, 0x84b072f}, {0x144d8c07, 0x20090800}, {0x1bb360e, 0x9338878}, {0x145da807, 0x200d4946}, {0x146dc407, 0x200d89ee}, {0x147dd215, 0x640dca97}, {0x148d5b1c, 0x98060b69}, {0x149dcb1c, 0x980e4c5c}, {0x14ad5b23, 0xba068d4f}, {0x14bdcb23, 0xba0ece42}, {0x14cd5b2a, 0xdc070f2b}, {0x14ddcb2a, 0xdc0f5000}, {0x30000000, 0x0}, {0x30000000, 0x0}, {0x30000000, 0x0}, {0x30000000, 0x0}, {0x30000000, 0x0}, {0x30000000, 0x0}, {0x30000000, 0x0}, {0x30000000, 0x0}},
    {{0x0, 0x0}, {0x3827400, 0x1700012}, {0x3897202, 0x27080ab}, {0x3907004, 0x3710144}, {0x2a240e31, 0xe8041d2}, {0x140e2300, 0x310002b5}, {0x19c3007, 0x431c348}, {0x141e3f00, 0x31044414}, {0x3636e08, 0x56a048e}, {0x142e5b00, 0x31048573}, {0x3ab760a, 0x67285eb}, {0x143e7700, 0x3108c6c4}, {0x74080d, 0x80b4744}, {0x144e9300, 0x31090815}, {0x3bb760e, 0x973888d}, {0x145eaf00, 0x310d4950}, {0x146ecb00, 0x310d89f9}, {0x147ed90e, 0x750dcaa1}, {0x148e621c, 0x98060b78}, {0x149ed21c, 0x980e4c6b}, {0x14ae6223, 0xba068d5e}, {0x14bed223, 0xba0ece51}, {0x14ce622a, 0xdc070f38}, {0x14ded22a, 0xdc0f500d}, {0x30000000, 0x0}, {0x30000000, 0x0}, {0x30000000, 0x0}, {0x30000000, 0x0}, {0x30000000, 0x0}, {0x30000000, 0x0}, {0x30000000, 0x0}, {0x30000000, 0x0}},
    {{0x0, 0x0}, {0x3c27c00, 0x1780013}, {0x3c97a02, 0x27880ac}, {0x3d07804, 0x3790145}, {0x2a250e32, 0xf8041d4}, {0x140f2307, 0x200002cb}, {0x2dc5807, 0x459c355}, {0x141f3f07, 0x2004442a}, {0x2244009, 0x54244ad}, {0x142f5b07, 0x20048588}, {0x16c280b, 0x72ac5fd}, {0x143f7707, 0x2008c6d9}, {0x234400d, 0x8434756}, {0x144f9307, 0x2009082a}, {0x17c280f, 0x92bc8a0}, {0x145faf07, 0x200d495b}, {0x146fcb07, 0x200d8a03}, {0x147fd915, 0x640dcaac}, {0x148f691c, 0x98060b87}, {0x149fd91c, 0x980e4c7a}, {0x14af6923, 0xba068d6d}, {0x14bfd923, 0xba0ece60}, {0x14cf692a, 0xdc070f46}, {0x14dfd92a, 0xdc0f501a}, {0x30000000, 0x0}, {0x30000000, 0x0}, {0x30000000, 0x0}, {0x30000000, 0x0}, {0x30000000, 0x0}, {0x30000000, 0x0}, {0x30000000, 0x0}, {0x30000000, 0x0}},
    {{0x0, 0x0}, {0x30600, 0x1000015}, {0xa0402, 0x20080ae}, {0x110204, 0x3010147}, {0x14e00001, 0x310001ef}, {0x170605, 0x401425c}, {0x14f00e0f, 0x750042e3}, {0x9d1207, 0x411c369}, {0x15002a0f, 0x75008443}, {0xa51209, 0x61244c8}, {0x1510460f, 0x7504c5a0}, {0x3ac700b, 0x772c615}, {0x1520620f, 0x750506f1}, {0x35020d, 0x803476b}, {0x15307e0f, 0x75094842}, {0x37c680f, 0x96bc8b5}, {0x15409a0f, 0x75098967}, {0x1550b60f, 0x750dca0f}, {0x1560001d, 0x98020ab8}, {0x1570701d, 0x980a4b99}, {0x15800024, 0xba028c8b}, {0x15907024, 0xba0acd7e}, {0x15a0002b, 0xdc030e71}, {0x15b0702b, 0xdc0b4f55}, {0x30000000, 0x0}, {0x30000000, 0x0}, {0x30000000, 0x0}, {0x30000000, 0x0}, {0x30000000, 0x0}, {0x30000000, 0x0}, {0x30000000, 0x0}, {0x30000000, 0x0}},
    {{0x0, 0x0}, {0x430e00, 0x1080016}, {0x4a0c02, 0x20880af}, {0x510a04, 0x3090148}, {0x14e10008, 0x200001fa}, {0x1d73e05, 0x439426d}, {0x14f10e16, 0x640042f9}, {0x21d4207, 0x441c379}, {0x15012a16, 0x64008459}, {0x2a55209, 0x65244de}, {0x15114616, 0x6404c5b5}, {0x1ad320b, 0x732c62a}, {0x15216216, 0x64050706}, {0x1f53a0d, 0x83b477d}, {0x38000e, 0x80387ea}, {0x15317e16, 0x64094857}, {0x3bd720f, 0x973c8e2}, {0x15419a16, 0x64098971}, {0x1551b616, 0x640dca1a}, {0x1561071d, 0x98020ac2}, {0x1571771d, 0x980a4ba8}, {0x15810724, 0xba028c9b}, {0x15917724, 0xba0acd8d}, {0x15a1072b, 0xdc030e80}, {0x15b1772b, 0xdc0b4f62}, {0x30000000, 0x0}, {0x30000000, 0x0}, {0x30000000, 0x0}, {0x30000000, 0x0}, {0x30000000, 0x0}, {0x30000000, 0x0}, {0x30000000, 0x0}},
    {{0x0, 0x0}, {0x831600, 0x1100017}, {0x8a1402, 0x21080b0}, {0x911204, 0x3110149}, {0x14e20701, 0x31000205}, {0x3576e05, 0x469427f}, {0x14f2150f, 0x7500430f}, {0x3dd7a07, 0x479c38b}, {0x1502310f, 0x7500846f}, {0xa61409, 0x61244f4}, {0x15124d0f, 0x7504c5ca}, {0x3ad720b, 0x772c63f}, {0x1522690f, 0x7505071b}, {0x3b5720d, 0x8734790}, {0x238400e, 0x84387ff}, {0x1532850f, 0x7509486c}, {0xbe140f, 0x913c8ec}, {0x1542a10f, 0x7509897c}, {0x1552bd0f, 0x750dca24}, {0x15620e1d, 0x98020acd}, {0x15727e1d, 0x980a4bb7}, {0x15820e24, 0xba028caa}, {0x15927e24, 0xba0acd9d}, {0x15a20e2b, 0xdc030e8f}, {0x15b27e2b, 0xdc0b4f6f}, {0x30000000, 0x0}, {0x30000000, 0x0}, {0x30000000, 0x0}, {0x30000000, 0x0}, {0x30000000, 0x0}, {0x30000000, 0x0}, {0x30000000, 0x0}},
    {{0x0, 0x0}, {0xc31e00, 0x1180018}, {0xca1c02, 0x21880b1}, {0xd11a04, 0x319014a}, {0x14e30708, 0x20000210}, {0xd81806, 0x4198290}, {0x14f31516, 0x64004325}, {0x15e2c07, 0x529c39d}, {0x15033116, 0x64008485}, {0x2664c09, 0x64a4507}, {0x15134d16, 0x6404c5df}, {0x16e2c0b, 0x72ac652}, {0x15236916, 0x64050730}, {0x1762c0d, 0x82b47a3}, {0x15338516, 0x64094881}, {0x3fd7a0f, 0x97bc8e3}, {0x1543a116, 0x64098986}, {0x1553bd16, 0x640dca2f}, {0x1563151d, 0x98020ad7}, {0x1573851d, 0x980a4bc6}, {0x15831524, 0xba028cb9}, {0x15938524, 0xba0acdac}, {0x15a3152b, 0xdc030e9f}, {0x15b3852b, 0xdc0b4f7d}, {0x30000000, 0x0}, {0x30000000, 0x0}, {0x30000000, 0x0}, {0x30000000, 0x0}, {0x30000000, 0x0}, {0x30000000, 0x0}, {0x30000000, 0x0}, {0x30000000, 0x0}},
    {{0x0, 0x0}, {0x1032600, 0x120001a}, {0x10a2402, 0x22080b3}, {0x1112204, 0x321014c}, {0x14e40e01, 0x3100021b}, {0x2584806, 0x44982a0}, {0x14f42a01, 0x3100433b}, {0x35e6c07, 0x569c3b3}, {0x15044601, 0x3104849b}, {0x270609, 0x602451a}, {0x15146201, 0x3104c5f4}, {0x32e640b, 0x762c664}, {0x15247e01, 0x31090745}, {0x236440d, 0x84347ab}, {0x139220e, 0x823881f}, {0x15349a01, 0x31094896}, {0x27e4c0f, 0x94bc8fe}, {0x1544b601, 0x310d8991}, {0x1554d201, 0x310dca39}, {0x15641c1d, 0x98020ae2}, {0x15748c1d, 0x980a4bd5}, {0x15841c24, 0xba028cc8}, {0x15948c24, 0xba0acdbb}, {0x15a41c2b, 0xdc030eae}, {0x15b48c2b, 0xdc0b4f8a}, {0x30000000, 0x0}, {0x30000000, 0x0}, {0x30000000, 0x0}, {0x30000000, 0x0}, {0x30000000, 0x0}, {0x30000000, 0x0}, {0x30000000, 0x0}},
    {{0x0, 0x0}, {0x1432e00, 0x128001b}, {0x14a2c02, 0x22880b4}, {0x1512a04, 0x329014d}, {0x14e50e08, 0x20000226}, {0x2a454632, 0x478242b2}, {0x14f52a08, 0x20004351}, {0x11f2607, 0x521c3c6}, {0x15054608, 0x200484b1}, {0x1a73609, 0x632452b}, {0x15156208, 0x2004c609}, {0x6f0e0b, 0x70ac671}, {0x3716a0c, 0x76b06e5}, {0x15257e08, 0x2009075a}, {0x1f73e0d, 0x83b47d1}, {0x15359a08, 0x200948ac}, {0x3f060f, 0x903c911}, {0x1545b608, 0x200d899b}, {0x1555d208, 0x200dca44}, {0x1565231d, 0x98020af2}, {0x1575931d, 0x980a4be4}, {0x15852324, 0xba028cd7}, {0x15959324, 0xba0acdca}, {0x15a5232b, 0xdc030ebd}, {0x15b5932b, 0xdc0b4f97}, {0x30000000, 0x0}, {0x30000000, 0x0}, {0x30000000, 0x0}, {0x30000000, 0x0}, {0x30000000, 0x0}, {0x30000000, 0x0}, {0x30000000, 0x0}},
    {{0x0, 0x0}, {0x1833600, 0x130001c}, {0x18a3402, 0x23080b5}, {0x1913204, 0x331014e}, {0x14e61501, 0x31000231}, {0x1993206, 0x43182c4}, {0x14f63101, 0x31004367}, {0x2df5e07, 0x559c3d9}, {0x15064d01, 0x310484c7}, {0x3276609, 0x662453b}, {0x15166901, 0x3104c61e}, {0x16f2e0b, 0x72ac67c}, {0x15268501, 0x3109076f}, {0x3f67c0d, 0x87b47bc}, {0x3796a0e, 0x86b8836}, {0x1536a101, 0x310948c1}, {0x1ff3e0f, 0x93bc922}, {0x1546bd01, 0x310d89a6}, {0x1556d901, 0x310dca4e}, {0x15662a1d, 0x98020b01}, {0x15769a1d, 0x980a4bf4}, {0x15862a24, 0xba028ce6}, {0x15969a24, 0xba0acdd9}, {0x15a62a2b, 0xdc030ecc}, {0x15b69a2b, 0xdc0b4fa4}, {0x30000000, 0x0}, {0x30000000, 0x0}, {0x30000000, 0x0}, {0x30000000, 0x0}, {0x30000000, 0x0}, {0x30000000, 0x0}, {0x30000000, 0x0}},
    {{0x0, 0x0}, {0x1c33e00, 0x138001e}, {0x1ca3c02, 0x23880b7}, {0x1d13a04, 0x3390150}, {0x14e71508, 0x2000023c}, {0x3196206, 0x46182d4}, {0x14f73108, 0x2000437d}, {0xa01008, 0x51203ec}, {0x15074d08, 0x200484dd}, {0x68080a, 0x60a8549}, {0x36a6c0a, 0x66a85be}, {0x15176908, 0x2004c633}, {0x1f0380c, 0x73b06aa}, {0x15278508, 0x20090785}, {0xf8180e, 0x81b87f2}, {0x1537a108, 0x200948d6}, {0x3bf760f, 0x973c936}, {0x1547bd08, 0x200d89b0}, {0x1557d908, 0x200dca59}, {0x1567311d, 0x98020b10}, {0x1577a11d, 0x980a4c03}, {0x15873124, 0xba028cf6}, {0x1597a124, 0xba0acde9}, {0x15a7312b, 0xdc030edb}, {0x15b7a12b, 0xdc0b4fb2}, {0x30000000, 0x0}, {0x30000000, 0x0}, {0x30000000, 0x0}, {0x30000000, 0x0}, {0x30000000, 0x0}, {0x30000000, 0x0}, {0x30000000, 0x0}},
    {{0x0, 0x0}, {0x2034600, 0x140001f}, {0x20a4402, 0x24080b8}, {0x2114204, 0x3410151}, {0x14e8000f, 0x75000247}, {0x9a1406, 0x41182e5}, {0x14f81c0f, 0x75004393}, {0x2604808, 0x54a0400}, {0x1508380f, 0x750484f3}, {0x1e8380a, 0x63a8558}, {0x12b260a, 0x62285d1}, {0x1518540f, 0x7504c648}, {0x370680c, 0x76b06bb}, {0x1528700f, 0x7509079a}, {0x338600e, 0x863880a}, {0x15388c0f, 0x750948eb}, {0x1548a80f, 0x750d89bb}, {0x1558c40f, 0x750dca63}, {0x1568381d, 0x98060b1f}, {0x1578a81d, 0x980e4c12}, {0x15883824, 0xba068d05}, {0x1598a824, 0xba0ecdf8}, {0x15a8382b, 0xdc070eeb}, {0x15b8a82b, 0xdc0f4fbf}, {0x30000000, 0x0}, {0x30000000, 0x0}, {0x30000000, 0x0}, {0x30000000, 0x0}, {0x30000000, 0x0}, {0x30000000, 0x0}, {0x30000000, 0x0}, {0x30000000, 0x0}},
    {{0x0, 0x0}, {0x2434e00, 0x1480020}, {0x24a4c02, 0x24880b9}, {0x2514a04, 0x3490152}, {0x14e90016, 0x64000252}, {0x21a4406, 0x44182f5}, {0x14f91c16, 0x640043a9}, {0x210208, 0x5020413}, {0x3236608, 0x562048c}, {0x15093816, 0x64048509}, {0x1e93a0a, 0x63a8583}, {0x15195416, 0x6404c65e}, {0x131220c, 0x72306cd}, {0x15297016, 0x640907af}, {0x1f93a0e, 0x83b8825}, {0x15398c16, 0x64094900}, {0x1549a816, 0x640d89c5}, {0x1559c416, 0x640dca6e}, {0x15693f1d, 0x98060b2e}, {0x1579af1d, 0x980e4c21}, {0x15893f24, 0xba068d14}, {0x1599af24, 0xba0ece07}, {0x15a93f2b, 0xdc070ef8}, {0x15b9af2b, 0xdc0f4fcc}, {0x30000000, 0x0}, {0x30000000, 0x0}, {0x30000000, 0x0}, {0x30000000, 0x0}, {0x30000000, 0x0}, {0x30000000, 0x0}, {0x30000000, 0x0}, {0x30000000, 0x0}},
    {{0x0, 0x0}, {0x2835600, 0x1500022}, {0x28a5402, 0x25080bb}, {0x2915204, 0x3510154}, {0x2a261531, 0x158041d5}, {0x14ea070f, 0x75000260}, {0x11b2606, 0x4218316}, {0x14fa230f, 0x750043bf}, {0x3a17208, 0x5720439}, {0x150a3f0f, 0x7504851e}, {0x2e95a0a, 0x65a858f}, {0x151a5b0f, 0x7504c673}, {0x3b1720c, 0x77306e8}, {0x152a770f, 0x750907c4}, {0x3a040e, 0x903883e}, {0x153a930f, 0x75094915}, {0x154aaf0f, 0x750d89d0}, {0x155acb0f, 0x750dca78}, {0x156a461d, 0x98060b3d}, {0x157ab61d, 0x980e4c30}, {0x158a4624, 0xba068d23}, {0x159ab624, 0xba0ece16}, {0x15aa462b, 0xdc070f05}, {0x15bab62b, 0xdc0f4fda}, {0x30000000, 0x0}, {0x30000000, 0x0}, {0x30000000, 0x0}, {0x30000000, 0x0}, {0x30000000, 0x0}, {0x30000000, 0x0}, {0x30000000, 0x0}, {0x30000000, 0x0}},
    {{0x0, 0x0}, {0x2c35e00, 0x1580023}, {0x2ca5c02, 0x25880bc}, {0x2d15a04, 0x3590155}, {0x2a271532, 0x168041d6}, {0x14eb0716, 0x64000276}, {0x2a4a3f33, 0x41828320}, {0x14fb2316, 0x640043d5}, {0x1a23408, 0x532044f}, {0x150b3f16, 0x64048534}, {0x16a2c0a, 0x62a85a9}, {0x151b5b16, 0x6404c688}, {0x1f23c0c, 0x73b06fe}, {0x152b7716, 0x640907d9}, {0x23a440e, 0x9438853}, {0x153b9316, 0x6409492a}, {0x154baf16, 0x640d89da}, {0x155bcb16, 0x640dca83}, {0x156b4d1d, 0x98060b4d}, {0x157bbd1d, 0x980e4c40}, {0x158b4d24, 0xba068d32}, {0x159bbd24, 0xba0ece25}, {0x15ab4d2b, 0xdc070f12}, {0x15bbbd2b, 0xdc0f4fe7}, {0x30000000, 0x0}, {0x30000000, 0x0}, {0x30000000, 0x0}, {0x30000000, 0x0}, {0x30000000, 0x0}, {0x30000000, 0x0}, {0x30000000, 0x0}, {0x30000000, 0x0}},
    {{0x0, 0x0}, {0x3036600, 0x1600024}, {0x30a6402, 0x26080bd}, {0x3116204, 0x3610156}, {0x2a280033, 0x28081d8}, {0x14ec1c01, 0x3100028c}, {0x35b6e06, 0x469832f}, {0x14fc3801, 0x310443eb}, {0x3a27408, 0x5720465}, {0x150c5401, 0x3104854a}, {0x3ea7c0a, 0x67a85c2}, {0x151c7001, 0x3108c69d}, {0x33060c, 0x8030717}, {0x152c8c01, 0x310907ee}, {0x3b060e, 0x9038868}, {0x153ca801, 0x310d493c}, {0x154cc401, 0x310d89e5}, {0x155cd20f, 0x750dca8e}, {0x156c541d, 0x98060b5c}, {0x157cc41d, 0x980e4c4f}, {0x158c5424, 0xba068d42}, {0x159cc424, 0xba0ece34}, {0x15ac542b, 0xdc070f20}, {0x15bcc42b, 0xdc0f4ff4}, {0x30000000, 0x0}, {0x30000000, 0x0}, {0x30000000, 0x0}, {0x30000000, 0x0}, {0x30000000, 0x0}, {0x30000000, 0x0}, {0x30000000, 0x0}, {0x30000000, 0x0}},
    {{0x0, 0x0}, {0x3436e00, 0x1680026}, {0x34a6c02, 0x26880bf}, {0x3516a04, 0x3690158}, {0x2a290034, 0x38081d9}, {0x14ed1c08, 0x200002a2}, {0x9c1007, 0x411c33d}, {0x14fd3808, 0x20044401}, {0x1a33608, 0x532047b}, {0x150d5408, 0x20048560}, {0x1ab360a, 0x63285d6}, {0x151d7008, 0x2008c6b2}, {0x2b3560c, 0x8530732}, {0x152d8c08, 0x20090803}, {0x1fb3e0e, 0x93b8879}, {0x153da808, 0x200d4947}, {0x154dc408, 0x200d89ef}, {0x155dd216, 0x640dca98}, {0x156d5b1d, 0x98060b6b}, {0x157dcb1d, 0x980e4c5e}, {0x158d5b24, 0xba068d51}, {0x159dcb24, 0xba0ece44}, {0x15ad5b2b, 0xdc070f2d}, {0x15bdcb2b, 0xdc0f5001}, {0x30000000, 0x0}, {0x30000000, 0x0}, {0x30000000, 0x0}, {0x30000000, 0x0}, {0x30000000, 0x0}, {0x30000000, 0x0}, {0x30000000, 0x0}, {0x30000000, 0x0}},
    {{0x0, 0x0}, {0x3837600, 0x1700027}, {0x38a7402, 0x27080c0}, {0x3917204, 0x3710159}, {0x2a2a0733, 0x98081da}, {0x14ee2301, 0x310002b7}, {0x1dc3807, 0x439c349}, {0x14fe3f01, 0x31044417}, {0x3a37608, 0x5720491}, {0x150e5b01, 0x31048576}, {0x3eb7e0a, 0x67a85ec}, {0x151e7701, 0x3108c6c7}, {0xb4100d, 0x8134747}, {0x152e9301, 0x31090818}, {0x3fb7e0e, 0x97b888f}, {0x153eaf01, 0x310d4951}, {0x154ecb01, 0x310d89fa}, {0x155ed90f, 0x750dcaa3}, {0x156e621d, 0x98060b7a}, {0x157ed21d, 0x980e4c6d}, {0x158e6224, 0xba068d60}, {0x159ed224, 0xba0ece53}, {0x15ae622b, 0xdc070f3a}, {0x15bed22b, 0xdc0f500f}, {0x30000000, 0x0}, {0x30000000, 0x0}, {0x30000000, 0x0}, {0x30000000, 0x0}, {0x30000000, 0x0}, {0x30000000, 0x0}, {0x30000000, 0x0}, {0x30000000, 0x0}},
    {{0x0, 0x0}, {0x3c37e00, 0x1780028}, {0x3ca7c02, 0x27880c1}, {0x3d17a04, 0x379015a}, {0x2a2b0734, 0xa8081dc}, {0x14ef2308, 0x200002cd}, {0x31c6007, 0x461c358}, {0x14ff3f08, 0x2004442d}, {0x2644809, 0x54a44af}, {0x150f5b08, 0x2004858b}, {0x1ac300b, 0x732c600}, {0x151f7708, 0x2008c6dc}, {0x274480d, 0x84b4759}, {0x152f9308, 0x2009082d}, {0x1bc300f, 0x933c8a2}, {0x153faf08, 0x200d495c}, {0x154fcb08, 0x200d8a05}, {0x155fd916, 0x640dcaad}, {0x156f691d, 0x98060b89}, {0x157fd91d, 0x980e4c7c}, {0x158f6924, 0xba068d6f}, {0x159fd924, 0xba0ece62}, {0x15af692b, 0xdc070f48}, {0x15bfd92b, 0xdc0f501c}, {0x30000000, 0x0}, {0x30000000, 0x0}, {0x30000000, 0x0}, {0x30000000, 0x0}, {0x30000000, 0x0}, {0x30000000, 0x0}, {0x30000000, 0x0}, {0x30000000, 0x0}},
    {{0x0, 0x0}, {0x40001, 0x100402a}, {0xb0602, 0x20080c3}, {0x120404, 0x301015c}, {0x15c00002, 0x310001f0}, {0x570e05, 0x409425e}, {0x15d00e10, 0x750042e6}, {0xdd1a07, 0x419c36b}, {0x15e02a10, 0x75008446}, {0x1252209, 0x62244cd}, {0x15f04610, 0x7504c5a3}, {0x3ec780b, 0x77ac616}, {0x16006210, 0x750506f4}, {0x750a0d, 0x80b476e}, {0x16107e10, 0x75094845}, {0x3bc700f, 0x973c8b7}, {0x16209a10, 0x75098968}, {0x1630b610, 0x750dca10}, {0x1640001e, 0x98020ab9}, {0x1650701e, 0x980a4b9a}, {0x16600025, 0xba028c8d}, {0x16707025, 0xba0acd80}, {0x1680002c, 0xdc030e73}, {0x1690702c, 0xdc0b4f57}, {0x30000000, 0x0}, {0x30000000, 0x0}, {0x30000000, 0x0}, {0x30000000, 0x0}, {0x30000000, 0x0}, {0x30000000, 0x0}, {0x30000000, 0x0}, {0x30000000, 0x0}},
    {{0x0, 0x0}, {0x440801, 0x108402b}, {0x4b0e02, 0x20880c4}, {0x520c04, 0x309015d}, {0x15c10009, 0x200001fb}, {0x2a423133, 0x33820270}, {0x15d10e17, 0x640042fc}, {0x25d4a07, 0x449c37c}, {0x15e12a17, 0x6400845c}, {0x2e55a09, 0x65a44e1}, {0x15f14617, 0x6404c5b8}, {0x1ed3a0b, 0x73ac62b}, {0x16016217, 0x64050709}, {0x235420d, 0x8434781}, {0x16117e17, 0x6409485a}, {0x13d220f, 0x923c8c7}, {0x16219a17, 0x64098972}, {0x1631b617, 0x640dca1b}, {0x1641071e, 0x98020ac4}, {0x1651771e, 0x980a4baa}, {0x16610725, 0xba028c9c}, {0x16717725, 0xba0acd8f}, {0x1681072c, 0xdc030e82}, {0x1691772c, 0xdc0b4f64}, {0x30000000, 0x0}, {0x30000000, 0x0}, {0x30000000, 0x0}, {0x30000000, 0x0}, {0x30000000, 0x0}, {0x30000000, 0x0}, {0x30000000, 0x0}, {0x30000000, 0x0}},
    {{0x0, 0x0}, {0x841001, 0x110402c}, {0x8b1602, 0x21080c5}, {0x921404, 0x311015e}, {0x15c20702, 0x31000206}, {0x3977605, 0x4714282}, {0x15d21510, 0x75004312}, {0x2a4f5b32, 0x5c82c38e}, {0x15e23110, 0x75008472}, {0xe61c09, 0x61a44f7}, {0x15f24d10, 0x7504c5cd}, {0x3ed7a0b, 0x77ac641}, {0x16026910, 0x7505071e}, {0x3f57a0d, 0x87b4792}, {0x16128510, 0x7509486f}, {0x27d4a0f, 0x94bc8d4}, {0x1622a110, 0x7509897d}, {0x1632bd10, 0x750dca25}, {0x16420e1e, 0x98020ace}, {0x16527e1e, 0x980a4bb9}, {0x16620e25, 0xba028cac}, {0x16727e25, 0xba0acd9f}, {0x16820e2c, 0xdc030e91}, {0x16927e2c, 0xdc0b4f71}, {0x30000000, 0x0}, {0x30000000, 0x0}, {0x30000000, 0x0}, {0x30000000, 0x0}, {0x30000000, 0x0}, {0x30000000, 0x0}, {0x30000000, 0x0}, {0x30000000, 0x0}},
    {{0x0, 0x0}, {0xc41801, 0x118402d}, {0xcb1e02, 0x21880c6}, {0xd21c04, 0x319015f}, {0x15c30709, 0x20000211}, {0x1182006, 0x4218292}, {0x15d31517, 0x64004328}, {0x19e3407, 0x531c39f}, {0x15e33117, 0x64008487}, {0x2a65409, 0x652450a}, {0x15f34d17, 0x6404c5e2}, {0x1ae340b, 0x732c654}, {0x31020c, 0x70306c3}, {0x16036917, 0x64050733}, {0x2b6540d, 0x85347b0}, {0x16138517, 0x64094884}, {0x13e240f, 0x923c8f1}, {0x1623a117, 0x64098987}, {0x1633bd17, 0x640dca30}, {0x1643151e, 0x98020ad9}, {0x1653851e, 0x980a4bc8}, {0x16631525, 0xba028cbb}, {0x16738525, 0xba0acdae}, {0x1683152c, 0xdc030ea1}, {0x1693852c, 0xdc0b4f7f}, {0x30000000, 0x0}, {0x30000000, 0x0}, {0x30000000, 0x0}, {0x30000000, 0x0}, {0x30000000, 0x0}, {0x30000000, 0x0}, {0x30000000, 0x0}},
    {{0x0, 0x0}, {0x1042001, 0x120402f}, {0x10b2602, 0x22080c8}, {0x1122404, 0x3210161}, {0x15c40e02, 0x3100021c}, {0x2985006, 0x45182a3}, {0x15d42a02, 0x3100433e}, {0x39e7407, 0x571c3b5}, {0x15e44602, 0x3104849d}, {0x670e09, 0x60a451d}, {0x15f46202, 0x3104c5f7}, {0x36e6c0b, 0x76ac667}, {0x16047e02, 0x31090748}, {0x2764c0d, 0x84b47ad}, {0x1b9320e, 0x8338824}, {0x16149a02, 0x31094899}, {0x2be540f, 0x953c901}, {0x1624b602, 0x310d8992}, {0x1634d202, 0x310dca3b}, {0x16441c1e, 0x98020ae4}, {0x16548c1e, 0x980a4bd7}, {0x16641c25, 0xba028cca}, {0x16748c25, 0xba0acdbd}, {0x16841c2c, 0xdc030eb0}, {0x16948c2c, 0xdc0b4f8c}, {0x30000000, 0x0}, {0x30000000, 0x0}, {0x30000000, 0x0}, {0x30000000, 0x0}, {0x30000000, 0x0}, {0x30000000, 0x0}, {0x30000000, 0x0}},
    {{0x0, 0x0}, {0x1442801, 0x1284030}, {0x14b2e02, 0x22880c9}, {0x1522c04, 0x3290162}, {0x15c50e09, 0x20000227}, {0x190206, 0x40182b3}, {0x15d52a09, 0x20004354}, {0x15f2e07, 0x529c3c9}, {0x15e54609, 0x200484b3}, {0x1e73e09, 0x63a452c}, {0x15f56209, 0x2004c60c}, {0xaf160b, 0x712c674}, {0x3f17a0c, 0x77b06e9}, {0x16057e09, 0x2009075d}, {0x237460d, 0x84347d5}, {0x16159a09, 0x200948ae}, {0x7f0e0f, 0x90bc914}, {0x1625b609, 0x200d899d}, {0x1635d209, 0x200dca45}, {0x1645231e, 0x98020af3}, {0x1655931e, 0x980a4be6}, {0x16652325, 0xba028cd9}, {0x16759325, 0xba0acdcc}, {0x1685232c, 0xdc030ebf}, {0x1695932c, 0xdc0b4f99}, {0x30000000, 0x0}, {0x30000000, 0x0}, {0x30000000, 0x0}, {0x30000000, 0x0}, {0x30000000, 0x0}, {0x30000000, 0x0}, {0x30000000, 0x0}},
    {{0x0, 0x0}, {0x1843001, 0x1304031}, {0x18b3602, 0x23080ca}, {0x1923404, 0x3310163}, {0x15c61502, 0x31000232}, {0x1d93a06, 0x43982c5}, {0x15d63102, 0x3100436a}, {0x31f6607, 0x561c3dc}, {0x15e64d02, 0x310484c9}, {0x3676e09, 0x66a453e}, {0x15f66902, 0x3104c621}, {0x1ef3e0b, 0x73ac680}, {0x16068502, 0x31090772}, {0x770e0d, 0x80b47c2}, {0x3f97a0e, 0x87b883a}, {0x1616a102, 0x310948c3}, {0x23f460f, 0x943c926}, {0x1626bd02, 0x310d89a7}, {0x1636d902, 0x310dca50}, {0x16462a1e, 0x98020b03}, {0x16569a1e, 0x980a4bf6}, {0x16662a25, 0xba028ce8}, {0x16769a25, 0xba0acddb}, {0x16862a2c, 0xdc030ece}, {0x16969a2c, 0xdc0b4fa6}, {0x30000000, 0x0}, {0x30000000, 0x0}, {0x30000000, 0x0}, {0x30000000, 0x0}, {0x30000000, 0x0}, {0x30000000, 0x0}, {0x30000000, 0x0}},
    {{0x0, 0x0}, {0x1c43801, 0x1384033}, {0x1cb3e02, 0x23880cc}, {0x1d23c04, 0x3390165}, {0x15c71509, 0x2000023d}, {0x3596a06, 0x46982d7}, {0x15d73109, 0x20004380}, {0xe01808, 0x51a03ef}, {0x15e74d09, 0x200484df}, {0xe8180a, 0x61a854f}, {0x15f76909, 0x2004c636}, {0x2af560b, 0x752c689}, {0x232440c, 0x7430702}, {0x16078509, 0x20090787}, {0x138200e, 0x82387f4}, {0x1617a109, 0x200948d8}, {0x3ff7e0f, 0x97bc937}, {0x1627bd09, 0x200d89b2}, {0x1637d909, 0x200dca5a}, {0x1647311e, 0x98020b12}, {0x1657a11e, 0x980a4c05}, {0x16673125, 0xba028cf8}, {0x1677a125, 0xba0acdea}, {0x1687312c, 0xdc030edd}, {0x1697a12c, 0xdc0b4fb4}, {0x30000000, 0x0}, {0x30000000, 0x0}, {0x30000000, 0x0}, {0x30000000, 0x0}, {0x30000000, 0x0}, {0x30000000, 0x0}, {0x30000000, 0x0}},
    {{0x0, 0x0}, {0x2044001, 0x1404034}, {0x20b4602, 0x24080cd}, {0x2124404, 0x3410166}, {0x15c80010, 0x75000248}, {0xda1c06, 0x41982e8}, {0x15d81c10, 0x75004396}, {0x2a05008, 0x5520402}, {0x1e33e08, 0x53a047d}, {0x15e83810, 0x750484f5}, {0x1692a0a, 0x62a857f}, {0x15f85410, 0x7504c64b}, {0x3b0700c, 0x77306be}, {0x16087010, 0x7509079c}, {0x378680e, 0x86b880c}, {0x16188c10, 0x750948ed}, {0x1628a810, 0x750d89bc}, {0x1638c410, 0x750dca65}, {0x1648381e, 0x98060b21}, {0x1658a81e, 0x980e4c14}, {0x16683825, 0xba068d07}, {0x1678a825, 0xba0ecdfa}, {0x1688382c, 0xdc070eec}, {0x1698a82c, 0xdc0f4fc1}, {0x30000000, 0x0}, {0x30000000, 0x0}, {0x30000000, 0x0}, {0x30000000, 0x0}, {0x30000000, 0x0}, {0x30000000, 0x0}, {0x30000000, 0x0}, {0x30000000, 0x0}},
    {{0x0, 0x0}, {0x2444801, 0x1484035}, {0x24b4e02, 0x24880ce}, {0x2524c04, 0x3490167}, {0x2a2c1c31, 0x1c80c1dd}, {0x15c90017, 0x64000253}, {0x15d91c17, 0x640043ac}, {0x610a08, 0x50a0416}, {0x15e93817, 0x6404850b}, {0x3a8700a, 0x672856d}, {0x32b660a, 0x66285e6}, {0x15f95417, 0x6404c660}, {0x1712a0c, 0x72b06d0}, {0x16097017, 0x640907b1}, {0x239420e, 0x8438829}, {0x16198c17, 0x64094902}, {0x1629a817, 0x640d89c7}, {0x1639c417, 0x640dca6f}, {0x16493f1e, 0x98060b30}, {0x1659af1e, 0x980e4c23}, {0x16693f25, 0xba068d16}, {0x1679af25, 0xba0ece09}, {0x16893f2c, 0xdc070efa}, {0x1699af2c, 0xdc0f4fce}, {0x30000000, 0x0}, {0x30000000, 0x0}, {0x30000000, 0x0}, {0x30000000, 0x0}, {0x30000000, 0x0}, {0x30000000, 0x0}, {0x30000000, 0x0}, {0x30000000, 0x0}},
    {{0x0, 0x0}, {0x2845001, 0x1504037}, {0x28b5602, 0x25080d0}, {0x2925404, 0x3510169}, {0x2a2d1c32, 0x1d80c1df}, {0x15ca0710, 0x75000262}, {0x9b1606, 0x4118311}, {0x15da2310, 0x750043c2}, {0x3e17a08, 0x57a043b}, {0x15ea3f10, 0x75048521}, {0x329620a, 0x6628591}, {0x15fa5b10, 0x7504c675}, {0x32040c, 0x70306ed}, {0x160a7710, 0x750907c6}, {0x7a0c0e, 0x90b8841}, {0x161a9310, 0x75094918}, {0x162aaf10, 0x750d89d1}, {0x163acb10, 0x750dca7a}, {0x164a461e, 0x98060b3f}, {0x165ab61e, 0x980e4c32}, {0x166a4625, 0xba068d25}, {0x167ab625, 0xba0ece18}, {0x168a462c, 0xdc070f07}, {0x169ab62c, 0xdc0f4fdc}, {0x30000000, 0x0}, {0x30000000, 0x0}, {0x30000000, 0x0}, {0x30000000, 0x0}, {0x30000000, 0x0}, {0x30000000, 0x0}, {0x30000000, 0x0}, {0x30000000, 0x0}},
    {{0x0, 0x0}, {0x2c45801, 0x1584038}, {0x2cb5e02, 0x25880d1}, {0x2d25c04, 0x359016a}, {0x2a2e2331, 0x2380c1e0}, {0x15cb0717, 0x64000278}, {0x21b4606, 0x4418321}, {0x15db2317, 0x640043d8}, {0x1e23c08, 0x53a0451}, {0x15eb3f17, 0x64048537}, {0x1aa340a, 0x63285ac}, {0x15fb5b17, 0x6404c68a}, {0x2724c0c, 0x74b0705}, {0x160b7717, 0x640907db}, {0x27a4c0e, 0x94b8856}, {0x161b9317, 0x6409492d}, {0x162baf17, 0x640d89dc}, {0x163bcb17, 0x640dca84}, {0x164b4d1e, 0x98060b4f}, {0x165bbd1e, 0x980e4c41}, {0x166b4d25, 0xba068d34}, {0x167bbd25, 0xba0ece27}, {0x168b4d2c, 0xdc070f14}, {0x169bbd2c, 0xdc0f4fe9}, {0x30000000, 0x0}, {0x30000000, 0x0}, {0x30000000, 0x0}, {0x30000000, 0x0}, {0x30000000, 0x0}, {0x30000000, 0x0}, {0x30000000, 0x0}, {0x30000000, 0x0}},
    {{0x0, 0x0}, {0x3046001, 0x1604039}, {0x30b6602, 0x26080d2}, {0x3126404, 0x361016b}, {0x2a2f2332, 0x2480c1e1}, {0x15cc1c02, 0x3100028e}, {0x39b7606, 0x4718332}, {0x15dc3802, 0x310443ee}, {0x3e27c08, 0x57a0467}, {0x15ec5402, 0x3104854d}, {0x2b060a, 0x60285c6}, {0x15fc7002, 0x3108c69f}, {0xb3160c, 0x813071c}, {0x160c8c02, 0x310907f1}, {0x7b0e0e, 0x90b886b}, {0x161ca802, 0x310d493e}, {0x162cc402, 0x310d89e6}, {0x163cd210, 0x750dca8f}, {0x164c541e, 0x98060b5e}, {0x165cc41e, 0x980e4c51}, {0x166c5425, 0xba068d43}, {0x167cc425, 0xba0ece36}, {0x168c542c, 0xdc070f22}, {0x169cc42c, 0xdc0f4ff6}, {0x30000000, 0x0}, {0x30000000, 0x0}, {0x30000000, 0x0}, {0x30000000, 0x0}, {0x30000000, 0x0}, {0x30000000, 0x0}, {0x30000000, 0x0}, {0x30000000, 0x0}},
    {{0x0, 0x0}, {0x3446801, 0x168403b}, {0x34b6e02, 0x26880d4}, {0x3526c04, 0x369016d}, {0x2a300e33, 0x108101e3}, {0x15cd1c09, 0x200002a4}, {0xdc1807, 0x419c33f}, {0x15dd3809, 0x20044404}, {0x2234608, 0x5420481}, {0x15ed5409, 0x20048563}, {0x22b460a, 0x64285db}, {0x15fd7009, 0x2008c6b4}, {0x333660c, 0x8630737}, {0x160d8c09, 0x20090806}, {0x23b460e, 0x943887d}, {0x161da809, 0x200d4948}, {0x162dc409, 0x200d89f1}, {0x163dd217, 0x640dca99}, {0x164d5b1e, 0x98060b6d}, {0x165dcb1e, 0x980e4c60}, {0x166d5b25, 0xba068d53}, {0x167dcb25, 0xba0ece45}, {0x168d5b2c, 0xdc070f2f}, {0x169dcb2c, 0xdc0f5003}, {0x30000000, 0x0}, {0x30000000, 0x0}, {0x30000000, 0x0}, {0x30000000, 0x0}, {0x30000000, 0x0}, {0x30000000, 0x0}, {0x30000000, 0x0}, {0x30000000, 0x0}},
    {{0x0, 0x0}, {0x3847001, 0x170403c}, {0x38b7602, 0x27080d5}, {0x3927404, 0x371016e}, {0x2a310e34, 0x118101e4}, {0x15ce2302, 0x310002ba}, {0x2a4c5431, 0x5482c34c}, {0x15de3f02, 0x3104441a}, {0x240009, 0x5024497}, {0x15ee5b02, 0x31048578}, {0x2c000b, 0x702c5f0}, {0x15fe7702, 0x3108c6ca}, {0xf4180d, 0x81b4749}, {0x160e9302, 0x3109081b}, {0x3c000f, 0x903c892}, {0x161eaf02, 0x310d4953}, {0x162ecb02, 0x310d89fb}, {0x163ed910, 0x750dcaa4}, {0x164e621e, 0x98060b7c}, {0x165ed21e, 0x980e4c6f}, {0x166e6225, 0xba068d62}, {0x167ed225, 0xba0ece55}, {0x168e622c, 0xdc070f3c}, {0x169ed22c, 0xdc0f5011}, {0x30000000, 0x0}, {0x30000000, 0x0}, {0x30000000, 0x0}, {0x30000000, 0x0}, {0x30000000, 0x0}, {0x30000000, 0x0}, {0x30000000, 0x0}, {0x30000000, 0x0}},
    {{0x0, 0x0}, {0x3c47801, 0x178403d}, {0x3cb7e02, 0x27880d6}, {0x3d27c04, 0x379016f}, {0x2a321533, 0x178101e5}, {0x15cf2309, 0x200002d0}, {0x35c6807, 0x469c35b}, {0x15df3f09, 0x20044430}, {0x2e45809, 0x55a44b5}, {0x15ef5b09, 0x2004858d}, {0x22c400b, 0x742c605}, {0x15ff7709, 0x2008c6df}, {0x2b4500d, 0x853475c}, {0x160f9309, 0x20090830}, {0x1fc380f, 0x93bc8a4}, {0x161faf09, 0x200d495d}, {0x162fcb09, 0x200d8a06}, {0x163fd917, 0x640dcaae}, {0x164f691e, 0x98060b8b}, {0x165fd91e, 0x980e4c7e}, {0x166f6925, 0xba068d71}, {0x167fd925, 0xba0ece64}, {0x168f692c, 0xdc070f49}, {0x169fd92c, 0xdc0f501e}, {0x30000000, 0x0}, {0x30000000, 0x0}, {0x30000000, 0x0}, {0x30000000, 0x0}, {0x30000000, 0x0}, {0x30000000, 0x0}, {0x30000000, 0x0}, {0x30000000, 0x0}},
    {{0x0, 0x0}, {0x50201, 0x100403f}, {0xc0003, 0x200c0d8}, {0x130604, 0x3010171}, {0x16a00003, 0x310001f2}, {0x971605, 0x4114261}, {0x16b00e11, 0x750042e9}, {0x11d2207, 0x421c36e}, {0x16c02a11, 0x75008448}, {0x1652a09, 0x62a44d0}, {0x16d04611, 0x7504c5a5}, {0x2d020b, 0x702c61a}, {0x16e06211, 0x750506f6}, {0xb5120d, 0x8134771}, {0x16f07e11, 0x75094847}, {0x3fc780f, 0x97bc8b9}, {0x17009a11, 0x75098969}, {0x1710b611, 0x750dca12}, {0x1720001f, 0x98020aba}, {0x1730701f, 0x980a4b9c}, {0x17400026, 0xba028c8f}, {0x17507026, 0xba0acd82}, {0x1760002d, 0xdc030e75}, {0x1770702d, 0xdc0b4f59}, {0x30000000, 0x0}, {0x30000000, 0x0}, {0x30000000, 0x0}, {0x30000000, 0x0}, {0x30000000, 0x0}, {0x30000000, 0x0}, {0x30000000, 0x0}, {0x30000000, 0x0}},
    {{0x0, 0x0}, {0x450a01, 0x1084040}, {0x4c0803, 0x208c0d9}, {0x530e04, 0x3090172}, {0x16a1000a, 0x200001fd}, {0x2174605, 0x4414271}, {0x16b10e18, 0x640042ff}, {0x29d5207, 0x451c37f}, {0x16c12a18, 0x6400845e}, {0x3656a09, 0x66a44e6}, {0x16d14618, 0x6404c5ba}, {0x22d420b, 0x742c62f}, {0x16e16218, 0x6405070b}, {0x2754a0d, 0x84b4783}, {0x16f17e18, 0x6409485d}, {0x17d2a0f, 0x92bc8ca}, {0x17019a18, 0x64098974}, {0x1711b618, 0x640dca1c}, {0x1721071f, 0x98020ac5}, {0x1731771f, 0x980a4bac}, {0x17410726, 0xba028c9e}, {0x17517726, 0xba0acd91}, {0x1761072d, 0xdc030e84}, {0x1771772d, 0xdc0b4f66}, {0x30000000, 0x0}, {0x30000000, 0x0}, {0x30000000, 0x0}, {0x30000000, 0x0}, {0x30000000, 0x0}, {0x30000000, 0x0}, {0x30000000, 0x0}, {0x30000000, 0x0}},
    {{0x0, 0x0}, {0x851201, 0x1104041}, {0x8c1003, 0x210c0da}, {0x931604, 0x3110173}, {0x16a20703, 0x31000208}, {0x3d77e05, 0x4794283}, {0x16b21511, 0x75004315}, {0x1e0407, 0x501c38f}, {0x16c23111, 0x75008474}, {0x1262409, 0x62244f9}, {0x16d24d11, 0x7504c5cf}, {0x2e040b, 0x702c644}, {0x16e26911, 0x75050720}, {0x36040d, 0x8034796}, {0x16f28511, 0x75094872}, {0x2bd520f, 0x953c8d7}, {0x1702a111, 0x7509897e}, {0x1712bd11, 0x750dca27}, {0x17220e1f, 0x98020acf}, {0x17327e1f, 0x980a4bbb}, {0x17420e26, 0xba028cae}, {0x17527e26, 0xba0acda0}, {0x17620e2d, 0xdc030e93}, {0x17727e2d, 0xdc0b4f73}, {0x30000000, 0x0}, {0x30000000, 0x0}, {0x30000000, 0x0}, {0x30000000, 0x0}, {0x30000000, 0x0}, {0x30000000, 0x0}, {0x30000000, 0x0}, {0x30000000, 0x0}},
    {{0x0, 0x0}, {0xc51a01, 0x1184042}, {0xcc1803, 0x218c0db}, {0xd31e04, 0x3190174}, {0x16a3070a, 0x20000213}, {0x1582806, 0x4298295}, {0x16b31518, 0x6400432b}, {0x1de3c07, 0x539c3a1}, {0x16c33118, 0x6400848a}, {0x2e65c09, 0x65a450d}, {0x16d34d18, 0x6404c5e4}, {0x1ee3c0b, 0x73ac656}, {0x710a0c, 0x70b06c6}, {0x16e36918, 0x64050736}, {0x2f65c0d, 0x85b47b3}, {0x16f38518, 0x64094887}, {0x17e2c0f, 0x92bc8f4}, {0x1703a118, 0x64098989}, {0x1713bd18, 0x640dca31}, {0x1723151f, 0x98020ada}, {0x1733851f, 0x980a4bca}, {0x17431526, 0xba028cbd}, {0x17538526, 0xba0acdb0}, {0x1763152d, 0xdc030ea2}, {0x1773852d, 0xdc0b4f80}, {0x30000000, 0x0}, {0x30000000, 0x0}, {0x30000000, 0x0}, {0x30000000, 0x0}, {0x30000000, 0x0}, {0x30000000, 0x0}, {0x30000000, 0x0}},
    {{0x0, 0x0}, {0x1052201, 0x1204044}, {0x10c2003, 0x220c0dd}, {0x1132604, 0x3210176}, {0x16a40e03, 0x3100021e}, {0x2d85806, 0x45982a6}, {0x16b42a03, 0x31004341}, {0x3de7c07, 0x579c3b7}, {0x2614a08, 0x54a042c}, {0x16c44603, 0x310484a0}, {0x2e75e09, 0x65a4539}, {0x16d46203, 0x3104c5f9}, {0x1af360b, 0x732c67e}, {0x16e47e03, 0x3109074b}, {0x37060d, 0x80347c0}, {0x16f49a03, 0x3109489c}, {0x2fe5c0f, 0x95bc904}, {0x1704b603, 0x310d8993}, {0x1714d203, 0x310dca3c}, {0x17241c1f, 0x98020ae6}, {0x17348c1f, 0x980a4bd9}, {0x17441c26, 0xba028ccc}, {0x17548c26, 0xba0acdbf}, {0x17641c2d, 0xdc030eb2}, {0x17748c2d, 0xdc0b4f8e}, {0x30000000, 0x0}, {0x30000000, 0x0}, {0x30000000, 0x0}, {0x30000000, 0x0}, {0x30000000, 0x0}, {0x30000000, 0x0}, {0x30000000, 0x0}},
    {{0x0, 0x0}, {0x1452a01, 0x1284045}, {0x14c2803, 0x228c0de}, {0x1532e04, 0x3290177}, {0x16a50e0a, 0x20000229}, {0x590a06, 0x40982b6}, {0x16b52a0a, 0x20004357}, {0x19f3607, 0x531c3cb}, {0x16c5460a, 0x200484b6}, {0x2274609, 0x6424530}, {0x16d5620a, 0x2004c60f}, {0xef1e0b, 0x71ac677}, {0x16e57e0a, 0x20090760}, {0x3766c0d, 0x86b47b8}, {0x2f95a0e, 0x85b8831}, {0x16f59a0a, 0x200948b1}, {0xbf160f, 0x913c916}, {0x1705b60a, 0x200d899e}, {0x1715d20a, 0x200dca46}, {0x1725231f, 0x98020af5}, {0x1735931f, 0x980a4be8}, {0x17452326, 0xba028cdb}, {0x17559326, 0xba0acdce}, {0x1765232d, 0xdc030ec1}, {0x1775932d, 0xdc0b4f9b}, {0x30000000, 0x0}, {0x30000000, 0x0}, {0x30000000, 0x0}, {0x30000000, 0x0}, {0x30000000, 0x0}, {0x30000000, 0x0}, {0x30000000, 0x0}},
    {{0x0, 0x0}, {0x1853201, 0x1304046}, {0x18c3003, 0x230c0df}, {0x1933604, 0x3310178}, {0x16a61503, 0x31000234}, {0x2a464d31, 0x4d8242c8}, {0x16b63103, 0x3100436d}, {0x35f6e07, 0x569c3df}, {0x16c64d03, 0x310484cc}, {0x3a77609, 0x6724541}, {0x16d66903, 0x3104c624}, {0x22f460b, 0x742c684}, {0x16e68503, 0x31090775}, {0xf71e0d, 0x81b47c8}, {0xba140e, 0x9138843}, {0x16f6a103, 0x310948c6}, {0x27f4e0f, 0x94bc929}, {0x1706bd03, 0x310d89a8}, {0x1716d903, 0x310dca51}, {0x17262a1f, 0x98020b05}, {0x17369a1f, 0x980a4bf7}, {0x17462a26, 0xba028cea}, {0x17569a26, 0xba0acddd}, {0x17662a2d, 0xdc030ed0}, {0x17769a2d, 0xdc0b4fa8}, {0x30000000, 0x0}, {0x30000000, 0x0}, {0x30000000, 0x0}, {0x30000000, 0x0}, {0x30000000, 0x0}, {0x30000000, 0x0}, {0x30000000, 0x0}},
    {{0x0, 0x0}, {0x1c53a01, 0x1384048}, {0x1cc3803, 0x238c0e1}, {0x1d33e04, 0x339017a}, {0x16a7150a, 0x2000023f}, {0x3997206, 0x47182da}, {0x16b7310a, 0x20004383}, {0x1202008, 0x52203f2}, {0x16c74d0a, 0x200484e2}, {0x168280a, 0x62a8554}, {0x16d7690a, 0x2004c639}, {0x32f660b, 0x762c68e}, {0x2f25c0c, 0x75b070a}, {0x16e7850a, 0x2009078a}, {0x178280e, 0x82b87f7}, {0x16f7a10a, 0x200948db}, {0x1707bd0a, 0x200d89b3}, {0x1717d90a, 0x200dca5b}, {0x1727311f, 0x98020b14}, {0x1737a11f, 0x980a4c07}, {0x17473126, 0xba028cf9}, {0x1757a126, 0xba0acdec}, {0x1767312d, 0xdc030edf}, {0x1777a12d, 0xdc0b4fb6}, {0x30000000, 0x0}, {0x30000000, 0x0}, {0x30000000, 0x0}, {0x30000000, 0x0}, {0x30000000, 0x0}, {0x30000000, 0x0}, {0x30000000, 0x0}, {0x30000000, 0x0}},
    {{0x0, 0x0}, {0x2054201, 0x1404049}, {0x20c4003, 0x240c0e2}, {0x2134604, 0x341017b}, {0x16a80011, 0x7500024a}, {0x11a2406, 0x42182ea}, {0x16b81c11, 0x75004399}, {0x2e05808, 0x55a0405}, {0x16c83811, 0x750484f8}, {0x2a8500a, 0x6528562}, {0x1eb3e0a, 0x63a85d7}, {0x16d85411, 0x7504c64e}, {0x3f0780c, 0x77b06bf}, {0x16e87011, 0x7509079f}, {0x3b8700e, 0x873880f}, {0x16f88c11, 0x750948f0}, {0x1708a811, 0x750d89bd}, {0x1718c411, 0x750dca66}, {0x1728381f, 0x98060b23}, {0x1738a81f, 0x980e4c16}, {0x17483826, 0xba068d09}, {0x1758a826, 0xba0ecdfb}, {0x1768382d, 0xdc070eee}, {0x1778a82d, 0xdc0f4fc3}, {0x30000000, 0x0}, {0x30000000, 0x0}, {0x30000000, 0x0}, {0x30000000, 0x0}, {0x30000000, 0x0}, {0x30000000, 0x0}, {0x30000000, 0x0}, {0x30000000, 0x0}},
    {{0x0, 0x0}, {0x2454a01, 0x148404a}, {0x24c4803, 0x248c0e3}, {0x2534e04, 0x349017c}, {0x2a331534, 0x188101e7}, {0x16a90018, 0x64000255}, {0x16b91c18, 0x640043af}, {0xa11208, 0x5120418}, {0x3e37e08, 0x57a0492}, {0x16c93818, 0x6404850e}, {0x229420a, 0x6428587}, {0x16d95418, 0x6404c663}, {0x1f13a0c, 0x73b06d4}, {0x16e97018, 0x640907b4}, {0x2794a0e, 0x84b882c}, {0x16f98c18, 0x64094905}, {0x1709a818, 0x640d89c8}, {0x1719c418, 0x640dca71}, {0x17293f1f, 0x98060b32}, {0x1739af1f, 0x980e4c25}, {0x17493f26, 0xba068d18}, {0x1759af26, 0xba0ece0b}, {0x17693f2d, 0xdc070efc}, {0x1779af2d, 0xdc0f4fd0}, {0x30000000, 0x0}, {0x30000000, 0x0}, {0x30000000, 0x0}, {0x30000000, 0x0}, {0x30000000, 0x0}, {0x30000000, 0x0}, {0x30000000, 0x0}, {0x30000000, 0x0}},
    {{0x0, 0x0}, {0x2855201, 0x150404c}, {0x28c5003, 0x250c0e5}, {0x2935604, 0x351017e}, {0x2a342a31, 0x2a8141e8}, {0x16aa0711, 0x75000265}, {0xdb1e06, 0x4198313}, {0x16ba2311, 0x750043c5}, {0x220408, 0x502043f}, {0x16ca3f11, 0x75048524}, {0x3696a0a, 0x66a8594}, {0x16da5b11, 0x7504c678}, {0x720c0c, 0x70b06f0}, {0x16ea7711, 0x750907c9}, {0xfa1c0e, 0x91b8846}, {0x16fa9311, 0x7509491a}, {0x170aaf11, 0x750d89d3}, {0x171acb11, 0x750dca7b}, {0x172a461f, 0x98060b41}, {0x173ab61f, 0x980e4c34}, {0x174a4626, 0xba068d27}, {0x175ab626, 0xba0ece1a}, {0x176a462d, 0xdc070f09}, {0x177ab62d, 0xdc0f4fdd}, {0x30000000, 0x0}, {0x30000000, 0x0}, {0x30000000, 0x0}, {0x30000000, 0x0}, {0x30000000, 0x0}, {0x30000000, 0x0}, {0x30000000, 0x0}, {0x30000000, 0x0}},
    {{0x0, 0x0}, {0x2c55a01, 0x158404d}, {0x2cc5803, 0x258c0e6}, {0x2d35e04, 0x359017f}, {0x2a352a32, 0x2b8141ea}, {0x16ab0718, 0x6400027b}, {0x25b4e06, 0x4498324}, {0x16bb2318, 0x640043db}, {0x2224408, 0x5420455}, {0x16cb3f18, 0x6404853a}, {0x1ea3c0a, 0x63a85ad}, {0x16db5b18, 0x6404c68d}, {0x2b2540c, 0x7530707}, {0x16eb7718, 0x640907de}, {0x2fa5c0e, 0x95b885b}, {0x16fb9318, 0x6409492f}, {0x170baf18, 0x640d89dd}, {0x171bcb18, 0x640dca86}, {0x172b4d1f, 0x98060b50}, {0x173bbd1f, 0x980e4c43}, {0x174b4d26, 0xba068d36}, {0x175bbd26, 0xba0ece29}, {0x176b4d2d, 0xdc070f16}, {0x177bbd2d, 0xdc0f4feb}, {0x30000000, 0x0}, {0x30000000, 0x0}, {0x30000000, 0x0}, {0x30000000, 0x0}, {0x30000000, 0x0}, {0x30000000, 0x0}, {0x30000000, 0x0}, {0x30000000, 0x0}},
    {{0x0, 0x0}, {0x3056201, 0x160404e}, {0x30c6003, 0x260c0e7}, {0x3136604, 0x3610180}, {0x2a363131, 0x318141eb}, {0x16ac1c03, 0x31000291}, {0x3db7e06, 0x4798333}, {0x16bc3803, 0x310443f0}, {0x230608, 0x502046b}, {0x16cc5403, 0x31048550}, {0x6b0e0a, 0x60a85c9}, {0x16dc7003, 0x3108c6a2}, {0xf31e0c, 0x81b071f}, {0x16ec8c03, 0x310907f3}, {0xbb160e, 0x913886e}, {0x16fca803, 0x310d493f}, {0x170cc403, 0x310d89e8}, {0x171cd211, 0x750dca90}, {0x172c541f, 0x98060b60}, {0x173cc41f, 0x980e4c52}, {0x174c5426, 0xba068d45}, {0x175cc426, 0xba0ece38}, {0x176c542d, 0xdc070f23}, {0x177cc42d, 0xdc0f4ff8}, {0x30000000, 0x0}, {0x30000000, 0x0}, {0x30000000, 0x0}, {0x30000000, 0x0}, {0x30000000, 0x0}, {0x30000000, 0x0}, {0x30000000, 0x0}, {0x30000000, 0x0}},
    {{0x0, 0x0}, {0x3456a01, 0x1684050}, {0x34c6803, 0x268c0e9}, {0x3536e04, 0x3690182}, {0x2a373132, 0x328141ec}, {0x16ad1c0a, 0x200002a7}, {0x11c2007, 0x421c342}, {0x16bd380a, 0x20044406}, {0x2634e08, 0x54a0483}, {0x16cd540a, 0x20048566}, {0x26b4e0a, 0x64a85de}, {0x16dd700a, 0x2008c6b7}, {0x3736e0c, 0x86b0739}, {0x16ed8c0a, 0x20090808}, {0x2bb560e, 0x9538883}, {0x16fda80a, 0x200d494a}, {0x170dc40a, 0x200d89f2}, {0x171dd218, 0x640dca9b}, {0x172d5b1f, 0x98060b6f}, {0x173dcb1f, 0x980e4c62}, {0x174d5b26, 0xba068d55}, {0x175dcb26, 0xba0ece47}, {0x176d5b2d, 0xdc070f31}, {0x177dcb2d, 0xdc0f5005}, {0x30000000, 0x0}, {0x30000000, 0x0}, {0x30000000, 0x0}, {0x30000000, 0x0}, {0x30000000, 0x0}, {0x30000000, 0x0}, {0x30000000, 0x0}, {0x30000000, 0x0}},
    {{0x0, 0x0}, {0x3857201, 0x1704051}, {0x38c7003, 0x270c0ea}, {0x3937604, 0x3710183}, {0x2a381c33, 0x1e8181f7}, {0x16ae2303, 0x310002bd}, {0x21c4007, 0x441c34d}, {0x16be3f03, 0x3104441c}, {0x640809, 0x50a4499}, {0x16ce5b03, 0x3104857b}, {0x6c080b, 0x70ac5f3}, {0x16de7703, 0x3108c6cc}, {0x134200d, 0x823474c}, {0x16ee9303, 0x3109081d}, {0x7c080f, 0x90bc895}, {0x16feaf03, 0x310d4954}, {0x170ecb03, 0x310d89fd}, {0x171ed911, 0x750dcaa5}, {0x172e621f, 0x98060b7e}, {0x173ed21f, 0x980e4c71}, {0x174e6226, 0xba068d64}, {0x175ed226, 0xba0ece57}, {0x176e622d, 0xdc070f3e}, {0x177ed22d, 0xdc0f5013}, {0x30000000, 0x0}, {0x30000000, 0x0}, {0x30000000, 0x0}, {0x30000000, 0x0}, {0x30000000, 0x0}, {0x30000000, 0x0}, {0x30000000, 0x0}, {0x30000000, 0x0}},
    {{0x0, 0x0}, {0x3c57a01, 0x1784052}, {0x3cc7803, 0x278c0eb}, {0x3d37e04, 0x3790184}, {0x2a391c34, 0x1f818202}, {0x16af230a, 0x200002d3}, {0x39c7007, 0x471c35e}, {0x16bf3f0a, 0x20044432}, {0x3646809, 0x56a44ba}, {0x16cf5b0a, 0x20048590}, {0x26c480b, 0x74ac608}, {0x16df770a, 0x2008c6e1}, {0x2f4580d, 0x85b475e}, {0x16ef930a, 0x20090832}, {0x23c400f, 0x943c8a8}, {0x16ffaf0a, 0x200d495f}, {0x170fcb0a, 0x200d8a07}, {0x171fd918, 0x640dcab0}, {0x172f691f, 0x98060b8d}, {0x173fd91f, 0x980e4c80}, {0x174f6926, 0xba068d73}, {0x175fd926, 0xba0ece66}, {0x176f692d, 0xdc070f4b}, {0x177fd92d, 0xdc0f5020}, {0x30000000, 0x0}, {0x30000000, 0x0}, {0x30000000, 0x0}, {0x30000000, 0x0}, {0x30000000, 0x0}, {0x30000000, 0x0}, {0x30000000, 0x0}, {0x30000000, 0x0}},
    {{0x0, 0x0}, {0x60401, 0x1004054}, {0xd0203, 0x200c0ed}, {0x140005, 0x3014186}, {0x17800004, 0x310001f3}, {0xd71e05, 0x4194264}, {0x17900e12, 0x750042ec}, {0x15d2a07, 0x429c371}, {0x17a02a12, 0x7500844b}, {0x1a53209, 0x63244d3}, {0x17b04612, 0x7504c5a8}, {0xad120b, 0x712c620}, {0x17c06212, 0x750506f9}, {0xf51a0d, 0x81b4773}, {0x17d07e12, 0x7509484a}, {0x3d020f, 0x903c8bd}, {0x17e09a12, 0x7509896a}, {0x17f0b612, 0x750dca13}, {0x18000020, 0x98020abc}, {0x18107020, 0x980a4b9e}, {0x18200027, 0xba028c91}, {0x18307027, 0xba0acd84}, {0x1840002e, 0xdc030e77}, {0x1850702e, 0xdc0b4f5a}, {0x30000000, 0x0}, {0x30000000, 0x0}, {0x30000000, 0x0}, {0x30000000, 0x0}, {0x30000000, 0x0}, {0x30000000, 0x0}, {0x30000000, 0x0}, {0x30000000, 0x0}},
    {{0x0, 0x0}, {0x460c01, 0x1084055}, {0x4d0a03, 0x208c0ee}, {0x540805, 0x3094187}, {0x1781000b, 0x200001fe}, {0x2574e05, 0x4494274}, {0x17910e19, 0x64004302}, {0x2dd5a07, 0x459c381}, {0x17a12a19, 0x64008461}, {0x3a57209, 0x67244e9}, {0x17b14619, 0x6404c5bd}, {0x26d4a0b, 0x74ac632}, {0x17c16219, 0x6405070e}, {0x2b5520d, 0x8534786}, {0x17d17e19, 0x6409485f}, {0x1bd320f, 0x933c8cc}, {0x17e19a19, 0x64098975}, {0x17f1b619, 0x640dca1e}, {0x18010720, 0x98020ac6}, {0x18117720, 0x980a4bad}, {0x18210727, 0xba028ca0}, {0x18317727, 0xba0acd93}, {0x1841072e, 0xdc030e86}, {0x1851772e, 0xdc0b4f68}, {0x30000000, 0x0}, {0x30000000, 0x0}, {0x30000000, 0x0}, {0x30000000, 0x0}, {0x30000000, 0x0}, {0x30000000, 0x0}, {0x30000000, 0x0}, {0x30000000, 0x0}},
    {{0x0, 0x0}, {0x861401, 0x1104056}, {0x8d1203, 0x210c0ef}, {0x941005, 0x3114188}, {0x17820704, 0x31000209}, {0x2a433134, 0x34820286}, {0x17921512, 0x75004318}, {0x5e0c07, 0x509c392}, {0x17a23112, 0x75008477}, {0x1662c09, 0x62a44fc}, {0x17b24d12, 0x7504c5d2}, {0x6e0c0b, 0x70ac647}, {0x17c26912, 0x75050723}, {0x760c0d, 0x80b4798}, {0x17d28512, 0x75094874}, {0x2fd5a0f, 0x95bc8da}, {0x17e2a112, 0x75098980}, {0x17f2bd12, 0x750dca28}, {0x18020e20, 0x98020ad1}, {0x18127e20, 0x980a4bbd}, {0x18220e27, 0xba028caf}, {0x18327e27, 0xba0acda2}, {0x18420e2e, 0xdc030e95}, {0x18527e2e, 0xdc0b4f75}, {0x30000000, 0x0}, {0x30000000, 0x0}, {0x30000000, 0x0}, {0x30000000, 0x0}, {0x30000000, 0x0}, {0x30000000, 0x0}, {0x30000000, 0x0}, {0x30000000, 0x0}},
    {{0x0, 0x0}, {0xc61c01, 0x1184057}, {0xcd1a03, 0x218c0f0}, {0xd41805, 0x3194189}, {0x1783070b, 0x20000214}, {0x1983006, 0x4318298}, {0x17931519, 0x6400432e}, {0x21e4407, 0x541c3a5}, {0x17a33119, 0x6400848d}, {0x3266409, 0x662450f}, {0x17b34d19, 0x6404c5e7}, {0x22e440b, 0x742c65a}, {0xb1120c, 0x71306c8}, {0x17c36919, 0x64050738}, {0x336640d, 0x86347b5}, {0x17d38519, 0x64094889}, {0x1be340f, 0x933c8f7}, {0x17e3a119, 0x6409898a}, {0x17f3bd19, 0x640dca33}, {0x18031520, 0x98020adb}, {0x18138520, 0x980a4bcc}, {0x18231527, 0xba028cbf}, {0x18338527, 0xba0acdb1}, {0x1843152e, 0xdc030ea4}, {0x1853852e, 0xdc0b4f82}, {0x30000000, 0x0}, {0x30000000, 0x0}, {0x30000000, 0x0}, {0x30000000, 0x0}, {0x30000000, 0x0}, {0x30000000, 0x0}, {0x30000000, 0x0}},
    {{0x0, 0x0}, {0x1062401, 0x1204059}, {0x10d2203, 0x220c0f2}, {0x1142005, 0x321418b}, {0x17840e04, 0x3100021f}, {0x3186006, 0x46182a8}, {0x17942a04, 0x31004344}, {0x1f0607, 0x501c3bb}, {0x17a44604, 0x310484a3}, {0xa71609, 0x6124520}, {0x17b46204, 0x3104c5fc}, {0x3ae740b, 0x772c669}, {0x2714a0c, 0x74b06db}, {0x17c47e04, 0x3109074d}, {0xb7160d, 0x81347c5}, {0x17d49a04, 0x3109489e}, {0x33e640f, 0x963c906}, {0x17e4b604, 0x310d8995}, {0x17f4d204, 0x310dca3d}, {0x18041c20, 0x98020ae8}, {0x18148c20, 0x980a4bdb}, {0x18241c27, 0xba028cce}, {0x18348c27, 0xba0acdc1}, {0x18441c2e, 0xdc030eb4}, {0x18548c2e, 0xdc0b4f90}, {0x30000000, 0x0}, {0x30000000, 0x0}, {0x30000000, 0x0}, {0x30000000, 0x0}, {0x30000000, 0x0}, {0x30000000, 0x0}, {0x30000000, 0x0}},
    {{0x0, 0x0}, {0x1462c01, 0x128405a}, {0x14d2a03, 0x228c0f3}, {0x1542805, 0x329418c}, {0x17850e0b, 0x2000022a}, {0x991206, 0x41182b9}, {0x17952a0b, 0x20004359}, {0x1df3e07, 0x539c3cd}, {0x620c08, 0x50a0441}, {0x17a5460b, 0x200484b9}, {0xa8100a, 0x612854c}, {0x17b5620b, 0x2004c611}, {0x2ef5e0b, 0x75ac68c}, {0x17c57e0b, 0x20090762}, {0x2774e0d, 0x84b47d7}, {0x17d59a0b, 0x200948b3}, {0xff1e0f, 0x91bc919}, {0x17e5b60b, 0x200d899f}, {0x17f5d20b, 0x200dca48}, {0x18052320, 0x98020af7}, {0x18159320, 0x980a4bea}, {0x18252327, 0xba028cdd}, {0x18359327, 0xba0acdd0}, {0x1845232e, 0xdc030ec3}, {0x1855932e, 0xdc0b4f9d}, {0x30000000, 0x0}, {0x30000000, 0x0}, {0x30000000, 0x0}, {0x30000000, 0x0}, {0x30000000, 0x0}, {0x30000000, 0x0}, {0x30000000, 0x0}},
    {{0x0, 0x0}, {0x1863401, 0x130405b}, {0x18d3203, 0x230c0f4}, {0x1943005, 0x331418d}, {0x17861504, 0x31000235}, {0x2194206, 0x44182c9}, {0x17963104, 0x3100436f}, {0x39f7607, 0x571c3e1}, {0x2624c08, 0x54a0457}, {0x17a64d04, 0x310484cf}, {0x228400a, 0x642855c}, {0x17b66904, 0x3104c626}, {0x30000c, 0x7030699}, {0x17c68504, 0x31090777}, {0x3b7760d, 0x87347e5}, {0x17d6a104, 0x310948c8}, {0x2bf560f, 0x953c92b}, {0x17e6bd04, 0x310d89aa}, {0x17f6d904, 0x310dca52}, {0x18062a20, 0x98020b06}, {0x18169a20, 0x980a4bf9}, {0x18262a27, 0xba028cec}, {0x18369a27, 0xba0acddf}, {0x18462a2e, 0xdc030ed2}, {0x18569a2e, 0xdc0b4faa}, {0x30000000, 0x0}, {0x30000000, 0x0}, {0x30000000, 0x0}, {0x30000000, 0x0}, {0x30000000, 0x0}, {0x30000000, 0x0}, {0x30000000, 0x0}},
    {{0x0, 0x0}, {0x1c63c01, 0x138405d}, {0x1cd3a03, 0x238c0f6}, {0x1d43805, 0x339418f}, {0x1787150b, 0x20000240}, {0x3d97a06, 0x47982db}, {0x1797310b, 0x20004385}, {0x1602808, 0x52a03f5}, {0x17a74d0b, 0x200484e5}, {0x1a8300a, 0x6328557}, {0x17b7690b, 0x2004c63b}, {0x3af760b, 0x772c694}, {0x17c7850b, 0x2009078c}, {0x2f75e0d, 0x85b47dd}, {0x2ba540e, 0x9538859}, {0x17d7a10b, 0x200948de}, {0x17e7bd0b, 0x200d89b4}, {0x17f7d90b, 0x200dca5d}, {0x18073120, 0x98020b16}, {0x1817a120, 0x980a4c08}, {0x18273127, 0xba028cfb}, {0x1837a127, 0xba0acdee}, {0x1847312e, 0xdc030ee1}, {0x1857a12e, 0xdc0b4fb7}, {0x30000000, 0x0}, {0x30000000, 0x0}, {0x30000000, 0x0}, {0x30000000, 0x0}, {0x30000000, 0x0}, {0x30000000, 0x0}, {0x30000000, 0x0}, {0x30000000, 0x0}},
    {{0x0, 0x0}, {0x2064401, 0x140405e}, {0x20d4203, 0x240c0f7}, {0x2144005, 0x3414190}, {0x17880012, 0x7500024b}, {0x15a2c06, 0x42982ed}, {0x17981c12, 0x7500439b}, {0x3206008, 0x5620408}, {0x17a83812, 0x750484fb}, {0x2e8580a, 0x65a8565}, {0x17b85412, 0x7504c650}, {0xb0100c, 0x713069e}, {0x730e0c, 0x80b071a}, {0x17c87012, 0x750907a1}, {0x39020e, 0x8038814}, {0x17d88c12, 0x750948f3}, {0x17e8a812, 0x750d89bf}, {0x17f8c412, 0x750dca67}, {0x18083820, 0x98060b25}, {0x1818a820, 0x980e4c18}, {0x18283827, 0xba068d0b}, {0x1838a827, 0xba0ecdfd}, {0x1848382e, 0xdc070ef0}, {0x1858a82e, 0xdc0f4fc5}, {0x30000000, 0x0}, {0x30000000, 0x0}, {0x30000000, 0x0}, {0x30000000, 0x0}, {0x30000000, 0x0}, {0x30000000, 0x0}, {0x30000000, 0x0}, {0x30000000, 0x0}},
    {{0x0, 0x0}, {0x2464c01, 0x148405f}, {0x24d4a03, 0x248c0f8}, {0x2544805, 0x3494191}, {0x17890019, 0x64000256}, {0x25a4c06, 0x44982f8}, {0x17991c19, 0x640043b1}, {0xe11a08, 0x51a041b}, {0x17a93819, 0x64048511}, {0x29020a, 0x6028572}, {0x36b6e0a, 0x66a85e8}, {0x17b95419, 0x6404c665}, {0x231420c, 0x74306d8}, {0x17c97019, 0x640907b7}, {0x2b9520e, 0x853882e}, {0x17d98c19, 0x64094908}, {0x17e9a819, 0x640d89c9}, {0x17f9c419, 0x640dca72}, {0x18093f20, 0x98060b34}, {0x1819af20, 0x980e4c27}, {0x18293f27, 0xba068d1a}, {0x1839af27, 0xba0ece0d}, {0x18493f2e, 0xdc070efe}, {0x1859af2e, 0xdc0f4fd2}, {0x30000000, 0x0}, {0x30000000, 0x0}, {0x30000000, 0x0}, {0x30000000, 0x0}, {0x30000000, 0x0}, {0x30000000, 0x0}, {0x30000000, 0x0}, {0x30000000, 0x0}},
    {{0x0, 0x0}, {0x2865401, 0x1504061}, {0x28d5203, 0x250c0fa}, {0x2945005, 0x3514193}, {0x178a0712, 0x75000268}, {0x31a6406, 0x4618300}, {0x179a2312, 0x750043c7}, {0x1a13208, 0x5320423}, {0x1242009, 0x52244a2}, {0x17aa3f12, 0x75048527}, {0x3a9720a, 0x6728597}, {0x17ba5b12, 0x7504c67a}, {0xf21c0c, 0x71b06f5}, {0x17ca7712, 0x750907cc}, {0x13a240e, 0x9238849}, {0x17da9312, 0x7509491d}, {0x17eaaf12, 0x750d89d4}, {0x17facb12, 0x750dca7c}, {0x180a4620, 0x98060b43}, {0x181ab620, 0x980e4c36}, {0x182a4627, 0xba068d29}, {0x183ab627, 0xba0ece1c}, {0x184a462e, 0xdc070f0b}, {0x185ab62e, 0xdc0f4fdf}, {0x30000000, 0x0}, {0x30000000, 0x0}, {0x30000000, 0x0}, {0x30000000, 0x0}, {0x30000000, 0x0}, {0x30000000, 0x0}, {0x30000000, 0x0}, {0x30000000, 0x0}},
    {{0x0, 0x0}, {0x2c65c01, 0x1584062}, {0x2cd5a03, 0x258c0fb}, {0x2d45805, 0x3594194}, {0x178b0719, 0x6400027e}, {0x3da7c06, 0x4798307}, {0x179b2319, 0x640043dd}, {0x2a15208, 0x552042e}, {0x2a45009, 0x55244b2}, {0x17ab3f19, 0x6404853d}, {0x22a440a, 0x64285b1}, {0x17bb5b19, 0x6404c690}, {0x332640c, 0x763070d}, {0x17cb7719, 0x640907e1}, {0x33a640e, 0x963885e}, {0x17db9319, 0x64094932}, {0x17ebaf19, 0x640d89de}, {0x17fbcb19, 0x640dca87}, {0x180b4d20, 0x98060b52}, {0x181bbd20, 0x980e4c45}, {0x182b4d27, 0xba068d38}, {0x183bbd27, 0xba0ece2b}, {0x184b4d2e, 0xdc070f18}, {0x185bbd2e, 0xdc0f4fed}, {0x30000000, 0x0}, {0x30000000, 0x0}, {0x30000000, 0x0}, {0x30000000, 0x0}, {0x30000000, 0x0}, {0x30000000, 0x0}, {0x30000000, 0x0}, {0x30000000, 0x0}},
    {{0x0, 0x0}, {0x3066401, 0x1604063}, {0x30d6203, 0x260c0fc}, {0x3146005, 0x3614195}, {0x2a3a2333, 0x2581820d}, {0x178c1c04, 0x31000294}, {0x2a4b3f34, 0x42828336}, {0x179c3804, 0x310443f3}, {0x630e08, 0x50a046d}, {0x17ac5404, 0x31048553}, {0xab160a, 0x61285cb}, {0x17bc7004, 0x3108c6a5}, {0x1732e0c, 0x82b0724}, {0x17cc8c04, 0x310907f6}, {0xfb1e0e, 0x91b8870}, {0x17dca804, 0x310d4940}, {0x17ecc404, 0x310d89e9}, {0x17fcd212, 0x750dca91}, {0x180c5420, 0x98060b62}, {0x181cc420, 0x980e4c54}, {0x182c5427, 0xba068d47}, {0x183cc427, 0xba0ece3a}, {0x184c542e, 0xdc070f25}, {0x185cc42e, 0xdc0f4ffa}, {0x30000000, 0x0}, {0x30000000, 0x0}, {0x30000000, 0x0}, {0x30000000, 0x0}, {0x30000000, 0x0}, {0x30000000, 0x0}, {0x30000000, 0x0}, {0x30000000, 0x0}},
    {{0x0, 0x0}, {0x3466c01, 0x1684065}, {0x34d6a03, 0x268c0fe}, {0x3546805, 0x3694197}, {0x2a3b2334, 0x26818218}, {0x178d1c0b, 0x200002aa}, {0x15c2807, 0x429c345}, {0x179d380b, 0x20044409}, {0x2a35608, 0x5520486}, {0x17ad540b, 0x20048569}, {0x2ab560a, 0x65285e0}, {0x17bd700b, 0x2008c6ba}, {0x3b3760c, 0x873073c}, {0x17cd8c0b, 0x2009080b}, {0x2fb5e0e, 0x95b8885}, {0x17dda80b, 0x200d494b}, {0x17edc40b, 0x200d89f3}, {0x17fdd219, 0x640dca9c}, {0x180d5b20, 0x98060b71}, {0x181dcb20, 0x980e4c64}, {0x182d5b27, 0xba068d56}, {0x183dcb27, 0xba0ece49}, {0x184d5b2e, 0xdc070f33}, {0x185dcb2e, 0xdc0f5007}, {0x30000000, 0x0}, {0x30000000, 0x0}, {0x30000000, 0x0}, {0x30000000, 0x0}, {0x30000000, 0x0}, {0x30000000, 0x0}, {0x30000000, 0x0}, {0x30000000, 0x0}},
    {{0x0, 0x0}, {0x3867401, 0x1704066}, {0x38d7203, 0x270c0ff}, {0x3947005, 0x3714198}, {0x2a3c3831, 0x3881c223}, {0x178e2304, 0x310002c0}, {0x25c4807, 0x449c350}, {0x179e3f04, 0x3104441f}, {0xa41009, 0x512449c}, {0x17ae5b04, 0x3104857e}, {0xac100b, 0x712c5f5}, {0x17be7704, 0x3108c6cf}, {0x174280d, 0x82b474f}, {0x17ce9304, 0x31090820}, {0xbc100f, 0x913c898}, {0x17deaf04, 0x310d4955}, {0x17eecb04, 0x310d89fe}, {0x17fed912, 0x750dcaa7}, {0x180e6220, 0x98060b80}, {0x181ed220, 0x980e4c73}, {0x182e6227, 0xba068d66}, {0x183ed227, 0xba0ece58}, {0x184e622e, 0xdc070f40}, {0x185ed22e, 0xdc0f5014}, {0x30000000, 0x0}, {0x30000000, 0x0}, {0x30000000, 0x0}, {0x30000000, 0x0}, {0x30000000, 0x0}, {0x30000000, 0x0}, {0x30000000, 0x0}, {0x30000000, 0x0}},
    {{0x0, 0x0}, {0x3c67c01, 0x1784067}, {0x3cd7a03, 0x278c100}, {0x3d47805, 0x3794199}, {0x2a3d3832, 0x3981c22e}, {0x178f230b, 0x200002d6}, {0x3dc7807, 0x479c35f}, {0x179f3f0b, 0x20044435}, {0x3a47009, 0x57244bd}, {0x17af5b0b, 0x20048593}, {0x2ac500b, 0x752c60b}, {0x17bf770b, 0x2008c6e4}, {0x334600d, 0x8634761}, {0x17cf930b, 0x20090835}, {0x27c480f, 0x94bc8aa}, {0x17dfaf0b, 0x200d4960}, {0x17efcb0b, 0x200d8a09}, {0x17ffd919, 0x640dcab1}, {0x180f6920, 0x98060b8f}, {0x181fd920, 0x980e4c82}, {0x182f6927, 0xba068d75}, {0x183fd927, 0xba0ece68}, {0x184f692e, 0xdc070f4d}, {0x185fd92e, 0xdc0f5022}, {0x30000000, 0x0}, {0x30000000, 0x0}, {0x30000000, 0x0}, {0x30000000, 0x0}, {0x30000000, 0x0}, {0x30000000, 0x0}, {0x30000000, 0x0}, {0x30000000, 0x0}},
    {{0x0, 0x0}, {0x70601, 0x1004069}, {0xe0403, 0x200c102}, {0x150205, 0x301419b}, {0x18600005, 0x310001f5}, {0x1172605, 0x4214267}, {0x18700e13, 0x750042ee}, {0x19d3207, 0x431c374}, {0x18802a13, 0x7500844e}, {0x1e53a09, 0x63a44d4}, {0x18904613, 0x7504c5aa}, {0xed1a0b, 0x71ac622}, {0x18a06213, 0x750506fc}, {0x135220d, 0x8234776}, {0x18b07e13, 0x7509484d}, {0x7d0a0f, 0x90bc8bf}, {0x18c09a13, 0x7509896c}, {0x18d0b613, 0x750dca14}, {0x18e00021, 0x98020abd}, {0x18f07021, 0x980a4ba0}, {0x19000028, 0xba028c93}, {0x19107028, 0xba0acd86}, {0x1920002f, 0xdc030e79}, {0x1930702f, 0xdc0b4f5c}, {0x30000000, 0x0}, {0x30000000, 0x0}, {0x30000000, 0x0}, {0x30000000, 0x0}, {0x30000000, 0x0}, {0x30000000, 0x0}, {0x30000000, 0x0}, {0x30000000, 0x0}},
    {{0x400800, 0x80000}, {0x470e01, 0x108406a}, {0x4e0c03, 0x208c103}, {0x550a05, 0x309419c}, {0x1861000c, 0x20000200}, {0x2975605, 0x4514277}, {0x18710e1a, 0x64004304}, {0x31d6207, 0x461c384}, {0x18812a1a, 0x64008464}, {0x3e57a09, 0x67a44ea}, {0x1891461a, 0x6404c5bf}, {0x2ad520b, 0x752c635}, {0x18a1621a, 0x64050711}, {0x2f55a0d, 0x85b4788}, {0x18b17e1a, 0x64094862}, {0x1fd3a0f, 0x93bc8ce}, {0x18c19a1a, 0x64098976}, {0x18d1b61a, 0x640dca1f}, {0x18e10721, 0x98020ac7}, {0x18f17721, 0x980a4baf}, {0x19010728, 0xba028ca2}, {0x19117728, 0xba0acd95}, {0x1921072f, 0xdc030e88}, {0x1931772f, 0xdc0b4f6a}, {0x30000000, 0x0}, {0x30000000, 0x0}, {0x30000000, 0x0}, {0x30000000, 0x0}, {0x30000000, 0x0}, {0x30000000, 0x0}, {0x30000000, 0x0}, {0x30000000, 0x0}},
    {{0x801000, 0x100000}, {0x871601, 0x110406b}, {0x8e1403, 0x210c104}, {0x951205, 0x311419d}, {0x18620705, 0x3100020b}, {0x180006, 0x4018287}, {0x18721513, 0x7500431a}, {0x9e1407, 0x511c395}, {0x18823113, 0x7500847a}, {0x1a63409, 0x63244ff}, {0x18924d13, 0x7504c5d5}, {0xae140b, 0x712c64a}, {0x18a26913, 0x75050726}, {0xb6140d, 0x813479b}, {0x18b28513, 0x75094877}, {0x33d620f, 0x963c8dc}, {0x18c2a113, 0x75098981}, {0x18d2bd13, 0x750dca29}, {0x18e20e21, 0x98020ad2}, {0x18f27e21, 0x980a4bbe}, {0x19020e28, 0xba028cb1}, {0x19127e28, 0xba0acda4}, {0x19220e2f, 0xdc030e97}, {0x19327e2f, 0xdc0b4f77}, {0x30000000, 0x0}, {0x30000000, 0x0}, {0x30000000, 0x0}, {0x30000000, 0x0}, {0x30000000, 0x0}, {0x30000000, 0x0}, {0x30000000, 0x0}, {0x30000000, 0x0}},
    {{0xc01800, 0x180000}, {0xc71e01, 0x118406c}, {0xce1c03, 0x218c105}, {0xd51a05, 0x319419e}, {0x1863070c, 0x20000216}, {0x1d83806, 0x4398299}, {0x1873151a, 0x64004330}, {0x25e4c07, 0x549c3a8}, {0x1883311a, 0x64008490}, {0x3666c09, 0x66a4512}, {0x18934d1a, 0x6404c5ea}, {0x26e4c0b, 0x74ac65c}, {0x18a3691a, 0x6405073b}, {0x1b6340d, 0x83347a5}, {0xb9120e, 0x8138819}, {0x18b3851a, 0x6409488c}, {0x1fe3c0f, 0x93bc8f8}, {0x18c3a11a, 0x6409898b}, {0x18d3bd1a, 0x640dca34}, {0x18e31521, 0x98020add}, {0x18f38521, 0x980a4bce}, {0x19031528, 0xba028cc1}, {0x19138528, 0xba0acdb3}, {0x1923152f, 0xdc030ea6}, {0x1933852f, 0xdc0b4f84}, {0x30000000, 0x0}, {0x30000000, 0x0}, {0x30000000, 0x0}, {0x30000000, 0x0}, {0x30000000, 0x0}, {0x30000000, 0x0}, {0x30000000, 0x0}},
    {{0x1002000, 0x200000}, {0x1072601, 0x120406e}, {0x10e2403, 0x220c107}, {0x1152205, 0x32141a0}, {0x18640e05, 0x31000220}, {0x3586806, 0x46982ab}, {0x18742a05, 0x31004346}, {0x5f0e07, 0x509c3be}, {0x18844605, 0x310484a6}, {0xe71e09, 0x61a4523}, {0x18946205, 0x3104c5ff}, {0x3ee7c0b, 0x77ac66b}, {0x2b1520c, 0x75306dd}, {0x18a47e05, 0x31090750}, {0x137260d, 0x82347ca}, {0x18b49a05, 0x310948a1}, {0x37e6c0f, 0x96bc909}, {0x18c4b605, 0x310d8996}, {0x18d4d205, 0x310dca3f}, {0x18e41c21, 0x98020aea}, {0x18f48c21, 0x980a4bdd}, {0x19041c28, 0xba028cd0}, {0x19148c28, 0xba0acdc3}, {0x19241c2f, 0xdc030eb5}, {0x19348c2f, 0xdc0b4f92}, {0x30000000, 0x0}, {0x30000000, 0x0}, {0x30000000, 0x0}, {0x30000000, 0x0}, {0x30000000, 0x0}, {0x30000000, 0x0}, {0x30000000, 0x0}},
    {{0x1402800, 0x280000}, {0x1472e01, 0x128406f}, {0x14e2c03, 0x228c108}, {0x1552a05, 0x32941a1}, {0x18650e0c, 0x2000022b}, {0xd91a06, 0x41982bc}, {0x18752a0c, 0x2000435c}, {0x21f4607, 0x541c3d1}, {0xe21c08, 0x51a0447}, {0x1885460c, 0x200484bc}, {0x128200a, 0x6228551}, {0x1895620c, 0x2004c614}, {0x36f6e0b, 0x76ac691}, {0x18a57e0c, 0x20090765}, {0x2b7560d, 0x85347da}, {0x18b59a0c, 0x200948b6}, {0x13f260f, 0x923c91b}, {0x18c5b60c, 0x200d89a0}, {0x18d5d20c, 0x200dca49}, {0x18e52321, 0x98020af9}, {0x18f59321, 0x980a4bec}, {0x19052328, 0xba028cdf}, {0x19159328, 0xba0acdd2}, {0x1925232f, 0xdc030ec5}, {0x1935932f, 0xdc0b4f9f}, {0x30000000, 0x0}, {0x30000000, 0x0}, {0x30000000, 0x0}, {0x30000000, 0x0}, {0x30000000, 0x0}, {0x30000000, 0x0}, {0x30000000, 0x0}},
    {{0x1803000, 0x300000}, {0x1873601, 0x1304070}, {0x18e3403, 0x230c109}, {0x1953205, 0x33141a2}, {0x18661505, 0x31000236}, {0x2594a06, 0x44982cc}, {0x18763105, 0x31004372}, {0x3df7e07, 0x579c3e3}, {0x2a25408, 0x552045a}, {0x18864d05, 0x310484d2}, {0x268480a, 0x64a855f}, {0x18966905, 0x3104c629}, {0x70080c, 0x70b069b}, {0x18a68505, 0x3109077a}, {0x3f77e0d, 0x87b47e6}, {0x18b6a105, 0x310948cb}, {0x2ff5e0f, 0x95bc92e}, {0x18c6bd05, 0x310d89ab}, {0x18d6d905, 0x310dca54}, {0x18e62a21, 0x98020b08}, {0x18f69a21, 0x980a4bfb}, {0x19062a28, 0xba028cee}, {0x19169a28, 0xba0acde1}, {0x19262a2f, 0xdc030ed4}, {0x19369a2f, 0xdc0b4fac}, {0x30000000, 0x0}, {0x30000000, 0x0}, {0x30000000, 0x0}, {0x30000000, 0x0}, {0x30000000, 0x0}, {0x30000000, 0x0}, {0x30000000, 0x0}},
    {{0x1c03800, 0x380000}, {0x1c73e01, 0x1384072}, {0x1ce3c03, 0x238c10b}, {0x1d53a05, 0x33941a4}, {0x1867150c, 0x20000241}, {0x2a474d32, 0x4e8242de}, {0x1877310c, 0x20004388}, {0x1a03008, 0x53203f7}, {0xa31608, 0x5120470}, {0x18874d0c, 0x200484e8}, {0x3e8780a, 0x67a856e}, {0x1897690c, 0x2004c63e}, {0x230400c, 0x74306ae}, {0x18a7850c, 0x2009078f}, {0x1f8380e, 0x83b87fb}, {0x18b7a10c, 0x200948e0}, {0x18c7bd0c, 0x200d89b6}, {0x18d7d90c, 0x200dca5e}, {0x18e73121, 0x98020b18}, {0x18f7a121, 0x980a4c0a}, {0x19073128, 0xba028cfd}, {0x1917a128, 0xba0acdf0}, {0x1927312f, 0xdc030ee3}, {0x1937a12f, 0xdc0b4fb9}, {0x30000000, 0x0}, {0x30000000, 0x0}, {0x30000000, 0x0}, {0x30000000, 0x0}, {0x30000000, 0x0}, {0x30000000, 0x0}, {0x30000000, 0x0}, {0x30000000, 0x0}},
    {{0x2004000, 0x400000}, {0x2074601, 0x1404073}, {0x20e4403, 0x240c10c}, {0x2154205, 0x34141a5}, {0x18680013, 0x7500024c}, {0x19a3406, 0x43182f0}, {0x18781c13, 0x7500439e}, {0x3606808, 0x56a040b}, {0x18883813, 0x750484fe}, {0x328600a, 0x6628567}, {0x18985413, 0x7504c653}, {0x130200c, 0x72306a3}, {0x133260c, 0x8230722}, {0x18a87013, 0x750907a4}, {0x790a0e, 0x80b8817}, {0x18b88c13, 0x750948f5}, {0x18c8a813, 0x750d89c0}, {0x18d8c413, 0x750dca69}, {0x18e83821, 0x98060b27}, {0x18f8a821, 0x980e4c1a}, {0x19083828, 0xba068d0c}, {0x1918a828, 0xba0ecdff}, {0x1928382f, 0xdc070ef2}, {0x1938a82f, 0xdc0f4fc7}, {0x30000000, 0x0}, {0x30000000, 0x0}, {0x30000000, 0x0}, {0x30000000, 0x0}, {0x30000000, 0x0}, {0x30000000, 0x0}, {0x30000000, 0x0}, {0x30000000, 0x0}},
    {{0x2404800, 0x480000}, {0x2474e01, 0x1484074}, {0x24e4c03, 0x248c10d}, {0x2554a05, 0x34941a6}, {0x1869001a, 0x64000257}, {0x29a5406, 0x45182fb}, {0x18791c1a, 0x640043b4}, {0x1212208, 0x522041e}, {0x1889381a, 0x64048514}, {0xa9120a, 0x6128577}, {0x1899541a, 0x6404c668}, {0x2b0500c, 0x75306b3}, {0x2f35e0c, 0x85b0734}, {0x18a9701a, 0x640907b9}, {0x339620e, 0x8638834}, {0x18b98c1a, 0x6409490a}, {0x18c9a81a, 0x640d89cb}, {0x18d9c41a, 0x640dca73}, {0x18e93f21, 0x98060b36}, {0x18f9af21, 0x980e4c29}, {0x19093f28, 0xba068d1c}, {0x1919af28, 0xba0ece0e}, {0x19293f2f, 0xdc070eff}, {0x1939af2f, 0xdc0f4fd4}, {0x30000000, 0x0}, {0x30000000, 0x0}, {0x30000000, 0x0}, {0x30000000, 0x0}, {0x30000000, 0x0}, {0x30000000, 0x0}, {0x30000000, 0x0}, {0x30000000, 0x0}},
    {{0x2805000, 0x500000}, {0x2875601, 0x1504076}, {0x28e5403, 0x250c10f}, {0x2955205, 0x35141a8}, {0x186a0713, 0x7500026b}, {0x35a6c06, 0x4698303}, {0x187a2313, 0x750043ca}, {0x1e13a08, 0x53a0425}, {0x1642809, 0x52a44a4}, {0x188a3f13, 0x75048529}, {0x2a040a, 0x602859c}, {0x189a5b13, 0x7504c67d}, {0x132240c, 0x72306f8}, {0x18aa7713, 0x750907ce}, {0x17a2c0e, 0x92b884b}, {0x18ba9313, 0x7509491f}, {0x18caaf13, 0x750d89d5}, {0x18dacb13, 0x750dca7e}, {0x18ea4621, 0x98060b45}, {0x18fab621, 0x980e4c38}, {0x190a4628, 0xba068d2b}, {0x191ab628, 0xba0ece1e}, {0x192a462f, 0xdc070f0d}, {0x193ab62f, 0xdc0f4fe1}, {0x30000000, 0x0}, {0x30000000, 0x0}, {0x30000000, 0x0}, {0x30000000, 0x0}, {0x30000000, 0x0}, {0x30000000, 0x0}, {0x30000000, 0x0}, {0x30000000, 0x0}},
    {{0x2c05800, 0x580000}, {0x2c75e01, 0x1584077}, {0x2ce5c03, 0x258c110}, {0x2d55a05, 0x35941a9}, {0x186b071a, 0x64000281}, {0x2a493834, 0x3b82830a}, {0x187b231a, 0x640043e0}, {0x2e15a08, 0x55a0431}, {0x3246009, 0x56244b8}, {0x188b3f1a, 0x6404853f}, {0x26a4c0a, 0x64a85b4}, {0x189b5b1a, 0x6404c692}, {0x3726c0c, 0x76b070f}, {0x18ab771a, 0x640907e3}, {0x37a6c0e, 0x96b8860}, {0x18bb931a, 0x64094934}, {0x18cbaf1a, 0x640d89e0}, {0x18dbcb1a, 0x640dca88}, {0x18eb4d21, 0x98060b54}, {0x18fbbd21, 0x980e4c47}, {0x190b4d28, 0xba068d3a}, {0x191bbd28, 0xba0ece2d}, {0x192b4d2f, 0xdc070f1a}, {0x193bbd2f, 0xdc0f4fee}, {0x30000000, 0x0}, {0x30000000, 0x0}, {0x30000000, 0x0}, {0x30000000, 0x0}, {0x30000000, 0x0}, {0x30000000, 0x0}, {0x30000000, 0x0}, {0x30000000, 0x0}},
    {{0x3006000, 0x600000}, {0x3076601, 0x1604078}, {0x30e6403, 0x260c111}, {0x3156205, 0x36141aa}, {0x186c1c05, 0x31000297}, {0x15b2e06, 0x4298319}, {0x187c3805, 0x310443f6}, {0xa21408, 0x5120444}, {0xe51a09, 0x61a44cb}, {0x188c5405, 0x31048555}, {0xeb1e0a, 0x61a85ce}, {0x189c7005, 0x3108c6a7}, {0x1b3360c, 0x8330727}, {0x18ac8c05, 0x310907f8}, {0x13b260e, 0x9238873}, {0x18bca805, 0x310d4942}, {0x18ccc405, 0x310d89ea}, {0x18dcd213, 0x750dca93}, {0x18ec5421, 0x98060b63}, {0x18fcc421, 0x980e4c56}, {0x190c5428, 0xba068d49}, {0x191cc428, 0xba0ece3c}, {0x192c542f, 0xdc070f27}, {0x193cc42f, 0xdc0f4ffc}, {0x30000000, 0x0}, {0x30000000, 0x0}, {0x30000000, 0x0}, {0x30000000, 0x0}, {0x30000000, 0x0}, {0x30000000, 0x0}, {0x30000000, 0x0}, {0x30000000, 0x0}},
    {{0x3406800, 0x680000}, {0x3476e01, 0x168407a}, {0x34e6c03, 0x268c113}, {0x3556a05, 0x36941ac}, {0x186d1c0c, 0x200002ad}, {0x29b5606, 0x4518327}, {0x187d380c, 0x2004440c}, {0x2e25c08, 0x55a045d}, {0x3256209, 0x66244e3}, {0x188d540c, 0x2004856b}, {0x2eb5e0a, 0x65a85e3}, {0x189d700c, 0x2008c6bc}, {0x3f37e0c, 0x87b073d}, {0x18ad8c0c, 0x2009080d}, {0x33b660e, 0x9638888}, {0x18bda80c, 0x200d494c}, {0x18cdc40c, 0x200d89f5}, {0x18ddd21a, 0x640dca9d}, {0x18ed5b21, 0x98060b73}, {0x18fdcb21, 0x980e4c65}, {0x190d5b28, 0xba068d58}, {0x191dcb28, 0xba0ece4b}, {0x192d5b2f, 0xdc070f35}, {0x193dcb2f, 0xdc0f5009}, {0x30000000, 0x0}, {0x30000000, 0x0}, {0x30000000, 0x0}, {0x30000000, 0x0}, {0x30000000, 0x0}, {0x30000000, 0x0}, {0x30000000, 0x0}, {0x30000000, 0x0}},
    {{0x3807000, 0x700000}, {0x3877601, 0x170407b}, {0x38e7403, 0x270c114}, {0x3957205, 0x37141ad}, {0x186e2305, 0x310002c2}, {0x1c0007, 0x401c337}, {0x2de5c07, 0x559c3ad}, {0x187e3f05, 0x31044422}, {0xe41809, 0x51a449f}, {0x188e5b05, 0x31048580}, {0xec180b, 0x71ac5f8}, {0x189e7705, 0x3108c6d1}, {0x1b4300d, 0x8334751}, {0x18ae9305, 0x31090823}, {0xfc180f, 0x91bc89a}, {0x18beaf05, 0x310d4957}, {0x18cecb05, 0x310d89ff}, {0x18ded913, 0x750dcaa8}, {0x18ee6221, 0x98060b82}, {0x18fed221, 0x980e4c75}, {0x190e6228, 0xba068d67}, {0x191ed228, 0xba0ece5a}, {0x192e622f, 0xdc070f42}, {0x193ed22f, 0xdc0f5016}, {0x30000000, 0x0}, {0x30000000, 0x0}, {0x30000000, 0x0}, {0x30000000, 0x0}, {0x30000000, 0x0}, {0x30000000, 0x0}, {0x30000000, 0x0}, {0x30000000, 0x0}},
    {{0x3c07800, 0x780000}, {0x3c77e01, 0x178407c}, {0x3ce7c03, 0x278c115}, {0x3d57a05, 0x37941ae}, {0x2a3e3f31, 0x3f81c239}, {0x186f230c, 0x200002d8}, {0x2a4d5432, 0x5582c362}, {0x187f3f0c, 0x20044438}, {0x3e47809, 0x57a44be}, {0x188f5b0c, 0x20048595}, {0x2ec580b, 0x75ac60d}, {0x189f770c, 0x2008c6e6}, {0x374680d, 0x86b4764}, {0x18af930c, 0x20090838}, {0x2bc500f, 0x953c8ad}, {0x18bfaf0c, 0x200d4961}, {0x18cfcb0c, 0x200d8a0a}, {0x18dfd91a, 0x640dcab2}, {0x18ef6921, 0x98060b91}, {0x18ffd921, 0x980e4c84}, {0x190f6928, 0xba068d77}, {0x191fd928, 0xba0ece6a}, {0x192f692f, 0xdc070f4f}, {0x193fd92f, 0xdc0f5024}, {0x30000000, 0x0}, {0x30000000, 0x0}, {0x30000000, 0x0}, {0x30000000, 0x0}, {0x30000000, 0x0}, {0x30000000, 0x0}, {0x30000000, 0x0}, {0x30000000, 0x0}},
    {{0x10200, 0x0}, {0x80002, 0x100807e}, {0xf0603, 0x200c117}, {0x160405, 0x30141b0}, {0x19400006, 0x310001f6}, {0x1572e05, 0x4294269}, {0x19500e14, 0x750042f3}, {0x1dd3a07, 0x439c375}, {0x19602a14, 0x75008452}, {0x2254209, 0x64244d8}, {0x19704614, 0x7504c5ae}, {0x12d220b, 0x722c625}, {0x19806214, 0x75050700}, {0x1752a0d, 0x82b4779}, {0x19907e14, 0x75094851}, {0xbd120f, 0x913c8c2}, {0x19a09a14, 0x7509896d}, {0x19b0b614, 0x750dca16}, {0x19c00022, 0x98020abe}, {0x19d07022, 0x980a4ba2}, {0x19e00029, 0xba028c95}, {0x19f07029, 0xba0acd88}, {0x1a000030, 0xdc030e7b}, {0x1a107030, 0xdc0b4f5e}, {0x30000000, 0x0}, {0x30000000, 0x0}, {0x30000000, 0x0}, {0x30000000, 0x0}, {0x30000000, 0x0}, {0x30000000, 0x0}, {0x30000000, 0x0}, {0x30000000, 0x0}},
    {{0x410a00, 0x80000}, {0x480802, 0x108807f}, {0x4f0e03, 0x208c118}, {0x560c05, 0x30941b1}, {0x1941000d, 0x20000201}, {0x2d75e05, 0x459427a}, {0x19510e1b, 0x64004308}, {0x35d6a07, 0x469c387}, {0x19612a1b, 0x64008468}, {0x260409, 0x60244ee}, {0x1971461b, 0x6404c5c3}, {0x32d620b, 0x762c63a}, {0x1981621b, 0x64050715}, {0x335620d, 0x863478b}, {0x19917e1b, 0x64094866}, {0x23d420f, 0x943c8d2}, {0x19a19a1b, 0x64098978}, {0x19b1b61b, 0x640dca20}, {0x19c10722, 0x98020ac9}, {0x19d17722, 0x980a4bb1}, {0x19e10729, 0xba028ca4}, {0x19f17729, 0xba0acd97}, {0x1a010730, 0xdc030e8a}, {0x1a117730, 0xdc0b4f6c}, {0x30000000, 0x0}, {0x30000000, 0x0}, {0x30000000, 0x0}, {0x30000000, 0x0}, {0x30000000, 0x0}, {0x30000000, 0x0}, {0x30000000, 0x0}, {0x30000000, 0x0}},
    {{0x811200, 0x100000}, {0x881002, 0x1108080}, {0x8f1603, 0x210c119}, {0x961405, 0x31141b2}, {0x19420706, 0x3100020c}, {0x580806, 0x409828a}, {0x19521514, 0x7500431e}, {0xde1c07, 0x519c397}, {0x19623114, 0x7500847e}, {0x1e63c09, 0x63a4500}, {0x19724d14, 0x7504c5d9}, {0xee1c0b, 0x71ac64c}, {0x19826914, 0x7505072a}, {0xf61c0d, 0x81b479e}, {0x19928514, 0x7509487b}, {0x37d6a0f, 0x96bc8df}, {0x19a2a114, 0x75098982}, {0x19b2bd14, 0x750dca2b}, {0x19c20e22, 0x98020ad3}, {0x19d27e22, 0x980a4bc0}, {0x19e20e29, 0xba028cb3}, {0x19f27e29, 0xba0acda6}, {0x1a020e30, 0xdc030e99}, {0x1a127e30, 0xdc0b4f79}, {0x30000000, 0x0}, {0x30000000, 0x0}, {0x30000000, 0x0}, {0x30000000, 0x0}, {0x30000000, 0x0}, {0x30000000, 0x0}, {0x30000000, 0x0}, {0x30000000, 0x0}},
    {{0xc11a00, 0x180000}, {0xc81802, 0x1188081}, {0xcf1e03, 0x218c11a}, {0xd61c05, 0x31941b3}, {0x1943070d, 0x20000217}, {0x2a444631, 0x4682429c}, {0x1953151b, 0x64004334}, {0x29e5407, 0x551c3aa}, {0x1963311b, 0x64008494}, {0x3a67409, 0x6724515}, {0x19734d1b, 0x6404c5ee}, {0x2ae540b, 0x752c65f}, {0x1983691b, 0x6405073f}, {0x1f63c0d, 0x83b47a7}, {0x1993851b, 0x64094890}, {0x7e0c0f, 0x90bc8e9}, {0x19a3a11b, 0x6409898d}, {0x19b3bd1b, 0x640dca35}, {0x19c31522, 0x98020ade}, {0x19d38522, 0x980a4bd0}, {0x19e31529, 0xba028cc2}, {0x19f38529, 0xba0acdb5}, {0x1a031530, 0xdc030ea8}, {0x1a138530, 0xdc0b4f86}, {0x30000000, 0x0}, {0x30000000, 0x0}, {0x30000000, 0x0}, {0x30000000, 0x0}, {0x30000000, 0x0}, {0x30000000, 0x0}, {0x30000000, 0x0}, {0x30000000, 0x0}},
    {{0x1012200, 0x200000}, {0x1082002, 0x1208083}, {0x10f2603, 0x220c11c}, {0x1162405, 0x32141b5}, {0x19440e06, 0x31000222}, {0x3987006, 0x47182ae}, {0x19542a06, 0x3100434a}, {0x9f1607, 0x511c3c0}, {0x19644606, 0x310484aa}, {0x1272609, 0x6224525}, {0x19746206, 0x3104c603}, {0x2f060b, 0x702c66f}, {0x2f15a0c, 0x75b06e0}, {0x19847e06, 0x31090754}, {0x1772e0d, 0x82b47cd}, {0x19949a06, 0x310948a5}, {0x3be740f, 0x973c90c}, {0x19a4b606, 0x310d8997}, {0x19b4d206, 0x310dca40}, {0x19c41c22, 0x98020aec}, {0x19d48c22, 0x980a4bdf}, {0x19e41c29, 0xba028cd2}, {0x19f48c29, 0xba0acdc4}, {0x1a041c30, 0xdc030eb7}, {0x1a148c30, 0xdc0b4f93}, {0x30000000, 0x0}, {0x30000000, 0x0}, {0x30000000, 0x0}, {0x30000000, 0x0}, {0x30000000, 0x0}, {0x30000000, 0x0}, {0x30000000, 0x0}},
    {{0x1412a00, 0x280000}, {0x1482802, 0x1288084}, {0x14f2e03, 0x228c11d}, {0x1562c05, 0x32941b6}, {0x19450e0d, 0x2000022d}, {0x1192206, 0x42182be}, {0x19552a0d, 0x20004360}, {0x25f4e07, 0x549c3d4}, {0x1965460d, 0x200484c0}, {0x2674e09, 0x64a4533}, {0xea1c0a, 0x61a85a4}, {0x1975620d, 0x2004c618}, {0x3ef7e0b, 0x77ac695}, {0x19857e0d, 0x20090769}, {0x337660d, 0x86347df}, {0x19959a0d, 0x200948ba}, {0x17f2e0f, 0x92bc91e}, {0x19a5b60d, 0x200d89a2}, {0x19b5d20d, 0x200dca4a}, {0x19c52322, 0x98020afb}, {0x19d59322, 0x980a4bee}, {0x19e52329, 0xba028ce1}, {0x19f59329, 0xba0acdd4}, {0x1a052330, 0xdc030ec6}, {0x1a159330, 0xdc0b4fa1}, {0x30000000, 0x0}, {0x30000000, 0x0}, {0x30000000, 0x0}, {0x30000000, 0x0}, {0x30000000, 0x0}, {0x30000000, 0x0}, {0x30000000, 0x0}},
    {{0x1813200, 0x300000}, {0x1883002, 0x1308085}, {0x18f3603, 0x230c11e}, {0x1963405, 0x33141b7}, {0x19461506, 0x31000238}, {0x2995206, 0x45182cf}, {0x19563106, 0x31004376}, {0x200008, 0x50203e7}, {0x19664d06, 0x310484d6}, {0x3e77e09, 0x67a4542}, {0x2aa540a, 0x65285b6}, {0x19766906, 0x3104c62d}, {0xf0180c, 0x71b06a1}, {0x19868506, 0x3109077e}, {0x78080e, 0x80b87ed}, {0x1996a106, 0x310948cf}, {0x33f660f, 0x963c931}, {0x19a6bd06, 0x310d89ac}, {0x19b6d906, 0x310dca55}, {0x19c62a22, 0x98020b0a}, {0x19d69a22, 0x980a4bfd}, {0x19e62a29, 0xba028cf0}, {0x19f69a29, 0xba0acde3}, {0x1a062a30, 0xdc030ed6}, {0x1a169a30, 0xdc0b4fae}, {0x30000000, 0x0}, {0x30000000, 0x0}, {0x30000000, 0x0}, {0x30000000, 0x0}, {0x30000000, 0x0}, {0x30000000, 0x0}, {0x30000000, 0x0}},
    {{0x1c13a00, 0x380000}, {0x1c83802, 0x1388087}, {0x1cf3e03, 0x238c120}, {0x1d63c05, 0x33941b9}, {0x1947150d, 0x20000243}, {0x1a0406, 0x40182df}, {0x1957310d, 0x2000438c}, {0x1e03808, 0x53a03f9}, {0xe31e08, 0x51a0473}, {0x19674d0d, 0x200484ec}, {0x690a0a, 0x60a8574}, {0x1977690d, 0x2004c642}, {0x270480c, 0x74b06b0}, {0x1987850d, 0x20090793}, {0x278480e, 0x84b8802}, {0x1997a10d, 0x200948e4}, {0x19a7bd0d, 0x200d89b7}, {0x19b7d90d, 0x200dca5f}, {0x19c73122, 0x98020b19}, {0x19d7a122, 0x980a4c0c}, {0x19e73129, 0xba028cff}, {0x19f7a129, 0xba0acdf2}, {0x1a073130, 0xdc030ee5}, {0x1a17a130, 0xdc0b4fbb}, {0x30000000, 0x0}, {0x30000000, 0x0}, {0x30000000, 0x0}, {0x30000000, 0x0}, {0x30000000, 0x0}, {0x30000000, 0x0}, {0x30000000, 0x0}, {0x30000000, 0x0}},
    {{0x2014200, 0x400000}, {0x2084002, 0x1408088}, {0x20f4603, 0x240c121}, {0x2164405, 0x34141ba}, {0x19480014, 0x7500024e}, {0x1da3c06, 0x43982f1}, {0x19581c14, 0x750043a2}, {0x3a07008, 0x572040d}, {0x19683814, 0x75048502}, {0x368680a, 0x66a856a}, {0x19785414, 0x7504c657}, {0x1b0300c, 0x73306a9}, {0x1f33e0c, 0x83b0728}, {0x19887014, 0x750907a8}, {0xf91a0e, 0x81b881c}, {0x19988c14, 0x750948f9}, {0x19a8a814, 0x750d89c1}, {0x19b8c414, 0x750dca6a}, {0x19c83822, 0x98060b29}, {0x19d8a822, 0x980e4c1b}, {0x19e83829, 0xba068d0e}, {0x19f8a829, 0xba0ece01}, {0x1a083830, 0xdc070ef4}, {0x1a18a830, 0xdc0f4fc9}, {0x30000000, 0x0}, {0x30000000, 0x0}, {0x30000000, 0x0}, {0x30000000, 0x0}, {0x30000000, 0x0}, {0x30000000, 0x0}, {0x30000000, 0x0}, {0x30000000, 0x0}},
    {{0x2414a00, 0x480000}, {0x2484802, 0x1488089}, {0x24f4e03, 0x248c122}, {0x2564c05, 0x34941bb}, {0x1949001b, 0x64000259}, {0x2da5c06, 0x45982fe}, {0x19591c1b, 0x640043b8}, {0x1612a08, 0x52a0421}, {0x1969381b, 0x64048518}, {0x129220a, 0x622857c}, {0x1979541b, 0x6404c66c}, {0x330600c, 0x76306b8}, {0x1989701b, 0x640907bd}, {0x2f8580e, 0x85b8807}, {0x27b4e0e, 0x94b8880}, {0x19998c1b, 0x6409490e}, {0x19a9a81b, 0x640d89cc}, {0x19b9c41b, 0x640dca75}, {0x19c93f22, 0x98060b38}, {0x19d9af22, 0x980e4c2b}, {0x19e93f29, 0xba068d1d}, {0x19f9af29, 0xba0ece10}, {0x1a093f30, 0xdc070f01}, {0x1a19af30, 0xdc0f4fd6}, {0x30000000, 0x0}, {0x30000000, 0x0}, {0x30000000, 0x0}, {0x30000000, 0x0}, {0x30000000, 0x0}, {0x30000000, 0x0}, {0x30000000, 0x0}, {0x30000000, 0x0}},
    {{0x2815200, 0x500000}, {0x2885002, 0x150808b}, {0x28f5603, 0x250c124}, {0x2965405, 0x35141bd}, {0x194a0714, 0x7500026f}, {0x39a7406, 0x4718306}, {0x195a2314, 0x750043ce}, {0x2214208, 0x5420429}, {0x1e43809, 0x53a44a8}, {0x196a3f14, 0x7504852e}, {0x6a0c0a, 0x60a859f}, {0x197a5b14, 0x7504c681}, {0x1722c0c, 0x72b06fa}, {0x198a7714, 0x750907d2}, {0x1ba340e, 0x933884e}, {0x199a9314, 0x75094923}, {0x19aaaf14, 0x750d89d6}, {0x19bacb14, 0x750dca7f}, {0x19ca4622, 0x98060b47}, {0x19dab622, 0x980e4c3a}, {0x19ea4629, 0xba068d2d}, {0x19fab629, 0xba0ece20}, {0x1a0a4630, 0xdc070f0f}, {0x1a1ab630, 0xdc0f4fe3}, {0x30000000, 0x0}, {0x30000000, 0x0}, {0x30000000, 0x0}, {0x30000000, 0x0}, {0x30000000, 0x0}, {0x30000000, 0x0}, {0x30000000, 0x0}, {0x30000000, 0x0}},
    {{0x2c15a00, 0x580000}, {0x2c85802, 0x158808c}, {0x2cf5e03, 0x258c125}, {0x2d65c05, 0x35941be}, {0x194b071b, 0x64000285}, {0x5b0e06, 0x409830e}, {0x195b231b, 0x640043e4}, {0x3616a08, 0x56a0436}, {0x196b3f1b, 0x64048544}, {0x2a9520a, 0x652858c}, {0x1ec380b, 0x73ac601}, {0x197b5b1b, 0x6404c696}, {0x3b2740c, 0x7730712}, {0x198b771b, 0x640907e7}, {0x3ba740e, 0x9738863}, {0x199b931b, 0x64094938}, {0x19abaf1b, 0x640d89e1}, {0x19bbcb1b, 0x640dca8a}, {0x19cb4d22, 0x98060b56}, {0x19dbbd22, 0x980e4c49}, {0x19eb4d29, 0xba068d3c}, {0x19fbbd29, 0xba0ece2f}, {0x1a0b4d30, 0xdc070f1c}, {0x1a1bbd30, 0xdc0f4ff0}, {0x30000000, 0x0}, {0x30000000, 0x0}, {0x30000000, 0x0}, {0x30000000, 0x0}, {0x30000000, 0x0}, {0x30000000, 0x0}, {0x30000000, 0x0}, {0x30000000, 0x0}},
    {{0x3016200, 0x600000}, {0x3086002, 0x160808d}, {0x30f6603, 0x260c126}, {0x3166405, 0x36141bf}, {0x194c1c06, 0x3100029b}, {0x1db3e06, 0x439831d}, {0x195c3806, 0x310443fa}, {0x1622c08, 0x52a044c}, {0x196c5406, 0x3104855a}, {0x12a240a, 0x62285a6}, {0x6d0a0b, 0x70ac61d}, {0x197c7006, 0x3108c6ab}, {0x233460c, 0x843072c}, {0x198c8c06, 0x310907fc}, {0x17b2e0e, 0x92b8876}, {0x199ca806, 0x310d4943}, {0x19acc406, 0x310d89ec}, {0x19bcd214, 0x750dca94}, {0x19cc5422, 0x98060b65}, {0x19dcc422, 0x980e4c58}, {0x19ec5429, 0xba068d4b}, {0x19fcc429, 0xba0ece3e}, {0x1a0c5430, 0xdc070f29}, {0x1a1cc430, 0xdc0f4ffe}, {0x30000000, 0x0}, {0x30000000, 0x0}, {0x30000000, 0x0}, {0x30000000, 0x0}, {0x30000000, 0x0}, {0x30000000, 0x0}, {0x30000000, 0x0}, {0x30000000, 0x0}},
    {{0x3416a00, 0x680000}, {0x3486802, 0x168808f}, {0x34f6e03, 0x268c128}, {0x3566c05, 0x36941c1}, {0x194d1c0d, 0x200002b1}, {0x31b6606, 0x461832c}, {0x195d380d, 0x20044410}, {0x3626c08, 0x56a0462}, {0x196d540d, 0x2004856f}, {0x3aa740a, 0x67285c1}, {0x2ed5a0b, 0x75ac637}, {0x197d700d, 0x2008c6c0}, {0x34000d, 0x8034741}, {0x198d8c0d, 0x20090811}, {0x37b6e0e, 0x96b888b}, {0x199da80d, 0x200d494e}, {0x19adc40d, 0x200d89f6}, {0x19bdd21b, 0x640dca9f}, {0x19cd5b22, 0x98060b74}, {0x19ddcb22, 0x980e4c67}, {0x19ed5b29, 0xba068d5a}, {0x19fdcb29, 0xba0ece4d}, {0x1a0d5b30, 0xdc070f36}, {0x1a1dcb30, 0xdc0f500b}, {0x30000000, 0x0}, {0x30000000, 0x0}, {0x30000000, 0x0}, {0x30000000, 0x0}, {0x30000000, 0x0}, {0x30000000, 0x0}, {0x30000000, 0x0}, {0x30000000, 0x0}},
    {{0x3817200, 0x700000}, {0x3887002, 0x1708090}, {0x38f7603, 0x270c129}, {0x3967405, 0x37141c2}, {0x2a3f3f32, 0x4081c244}, {0x194e2306, 0x310002c7}, {0x29c5007, 0x451c353}, {0x195e3f06, 0x31044426}, {0x1a43009, 0x53244a7}, {0x196e5b06, 0x31048584}, {0x12c200b, 0x722c5fb}, {0x197e7706, 0x3108c6d5}, {0x1f4380d, 0x83b4752}, {0x198e9306, 0x31090827}, {0x13c200f, 0x923c89d}, {0x199eaf06, 0x310d4958}, {0x19aecb06, 0x310d8a01}, {0x19bed914, 0x750dcaa9}, {0x19ce6222, 0x98060b84}, {0x19ded222, 0x980e4c77}, {0x19ee6229, 0xba068d69}, {0x19fed229, 0xba0ece5c}, {0x1a0e6230, 0xdc070f44}, {0x1a1ed230, 0xdc0f5018}, {0x30000000, 0x0}, {0x30000000, 0x0}, {0x30000000, 0x0}, {0x30000000, 0x0}, {0x30000000, 0x0}, {0x30000000, 0x0}, {0x30000000, 0x0}, {0x30000000, 0x0}},
    {{0x3c17a00, 0x780000}, {0x3c87802, 0x1788091}, {0x3cf7e03, 0x278c12a}, {0x3d67c05, 0x37941c3}, {0x2a402a33, 0x2c82024f}, {0x194f230d, 0x200002dd}, {0x1d0207, 0x401c363}, {0x195f3f0d, 0x2004443c}, {0x250209, 0x60244c3}, {0x196f5b0d, 0x20048599}, {0x32c600b, 0x762c610}, {0x197f770d, 0x2008c6ea}, {0x3b4700d, 0x8734766}, {0x198f930d, 0x2009083c}, {0x2fc580f, 0x95bc8af}, {0x199faf0d, 0x200d4963}, {0x19afcb0d, 0x200d8a0b}, {0x19bfd91b, 0x640dcab4}, {0x19cf6922, 0x98060b93}, {0x19dfd922, 0x980e4c86}, {0x19ef6929, 0xba068d79}, {0x19ffd929, 0xba0ece6b}, {0x1a0f6930, 0xdc070f51}, {0x1a1fd930, 0xdc0f5025}, {0x30000000, 0x0}, {0x30000000, 0x0}, {0x30000000, 0x0}, {0x30000000, 0x0}, {0x30000000, 0x0}, {0x30000000, 0x0}, {0x30000000, 0x0}, {0x30000000, 0x0}}
}};
static_assert(NJOB + NCONV == 32, "");

__device__ __forceinline__ unsigned read_back(const void* p) {
    unsigned v = 0;
    asm volatile("ld.relaxed.gpu.global.u32 %0, [%1];" : "=r"(v) : "l"(p) : "memory");
    return v;
}
__device__ __forceinline__ void publish(unsigned* flag, unsigned seen, unsigned zero) {
    asm volatile("{\n.reg .pred p;\n.reg .u32 t;\nredux.sync.or.b32 t, %1, 0xffffffff;\nand.b32 t, t, %2;\nadd.u32 t, t, 1;\n"
                 "elect.sync _|p, 0xffffffff;\n@p red.relaxed.gpu.global.add.u32 [%0], t;\n}" :: "l"(flag), "r"(seen), "r"(zero) : "memory");
}

__device__ __forceinline__ void load_w(uint2 (&v)[32], const char* g) {
#pragma unroll
    for (int k = 0; k < 32; k++)
        asm volatile("ld.global.nc.L1::no_allocate.v2.b32 {%0,%1}, [%2];" : "=r"(v[k].x), "=r"(v[k].y) : "l"(g + k * (N_ * 4)));
}
__device__ __forceinline__ void store_w(const uint2 (&v)[32], unsigned (&o)[16], char* d) {
#pragma unroll
    for (int i = 0; i < 8; i++) {
        o[i] = pack4(v[4 * i].x, v[4 * i + 1].x, v[4 * i + 2].x, v[4 * i + 3].x);
        o[8 + i] = pack4(v[4 * i].y, v[4 * i + 1].y, v[4 * i + 2].y, v[4 * i + 3].y);
        if ((i & 3) == 3) {
            stg128(d + (i >> 2) * 128, make_uint4(o[i - 3], o[i - 2], o[i - 1], o[i]));
            stg128(d + (i >> 2) * 128 + 256, make_uint4(o[i + 5], o[i + 6], o[i + 7], o[i + 8]));
        }
    }
}
__device__ __forceinline__ unsigned col_sums(const unsigned (&o)[16]) {
    int cs[4];
#pragma unroll
    for (int i = 0; i < 4; i++)
        cs[i] = __dp4a((int)o[4 * i], 0x01010101, __dp4a((int)o[4 * i + 1], 0x01010101,
                __dp4a((int)o[4 * i + 2], 0x01010101, __dp4a((int)o[4 * i + 3], 0x01010101, 0))));
    return cs[0] + cs[1] + (cs[2] + cs[3]) * 65536;
}
__device__ __forceinline__ void wait_until(int due, unsigned t0) {
    for (int rem; (rem = due - (int)(clk() - t0)) > 0;) if (rem > CFG_SLEEP) __nanosleep(CFG_SLEEP / 4);
}

__device__ __forceinline__ uint32_t zero_term(const unsigned (&sv)[4], float zxf) {
    int lo = 0, hi = 0;
#pragma unroll
    for (int h = 0; h < 4; h++) {
        const int l = (int)(short)(sv[h] & 0xFFFF);
        lo += l; hi += ((int)(sv[h] - (unsigned)l)) >> 16;
    }
    const float fl = __bfloat162float(__float2bfloat16_rn((float)lo)) * zxf, fh = __bfloat162float(__float2bfloat16_rn((float)hi)) * zxf;
    uint32_t z;
    asm("cvt.rn.bf16x2.f32 %0, %1, %2;" : "=r"(z) : "f"(fh), "f"(fl));
    return z;
}

__device__ __forceinline__ void load_x(Scratch* scr, uint32_t sb, int b, int lane) {
    const int r = b & 15;
    const unsigned tgt = (*(volatile unsigned*)&scr->epoch[b] + 1) * 4;
    const unsigned* f = scr->flag + r * FS + (lane & 15);
    const uint32_t sa = __shfl_sync(~0u, sb, 0);
    const char* const ga = (const char*)scr->a8 + __shfl_sync(~0u, r * 16 * 8192, 0);
    unsigned todo = 0xFFFF, v = ld_flag(f);
    asm volatile("barrier.cluster.wait.aligned;" ::: "memory");
#pragma unroll 1
    for (int it = 0; todo; it++) {
        unsigned m = __ballot_sync(~0u, (int)(v - tgt) >= 0) & todo;
        v = ld_flag(f);
        todo &= ~m;
        while (m) {
            const int sl = __ffs(m) - 1;
            m &= m - 1;
            asm volatile("{\n.reg .pred p;\nelect.sync _|p, 0xffffffff;\n"
                         "@p cp.async.bulk.shared::cluster.global.mbarrier::complete_tx::bytes [%0], [%1], 8192, [%2];\n}"
                         :: "r"(sa + sl * 8192), "l"(ga + (unsigned)sl * 8192), "r"(sa + SM_BAR + (B_FULL + sl) * 8) : "memory");
        }
        if (it > (1 << 20)) __trap();
    }
}

__device__ __forceinline__ void load_x4(Scratch* scr, uint32_t sb, int b, int h, int lane) {
    const uint32_t bars = sb + SM_BAR;
    const unsigned tgt = (*(volatile unsigned*)&scr->epoch[b] + 1) * 4;
    const unsigned* f = scr->flag + (4 * h + (lane >> 4)) * FS + (lane & 15);
    asm volatile("barrier.cluster.wait.aligned;" ::: "memory");
#pragma unroll 1
    for (int it = 0, sl = 0; sl < 16; it++) {
        const unsigned v0 = ld_flag(f), v1 = ld_flag(f + 2 * FS);
        unsigned m = __ballot_sync(~0u, (int)(v0 - tgt) >= 0 && (int)(v1 - tgt) >= 0);
        m &= m >> 16;
#pragma unroll 1
        for (; m >> sl & 1; sl++) {
            if (sl >= 4) mbar_wait(bars + (B_GO + sl - 4) * 8);
            if (elect_one()) {
#pragma unroll
                for (int k = 0; k < 4; k++)
                    asm volatile("cp.async.bulk.shared::cluster.global.mbarrier::complete_tx::bytes [%0], [%1], %2, [%3];"
                                 :: "r"(sb + SM_A + ((sl & 3) * 4 + k) * 8192), "l"((const char*)scr->a8 + ((4 * h + k) * 16 + sl) * 8192),
                                    "r"(8192), "r"(bars + (B_FULL + (k >> 1) * 16 + sl) * 8) : "memory");
            }
        }
        if (it > (1 << 20)) __trap();
    }
}

__device__ __forceinline__ void store_out(const CUtensorMap* map, uint32_t sb, int b, int agent, int lane, int n, unsigned seq, int col, int dcol, int row, int drow) {
    const uint32_t bars = sb + SM_BAR;
    const uint32_t buf = sb + SM_OUT + agent * 4096, full = bars + (B_OFULL + agent) * 8;
#pragma unroll 1
    for (int t = 0; t < n; t++, seq >>= 4) {
        asm volatile("{\n.reg .pred p;\n.reg .u32 c;\nmov.u32 c, 0;\n"
                     "WAIT_LOOP:\n"
                     "mbarrier.try_wait.parity.shared::cta.b64 p, [%4], %5;\n"
                     "@p bra WAIT_DONE;\n"
                     "add.u32 c, c, 1;\nsetp.lt.u32 p, c, 0x100000;\n"
                     "@p bra WAIT_LOOP;\n"
                     "trap;\n"
                     "WAIT_DONE:\n"
                     "fence.proxy.async.shared::cta;\n"
                     "elect.sync _|p, 0xffffffff;\n"
                     "@p cp.async.bulk.tensor.2d.global.shared::cta.tile.bulk_group [%0, {%1, %2}], [%3];\n"
                     "cp.async.bulk.commit_group;\n}"
                     :: "l"(map), "r"(col + (seq & 7) * dcol), "r"(row + agent * 32 + (seq & 7) * drow), "r"(buf), "r"(full), "r"(t & 1) : "memory");
        asm volatile("cp.async.bulk.wait_group.read 0;" ::: "memory");
        if (elect_one()) mbar_arrive(bars + (B_OFREE + t * 4 + 4 + agent) * 8);
    }
}

template <int V> struct I { static constexpr int v = V; };
template <int MODE>
__device__ __forceinline__ void consume(Scratch* scr, const __nv_bfloat16* __restrict__ scale_w, const __nv_bfloat16* __restrict__ bias,
                                        const __nv_bfloat16* __restrict__ scale_x, uint32_t sb, int b, int warp, int lane) {
    constexpr bool SIDE = MODE != 0;
    constexpr int NR = NRING, NG = SIDE ? 48 : 56;
    const uint32_t bars = sb + SM_BAR;
    const int c = SIDE ? 7 : b >> 4;
    constexpr uint32_t SD = 0x400 >> 4;
    if ((sb & 0xFFFFFF) != 0x400) __trap();
    const int wg = warp >> 2;
    const unsigned short sxr = __ldg((const unsigned short*)scale_x);
    const uint32_t sx2 = (uint32_t)sxr * 0x10001u;
    const int c0 = (warp & 3) * 16 + (lane >> 2) * 2;
    uint32_t sw[4], bi[4];
#pragma unroll
    for (int i = 0; i < 4; i++) {
        const int col = col_of(c, i < 2 ? wg * 2 + i : i == 2 ? 4 + wg : 6) + c0;
        sw[i] = __ldg((const uint32_t*)(scale_w + col));
        bi[i] = __ldg((const uint32_t*)(bias + col));
    }
    const uint32_t st0 = sb + SM_OUT + (lane & 3) * 256 + (((c0 >> 3) ^ ((lane & 3) * 2)) << 4) + (c0 & 7) * 2;
    constexpr uint32_t DX0 = (SD + (SM_A >> 4)) | (1 << 16), DW0 = (SD + (SM_RING >> 4)) | (8 << 16);
    asm volatile("barrier.cluster.wait.aligned;" ::: "memory");
    int a0[64], a1[64];
    constexpr int MUL = SIDE ? 4 : 2, NONE = 64 * MUL, BIAS = NR + 64 - NG;
    const uint32_t go = mapa(bars + B_GO * 8, lane & (SIDE ? 1 : 15)) - (64 - NG) * MUL;
    const int key = SIDE ? (lane < 2 ? lane * 4 : 1) : (lane < 16 ? (lane >> 2) * 2 : 1);
    int pend = NONE;
    uint32_t bb = bars + (B_FULL + wg * 16) * 8;
#define RELEASE() { if ((pend & (NONE + 8 - MUL)) == key) mbar_arrive_cluster(go + (pend & ~7)); }
    struct Par { uint32_t a, b, c, d; };
    auto load_par = [&](int blk, uint32_t swv, uint32_t biv) {
        mbar_wait_cluster(bars + (B_PAR + blk) * 8);
        const uint32_t zc = lds32(sb + SM_PAR + (blk * 64 + c0) * 2);
        const float sxf = __uint_as_float(sx2 << 16);
        const float s0 = sxf * __uint_as_float(swv << 16), s1 = sxf * __uint_as_float(swv & 0xFFFF0000u);
        Par P = {__float_as_uint(s0), __float_as_uint(s1), __float_as_uint(fmaf(-__uint_as_float(zc << 16), s0, __uint_as_float(biv << 16))),
                 __float_as_uint(fmaf(-__uint_as_float(zc & 0xFFFF0000u), s1, __uint_as_float(biv & 0xFFFF0000u)))};
        asm volatile("{\n.reg .pred p;\nsetp.ne.u32 p, %3, 0;\n@p st.shared.v2.b32 [%0], {%1, %2};\n}" :: "r"(st0), "r"(P.c), "r"(P.d), "r"(blockIdx.y) : "memory");
        return P;
    };
    auto drain = [&](int (&a)[64], auto Q, int t, const Par& P) {
#pragma unroll
        for (int q = Q.v; q < Q.v + 2; q++) {
#pragma unroll
            for (int j = 0; j < 8; j++) {
                const int o = q * 16 + (j >> 1) * 4 + (j & 1);
                asm("cvt.rn.f32.s32 %0, %0;\n\tcvt.rn.f32.s32 %1, %1;\n\tfma.rn.f32 %0, %0, %2, %4;\n\tfma.rn.f32 %1, %1, %3, %5;\n\t"
                    "cvt.rn.bf16x2.f32 %0, %1, %0;" : "+r"(a[o]), "+r"(a[o + 2]) : "r"(P.a), "r"(P.b), "r"(P.c), "r"(P.d));
            }
            mbar_wait(bars + (B_OFREE + t * 4 + q) * 8);
#pragma unroll
            for (int j = 0; j < 8; j++) sts32((st0 ^ ((j & 1) * 16)) + q * 4096 + (j >> 1) * 1024 + (j & 1) * 128, a[q * 16 + (j >> 1) * 4 + (j & 1)]);
            __syncwarp();
            if (lane == 0) mbar_arrive(bars + (B_OFULL + q) * 8);
        }
    };
    wg_fence();
    if (MODE == 2) {
#pragma unroll 1
        for (int s = 0; s < 16; s++) {
            mbar_wait2(bars + (B_FULL + 48 + (s >> 2) * 2) * 8, bb + s * 8);
            mma_rows2(a0, a1, DW0 + s * 256, DX0 + ((s & 3) * 4 + 2 * wg) * 512, s);
            wg_wait<1>();
            if (s && lane == 0) mbar_arrive(bars + (B_GO + s - 1) * 8);
        }
        const Par P = load_par(6, sw[3], bi[3]);
        wg_wait<0>();
        drain(a0, I<0>(), wg, P); drain(a0, I<2>(), wg, P);
        drain(a1, I<0>(), 2 + wg, P); drain(a1, I<2>(), 2 + wg, P);
    } else {
    {
        uint32_t tbl = wg ? STEPS1 : STEPS0;
        uint32_t ba = bars + B_FULL * 8;
        int u = MUL * (wg * D_ + BIAS);
        uint32_t dw = DW0 + wg * D_ * 512;
        static_assert(D_ < NR, "");
        mbar_wait2(ba, bb);
#pragma unroll 1
        for (uint32_t dx = DX0;;) {
            mma_unit2(a0, a1, dw, dx, dx - DX0);
            dx += 512; ba += 8; bb += 8;
            const bool ready = mbar_test2(ba, bb);
            wg_wait<1>();
            RELEASE()
            pend = u;
            if (dx == DX0 + 16 * 512) break;
            u += MUL + (tbl & 1) * MUL;
            dw += 512 + (tbl & 1) * 512;
            if (dw >= DW0 + NR * 512) dw -= NR * 512;
            tbl >>= 1;
            if (!ready && !mbar_test2(ba, bb)) {
                wg_wait<0>();
                RELEASE()
                pend = NONE;
                mbar_wait(ba);
                if (wg) mbar_wait(bb);
            }
        }
    }
    Par P0 = load_par(2 * wg, sw[0], bi[0]);
    const Par P1 = load_par(2 * wg + 1, sw[1], bi[1]);
#define RELEASE2() { if ((pend & (NONE + 8 - 2 * MUL)) == (key & ~MUL)) mbar_arrive_cluster(go + (pend & ~7)); }
    static_assert(NR % 2 == 0, "");
    wg_wait<0>();
#pragma unroll 1
    for (int ph = 0;; ph++) {
        const int m = ph ? MUL : 0;
        const int u0 = 32 + ph * 16 + wg * 8;
        uint32_t dw = DW0 + (ph ? 48 % NR : wg ? 40 % NR : 32 % NR) * 512;
        bb = bars + (B_FULL + u0) * 8;
        if ((pend & (NONE + 8 - MUL - m)) == (key & ~m)) mbar_arrive_cluster(go + (pend & ~7));
        drain(a0, I<0>(), ph ? (ph + wg) * 2 + (ph & 2) + SIDE : wg, P0);
        const bool first = mbar_test(bb);
        drain(a0, I<2>(), wg ? 4 * ph + 1 : 3 * ph, P0);
        if (SIDE ? ph + wg == 1 : ph == 1) drain(a1, I<0>(), SIDE ? 4 - 2 * wg : 3 + 2 * wg, P1);
        if (SIDE ? ph == 1 : ph + wg == 2) break;
        pend = NONE;
        if (!first) mbar_wait(bb);
        if (ph + wg) mbar_wait(bars + (B_TURN + ph) * 8);
        wg_fence();
#pragma unroll 1
        for (int n = 0;; n += 2) {
            RELEASE2()
            const bool ready = mma_pair(a0, dw, DX0 + n * 1024, n, bb + n * 8 + 16);
            wg_wait<1>();
            pend = n ? MUL * (u0 + BIAS + n - 2) : NONE;
            if (n == 6) break;
            dw += 1024;
            if (dw == DW0 + NR * 512) dw = DW0;
            if (!ready) {
                RELEASE2()
                pend = NONE;
                mbar_wait(bb + n * 8 + 16);
            }
        }
        if (ph == 0 && (threadIdx.x & 127) == 0) mbar_arrive(bars + (B_TURN + wg) * 8);
        RELEASE2()
        pend = MUL * (u0 + BIAS + 6);
        if (ph == 0) drain(a1, I<2>(), 2 + 2 * wg, P1);
        P0 = load_par(4 + 2 * ph + wg, ph ? sw[3] : sw[2], ph ? bi[3] : bi[2]);
        wg_wait<0>();
    }
    }
    if (threadIdx.x == 128) asm volatile("red.relaxed.gpu.global.add.u32 [%0], 1;" :: "l"(scr->epoch + b) : "memory");
}

__global__ void __cluster_dims__(CS, 1, 1) __launch_bounds__(512, 1)
w8a8_kernel(const char* __restrict__ qx, const char* __restrict__ qw, Scratch* scr, const JobTable* __restrict__ jobs, const __nv_bfloat16* __restrict__ scale_w,
            const __nv_bfloat16* __restrict__ bias, const __nv_bfloat16* __restrict__ scale_x, const int* __restrict__ zero_x,
            const __grid_constant__ CUtensorMap map) {
    extern __shared__ __align__(1024) unsigned char smem_raw[];
    const uint32_t sb = (uint32_t)__cvta_generic_to_shared(smem_raw);
    const uint32_t bars = sb + SM_BAR;
    const int warp = __shfl_sync(~0u, threadIdx.x >> 5, 0), lane = threadIdx.x & 31;
    const int b = blockIdx.x, r = b & 15, c = b >> 4;
    const unsigned t0 = clk() + CFG_PF0;
    if (warp < CFG_NINIT) {
#pragma unroll 1
        for (int w = warp; w < 8; w += CFG_NINIT) {
            if (elect_one()) {
                const uint32_t cnt = w < B_GO / 16 ? 1 : 4 * CS + 1;
#pragma unroll
                for (int i = 0; i < 16; i++) mbar_init(bars + (w * 16 + i) * 8, cnt);
            }
            __syncwarp();
            const int i = w * 16 + lane;
            if (lane < 16 && i < B_OFREE + NOUT && (i >> 1) != B_TURN / 2) mbar_expect_tx(bars + i * 8, i >= B_AFREE ? 0 : i >= B_PAR ? 128 : w == 1 ? 8192 : 16384);
            if (w == B_GO / 16 && 4 * lane + (r >> 2) < NRING)
                asm volatile("mbarrier.arrive.shared::cta.b64 _, [%0], %1;" :: "r"(bars + i * 8), "r"(4 * CS) : "memory");
        }
        if (warp == (B_SUM / 16) % CFG_NINIT) {
            if (elect_one()) {
#pragma unroll
                for (int k = 0; k < NOUT; k++) mbar_init(bars + (B_OFULL + k) * 8, 4);
                mbar_init(bars + B_SUM * 8, r < 8 ? 1 : 3);
                mbar_expect_tx(bars + B_SUM * 8, r < 8 ? 32 * 64 : 30 * 64);
            }
        }
        asm volatile("fence.mbarrier_init.release.cluster;" ::: "memory");
    } else if (warp == 7) {
        asm volatile("st.shared.v2.b32 [%0], {%1, %1};" :: "r"(sb + SM_SUM + lane * 8), "r"(0) : "memory");
        asm volatile("fence.release.sync_restrict::shared::cta.cluster;" ::: "memory");
    } else if (warp == 9) {
        asm volatile("griddepcontrol.launch_dependents;");
        if (elect_one()) asm volatile("prefetch.tensormap [%0];" :: "l"(&map) : "memory");
    } else if (warp >= 14) {
        const char* pf = qx + (r * 128 + ((threadIdx.x >> 1) & 31)) * (K_ * 4) + (lane & 1) * 128;
        if (c >= 5) asm volatile("prefetch.global.L2 [%0];" :: "l"(pf + (c - 5) * (32 * K_ * 4)) : "memory");
        asm volatile("prefetch.global.L2 [%0];" :: "l"(pf + ((c + 2) & 3) * (32 * K_ * 4) + ((c + 2) >> 2) * 256) : "memory");
    }
    asm volatile("barrier.cluster.arrive.relaxed.aligned;" ::: "memory");

    if (warp >= 8) {
        asm volatile("setmaxnreg.dec.sync.aligned.u32 88;");
        int agent = -1;
        if (warp >= 16 - NCONV) {
            const int cw = warp - (16 - NCONV);
            const unsigned zero = blockIdx.y;
            const char* const gx = qx + (lane >> 4) * (K_ * 4) + (lane & 15) * 16;
            const char* const gw = qw + lane * 8;
            const int wrB = ((lane >> 3) * 32 + (lane & 7)) * 16;
            uint2 tab;
            asm volatile("ld.global.nc.v2.u32 {%0, %1}, [%2];" : "=r"(tab.x), "=r"(tab.y) : "l"(&jobs->e[b][lane]));
            bool synced = false;
#pragma unroll 1
            for (int p = cw || c >= 5 ? cw : NCONV;; p = p < CFG_PZ ? p + NCONV : p < CFG_PZ + 3 ? 31 : p + 3) {
                uint2 j;
                if (p < 4) {
                    const int g = 7 * p + c - 5;
                    j.x = ((r * 128 + (g & 3) * 32) * 16 + (g >> 2)) | (r * 64 + g) << 16;
                    j.y = max((p - 1) * (CFG_P0 / 4) + b * (CFG_P0 * 4 / NCTA) / 16, 0) | (r * FS + (g >> 2)) << 14 | p << 24;
                } else { j.x = __shfl_sync(~0u, tab.x, p); j.y = __shfl_sync(~0u, tab.y, p); }
                if (j.x >= 3u << 28) break;
                const int kind = j.x >> 28, sig = (j.y >> 14) & 0x3FF;
                char* tile = (char*)scr + ((j.x >> 16) & 0xFFF) * 2048;
                const char* g = (kind ? gw : gx) + (j.x & 0xFFFF) * 256;
                wait_until((j.y & 0x3FFF) * 4, t0);
                if (kind == 0) {
                    uint4 v[16];
#pragma unroll
                    for (int i = 0; i < 16; i++)
                        asm volatile("ld.global.nc.L1::no_allocate.v4.b32 {%0,%1,%2,%3}, [%4];"
                                     : "=r"(v[i].x), "=r"(v[i].y), "=r"(v[i].z), "=r"(v[i].w) : "l"(g + i * (2 * K_ * 4)));
#pragma unroll
                    for (int i = 0; i < 16; i++)
                        asm volatile("st.global.b32 [%0], %1;" :: "l"(tile + ((lane * 4) ^ ((i & 3) * 16)) + i * 128),
                                     "r"(pack4(v[i].x, v[i].y, v[i].z, v[i].w)) : "memory");
                    asm volatile("fence.proxy.async.global;" ::: "memory");
                    __syncwarp();
                    publish(scr->flag + sig, read_back(tile + lane * 64), zero);
                } else {
                    uint2 v[32];
                    unsigned o[16];
                    load_w(v, g);
                    if (!synced) asm volatile("barrier.cluster.wait.aligned;" ::: "memory");
                    synced = true;
                    store_w(v, o, tile + wrB);
                    asm volatile("{\n.reg .pred p;\nsetp.eq.u32 p, %1, 0;\nfence.proxy.async.global;\nbar.warp.sync 0xffffffff;\n"
                                 "@p mbarrier.arrive.shared::cta.b64 _, [%0];\n}" :: "r"(bars + (B_GO + (sig & 15)) * 8), "r"(lane | (kind & 2)) : "memory");
                    const unsigned csv = col_sums(o);
                    if (kind == 1) {
                        const int own = (j.y >> (24 + (lane >> 4) * 4)) & 15;
                        const uint32_t so = SM_SUM + (sig & 48) * 4 + (lane & 15) * 4;
                        if (own != r) {
                            const uint32_t ro = mapa(sb, own);
                            asm volatile("red.async.relaxed.cluster.shared::cluster.mbarrier::complete_tx::bytes.add.u32 [%0], %1, [%2];"
                                         :: "r"(ro + so), "r"(csv), "r"(ro + SM_BAR + B_SUM * 8) : "memory");
                        } else asm volatile("red.relaxed.cluster.shared::cta.add.u32 [%0], %1;" :: "r"(sb + so), "r"(csv) : "memory");
                        __syncwarp();
                        if (own == r && (lane & 15) == 0) mbar_arrive(bars + B_SUM * 8);
                    } else {
                        unsigned* csp = scr->cs + (j.y >> 24) * 32 + lane;
                        asm volatile("st.global.u32 [%0], %1;" :: "l"(csp), "r"(csv) : "memory");
                        publish(scr->flag + sig, read_back(tile + lane * 64) | read_back(csp), zero);
                    }
                }
                __syncwarp();
            }
            if (!synced) asm volatile("barrier.cluster.wait.aligned;" ::: "memory");
            agent = (cw + 6 * NCONV - CFG_PZ) % NCONV + 1;
            if (agent > 3) agent = -1;
        } else if (warp == 9) {
            asm volatile("barrier.cluster.wait.aligned;" ::: "memory");
        } else {
            load_x(scr, sb, b, lane);
            agent = 0;
        }
        const char* src = (const char*)scr->b8 + (c * 224 + r) * 2048;
        const int zxi = __ldg(zero_x);
#pragma unroll 1
        for (int i = 0, slot = r >> 2, end = 8;; end = NG / 4) {
#pragma unroll 1
            for (; warp == 9 && i < end; i++) {
                asm volatile("{\n.reg .pred p;\nWAIT_LOOP:\nmbarrier.try_wait.parity.shared::cta.b64 p, [%4], 0;\n@!p bra WAIT_LOOP;\n"
                             "elect.sync _|p, 0xffffffff;\n"
                             "@p cp.async.bulk.shared::cluster.global.mbarrier::complete_tx::bytes.multicast::cluster [%0], [%1], 2048, [%2], %3;\n}"
                             :: "r"(sb + SM_RING + slot * 8192 + (r & 3) * 2048), "l"(src + i * 32768),
                                "r"(bars + (B_FULL + bar_of(4 * i + (r >> 2))) * 8), "h"((uint16_t)0xFFFF), "r"(bars + (B_GO + i) * 8) : "memory");
                slot += slot >= NRING - 4 ? 4 - NRING : 4;
            }
            if (end != 8) break;
            if (warp == (r < 8 ? 9 : r < 10 ? 8 : r < 14 ? 16 - NCONV + (CFG_PZ + 3) % NCONV : 0)) {
                const float zxf = __bfloat162float(__float2bfloat16_rn((float)zxi));
                const int grp = sum_group(r);
                mbar_wait_cluster(bars + B_SUM * 8);
                unsigned sv[4];
#pragma unroll
                for (int h = 0; h < 4; h++) sv[h] = lds32(sb + SM_SUM + h * 64 + (lane & 15) * 4);
                const uint32_t z = zero_term(sv, zxf);
#pragma unroll 2
                for (int k = 0; k < 8; k++) {
                    const uint32_t rb = mapa(sb, k * 2 + (lane >> 4));
                    st_async32(rb + SM_PAR + grp * 64 + (lane & 15) * 4, z, rb + SM_BAR + (B_PAR + (grp >> 1)) * 8);
                }
            }
        }
        __syncwarp();
        if (agent >= 0) store_out(&map, sb, b, agent, lane, 7, agent < 2 ? 0x6351420 : 0x6534120, c * 64, 7 * 64, r * 128, 0);
    } else {
        asm volatile("setmaxnreg.inc.sync.aligned.u32 168;");
        consume<0>(scr, scale_w, bias, scale_x, sb, b, warp, lane);
    }
}

__global__ void __cluster_dims__(2, 1, 1) __launch_bounds__(512, 1)
w8a8_side(const char* __restrict__ qw, Scratch* scr, const __nv_bfloat16* __restrict__ scale_w, const __nv_bfloat16* __restrict__ bias,
          const __nv_bfloat16* __restrict__ scale_x, const int* __restrict__ zero_x, const __grid_constant__ CUtensorMap map) {
    extern __shared__ __align__(1024) unsigned char smem_raw[];
    const uint32_t sb = (uint32_t)__cvta_generic_to_shared(smem_raw);
    const uint32_t bars = sb + SM_BAR;
    const int warp = __shfl_sync(~0u, threadIdx.x >> 5, 0), lane = threadIdx.x & 31;
    const int b = NCTA + blockIdx.x, rank = b & 1;
    const bool helper = blockIdx.x >= 16;
    constexpr int NR = NRING;
    const unsigned t0 = clk();
    if (warp < 3) {
#pragma unroll 1
        for (int w = warp; w < B_OFULL / 16; w += 3) {
            if (elect_one()) {
                const uint32_t cnt = w < B_GO / 16 ? 1 : !helper ? 9 : w == B_GO / 16 ? 8 : 1;
#pragma unroll
                for (int i = 0; i < 16; i++) mbar_init(bars + (w * 16 + i) * 8, cnt);
            }
            __syncwarp();
            const int i = w * 16 + lane;
            if (lane < 16 && i < B_PAR) mbar_expect_tx(bars + i * 8, w == 1 && !helper ? 8192 : 16384);
            if (lane < 16 && i >= B_OFREE && i < B_OFREE + NOUT) mbar_arrive(bars + i * 8);
            if (w == B_GO / 16 && 2 * lane + rank < NR && !helper)
                asm volatile("mbarrier.arrive.shared::cta.b64 _, [%0], %1;" :: "r"(bars + i * 8), "r"(8) : "memory");
        }
        asm volatile("fence.mbarrier_init.release.cluster;" ::: "memory");
    } else if (warp == 3) {
        if (elect_one()) {
#pragma unroll
            for (int i = 0; i < NOUT; i++) mbar_init(bars + (B_OFULL + i) * 8, 4);
            asm volatile("fence.mbarrier_init.release.cluster;" ::: "memory");
        }
        __syncwarp();
    } else if (warp == 11 && elect_one()) asm volatile("prefetch.tensormap [%0];" :: "l"(&map) : "memory");
    asm volatile("barrier.cluster.arrive.relaxed.aligned;" ::: "memory");

    if (warp >= 8) {
        asm volatile("setmaxnreg.dec.sync.aligned.u32 88;");
        int agent = -1;
        if (warp == 10 || warp >= 12) {
#pragma unroll 1
            for (int i = (0x032401 >> (4 * (warp - 10))) & 7; i < (helper ? 8 : 12 - CFG_NOC / 4); i += 5) {
                const int G = (helper ? 192 - 16 + i * 4 : CFG_NOC * 4 + i * 16) + blockIdx.x, u = G >> 2, f = bar_of(u);
                const int blk = u < 32 ? (f >> 4) * 2 + (G & 1) : u >> 3, step = u < 32 ? (f & 15) * 2 + (G >> 1 & 1) : G & 31;
                char* const tile = (char*)scr->b8 + (7 * 224 + G) * 2048;
                unsigned* const csp = scr->cs + (step * 7 + blk) * 32 + lane;
                uint2 v[32];
                unsigned o[16];
                wait_until(helper ? i * CFG_YH + CFG_YH0 : (G - CFG_NOC * 4) * (CFG_YP / 16) + CFG_Y0, t0);
                load_w(v, qw + step * (32 * N_ * 4) + (49 + blk) * 256 + lane * 8);
                store_w(v, o, tile + ((lane >> 3) * 32 + (lane & 7)) * 16);
                asm volatile("st.global.u32 [%0], %1;" :: "l"(csp), "r"(col_sums(o)) : "memory");
                asm volatile("fence.proxy.async.global;" ::: "memory");
                __syncwarp();
                publish(scr->flag + CS * FS + u, read_back(tile + lane * 64) | read_back(csp), blockIdx.y);
            }
        }
        if (warp == 8) {
            if (helper) load_x4(scr, sb, b, blockIdx.x - 16, lane);
            else load_x(scr, sb, b, lane);
            agent = 0;
        } else if (warp == 11) {
            const unsigned tgt = (*(volatile unsigned*)&scr->epoch[b] + 1) * 4;
            const unsigned* f = scr->flag + CS * FS + lane;
            unsigned todo0 = helper ? 0 : ~0u, todo1 = helper ? 0xFF0000 : 0xFFFF, v0 = ld_flag(f), v1 = ld_flag(f + 32);
            bool par = lane >= 2;
            asm volatile("barrier.cluster.wait.aligned;" ::: "memory");
#pragma unroll 1
            for (int it = 0; todo0 | todo1; it++) {
                const unsigned m0 = __ballot_sync(~0u, (int)(v0 - tgt) >= 0) & todo0, m1 = __ballot_sync(~0u, (int)(v1 - tgt) >= 0) & todo1;
                v0 = ld_flag(f); v1 = ld_flag(f + 32);
                todo0 &= ~m0; todo1 &= ~m1;
                if ((lane & 1) == rank) {
                    if (m0 >> lane & 1) mbar_arrive(bars + (B_GO + (lane >> 1)) * 8);
                    if (m1 >> lane & 1) mbar_arrive(bars + (B_GO + 16 + (lane >> 1)) * 8);
                }
                if (!par && !(lane ? todo1 : todo0)) { par = true; mbar_arrive(bars + (B_AFREE + lane) * 8); }
                if (it > (1 << 20)) __trap();
            }
        } else if (warp == 9) {
            asm volatile("barrier.cluster.wait.aligned;" ::: "memory");
            const char* src = (const char*)scr->b8 + (7 * NG + rank) * 8192;
#pragma unroll 1
            for (int i = helper ? 24 : 0, slot = rank; i < (helper ? 28 : 24); i++) {
                asm volatile("{\n.reg .pred p;\nWAIT_LOOP:\nmbarrier.try_wait.parity.shared::cta.b64 p, [%4], 0;\n@!p bra WAIT_LOOP;\n"
                             "elect.sync _|p, 0xffffffff;\n"
                             "@p cp.async.bulk.shared::cluster.global.mbarrier::complete_tx::bytes.multicast::cluster [%0], [%1], 8192, [%2], %3;\n}"
                             :: "r"(sb + SM_RING + slot * 8192), "l"(src + i * 16384),
                                "r"(bars + (B_FULL + bar_of(2 * i + rank)) * 8), "h"((uint16_t)3), "r"(bars + (B_GO + i) * 8) : "memory");
                slot += slot >= NR - 2 ? 2 - NR : 2;
            }
        } else if (warp == 12 || warp == 15) {
            asm volatile("barrier.cluster.wait.aligned;" ::: "memory");
#pragma unroll 1
            for (int blk = helper ? 6 + (warp & 2) : warp & 2; blk < (helper ? 7 : 6); blk += 4) {
                const int w = min(blk * 32 + lane * 2, TN / 2 - 2);
                mbar_wait(bars + (B_AFREE + (blk >> 2)) * 8);
                uint2 v[32];
                unsigned s0[4], s1[4];
                const float zxf = __bfloat162float(__float2bfloat16_rn((float)__ldcg(zero_x)));
#pragma unroll
                for (int k = 0; k < 32; k++) v[k] = __ldcg((const uint2*)(scr->cs + k * (TN / 2) + w));
#pragma unroll
                for (int h = 0; h < 4; h++) {
                    s0[h] = s1[h] = 0;
#pragma unroll
                    for (int k = 0; k < 8; k++) { s0[h] += v[8 * h + k].x; s1[h] += v[8 * h + k].y; }
                }
                sts32(sb + SM_PAR + w * 4, zero_term(s0, zxf));
                sts32(sb + SM_PAR + w * 4 + 4, zero_term(s1, zxf));
                __syncwarp();
                if (lane < 2) mbar_arrive(bars + (B_PAR + blk + lane) * 8);
            }
        } else {
            asm volatile("barrier.cluster.wait.aligned;" ::: "memory");
            agent = warp == 10 ? 1 : warp - 11;
        }
        if (agent >= 0) {
            if (helper) store_out(&map, sb, b, agent, lane, 4, 0x3120, col_of(7, 6), 0, (blockIdx.x - 16) * 512, 128);
            else store_out(&map, sb, b, agent, lane, 6, agent < 2 ? 0x514320 : 0x534120, col_of(7, 0), 64, blockIdx.x * 128, 0);
        }
    } else {
        asm volatile("setmaxnreg.inc.sync.aligned.u32 168;");
        if (helper) consume<2>(scr, scale_w, bias, scale_x, sb, b, warp, lane);
        else consume<1>(scr, scale_w, bias, scale_x, sb, b, warp, lane);
    }
}

}

typedef CUresult (*EncodeFn)(CUtensorMap*, CUtensorMapDataType, cuuint32_t, void*, const cuuint64_t*, const cuuint64_t*,
                             const cuuint32_t*, const cuuint32_t*, CUtensorMapInterleave, CUtensorMapSwizzle,
                             CUtensorMapL2promotion, CUtensorMapFloatOOBfill);

namespace w8 {

constexpr int M_ = 2048, K_ = 1024, N_ = 3584;
constexpr int WA = 160, WB = 64;
constexpr int TN = 2 * WA + 2 * WB;
static_assert(TN == 448, "");
constexpr int X1 = 13;
constexpr int NSLOT = 7, SLOT = WA * 64;
constexpr int NSTG = 3, PFD = 700, NCONV = 5;
constexpr int NU = 48;
constexpr int UX = 32 + NSLOT;
constexpr int NJOB = 22;
constexpr int NCTA = 128;

constexpr int nA = 64, nWA = WA / 4, nWB = WB / 4;
constexpr int SEG1 = X1 * (nA + 2 * nWA);
constexpr int SEG2 = SEG1 + (16 - X1) * (nA + nWA);
constexpr int SEG3 = SEG2 + (16 - X1) * nWA;
constexpr int SEG4 = SEG3 + 16 * nWB;
constexpr int SEG5 = SEG4 + 16 * nWB;
static_assert(SEG5 == NJOB * NCTA, "");

constexpr int SM_A = 0;
constexpr int SM_RING = 131072;
constexpr int SM_STG = SM_RING + NSLOT * SLOT;
constexpr int SM_PAR = SM_STG + NSTG * 8192;
constexpr int SM_BAR = SM_PAR + 3 * TN * 2;
constexpr int B_FULLB = 0, B_FULLA = 48, B_GO = 64, B_PAR = 88, B_PSTEP = 92, B_AFREE = 100, B_NINIT = 102, B_FULLS = 102, B_END = 108;
constexpr int SM_TOTAL = SM_BAR + B_END * 8;
static_assert(SM_TOTAL <= 232448, "");

__device__ uint4 g_a8[M_ * K_ / 16];
__device__ uint4 g_b8[N_ * K_ / 16];
__device__ uint4 g_cs[16 * N_ * 2 / 16];
__device__ unsigned g_flag[16 * 16 + 8 * 64];
__device__ unsigned g_epoch[NCTA];
__device__ unsigned g_sink;
constexpr int SM_ALLOC = SM_TOTAL;

__device__ __forceinline__ void mbar_init(uint32_t bar, uint32_t cnt) {
    asm volatile("mbarrier.init.shared::cta.b64 [%0], %1;" :: "r"(bar), "r"(cnt) : "memory");
}
__device__ __forceinline__ void mbar_expect_tx(uint32_t bar, uint32_t bytes) {
    asm volatile("mbarrier.arrive.expect_tx.shared::cta.b64 _, [%0], %1;" :: "r"(bar), "r"(bytes) : "memory");
}
__device__ __forceinline__ void mbar_arrive(uint32_t bar) {
    asm volatile("mbarrier.arrive.shared::cta.b64 _, [%0];" :: "r"(bar) : "memory");
}
__device__ __forceinline__ void mbar_arrive_cluster(uint32_t bar) {
    asm volatile("mbarrier.arrive.shared::cluster.b64 _, [%0];" :: "r"(bar) : "memory");
}
__device__ __forceinline__ void mbar_wait(uint32_t bar, uint32_t parity = 0) {
    asm volatile("{\n.reg .pred p;\n.reg .u32 c;\n"
                 "mbarrier.try_wait.parity.shared::cta.b64 p, [%0], %1;\n"
                 "@p bra WAIT_DONE;\n"
                 "mov.u32 c, 0;\n"
                 "WAIT_LOOP:\n"
                 "mbarrier.try_wait.parity.shared::cta.b64 p, [%0], %1;\n"
                 "@p bra WAIT_DONE;\n"
                 "add.u32 c, c, 1;\nsetp.lt.u32 p, c, 0x100000;\n"
                 "@p bra WAIT_LOOP;\n"
                 "trap;\n"
                 "WAIT_DONE:\n}" :: "r"(bar), "r"(parity) : "memory");
}
__device__ __forceinline__ void mbar_wait2(uint32_t bar0, uint32_t bar1) {
    asm volatile("{\n.reg .pred p, q;\n.reg .u32 c;\nmov.u32 c, 0;\n"
                 "WAIT_LOOP:\n"
                 "mbarrier.try_wait.parity.shared::cta.b64 p, [%0], 0;\n"
                 "mbarrier.try_wait.parity.shared::cta.b64 q, [%1], 0;\n"
                 "and.pred p, p, q;\n"
                 "@p bra WAIT_DONE;\n"
                 "add.u32 c, c, 1;\nsetp.lt.u32 p, c, 0x100000;\n"
                 "@p bra WAIT_LOOP;\n"
                 "trap;\n"
                 "WAIT_DONE:\n}" :: "r"(bar0), "r"(bar1) : "memory");
}
__device__ __forceinline__ bool mbar_test(uint32_t bar) {
    uint32_t ok;
    asm volatile("{\n.reg .pred p;\nmbarrier.test_wait.parity.shared::cta.b64 p, [%1], 0;\nselp.u32 %0, 1, 0, p;\n}" : "=r"(ok) : "r"(bar) : "memory");
    return ok;
}
__device__ __forceinline__ bool mbar_test2(uint32_t bar0, uint32_t bar1) {
    uint32_t ok;
    asm volatile("{\n.reg .pred p, q;\nmbarrier.test_wait.parity.shared::cta.b64 p, [%1], 0;\n"
                 "mbarrier.test_wait.parity.shared::cta.b64 q, [%2], 0;\nand.pred p, p, q;\nselp.u32 %0, 1, 0, p;\n}"
                 : "=r"(ok) : "r"(bar0), "r"(bar1) : "memory");
    return ok;
}
__device__ __forceinline__ bool elect_one() {
    uint32_t ok;
    asm volatile("{\n.reg .pred p;\nelect.sync _|p, 0xffffffff;\nselp.u32 %0, 1, 0, p;\n}" : "=r"(ok));
    return ok;
}
__device__ __forceinline__ unsigned ld_acquire(const unsigned* p) {
    unsigned v;
    asm volatile("ld.acquire.gpu.global.u32 %0, [%1];" : "=r"(v) : "l"(p) : "memory");
    return v;
}
__device__ __forceinline__ unsigned ld_flag(const unsigned* p) {
    unsigned v;
    asm volatile("ld.relaxed.gpu.global.u32 %0, [%1];" : "=r"(v) : "l"(p) : "memory");
    return v;
}
__device__ __forceinline__ uint4 lds128(uint32_t a) {
    uint4 v;
    asm volatile("ld.shared.v4.b32 {%0,%1,%2,%3}, [%4];" : "=r"(v.x), "=r"(v.y), "=r"(v.z), "=r"(v.w) : "r"(a) : "memory");
    return v;
}
__device__ __forceinline__ void sts128(uint32_t a, uint4 v) {
    asm volatile("st.shared.v4.b32 [%0], {%1,%2,%3,%4};" :: "r"(a), "r"(v.x), "r"(v.y), "r"(v.z), "r"(v.w) : "memory");
}
__device__ __forceinline__ uint32_t lds32(uint32_t a) {
    uint32_t v;
    asm volatile("ld.shared.b32 %0, [%1];" : "=r"(v) : "r"(a) : "memory");
    return v;
}
__device__ __forceinline__ void sts32(uint32_t a, uint32_t v) {
    asm volatile("st.shared.b32 [%0], %1;" :: "r"(a), "r"(v) : "memory");
}
__device__ __forceinline__ void stg128(void* p, uint4 v) {
    asm volatile("st.global.v4.b32 [%0], {%1,%2,%3,%4};" :: "l"(p), "r"(v.x), "r"(v.y), "r"(v.z), "r"(v.w) : "memory");
}
__device__ __forceinline__ unsigned pack4(unsigned a, unsigned b, unsigned c, unsigned d) {
    unsigned lo, r;
    asm("cvt.pack.sat.s8.s32.b32 %0, %1, %2, 0;" : "=r"(lo) : "r"(d), "r"(c));
    asm("cvt.pack.sat.s8.s32.b32 %0, %1, %2, %3;" : "=r"(r) : "r"(b), "r"(a), "r"(lo));
    return r;
}
__device__ __forceinline__ void cpasync16(uint32_t dst, const void* src) {
    asm volatile("cp.async.cg.shared.global [%0], [%1], 16;" :: "r"(dst), "l"(src) : "memory");
}
__device__ __forceinline__ unsigned pf_l2(const void* p) {
    unsigned v;
    asm volatile("ld.global.cg.L2::128B.u32 %0, [%1];" : "=r"(v) : "l"(p) : "memory");
    return v;
}

constexpr uint32_t DESC_A_HI = 0x80000000u | (512 >> 4);
constexpr uint32_t DESC_B_HI = 128 >> 4;
template <int NR> __device__ __forceinline__ void wgmma_n160(int (&d)[NR], uint32_t alo, uint32_t blo, int scale_d) {
    asm volatile("{\n.reg .pred p;\n.reg .b64 da, db;\nsetp.ne.b32 p, %82, 0;\n"
        "mov.b64 da, {%80, %83};\nmov.b64 db, {%81, %84};\n"
        "wgmma.mma_async.sync.aligned.m64n160k32.s32.s8.s8 "
        "{%0, %1, %2, %3, %4, %5, %6, %7, %8, %9, %10, %11, %12, %13, %14, %15, "
        "%16, %17, %18, %19, %20, %21, %22, %23, %24, %25, %26, %27, %28, %29, %30, %31, "
        "%32, %33, %34, %35, %36, %37, %38, %39, %40, %41, %42, %43, %44, %45, %46, %47, "
        "%48, %49, %50, %51, %52, %53, %54, %55, %56, %57, %58, %59, %60, %61, %62, %63, "
        "%64, %65, %66, %67, %68, %69, %70, %71, %72, %73, %74, %75, %76, %77, %78, %79}, "
        "da, db, p;\n}\n"
        : "+r"(d[0]), "+r"(d[1]), "+r"(d[2]), "+r"(d[3]), "+r"(d[4]), "+r"(d[5]), "+r"(d[6]), "+r"(d[7]),
          "+r"(d[8]), "+r"(d[9]), "+r"(d[10]), "+r"(d[11]), "+r"(d[12]), "+r"(d[13]), "+r"(d[14]), "+r"(d[15]),
          "+r"(d[16]), "+r"(d[17]), "+r"(d[18]), "+r"(d[19]), "+r"(d[20]), "+r"(d[21]), "+r"(d[22]), "+r"(d[23]),
          "+r"(d[24]), "+r"(d[25]), "+r"(d[26]), "+r"(d[27]), "+r"(d[28]), "+r"(d[29]), "+r"(d[30]), "+r"(d[31]),
          "+r"(d[32]), "+r"(d[33]), "+r"(d[34]), "+r"(d[35]), "+r"(d[36]), "+r"(d[37]), "+r"(d[38]), "+r"(d[39]),
          "+r"(d[40]), "+r"(d[41]), "+r"(d[42]), "+r"(d[43]), "+r"(d[44]), "+r"(d[45]), "+r"(d[46]), "+r"(d[47]),
          "+r"(d[48]), "+r"(d[49]), "+r"(d[50]), "+r"(d[51]), "+r"(d[52]), "+r"(d[53]), "+r"(d[54]), "+r"(d[55]),
          "+r"(d[56]), "+r"(d[57]), "+r"(d[58]), "+r"(d[59]), "+r"(d[60]), "+r"(d[61]), "+r"(d[62]), "+r"(d[63]),
          "+r"(d[64]), "+r"(d[65]), "+r"(d[66]), "+r"(d[67]), "+r"(d[68]), "+r"(d[69]), "+r"(d[70]), "+r"(d[71]),
          "+r"(d[72]), "+r"(d[73]), "+r"(d[74]), "+r"(d[75]), "+r"(d[76]), "+r"(d[77]), "+r"(d[78]), "+r"(d[79])
        : "r"(alo), "r"(blo), "r"(scale_d), "r"(DESC_A_HI), "r"(DESC_B_HI));
}
template <int NR> __device__ __forceinline__ void wgmma_t128(int (&d)[NR], uint32_t alo, uint32_t blo, int scale_d) {
    asm volatile("{\n.reg .pred p;\n.reg .b64 da, db;\nsetp.ne.b32 p, %66, 0;\n"
        "mov.b64 da, {%64, %67};\nmov.b64 db, {%65, %68};\n"
        "wgmma.mma_async.sync.aligned.m64n128k32.s32.s8.s8 "
        "{%0, %1, %2, %3, %4, %5, %6, %7, %8, %9, %10, %11, %12, %13, %14, %15, "
        "%16, %17, %18, %19, %20, %21, %22, %23, %24, %25, %26, %27, %28, %29, %30, %31, "
        "%32, %33, %34, %35, %36, %37, %38, %39, %40, %41, %42, %43, %44, %45, %46, %47, "
        "%48, %49, %50, %51, %52, %53, %54, %55, %56, %57, %58, %59, %60, %61, %62, %63}, "
        "da, db, p;\n}\n"
        : "+r"(d[0]), "+r"(d[1]), "+r"(d[2]), "+r"(d[3]), "+r"(d[4]), "+r"(d[5]), "+r"(d[6]), "+r"(d[7]),
          "+r"(d[8]), "+r"(d[9]), "+r"(d[10]), "+r"(d[11]), "+r"(d[12]), "+r"(d[13]), "+r"(d[14]), "+r"(d[15]),
          "+r"(d[16]), "+r"(d[17]), "+r"(d[18]), "+r"(d[19]), "+r"(d[20]), "+r"(d[21]), "+r"(d[22]), "+r"(d[23]),
          "+r"(d[24]), "+r"(d[25]), "+r"(d[26]), "+r"(d[27]), "+r"(d[28]), "+r"(d[29]), "+r"(d[30]), "+r"(d[31]),
          "+r"(d[32]), "+r"(d[33]), "+r"(d[34]), "+r"(d[35]), "+r"(d[36]), "+r"(d[37]), "+r"(d[38]), "+r"(d[39]),
          "+r"(d[40]), "+r"(d[41]), "+r"(d[42]), "+r"(d[43]), "+r"(d[44]), "+r"(d[45]), "+r"(d[46]), "+r"(d[47]),
          "+r"(d[48]), "+r"(d[49]), "+r"(d[50]), "+r"(d[51]), "+r"(d[52]), "+r"(d[53]), "+r"(d[54]), "+r"(d[55]),
          "+r"(d[56]), "+r"(d[57]), "+r"(d[58]), "+r"(d[59]), "+r"(d[60]), "+r"(d[61]), "+r"(d[62]), "+r"(d[63])
        : "r"(alo), "r"(blo), "r"(scale_d), "r"(DESC_B_HI), "r"(DESC_A_HI));
}

__device__ __forceinline__ void wg_fence() { asm volatile("wgmma.fence.sync.aligned;" ::: "memory"); }
__device__ __forceinline__ void wg_commit() { asm volatile("wgmma.commit_group.sync.aligned;" ::: "memory"); }
template <int N> __device__ __forceinline__ void wg_wait() { asm volatile("wgmma.wait_group.sync.aligned %0;" :: "n"(N) : "memory"); }

struct Job { int src; int dst; };
__host__ __device__ constexpr int unit_of(int piece, int slab) {
    return piece < 2 ? (slab < X1 ? 2 * slab + piece : (piece ? 16 : X1) + slab) : 32 + (piece - 2) * 8 + (slab >> 1);
}
__device__ __forceinline__ Job decode_job(int g) {
    int slab, idx, piece;
    if (g < SEG2) {
        int r;
        if (g < SEG1) { slab = g / (nA + 2 * nWA); r = g - slab * (nA + 2 * nWA); }
        else { g -= SEG1; slab = g / (nA + nWA); r = g - slab * (nA + nWA); slab += X1; }
        piece = r < nA ? -1 : (r < nA + nWA ? 0 : 1);
        idx = r < nA ? r : r - nA - piece * nWA;
    } else if (g < SEG3) {
        g -= SEG2; slab = g / nWA; idx = g - slab * nWA; slab += X1; piece = 1;
    } else {
        g -= SEG3; piece = 2 + (g >> 8); slab = (g >> 4) & 15; idx = g & 15;
        static_assert(nWB == 16, "");
    }
    Job j;
    if (piece < 0) {
        const int flag = (idx >> 2) * 16 + slab;
        j.src = idx * 32 + (slab << 12);
        j.dst = (flag * 512 + (idx & 3) * 128) | (flag << 18);
    } else {
        const bool wide = piece < 2;
        const int w = wide ? WA : WB;
        const int nb = wide ? idx / (WA / 32) : idx / (WB / 32);
        const int J = idx - nb * (w / 32);
        const int cb = nb * TN + (wide ? piece * WA : 2 * WA - 2 * WB + piece * WB);
        j.src = cb + J * 32 + (slab << 12) + (wide ? 1 << 16 : 2 << 16);
        j.dst = (cb * (K_ / 16) + slab * w * 4 + J * 32) | ((256 + nb * 64 + unit_of(piece, slab)) << 18);
    }
    return j;
}
struct Coord { const CUtensorMap* m; int x, y, z; };
__device__ __forceinline__ Coord job_coord(const CUtensorMap* maps, int src) {
    const bool w = src >> 16;
    const int c0 = src & 0xFFF, slab = (src >> 12) & 15;
    return {maps + (w ? 1 : 0), w ? c0 : 0, w ? slab * 64 : slab * 2, w ? 0 : c0};
}
__device__ __forceinline__ void raw_load(const Coord& c, uint32_t dst, uint32_t bar) {
    mbar_expect_tx(bar, 8192);
    asm volatile("cp.async.bulk.tensor.3d.shared::cluster.global.tile.mbarrier::complete_tx::bytes [%0], [%1, {%2, %3, %4}], [%5];"
                 :: "r"(dst), "l"(c.m), "r"(c.x), "r"(c.y), "r"(c.z), "r"(bar) : "memory");
}
__device__ __forceinline__ void raw_prefetch(const Coord& c) {
    asm volatile("cp.async.bulk.prefetch.tensor.3d.L2.global.tile [%0, {%1, %2, %3}];"
                 :: "l"(c.m), "r"(c.x), "r"(c.y), "r"(c.z) : "memory");
}
__host__ __device__ constexpr unsigned unit_mask(int piece, int s0, int s1) {
    unsigned m = 0;
    for (int s = s0; s < s1; s++) m |= 1u << (unit_of(piece, s) & 31);
    return m;
}
__host__ __device__ constexpr int slot_of(int u) {
    return u < UX ? (u % NSLOT) * (SLOT / 2048) : u < UX + NSTG ? NSLOT * (SLOT / 2048) + (u - UX) * 4 : ((u - NSTG) % NSLOT) * (SLOT / 2048);
}
__host__ __device__ constexpr uint64_t slot_table(int piece) {
    uint64_t t = 0;
    if (piece < 2) for (int s = 0; s < 16; s++) t |= (uint64_t)(unit_of(piece, s) % NSLOT) << (4 * s);
    else for (int s = 0; s < 8; s++) t |= (uint64_t)slot_of(unit_of(piece, 2 * s)) << (8 * s);
    return t;
}
struct Maps { CUtensorMap m[3]; };

__device__ __forceinline__ uint32_t bf2_op_epi(int a, int b, uint32_t zc, uint32_t sx, uint32_t sw, uint32_t bi) {
    uint32_t v;
    float fa = __int2float_rn(a), fb = __int2float_rn(b);
    asm("cvt.rn.bf16x2.f32 %0, %1, %2;" : "=r"(v) : "f"(fb), "f"(fa));
    asm("sub.rn.bf16x2 %0, %0, %1;" : "+r"(v) : "r"(zc));
    asm("mul.rn.bf16x2 %0, %0, %1;" : "+r"(v) : "r"(sx));
    asm("mul.rn.bf16x2 %0, %0, %1;" : "+r"(v) : "r"(sw));
    asm("add.rn.bf16x2 %0, %0, %1;" : "+r"(v) : "r"(bi));
    return v;
}

struct Par { uint4 zc, sw, bi; };
__device__ __forceinline__ Par ld_par(uint32_t p) { return {lds128(p), lds128(p + TN * 2), lds128(p + TN * 4)}; }
__device__ __forceinline__ void epi_row(const int (&a)[WA / 2], int o, const Par& p, uint32_t sx2, char* out) {
    uint4 r;
    r.x = bf2_op_epi(a[o + 0], a[o + 4], p.zc.x, sx2, p.sw.x, p.bi.x);
    r.y = bf2_op_epi(a[o + 8], a[o + 12], p.zc.y, sx2, p.sw.y, p.bi.y);
    r.z = bf2_op_epi(a[o + 1], a[o + 5], p.zc.z, sx2, p.sw.z, p.bi.z);
    r.w = bf2_op_epi(a[o + 9], a[o + 13], p.zc.w, sx2, p.sw.w, p.bi.w);
    stg128(out, r);
}
template <int J, int JN>
__device__ __forceinline__ void epilogue(const int (&a)[WA / 2], Par& p, uint32_t par, uint32_t sx2, char* out) {
    epi_row(a, J * 16, p, sx2, out + J * 64);
    Par n = p;
    if (JN != J) n = ld_par(par + JN * 64);
    epi_row(a, J * 16 + 2, p, sx2, out + 8 * (N_ * 2) + J * 64);
    p = n;
}

__global__ void __cluster_dims__(2, 1, 1) __launch_bounds__(512, 1)
w8a8_kernel(const __grid_constant__ Maps maps, const char* __restrict__ qx, const char* __restrict__ qw, const __nv_bfloat16* __restrict__ scale_x, const int* __restrict__ zero_x,
            const __nv_bfloat16* __restrict__ scale_w, const __nv_bfloat16* __restrict__ bias,
            __nv_bfloat16* __restrict__ out) {
    extern __shared__ __align__(1024) unsigned char smem_raw[];
    const uint32_t sb = (uint32_t)__cvta_generic_to_shared(smem_raw);
    const uint32_t bars = sb + SM_BAR;
    const int warp = __shfl_sync(~0u, threadIdx.x >> 5, 0), lane = threadIdx.x & 31;
    const int b = blockIdx.x, rank = b & 1, nb = (b >> 1) & 7, mb = (b >> 4) * 2 + rank;

    if (warp >= 8) {
        asm volatile("setmaxnreg.dec.sync.aligned.u32 56;");
        if (warp >= 16 - NCONV) {
            const int cw = warp - (16 - NCONV);
            unsigned t0;
            asm volatile("mov.u32 %0, %clock;" : "=r"(t0));
            t0 += 100;
            asm volatile("barrier.cluster.arrive.relaxed.aligned;" ::: "memory");
            const Job mj = decode_job(min(lane, NJOB - 1) * NCTA + b);
            static_assert(NCONV == NSTG + 2 && NJOB == 22, "");
            const uint32_t s = sb + (cw < NSTG ? SM_STG + cw * 8192 : SM_A + (14 - NSTG + cw) * 8192);
            const uint32_t sbar = bars + (B_FULLS + cw) * 8;
            {
                const Coord c = job_coord(maps.m, __shfl_sync(~0u, mj.src, cw));
                if (elect_one()) {
                    mbar_init(sbar, 1);
                    asm volatile("fence.mbarrier_init.release.cluster;" ::: "memory");
                    unsigned t;
                    do { asm volatile("mov.u32 %0, %clock;" : "=r"(t)); } while ((int)(t - t0) < cw * PFD + (cw ? b * 88 : b * 0) / 16);
                    raw_load(c, s, sbar);
                }
                __syncwarp();
            }
            asm volatile("barrier.cluster.wait.aligned;" ::: "memory");
            t0 += b * 88 / 16;
            const int c4 = lane & 3, ln = (lane >> 2) * 2 + (c4 >> 1);
            const uint32_t rdA = ln * 128 + ((((c4 & 1) << 2) ^ (ln & 7)) << 4);
            const uint32_t rdB = (lane >> 3) * 2048 + (lane & 7) * 16;
            const int wrA = (lane >> 2) * 4 + (c4 ^ ((lane >> 3) & 3));
            uint32_t par = 0;
#pragma unroll 1
            for (int j = cw, jn; j < NJOB; j = jn, par ^= 1) {
                jn = j < 13 ? j + NCONV : (j < 15 ? 31 : j + NSTG);
                const int src = __shfl_sync(~0u, mj.src, j), dst = __shfl_sync(~0u, mj.dst, j);
                const int nsrc = __shfl_sync(~0u, mj.src, jn);
                const int kind = src >> 16;
                uint4 o[4];
                uint4* d;
                int dstep;
                mbar_wait(sbar, par);
                if (kind == 0) {
                    const uint32_t a0 = s + rdA;
                    d = g_a8 + (dst & 0x3FFFF) + wrA;
                    dstep = 32;
#pragma unroll
                    for (int i = 0; i < 4; i++) {
                        uint4 v0 = lds128(a0 + i * 2048), v1 = lds128((a0 ^ 16) + i * 2048);
                        uint4 v2 = lds128((a0 ^ 32) + i * 2048), v3 = lds128((a0 ^ 48) + i * 2048);
                        o[i].x = pack4(v0.x, v0.y, v0.z, v0.w); o[i].y = pack4(v1.x, v1.y, v1.z, v1.w);
                        o[i].z = pack4(v2.x, v2.y, v2.z, v2.w); o[i].w = pack4(v3.x, v3.y, v3.z, v3.w);
                    }
                } else {
                    const uint32_t a0 = s + rdB;
                    d = g_b8 + (dst & 0x3FFFF) + (lane >> 3) * (kind == 1 ? WA : WB) + (lane & 7);
                    dstep = 8;
#define CV_B(m, f)                                                                                    \
                    {                                                                                 \
                        uint4 v0 = lds128(a0 + m * 512), v1 = lds128(a0 + m * 512 + 128);             \
                        uint4 v2 = lds128(a0 + m * 512 + 256), v3 = lds128(a0 + m * 512 + 384);       \
                        o[0].f = pack4(v0.x, v1.x, v2.x, v3.x); o[1].f = pack4(v0.y, v1.y, v2.y, v3.y); \
                        o[2].f = pack4(v0.z, v1.z, v2.z, v3.z); o[3].f = pack4(v0.w, v1.w, v2.w, v3.w); \
                    }
                    CV_B(0, x) CV_B(1, y) CV_B(2, z) CV_B(3, w)
                }
#pragma unroll
                for (int i = 0; i < 4; i++) stg128(d + i * dstep, o[i]);
                unsigned tn;
                asm volatile("mov.u32 %0, %clock;" : "=r"(tn));
                const bool late = jn < NJOB && (int)(tn - t0) < jn * PFD;
                if (!late && elect_one()) {
                    if (jn < NJOB) { raw_load(job_coord(maps.m, nsrc), s, sbar); }
                    else if (jn == 31) mbar_arrive(bars + (B_AFREE - NSTG + cw) * 8);
                    else if (0 != 1) {
                        uint32_t ra;
                        asm("mapa.shared::cluster.u32 %0, %1, %2;" : "=r"(ra) : "r"(bars + (B_GO + ((UX + cw) >> 1)) * 8), "r"((UX + cw) & 1));
                        mbar_arrive_cluster(ra);
                    }
                }
                const int* csp = (const int*)d;
                unsigned csv = o[0].x;
                if (kind != 0) {
                    int cs[4];
#pragma unroll
                    for (int i = 0; i < 4; i++)
                        cs[i] = __dp4a((int)o[i].x, 0x01010101, __dp4a((int)o[i].y, 0x01010101,
                                __dp4a((int)o[i].z, 0x01010101, __dp4a((int)o[i].w, 0x01010101, 0))));
                    const int p01 = cs[0] + cs[1] * 65536, p23 = cs[2] + cs[3] * 65536;
                    const bool odd = lane & 8;
                    int v = (odd ? p23 : p01) + __shfl_xor_sync(~0u, odd ? p01 : p23, 8);
                    v += __shfl_xor_sync(~0u, v, 16);
                    int* p = (int*)g_cs + ((src >> 12) & 15) * (N_ / 2) + ((src & 0xFFF) >> 1) + (lane & 15);
                    if (lane < 16) *p = v;
                    csp = p; csv = v;
                }
#pragma unroll 1
                for (int it = 0; it < 1000; it++) {
                    bool ok = true;
                    if ((lane & 3) == 0) {
                        unsigned rb[5];
#pragma unroll
                        for (int i = 0; i < 4; i++)
                            asm volatile("ld.relaxed.gpu.global.u32 %0, [%1];" : "=r"(rb[i]) : "l"(d + i * dstep) : "memory");
                        asm volatile("ld.relaxed.gpu.global.u32 %0, [%1];" : "=r"(rb[4]) : "l"(csp) : "memory");
                        ok = rb[0] == o[0].x && rb[1] == o[1].x && rb[2] == o[2].x && rb[3] == o[3].x && rb[4] == csv;
                    }
                    if (__all_sync(~0u, ok)) break;
                }
                if (elect_one()) asm volatile("red.relaxed.gpu.global.add.u32 [%0], 1;" :: "l"(g_flag + ((unsigned)dst >> 18)) : "memory");
                __syncwarp();
                if (late && elect_one()) {
                    do { asm volatile("mov.u32 %0, %clock;" : "=r"(tn)); } while ((int)(tn - t0) < jn * PFD);
                    raw_load(job_coord(maps.m, nsrc), s, sbar);
                }
                __syncwarp();
            }
        } else if (warp == 8) {
            asm volatile("barrier.cluster.arrive.relaxed.aligned;" ::: "memory");
            const unsigned ep = *(volatile unsigned*)&g_epoch[b] + 1;
            const unsigned* f1 = g_flag + 256 + nb * 64 + lane;
            const unsigned* f2 = lane < 16 ? f1 + 32 : g_flag + mb * 16 + lane - 16;
            const unsigned t1 = ep * (WA / 32), t2 = ep * 4;
            static_assert(WB / 16 == 4, "");
            const unsigned n1 = lane == 0 ? unit_mask(0, 0, 8) : lane == 1 ? unit_mask(1, 0, 8) : lane == 2 ? unit_mask(0, 8, 16)
                              : lane == 3 ? unit_mask(1, 8, 16) : 0u;
            const unsigned n2 = lane < 4 ? 0u : 0xFFFFu;
            bool d1 = false, d2 = false, d3 = lane >= 5, fr = lane < 30;
            asm volatile("barrier.cluster.wait.aligned;" ::: "memory");
            for (int it = 0; 0 != 1; it++) {
                unsigned v1 = t1, v2 = t2;
                if (!d1) v1 = ld_flag(f1);
                if (!d2) v2 = ld_flag(f2);
                if (!fr) fr = mbar_test(bars + (B_AFREE - 30 + lane) * 8);
                if (!d2 && fr && (int)(v2 - t2) >= 0) {
                    d2 = true;
                    if (lane >= 16) {
                        asm volatile("fence.proxy.async.global;" ::: "memory");
                        asm volatile("cp.async.bulk.shared::cluster.global.mbarrier::complete_tx::bytes [%0], [%1], %2, [%3];"
                                     :: "r"(sb + SM_A + (lane - 16) * 8192), "l"((const char*)g_a8 + (mb * 16 + lane - 16) * 8192),
                                        "r"(8192), "r"(bars + (B_FULLA + lane - 16) * 8) : "memory");
                    } else if ((lane & 1) == rank) mbar_arrive(bars + (B_GO + 16 + (lane >> 1)) * 8);
                }
                if (!d1 && (int)(v1 - t1) >= 0) {
                    d1 = true;
                    if ((lane & 1) == rank) mbar_arrive(bars + (B_GO + (lane >> 1)) * 8);
                }
                const unsigned m1 = __ballot_sync(~0u, d1), m2 = __ballot_sync(~0u, d2);
                if (!d3 && (m1 & n1) == n1 && (m2 & n2) == n2) { d3 = true; mbar_arrive(bars + (B_PSTEP + lane) * 8); }
                if ((m1 & m2) == ~0u) break;
                if (it > (1 << 22)) __trap();
            }
        } else if (warp == 9) {
            asm volatile("barrier.cluster.arrive.relaxed.aligned;" ::: "memory");
            const int u = 2 * lane + rank;
            int so, fb;
            if (u < 2 * X1) { so = (u & 1) * (WA * K_) + (u >> 1) * (WA * 64); fb = (u & 1) * 24 + (u >> 1); }
            else if (u < X1 + 16) { so = (u - X1) * (WA * 64); fb = u - X1; }
            else if (u < 32) { so = WA * K_ + (u - 16) * (WA * 64); fb = 24 + u - 16; }
            else { so = 2 * WA * K_ + (u - 32) * (WB * 128); fb = u < 40 ? u - 16 : u; }
            const char* srcB = (const char*)g_b8 + nb * TN * K_ + so;
            const uint32_t dstB = sb + SM_RING + slot_of(u) * 2048;
            asm volatile("barrier.cluster.wait.aligned;" ::: "memory");
#pragma unroll 1
            for (int i = 0; i < NU / 2 && 0 != 1; i++) {
                mbar_wait(bars + (B_GO + i) * 8);
                if (lane == i) {
                    asm volatile("fence.proxy.async.global;" ::: "memory");
                    asm volatile("cp.async.bulk.shared::cluster.global.mbarrier::complete_tx::bytes.multicast::cluster [%0], [%1], %2, [%3], %4;"
                                 :: "r"(dstB), "l"(srcB), "r"(u < 32 ? WA * 64 : WB * 128), "r"(bars + (B_FULLB + fb) * 8), "h"((uint16_t)3) : "memory");
                }
                __syncwarp();
            }
        } else if (warp == 10) {
            unsigned pv, pv2;
            {
                static_assert(X1 > 0 && nA == 64 && nWA == 40, "");
                const int i = b - (b < 104 ? 64 : 104), q = i / 5;
                const char* p = b < 64 ? qx + (b * 32 + (lane >> 1)) * (K_ * 4) + (lane & 1) * 128
                                       : qw + lane * (N_ * 4) + (q * TN + (b < 104 ? 0 : WA) + (i - q * 5) * 32) * 4;
                pv = pf_l2(p);
                pv2 = pf_l2(p + (b < 64 ? 16 * K_ * 4 : 32 * N_ * 4));
                if (lane < 3) asm volatile("prefetch.tensormap [%0];" :: "l"(maps.m + lane) : "memory");
            }
            asm volatile("barrier.cluster.arrive.relaxed.aligned;" ::: "memory");
            if ((pv ^ pv2) == 0x40000000u) g_sink = pv;
            const float zxf = __bfloat162float(__float2bfloat16_rn((float)__ldg(zero_x)));
#pragma unroll 1
            for (int i = lane; i < TN / 4; i += 32) {
                const bool hi = i >= TN / 8;
                sts128(sb + SM_PAR + TN * 2 + i * 16, __ldg((const uint4*)((hi ? bias : scale_w) + nb * TN) + (hi ? i - TN / 8 : i)));
            }
            asm volatile("barrier.cluster.wait.aligned;" ::: "memory");
            int c[8], cs[8];
#pragma unroll
            for (int i = 0; i < 8; i++) { c[i] = 0; cs[i] = 0; }
#pragma unroll 1
            for (int st = 0; st < 5 && 0 != 1; st++) {
                const bool wide = st < 4;
                const int half = wide ? (st >> 1) : (lane >> 4);
                const int col = wide ? (st & 1) * WA + min(lane, WA / 8 - 1) * 8 : 2 * WA + (lane & 15) * 8;
                const uint4* src = g_cs + (half * 8 * N_ + nb * TN + col) / 8;
                mbar_wait(bars + (B_PSTEP + st) * 8);
                uint4 v[8];
#pragma unroll
                for (int i = 0; i < 8; i++) v[i] = __ldcg(src + i * (N_ / 8));
#pragma unroll
                for (int h = 0; h < 8; h += 4) {
                    const unsigned sv[4] = {v[h].x + v[h + 1].x + v[h + 2].x + v[h + 3].x, v[h].y + v[h + 1].y + v[h + 2].y + v[h + 3].y,
                                            v[h].z + v[h + 1].z + v[h + 2].z + v[h + 3].z, v[h].w + v[h + 1].w + v[h + 2].w + v[h + 3].w};
#pragma unroll
                    for (int i = 0; i < 4; i++) {
                        const int lo = (int)(short)(sv[i] & 0xFFFF);
                        c[2 * i] += lo; c[2 * i + 1] += ((int)(sv[i] - (unsigned)lo)) >> 16;
                    }
                }
                if (st >= 2) {
                    uint32_t z[4];
#pragma unroll
                    for (int i = 0; i < 8; i++) {
                        const int o = __shfl_xor_sync(~0u, c[i], 16);
                        if (!wide) c[i] += o;
                    }
#pragma unroll
                    for (int i = 0; i < 4; i++) {
                        const float lo = __bfloat162float(__float2bfloat16_rn((float)c[2 * i])) * zxf;
                        const float hi = __bfloat162float(__float2bfloat16_rn((float)c[2 * i + 1])) * zxf;
                        asm("cvt.rn.bf16x2.f32 %0, %1, %2;" : "=r"(z[i]) : "f"(hi), "f"(lo));
                    }
                    const uint32_t za = sb + SM_PAR + ((col & ~31) + (col & 8) * 2 + ((col >> 3) & 2)) * 2;
#pragma unroll
                    for (int i = 0; i < 4; i++) sts32(za + i * 8, z[i]);
                    __syncwarp();
                    if (lane == 0) { mbar_arrive(bars + (B_PAR + st - 2) * 8); }
#pragma unroll
                    for (int i = 0; i < 8; i++) c[i] = 0;
                }
#pragma unroll
                for (int i = 0; i < 8; i++) { const int t = c[i]; c[i] = cs[i]; cs[i] = t; }
            }
        } else {
            asm volatile("barrier.cluster.arrive.relaxed.aligned;" ::: "memory");
            asm volatile("barrier.cluster.wait.aligned;" ::: "memory");
        }
    } else {
        asm volatile("setmaxnreg.inc.sync.aligned.u32 200;");
        {
            constexpr int PER = (B_NINIT + 7) / 8;
            if (elect_one()) {
#pragma unroll 1
                for (int i = warp * PER; i < min(warp * PER + PER, B_NINIT); i++)
                    {
                    const int u = 2 * (i - B_GO) + rank;
                    mbar_init(bars + i * 8, (i < B_GO || i >= B_PAR || u < NSLOT) ? 1 : (u >= UX && u < UX + NSTG) ? 3 : 9);
                }
            }
            __syncwarp();
            const int i = warp * PER + lane;
            if (lane < PER && i < B_GO) mbar_expect_tx(bars + i * 8, (i < 16 || (i >= 24 && i < 40)) ? WA * 64 : 8192);
            static_assert(WB * 128 == 8192, "");
            asm volatile("fence.mbarrier_init.release.cluster;" ::: "memory");
        }
        asm volatile("barrier.cluster.arrive.relaxed.aligned;" ::: "memory");
        const int wg = warp >> 2;
        const uint32_t sd = (sb & 0x3FFFF) >> 4;
        const unsigned short sxr = __ldg((const unsigned short*)scale_x);
        const uint32_t sx2 = (uint32_t)sxr * 0x10001u;
        char* orow = (char*)out + (size_t)(mb * 128 + (warp & 3) * 16 + (lane >> 2)) * (N_ * 2) + (nb * TN + (lane & 3) * 8 + wg * WA) * 2;
        const uint32_t par = sb + SM_PAR + (lane & 3) * 16 + wg * WA * 2;
        uint32_t reladdr;
        int rell;
        {
            const int u = lane < 16 ? (lane < X1 ? 2 * lane + wg : (wg ? 16 : X1) + lane) : 16 + wg * 8 + lane;
            const int v = u + (u < 32 ? NSLOT : NSLOT + NSTG);
            rell = (lane < 24 && v < NU) ? lane : 99;
            asm("mapa.shared::cluster.u32 %0, %1, %2;" : "=r"(reladdr) : "r"(bars + (B_GO + (v >> 1)) * 8), "r"(v & 1));
        }
        asm volatile("barrier.cluster.wait.aligned;" ::: "memory");
        int a0[WA / 2], a1[WA / 2];
        uint32_t barB = bars + (B_FULLB + wg * 24) * 8;
        bool ready = false;
#define HAND_BACK(done) if (rell <= (done)) { mbar_arrive_cluster(reladdr); rell = 99; }
        if (0 != 1) {
            wg_fence();
            {
                uint64_t tbl = wg ? slot_table(1) : slot_table(0);
                uint32_t da = (sd + (SM_A >> 4)) | (1 << 16);
#pragma unroll 1
                for (int s = 0; s < 16; s++) {
                    const uint32_t db = ((sd + (SM_RING >> 4)) | (WA << 16)) + ((uint32_t)tbl & 15) * (SLOT >> 4);
                    const bool starved = !ready && !mbar_test2(bars + (B_FULLA + s) * 8, barB);
                    if (starved) {
                        wg_wait<0>();
                        HAND_BACK(s - 1)
                        mbar_wait2(bars + (B_FULLA + s) * 8, barB);
                    }
                    wgmma_n160(a0, da, db, s);
                    wgmma_n160(a1, da + 256, db, s);
                    wgmma_n160(a0, da + 2, db + 2 * WA, 1);
                    wgmma_n160(a1, da + 258, db + 2 * WA, 1);
                    wg_commit();
                    HAND_BACK(s - 2)
                    tbl >>= 4; da += 512; barB += 8;
                    ready = mbar_test2(bars + (B_FULLA + min(s + 1, 15)) * 8, barB);
                    wg_wait<1>();
                }
            }
            HAND_BACK(14)
            wg_wait<0>();
            HAND_BACK(15)
            mbar_wait(bars + (B_PAR + wg) * 8);
            Par P = ld_par(par);
            char* const orow1 = orow + 64 * (N_ * 2);
            epilogue<0, 1>(a0, P, par, sx2, orow); epilogue<1, 2>(a0, P, par, sx2, orow);
            epilogue<2, 3>(a0, P, par, sx2, orow); epilogue<3, 0>(a0, P, par, sx2, orow);
            int t[64];
            wg_fence();
            {
                uint64_t tbl = wg ? slot_table(3) : slot_table(2);
                uint32_t da = (sd + (SM_A >> 4)) | (1 << 16);
#pragma unroll
                for (int i = 16; i < 24; i++) {
                    const uint32_t db = ((sd + (SM_RING >> 4)) | (WB << 16)) + ((uint32_t)tbl & 255) * 128;
                    const bool starved = !ready && !mbar_test(barB);
                    if (starved) {
                        wg_wait<0>();
                        HAND_BACK(i - 1)
                        mbar_wait(barB);
                    }
#pragma unroll
                    for (int k = 0; k < 4; k++) wgmma_t128(t, db + k * 2 * WB, da + (k >> 1) * 512 + (k & 1) * 2, k ? 1 : i - 16);
                    wg_commit();
                    HAND_BACK(i - 2)
                    tbl >>= 8; da += 1024; barB += 8;
                    ready = mbar_test(barB);
                    switch (i) {
                        case 16: epilogue<0, 0>(a1, P, par, sx2, orow1); break;
                        case 17: epilogue<1, 1>(a1, P, par, sx2, orow1); break;
                        case 18: epilogue<2, 2>(a1, P, par, sx2, orow1); break;
                        case 19: epilogue<3, 3>(a1, P, par, sx2, orow1); break;
                        case 20: epilogue<4, 4>(a1, P, par, sx2, orow1); break;
                        case 21: epilogue<4, 4>(a0, P, par, sx2, orow); break;
                        default: break;
                    }
                    if (i < 20) P = ld_par(par + (i - 15) * 64);
                    wg_wait<1>();
                }
            }
            HAND_BACK(22)
            mbar_wait(bars + (B_PAR + 2) * 8);
            const int w = warp & 3, q = lane >> 2, c0 = (w >> 1) * 32 + q * 4 + (w & 1) * 2;
            const uint32_t pp = sb + SM_PAR + (2 * WA + wg * WB + c0) * 2;
            const uint32_t zc = lds32(pp), sw = lds32(pp + TN * 2), bi = lds32(pp + TN * 4);
            const int r0 = (lane & 3) * 2;
            const uint32_t st0 = r0 * 128 + (((c0 >> 3) ^ r0) << 4) + (c0 & 7) * 2, st1 = (st0 ^ 16) + 128;
            wg_wait<0>();
            asm volatile("bar.sync %0, 128;" :: "r"(3 + wg) : "memory");
#pragma unroll
            for (int h = 0; h < 2; h++) {
                const uint32_t buf = sb + SM_RING + (wg ? slot_of(UX + 1 + h) : slot_of(UX - 1 + h)) * 2048;
#pragma unroll
                for (int j = 0; j < 8; j++) {
                    const int o = h * 32 + j * 4;
                    sts32(buf + st0 + j * 1024, bf2_op_epi(t[o], t[o + 2], zc, sx2, sw, bi));
                    sts32(buf + st1 + j * 1024, bf2_op_epi(t[o + 1], t[o + 3], zc, sx2, sw, bi));
                }
                asm volatile("fence.proxy.async.shared::cta;" ::: "memory");
                asm volatile("bar.sync %0, 128;" :: "r"(3 + wg) : "memory");
                if (w == 0 && elect_one())
                    asm volatile("cp.async.bulk.tensor.2d.global.shared::cta.tile.bulk_group [%0, {%1, %2}], [%3];"
                                 :: "l"(maps.m + 2), "r"(nb * TN + 2 * WA + wg * WB), "r"(mb * 128 + h * 64), "r"(buf) : "memory");
            }
            if (w == 0) {
                asm volatile("cp.async.bulk.commit_group;" ::: "memory");
                asm volatile("cp.async.bulk.wait_group.read 0;" ::: "memory");
            }
        }
        if (threadIdx.x == 128) asm volatile("red.relaxed.gpu.global.add.u32 [%0], 1;" :: "l"(g_epoch + b) : "memory");
    }
}

static void launch(EncodeFn encode, void* const* d_in, void* d_out) {
    Maps maps;
    CUtensorMap &mx = maps.m[0], &mw = maps.m[1];
    {
        const cuuint64_t dim[3] = {32, K_ / 32, M_}, str[2] = {128, K_ * 4};
        const cuuint32_t box[3] = {32, 2, 32}, es[3] = {1, 1, 1};
        encode(&mx, CU_TENSOR_MAP_DATA_TYPE_INT32, 3, d_in[0], dim, str, box, es, CU_TENSOR_MAP_INTERLEAVE_NONE,
               CU_TENSOR_MAP_SWIZZLE_128B, CU_TENSOR_MAP_L2_PROMOTION_NONE, CU_TENSOR_MAP_FLOAT_OOB_FILL_NONE);
    }
    {
        const cuuint64_t dim[3] = {N_, K_, 1}, str[2] = {N_ * 4, (cuuint64_t)N_ * K_ * 4};
        const cuuint32_t box[3] = {32, 64, 1}, es[3] = {1, 1, 1};
        encode(&mw, CU_TENSOR_MAP_DATA_TYPE_INT32, 3, d_in[1], dim, str, box, es, CU_TENSOR_MAP_INTERLEAVE_NONE,
               CU_TENSOR_MAP_SWIZZLE_NONE, CU_TENSOR_MAP_L2_PROMOTION_NONE, CU_TENSOR_MAP_FLOAT_OOB_FILL_NONE);
    }
    {
        const cuuint64_t dim[2] = {N_, M_}, str[1] = {N_ * 2};
        const cuuint32_t box[2] = {WB, 64}, es[2] = {1, 1};
        encode(&maps.m[2], CU_TENSOR_MAP_DATA_TYPE_BFLOAT16, 2, d_out, dim, str, box, es, CU_TENSOR_MAP_INTERLEAVE_NONE,
               CU_TENSOR_MAP_SWIZZLE_128B, CU_TENSOR_MAP_L2_PROMOTION_NONE, CU_TENSOR_MAP_FLOAT_OOB_FILL_NONE);
    }
    w8a8_kernel<<<NCTA, 512, SM_ALLOC>>>(maps, (const char*)d_in[0], (const char*)d_in[1], (const __nv_bfloat16*)d_in[2], (const int*)d_in[3],
                                         (const __nv_bfloat16*)d_in[4], (const __nv_bfloat16*)d_in[5],
                                         (__nv_bfloat16*)d_out);
}

}

extern "C" void kernel_launch(void* const* d_in, const int* in_sizes, int n_in, void* d_out, int out_size) {
    using namespace ra;
    static EncodeFn encode = nullptr;
    static Scratch* scr = nullptr;
    static const JobTable* jobs = nullptr;
    static bool fits = false;
    if (!encode) {
        void* fn = nullptr;
        cudaDriverEntryPointQueryResult qr;
        cudaGetDriverEntryPoint("cuTensorMapEncodeTiled", &fn, cudaEnableDefault, &qr);
        encode = (EncodeFn)fn;
        cudaGetSymbolAddress((void**)&scr, g_scratch);
        cudaGetSymbolAddress((void**)&jobs, g_jobs);
        cudaFuncSetAttribute(w8a8_kernel, cudaFuncAttributeMaxDynamicSharedMemorySize, SM_ALLOC);
        cudaFuncSetAttribute(w8a8_kernel, cudaFuncAttributeNonPortableClusterSizeAllowed, 1);
        cudaFuncSetAttribute(w8a8_side, cudaFuncAttributeMaxDynamicSharedMemorySize, SM_ALLOC);
        cudaFuncSetAttribute(w8::w8a8_kernel, cudaFuncAttributeMaxDynamicSharedMemorySize, w8::SM_ALLOC);
        cudaLaunchConfig_t oc = {};
        oc.gridDim = dim3(NCTA); oc.blockDim = dim3(512); oc.dynamicSmemBytes = SM_ALLOC;
        cudaLaunchAttribute oa[1];
        oa[0].id = cudaLaunchAttributeClusterDimension; oa[0].val.clusterDim.x = CS; oa[0].val.clusterDim.y = 1; oa[0].val.clusterDim.z = 1;
        oc.attrs = oa; oc.numAttrs = 1;
        int nc = 0, dev = 0, sms = 0;
        cudaGetDevice(&dev);
        cudaDeviceGetAttribute(&sms, cudaDevAttrMultiProcessorCount, dev);
        fits = cudaOccupancyMaxActiveClusters(&nc, w8a8_kernel, &oc) == cudaSuccess && nc >= NCTA / CS && sms >= NCTA + NSIDE;
        cudaGetLastError();
    }
    if (!fits) { w8::launch(encode, d_in, d_out); return; }
    CUtensorMap map;
    {
        const cuuint64_t dim[2] = {N_, M_}, str[1] = {N_ * 2};
        const cuuint32_t box[2] = {64, 32}, es[2] = {1, 1};
        encode(&map, CU_TENSOR_MAP_DATA_TYPE_BFLOAT16, 2, d_out, dim, str, box, es, CU_TENSOR_MAP_INTERLEAVE_NONE,
               CU_TENSOR_MAP_SWIZZLE_128B, CU_TENSOR_MAP_L2_PROMOTION_NONE, CU_TENSOR_MAP_FLOAT_OOB_FILL_NONE);
    }
    w8a8_kernel<<<NCTA, 512, SM_ALLOC, cudaStreamPerThread>>>((const char*)d_in[0], (const char*)d_in[1], scr, jobs, (const __nv_bfloat16*)d_in[4],
                                                             (const __nv_bfloat16*)d_in[5], (const __nv_bfloat16*)d_in[2], (const int*)d_in[3], map);
    cudaLaunchConfig_t cfg = {};
    cfg.gridDim = dim3(NSIDE); cfg.blockDim = dim3(512); cfg.dynamicSmemBytes = SM_ALLOC; cfg.stream = cudaStreamPerThread;
    cudaLaunchAttribute at[1];
    at[0].id = cudaLaunchAttributeProgrammaticStreamSerialization; at[0].val.programmaticStreamSerializationAllowed = 1;
    cfg.attrs = at; cfg.numAttrs = 1;
    cudaLaunchKernelEx(&cfg, w8a8_side, (const char*)d_in[1], scr, (const __nv_bfloat16*)d_in[4], (const __nv_bfloat16*)d_in[5], (const __nv_bfloat16*)d_in[2],
                       (const int*)d_in[3], map);
}
```

```cpp
#include <cuda_runtime.h>
#include <cuda.h>
#include <cuda_bf16.h>
#include <stdint.h>

namespace ra {

constexpr int CFG_D = 2;
constexpr int CFG_P0 = 615;
constexpr int CFG_PF0 = 0;
constexpr int CFG_SLEEP = 400;
constexpr int CFG_NINIT = 2;
constexpr int CFG_NR = 10;
constexpr int CFG_PZ = 16;
constexpr int CFG_NOC = 12;
constexpr int CFG_YP = 1100;
constexpr int CFG_YH = 1000;
constexpr int CFG_YH0 = 1700;
constexpr int CFG_Y0 = 1000;

constexpr int M_ = 2048, K_ = 1024, N_ = 3584;
constexpr int CS = 16, NCTA = 112, NSIDE = 20, TN = 448;
constexpr int NRING = CFG_NR, NCONV = 6, NJOB = 26, NG = 56, NOUT = 4, D_ = CFG_D;

constexpr int SM_A = 0;
constexpr int SM_RING = 131072;
constexpr int SM_OUT = SM_RING + NRING * 8192;
constexpr int SM_PAR = SM_OUT + NOUT * 4096;
constexpr int SM_SUM = SM_PAR + 1024;
constexpr int SM_BAR = SM_SUM + 256;
constexpr int B_FULL = 0, B_PAR = 64, B_AFREE = 72, B_TURN = 74, B_OFREE = 76, B_SUM = 108, B_GO = 112, B_OFULL = 144, B_END = 148;
constexpr int SM_TOTAL = SM_BAR + B_END * 8;

constexpr int FS = 32;
struct __align__(2048) Scratch {
    uint4 a8[M_ * K_ / 16];
    uint4 b8[N_ * K_ / 16];
    unsigned cs[32 * TN / 2];
    unsigned flag[CS * FS + 64];
    unsigned epoch[NCTA + NSIDE];
};
__device__ Scratch g_scratch;
constexpr int SM_ALLOC = SM_TOTAL;
static_assert(SM_ALLOC <= 232448, "");

__device__ __forceinline__ void mbar_init(uint32_t bar, uint32_t cnt) {
    asm volatile("mbarrier.init.shared::cta.b64 [%0], %1;" :: "r"(bar), "r"(cnt) : "memory");
}
__device__ __forceinline__ void mbar_expect_tx(uint32_t bar, uint32_t bytes) {
    asm volatile("mbarrier.arrive.expect_tx.shared::cta.b64 _, [%0], %1;" :: "r"(bar), "r"(bytes) : "memory");
}
__device__ __forceinline__ void mbar_arrive(uint32_t bar) {
    asm volatile("mbarrier.arrive.shared::cta.b64 _, [%0];" :: "r"(bar) : "memory");
}
__device__ __forceinline__ void mbar_arrive_cluster_if(uint32_t bar, int a, int b) {
    asm volatile("{\n.reg .pred p;\nsetp.eq.s32 p, %1, %2;\n@p mbarrier.arrive.shared::cluster.b64 _, [%0];\n}" :: "r"(bar), "r"(a), "r"(b) : "memory");
}
__device__ __forceinline__ void mbar_wait(uint32_t bar) {
    asm volatile("{\n.reg .pred p;\nWAIT_LOOP:\nmbarrier.try_wait.parity.shared::cta.b64 p, [%0], 0;\n@!p bra WAIT_LOOP;\n}" :: "r"(bar) : "memory");
}
__device__ __forceinline__ void mbar_wait_cluster(uint32_t bar) {
    asm volatile("{\n.reg .pred p;\nWAIT_LOOP:\nmbarrier.try_wait.parity.relaxed.cluster.shared::cta.b64 p, [%0], 0;\n@!p bra WAIT_LOOP;\n"
                 "fence.acquire.sync_restrict::shared::cluster.cluster;\n}" :: "r"(bar) : "memory");
}
__device__ __forceinline__ void mbar_wait2(uint32_t bar0, uint32_t bar1) { mbar_wait(bar0); mbar_wait(bar1); }
__device__ __forceinline__ bool mbar_test(uint32_t bar) {
    uint32_t ok;
    asm volatile("{\n.reg .pred p;\nmbarrier.test_wait.parity.shared::cta.b64 p, [%1], 0;\nselp.u32 %0, 1, 0, p;\n}" : "=r"(ok) : "r"(bar) : "memory");
    return ok;
}
__device__ __forceinline__ bool mbar_test2(uint32_t bar0, uint32_t bar1) {
    uint32_t ok;
    asm volatile("{\n.reg .pred p, q;\nmbarrier.test_wait.parity.shared::cta.b64 p, [%1], 0;\n"
                 "mbarrier.test_wait.parity.shared::cta.b64 q, [%2], 0;\nand.pred p, p, q;\nselp.u32 %0, 1, 0, p;\n}"
                 : "=r"(ok) : "r"(bar0), "r"(bar1) : "memory");
    return ok;
}
__device__ __forceinline__ bool elect_one() {
    uint32_t ok;
    asm volatile("{\n.reg .pred p;\nelect.sync _|p, 0xffffffff;\nselp.u32 %0, 1, 0, p;\n}" : "=r"(ok));
    return ok;
}
__device__ __forceinline__ uint32_t mapa(uint32_t a, uint32_t cta) {
    uint32_t r;
    asm("mapa.shared::cluster.u32 %0, %1, %2;" : "=r"(r) : "r"(a), "r"(cta));
    return r;
}
__device__ __forceinline__ void st_async32(uint32_t a, uint32_t v, uint32_t bar) {
    asm volatile("st.async.shared::cluster.mbarrier::complete_tx::bytes.b32 [%0], %1, [%2];" :: "r"(a), "r"(v), "r"(bar) : "memory");
}
__device__ __forceinline__ unsigned ld_flag(const unsigned* p) {
    unsigned v;
    asm volatile("ld.relaxed.gpu.global.u32 %0, [%1];" : "=r"(v) : "l"(p) : "memory");
    return v;
}
__device__ __forceinline__ unsigned clk() { unsigned t; asm volatile("mov.u32 %0, %clock;" : "=r"(t)); return t; }
__device__ __forceinline__ uint32_t lds32(uint32_t a) {
    uint32_t v;
    asm volatile("ld.shared.b32 %0, [%1];" : "=r"(v) : "r"(a) : "memory");
    return v;
}
__device__ __forceinline__ void sts32(uint32_t a, uint32_t v) {
    asm volatile("st.shared.b32 [%0], %1;" :: "r"(a), "r"(v) : "memory");
}
__device__ __forceinline__ void stg128(void* p, uint4 v) {
    asm volatile("st.global.v4.b32 [%0], {%1,%2,%3,%4};" :: "l"(p), "r"(v.x), "r"(v.y), "r"(v.z), "r"(v.w) : "memory");
}
__device__ __forceinline__ unsigned pack4(unsigned a, unsigned b, unsigned c, unsigned d) {
    unsigned lo, r;
    asm("cvt.pack.sat.s8.s32.b32 %0, %1, %2, 0;" : "=r"(lo) : "r"(d), "r"(c));
    asm("cvt.pack.sat.s8.s32.b32 %0, %1, %2, %3;" : "=r"(r) : "r"(b), "r"(a), "r"(lo));
    return r;
}
constexpr uint32_t DESC_A_HI = 256 >> 4;
constexpr uint32_t DESC_B_HI = 0x80000000u | (512 >> 4);
__device__ __forceinline__ void mma_unit2(int (&d)[64], int (&e)[64], uint32_t alo, uint32_t blo, int scale_d) {
    asm volatile("{\n.reg .pred p;\n.reg .b64 da, db;\nsetp.ne.b32 p, %130, 0;\n"
        "mov.b64 da, {%128, %131};\nmov.b64 db, {%129, %132};\n"
        "wgmma.mma_async.sync.aligned.m64n128k32.s32.s8.s8 "
        "{%0, %1, %2, %3, %4, %5, %6, %7, %8, %9, %10, %11, %12, %13, %14, %15, "
        "%16, %17, %18, %19, %20, %21, %22, %23, %24, %25, %26, %27, %28, %29, %30, %31, "
        "%32, %33, %34, %35, %36, %37, %38, %39, %40, %41, %42, %43, %44, %45, %46, %47, "
        "%48, %49, %50, %51, %52, %53, %54, %55, %56, %57, %58, %59, %60, %61, %62, %63}, "
        "da, db, p;\n"
        "add.s64 da, da, 128;\n"
        "wgmma.mma_async.sync.aligned.m64n128k32.s32.s8.s8 "
        "{%64, %65, %66, %67, %68, %69, %70, %71, %72, %73, %74, %75, %76, %77, %78, %79, "
        "%80, %81, %82, %83, %84, %85, %86, %87, %88, %89, %90, %91, %92, %93, %94, %95, "
        "%96, %97, %98, %99, %100, %101, %102, %103, %104, %105, %106, %107, %108, %109, %110, %111, "
        "%112, %113, %114, %115, %116, %117, %118, %119, %120, %121, %122, %123, %124, %125, %126, %127}, "
        "da, db, p;\n"
        "add.s64 da, da, 128;\nadd.s64 db, db, 2;\n"
        "wgmma.mma_async.sync.aligned.m64n128k32.s32.s8.s8 "
        "{%0, %1, %2, %3, %4, %5, %6, %7, %8, %9, %10, %11, %12, %13, %14, %15, "
        "%16, %17, %18, %19, %20, %21, %22, %23, %24, %25, %26, %27, %28, %29, %30, %31, "
        "%32, %33, %34, %35, %36, %37, %38, %39, %40, %41, %42, %43, %44, %45, %46, %47, "
        "%48, %49, %50, %51, %52, %53, %54, %55, %56, %57, %58, %59, %60, %61, %62, %63}, "
        "da, db, 1;\n"
        "add.s64 da, da, 128;\n"
        "wgmma.mma_async.sync.aligned.m64n128k32.s32.s8.s8 "
        "{%64, %65, %66, %67, %68, %69, %70, %71, %72, %73, %74, %75, %76, %77, %78, %79, "
        "%80, %81, %82, %83, %84, %85, %86, %87, %88, %89, %90, %91, %92, %93, %94, %95, "
        "%96, %97, %98, %99, %100, %101, %102, %103, %104, %105, %106, %107, %108, %109, %110, %111, "
        "%112, %113, %114, %115, %116, %117, %118, %119, %120, %121, %122, %123, %124, %125, %126, %127}, "
        "da, db, 1;\n"
        "wgmma.commit_group.sync.aligned;\n}\n"
        : "+r"(d[0]), "+r"(d[1]), "+r"(d[2]), "+r"(d[3]), "+r"(d[4]), "+r"(d[5]), "+r"(d[6]), "+r"(d[7]),
          "+r"(d[8]), "+r"(d[9]), "+r"(d[10]), "+r"(d[11]), "+r"(d[12]), "+r"(d[13]), "+r"(d[14]), "+r"(d[15]),
          "+r"(d[16]), "+r"(d[17]), "+r"(d[18]), "+r"(d[19]), "+r"(d[20]), "+r"(d[21]), "+r"(d[22]), "+r"(d[23]),
          "+r"(d[24]), "+r"(d[25]), "+r"(d[26]), "+r"(d[27]), "+r"(d[28]), "+r"(d[29]), "+r"(d[30]), "+r"(d[31]),
          "+r"(d[32]), "+r"(d[33]), "+r"(d[34]), "+r"(d[35]), "+r"(d[36]), "+r"(d[37]), "+r"(d[38]), "+r"(d[39]),
          "+r"(d[40]), "+r"(d[41]), "+r"(d[42]), "+r"(d[43]), "+r"(d[44]), "+r"(d[45]), "+r"(d[46]), "+r"(d[47]),
          "+r"(d[48]), "+r"(d[49]), "+r"(d[50]), "+r"(d[51]), "+r"(d[52]), "+r"(d[53]), "+r"(d[54]), "+r"(d[55]),
          "+r"(d[56]), "+r"(d[57]), "+r"(d[58]), "+r"(d[59]), "+r"(d[60]), "+r"(d[61]), "+r"(d[62]), "+r"(d[63]),
          "+r"(e[0]), "+r"(e[1]), "+r"(e[2]), "+r"(e[3]), "+r"(e[4]), "+r"(e[5]), "+r"(e[6]), "+r"(e[7]),
          "+r"(e[8]), "+r"(e[9]), "+r"(e[10]), "+r"(e[11]), "+r"(e[12]), "+r"(e[13]), "+r"(e[14]), "+r"(e[15]),
          "+r"(e[16]), "+r"(e[17]), "+r"(e[18]), "+r"(e[19]), "+r"(e[20]), "+r"(e[21]), "+r"(e[22]), "+r"(e[23]),
          "+r"(e[24]), "+r"(e[25]), "+r"(e[26]), "+r"(e[27]), "+r"(e[28]), "+r"(e[29]), "+r"(e[30]), "+r"(e[31]),
          "+r"(e[32]), "+r"(e[33]), "+r"(e[34]), "+r"(e[35]), "+r"(e[36]), "+r"(e[37]), "+r"(e[38]), "+r"(e[39]),
          "+r"(e[40]), "+r"(e[41]), "+r"(e[42]), "+r"(e[43]), "+r"(e[44]), "+r"(e[45]), "+r"(e[46]), "+r"(e[47]),
          "+r"(e[48]), "+r"(e[49]), "+r"(e[50]), "+r"(e[51]), "+r"(e[52]), "+r"(e[53]), "+r"(e[54]), "+r"(e[55]),
          "+r"(e[56]), "+r"(e[57]), "+r"(e[58]), "+r"(e[59]), "+r"(e[60]), "+r"(e[61]), "+r"(e[62]), "+r"(e[63])
        : "r"(alo), "r"(blo), "r"(scale_d), "n"(DESC_A_HI), "n"(DESC_B_HI) : "memory");
}
__device__ __forceinline__ bool mma_pair(int (&d)[64], uint32_t alo, uint32_t blo, int scale_d, uint32_t bar, uint32_t rel, int ka, int kb) {
    uint32_t ok;
    asm volatile("{\n.reg .pred p, q, r;\n.reg .b64 da, db;\nsetp.ne.b32 p, %67, 0;\n"
        "mov.b64 da, {%65, %68};\nmov.b64 db, {%66, %69};\n"
        "wgmma.mma_async.sync.aligned.m64n128k32.s32.s8.s8 "
        "{%0, %1, %2, %3, %4, %5, %6, %7, %8, %9, %10, %11, %12, %13, %14, %15, "
        "%16, %17, %18, %19, %20, %21, %22, %23, %24, %25, %26, %27, %28, %29, %30, %31, "
        "%32, %33, %34, %35, %36, %37, %38, %39, %40, %41, %42, %43, %44, %45, %46, %47, "
        "%48, %49, %50, %51, %52, %53, %54, %55, %56, %57, %58, %59, %60, %61, %62, %63}, "
        "da, db, p;\n"
        "setp.eq.s32 r, %72, %73;\n@r mbarrier.arrive.shared::cluster.b64 _, [%71];\n"
        "add.s64 da, da, 128;\nadd.s64 db, db, 2;\n"
        "wgmma.mma_async.sync.aligned.m64n128k32.s32.s8.s8 "
        "{%0, %1, %2, %3, %4, %5, %6, %7, %8, %9, %10, %11, %12, %13, %14, %15, "
        "%16, %17, %18, %19, %20, %21, %22, %23, %24, %25, %26, %27, %28, %29, %30, %31, "
        "%32, %33, %34, %35, %36, %37, %38, %39, %40, %41, %42, %43, %44, %45, %46, %47, "
        "%48, %49, %50, %51, %52, %53, %54, %55, %56, %57, %58, %59, %60, %61, %62, %63}, "
        "da, db, 1;\n"
        "add.s64 da, da, 128;\nadd.s64 db, db, 510;\n"
        "wgmma.mma_async.sync.aligned.m64n128k32.s32.s8.s8 "
        "{%0, %1, %2, %3, %4, %5, %6, %7, %8, %9, %10, %11, %12, %13, %14, %15, "
        "%16, %17, %18, %19, %20, %21, %22, %23, %24, %25, %26, %27, %28, %29, %30, %31, "
        "%32, %33, %34, %35, %36, %37, %38, %39, %40, %41, %42, %43, %44, %45, %46, %47, "
        "%48, %49, %50, %51, %52, %53, %54, %55, %56, %57, %58, %59, %60, %61, %62, %63}, "
        "da, db, 1;\n"
        "add.s64 da, da, 128;\nadd.s64 db, db, 2;\n"
        "wgmma.mma_async.sync.aligned.m64n128k32.s32.s8.s8 "
        "{%0, %1, %2, %3, %4, %5, %6, %7, %8, %9, %10, %11, %12, %13, %14, %15, "
        "%16, %17, %18, %19, %20, %21, %22, %23, %24, %25, %26, %27, %28, %29, %30, %31, "
        "%32, %33, %34, %35, %36, %37, %38, %39, %40, %41, %42, %43, %44, %45, %46, %47, "
        "%48, %49, %50, %51, %52, %53, %54, %55, %56, %57, %58, %59, %60, %61, %62, %63}, "
        "da, db, 1;\n"
        "add.s64 da, da, 128;\nadd.s64 db, db, 510;\n"
        "wgmma.mma_async.sync.aligned.m64n128k32.s32.s8.s8 "
        "{%0, %1, %2, %3, %4, %5, %6, %7, %8, %9, %10, %11, %12, %13, %14, %15, "
        "%16, %17, %18, %19, %20, %21, %22, %23, %24, %25, %26, %27, %28, %29, %30, %31, "
        "%32, %33, %34, %35, %36, %37, %38, %39, %40, %41, %42, %43, %44, %45, %46, %47, "
        "%48, %49, %50, %51, %52, %53, %54, %55, %56, %57, %58, %59, %60, %61, %62, %63}, "
        "da, db, 1;\n"
        "add.s64 da, da, 128;\nadd.s64 db, db, 2;\n"
        "mbarrier.test_wait.parity.shared::cta.b64 q, [%70], 0;\n"
        "wgmma.mma_async.sync.aligned.m64n128k32.s32.s8.s8 "
        "{%0, %1, %2, %3, %4, %5, %6, %7, %8, %9, %10, %11, %12, %13, %14, %15, "
        "%16, %17, %18, %19, %20, %21, %22, %23, %24, %25, %26, %27, %28, %29, %30, %31, "
        "%32, %33, %34, %35, %36, %37, %38, %39, %40, %41, %42, %43, %44, %45, %46, %47, "
        "%48, %49, %50, %51, %52, %53, %54, %55, %56, %57, %58, %59, %60, %61, %62, %63}, "
        "da, db, 1;\n"
        "add.s64 da, da, 128;\nadd.s64 db, db, 510;\n"
        "wgmma.mma_async.sync.aligned.m64n128k32.s32.s8.s8 "
        "{%0, %1, %2, %3, %4, %5, %6, %7, %8, %9, %10, %11, %12, %13, %14, %15, "
        "%16, %17, %18, %19, %20, %21, %22, %23, %24, %25, %26, %27, %28, %29, %30, %31, "
        "%32, %33, %34, %35, %36, %37, %38, %39, %40, %41, %42, %43, %44, %45, %46, %47, "
        "%48, %49, %50, %51, %52, %53, %54, %55, %56, %57, %58, %59, %60, %61, %62, %63}, "
        "da, db, 1;\n"
        "add.s64 da, da, 128;\nadd.s64 db, db, 2;\n"
        "wgmma.mma_async.sync.aligned.m64n128k32.s32.s8.s8 "
        "{%0, %1, %2, %3, %4, %5, %6, %7, %8, %9, %10, %11, %12, %13, %14, %15, "
        "%16, %17, %18, %19, %20, %21, %22, %23, %24, %25, %26, %27, %28, %29, %30, %31, "
        "%32, %33, %34, %35, %36, %37, %38, %39, %40, %41, %42, %43, %44, %45, %46, %47, "
        "%48, %49, %50, %51, %52, %53, %54, %55, %56, %57, %58, %59, %60, %61, %62, %63}, "
        "da, db, 1;\n"
        "wgmma.commit_group.sync.aligned;\nselp.u32 %64, 1, 0, q;\n}\n"
        : "+r"(d[0]), "+r"(d[1]), "+r"(d[2]), "+r"(d[3]), "+r"(d[4]), "+r"(d[5]), "+r"(d[6]), "+r"(d[7]),
          "+r"(d[8]), "+r"(d[9]), "+r"(d[10]), "+r"(d[11]), "+r"(d[12]), "+r"(d[13]), "+r"(d[14]), "+r"(d[15]),
          "+r"(d[16]), "+r"(d[17]), "+r"(d[18]), "+r"(d[19]), "+r"(d[20]), "+r"(d[21]), "+r"(d[22]), "+r"(d[23]),
          "+r"(d[24]), "+r"(d[25]), "+r"(d[26]), "+r"(d[27]), "+r"(d[28]), "+r"(d[29]), "+r"(d[30]), "+r"(d[31]),
          "+r"(d[32]), "+r"(d[33]), "+r"(d[34]), "+r"(d[35]), "+r"(d[36]), "+r"(d[37]), "+r"(d[38]), "+r"(d[39]),
          "+r"(d[40]), "+r"(d[41]), "+r"(d[42]), "+r"(d[43]), "+r"(d[44]), "+r"(d[45]), "+r"(d[46]), "+r"(d[47]),
          "+r"(d[48]), "+r"(d[49]), "+r"(d[50]), "+r"(d[51]), "+r"(d[52]), "+r"(d[53]), "+r"(d[54]), "+r"(d[55]),
          "+r"(d[56]), "+r"(d[57]), "+r"(d[58]), "+r"(d[59]), "+r"(d[60]), "+r"(d[61]), "+r"(d[62]), "+r"(d[63]), "=r"(ok)
        : "r"(alo), "r"(blo), "r"(scale_d), "n"(DESC_A_HI), "n"(DESC_B_HI), "r"(bar), "r"(rel), "r"(ka), "r"(kb) : "memory");
    return ok;
}
__device__ __forceinline__ void mma_rows2(int (&d)[64], int (&e)[64], uint32_t alo, uint32_t blo, int scale_d) {
    asm volatile("{\n.reg .pred p;\n.reg .b64 da, db;\nsetp.ne.b32 p, %130, 0;\n"
        "mov.b64 da, {%128, %131};\nmov.b64 db, {%129, %132};\n"
        "wgmma.mma_async.sync.aligned.m64n128k32.s32.s8.s8 "
        "{%0, %1, %2, %3, %4, %5, %6, %7, %8, %9, %10, %11, %12, %13, %14, %15, "
        "%16, %17, %18, %19, %20, %21, %22, %23, %24, %25, %26, %27, %28, %29, %30, %31, "
        "%32, %33, %34, %35, %36, %37, %38, %39, %40, %41, %42, %43, %44, %45, %46, %47, "
        "%48, %49, %50, %51, %52, %53, %54, %55, %56, %57, %58, %59, %60, %61, %62, %63}, "
        "da, db, p;\n"
        "add.s64 db, db, 512;\n"
        "wgmma.mma_async.sync.aligned.m64n128k32.s32.s8.s8 "
        "{%64, %65, %66, %67, %68, %69, %70, %71, %72, %73, %74, %75, %76, %77, %78, %79, "
        "%80, %81, %82, %83, %84, %85, %86, %87, %88, %89, %90, %91, %92, %93, %94, %95, "
        "%96, %97, %98, %99, %100, %101, %102, %103, %104, %105, %106, %107, %108, %109, %110, %111, "
        "%112, %113, %114, %115, %116, %117, %118, %119, %120, %121, %122, %123, %124, %125, %126, %127}, "
        "da, db, p;\n"
        "add.s64 da, da, 128;\nadd.s64 db, db, -510;\n"
        "wgmma.mma_async.sync.aligned.m64n128k32.s32.s8.s8 "
        "{%0, %1, %2, %3, %4, %5, %6, %7, %8, %9, %10, %11, %12, %13, %14, %15, "
        "%16, %17, %18, %19, %20, %21, %22, %23, %24, %25, %26, %27, %28, %29, %30, %31, "
        "%32, %33, %34, %35, %36, %37, %38, %39, %40, %41, %42, %43, %44, %45, %46, %47, "
        "%48, %49, %50, %51, %52, %53, %54, %55, %56, %57, %58, %59, %60, %61, %62, %63}, "
        "da, db, 1;\n"
        "add.s64 db, db, 512;\n"
        "wgmma.mma_async.sync.aligned.m64n128k32.s32.s8.s8 "
        "{%64, %65, %66, %67, %68, %69, %70, %71, %72, %73, %74, %75, %76, %77, %78, %79, "
        "%80, %81, %82, %83, %84, %85, %86, %87, %88, %89, %90, %91, %92, %93, %94, %95, "
        "%96, %97, %98, %99, %100, %101, %102, %103, %104, %105, %106, %107, %108, %109, %110, %111, "
        "%112, %113, %114, %115, %116, %117, %118, %119, %120, %121, %122, %123, %124, %125, %126, %127}, "
        "da, db, 1;\n"
        "wgmma.commit_group.sync.aligned;\n}\n"
        : "+r"(d[0]), "+r"(d[1]), "+r"(d[2]), "+r"(d[3]), "+r"(d[4]), "+r"(d[5]), "+r"(d[6]), "+r"(d[7]),
          "+r"(d[8]), "+r"(d[9]), "+r"(d[10]), "+r"(d[11]), "+r"(d[12]), "+r"(d[13]), "+r"(d[14]), "+r"(d[15]),
          "+r"(d[16]), "+r"(d[17]), "+r"(d[18]), "+r"(d[19]), "+r"(d[20]), "+r"(d[21]), "+r"(d[22]), "+r"(d[23]),
          "+r"(d[24]), "+r"(d[25]), "+r"(d[26]), "+r"(d[27]), "+r"(d[28]), "+r"(d[29]), "+r"(d[30]), "+r"(d[31]),
          "+r"(d[32]), "+r"(d[33]), "+r"(d[34]), "+r"(d[35]), "+r"(d[36]), "+r"(d[37]), "+r"(d[38]), "+r"(d[39]),
          "+r"(d[40]), "+r"(d[41]), "+r"(d[42]), "+r"(d[43]), "+r"(d[44]), "+r"(d[45]), "+r"(d[46]), "+r"(d[47]),
          "+r"(d[48]), "+r"(d[49]), "+r"(d[50]), "+r"(d[51]), "+r"(d[52]), "+r"(d[53]), "+r"(d[54]), "+r"(d[55]),
          "+r"(d[56]), "+r"(d[57]), "+r"(d[58]), "+r"(d[59]), "+r"(d[60]), "+r"(d[61]), "+r"(d[62]), "+r"(d[63]),
          "+r"(e[0]), "+r"(e[1]), "+r"(e[2]), "+r"(e[3]), "+r"(e[4]), "+r"(e[5]), "+r"(e[6]), "+r"(e[7]),
          "+r"(e[8]), "+r"(e[9]), "+r"(e[10]), "+r"(e[11]), "+r"(e[12]), "+r"(e[13]), "+r"(e[14]), "+r"(e[15]),
          "+r"(e[16]), "+r"(e[17]), "+r"(e[18]), "+r"(e[19]), "+r"(e[20]), "+r"(e[21]), "+r"(e[22]), "+r"(e[23]),
          "+r"(e[24]), "+r"(e[25]), "+r"(e[26]), "+r"(e[27]), "+r"(e[28]), "+r"(e[29]), "+r"(e[30]), "+r"(e[31]),
          "+r"(e[32]), "+r"(e[33]), "+r"(e[34]), "+r"(e[35]), "+r"(e[36]), "+r"(e[37]), "+r"(e[38]), "+r"(e[39]),
          "+r"(e[40]), "+r"(e[41]), "+r"(e[42]), "+r"(e[43]), "+r"(e[44]), "+r"(e[45]), "+r"(e[46]), "+r"(e[47]),
          "+r"(e[48]), "+r"(e[49]), "+r"(e[50]), "+r"(e[51]), "+r"(e[52]), "+r"(e[53]), "+r"(e[54]), "+r"(e[55]),
          "+r"(e[56]), "+r"(e[57]), "+r"(e[58]), "+r"(e[59]), "+r"(e[60]), "+r"(e[61]), "+r"(e[62]), "+r"(e[63])
        : "r"(alo), "r"(blo), "r"(scale_d), "n"(DESC_A_HI), "n"(DESC_B_HI) : "memory");
}

__device__ __forceinline__ void wg_fence() { asm volatile("wgmma.fence.sync.aligned;" ::: "memory"); }
template <int N> __device__ __forceinline__ void wg_wait() { asm volatile("wgmma.wait_group.sync.aligned %0;" :: "n"(N) : "memory"); }

__host__ __device__ constexpr int unit_of(int wg, int s) { return wg ? (s < 16 - D_ ? D_ + 2 * s : s + 16) : (s < D_ ? s : 2 * s - D_ + 1); }

__host__ __device__ constexpr int bar_of(int u) { return u >= 32 ? u & ~1 : u < D_ || u >= 32 - D_ ? u : ((u - D_) & 1) ? D_ + ((u - D_) >> 1) : 16 + ((u - D_) >> 1); }
constexpr uint32_t step_table(int wg) {
    uint32_t t = 0;
    for (int s = 0; s < 15; s++) t |= (uint32_t)(unit_of(wg, s + 1) - unit_of(wg, s) - 1) << s;
    return t;
}
constexpr uint32_t STEPS0 = step_table(0), STEPS1 = step_table(1);
__device__ __forceinline__ int sum_group(int r) { return r < 8 ? (r & 4) | (~r & 1) << 1 | (r >> 1 & 1) : r; }
__device__ __forceinline__ int col_of(int c, int blk) { return (c < 7 ? blk * 7 + c : 49 + blk) * 64; }

struct JobTable { uint2 e[NCTA][NJOB + NCONV]; };
__device__ const JobTable g_jobs = {{
    {{0x0, 0x0}, {0x20400, 0x1000000}, {0x90202, 0x2008099}, {0x100004, 0x3010132}, {0x14000000, 0x310001ee}, {0x2a412a34, 0x2d82025a}, {0x14100e0e, 0x750042e1}, {0x5d0a07, 0x409c366}, {0x14202a0e, 0x75008440}, {0x650a09, 0x60a44c5}, {0x1430460e, 0x7504c59d}, {0x36c680b, 0x76ac612}, {0x1440620e, 0x750506ee}, {0x3f4780d, 0x87b4768}, {0x14507e0e, 0x75094840}, {0x33c600f, 0x963c8b2}, {0x14609a0e, 0x75098965}, {0x1470b60e, 0x750dca0e}, {0x1480001c, 0x98020ab6}, {0x1490701c, 0x980a4b97}, {0x14a00023, 0xba028c8a}, {0x14b07023, 0xba0acd7c}, {0x14c0002a, 0xdc030e6f}, {0x14d0702a, 0xdc0b4f53}, {0x30000000, 0x0}, {0x30000000, 0x0}, {0x30000000, 0x0}, {0x30000000, 0x0}, {0x30000000, 0x0}, {0x30000000, 0x0}, {0x30000000, 0x0}, {0x30000000, 0x0}},
    {{0x0, 0x0}, {0x420c00, 0x1080001}, {0x490a02, 0x208809a}, {0x500804, 0x3090133}, {0x14010007, 0x200001f9}, {0x1973605, 0x431426c}, {0x14110e15, 0x640042f7}, {0x2a4e5b31, 0x5b82c378}, {0x14212a15, 0x64008456}, {0x2654a09, 0x64a44db}, {0x14314615, 0x6404c5b2}, {0x16d2a0b, 0x72ac628}, {0x14416215, 0x64050703}, {0x1b5320d, 0x833477b}, {0x14517e15, 0x64094855}, {0xfd1a0f, 0x91bc8c5}, {0x14619a15, 0x64098970}, {0x1471b615, 0x640dca18}, {0x1481071c, 0x98020ac1}, {0x1491771c, 0x980a4ba6}, {0x14a10723, 0xba028c99}, {0x14b17723, 0xba0acd8c}, {0x14c1072a, 0xdc030e7e}, {0x14d1772a, 0xdc0b4f60}, {0x30000000, 0x0}, {0x30000000, 0x0}, {0x30000000, 0x0}, {0x30000000, 0x0}, {0x30000000, 0x0}, {0x30000000, 0x0}, {0x30000000, 0x0}, {0x30000000, 0x0}},
    {{0x0, 0x0}, {0x821400, 0x1100002}, {0x891202, 0x210809b}, {0x901004, 0x3110134}, {0x14020700, 0x31000204}, {0x3176605, 0x461427c}, {0x1412150e, 0x7500430d}, {0x39d7207, 0x471c38a}, {0x1422310e, 0x7500846c}, {0x660c09, 0x60a44f1}, {0x14324d0e, 0x7504c5c7}, {0x36d6a0b, 0x76ac63d}, {0x1442690e, 0x75050719}, {0x3756a0d, 0x86b478e}, {0x1b8300e, 0x83387fa}, {0x1452850e, 0x7509486a}, {0x3e040f, 0x903c8e7}, {0x1462a10e, 0x7509897a}, {0x1472bd0e, 0x750dca23}, {0x14820e1c, 0x98020acb}, {0x14927e1c, 0x980a4bb5}, {0x14a20e23, 0xba028ca8}, {0x14b27e23, 0xba0acd9b}, {0x14c20e2a, 0xdc030e8e}, {0x14d27e2a, 0xdc0b4f6d}, {0x30000000, 0x0}, {0x30000000, 0x0}, {0x30000000, 0x0}, {0x30000000, 0x0}, {0x30000000, 0x0}, {0x30000000, 0x0}, {0x30000000, 0x0}},
    {{0x0, 0x0}, {0xc21c00, 0x1180003}, {0xc91a02, 0x218809c}, {0xd01804, 0x3190135}, {0x14030707, 0x2000020f}, {0x981006, 0x411828d}, {0x14131515, 0x64004323}, {0x11e2407, 0x521c39a}, {0x14233115, 0x64008482}, {0x2264409, 0x6424504}, {0x14334d15, 0x6404c5dc}, {0x12e240b, 0x722c64f}, {0x14436915, 0x6405072e}, {0x136240d, 0x82347a0}, {0x3f8780e, 0x87b8810}, {0x14538515, 0x6409487f}, {0xfe1c0f, 0x91bc8ef}, {0x1463a115, 0x64098985}, {0x1473bd15, 0x640dca2d}, {0x1483151c, 0x98020ad6}, {0x1493851c, 0x980a4bc4}, {0x14a31523, 0xba028cb7}, {0x14b38523, 0xba0acdaa}, {0x14c3152a, 0xdc030e9d}, {0x14d3852a, 0xdc0b4f7b}, {0x30000000, 0x0}, {0x30000000, 0x0}, {0x30000000, 0x0}, {0x30000000, 0x0}, {0x30000000, 0x0}, {0x30000000, 0x0}, {0x30000000, 0x0}},
    {{0x0, 0x0}, {0x1022400, 0x1200005}, {0x1092202, 0x220809e}, {0x1102004, 0x3210137}, {0x14040e00, 0x3100021a}, {0x2184006, 0x441829d}, {0x14142a00, 0x31004339}, {0x31e6407, 0x561c3b0}, {0x14244600, 0x31048498}, {0x3e67c09, 0x67a4516}, {0x14346200, 0x3104c5f2}, {0x2ee5c0b, 0x75ac661}, {0x1b1320c, 0x73306d3}, {0x14447e00, 0x31090743}, {0x3b6740d, 0x87347bb}, {0x14549a00, 0x31094894}, {0x23e440f, 0x943c8fc}, {0x1464b600, 0x310d898f}, {0x1474d200, 0x310dca38}, {0x14841c1c, 0x98020ae1}, {0x14948c1c, 0x980a4bd3}, {0x14a41c23, 0xba028cc6}, {0x14b48c23, 0xba0acdb9}, {0x14c41c2a, 0xdc030eac}, {0x14d48c2a, 0xdc0b4f88}, {0x30000000, 0x0}, {0x30000000, 0x0}, {0x30000000, 0x0}, {0x30000000, 0x0}, {0x30000000, 0x0}, {0x30000000, 0x0}, {0x30000000, 0x0}},
    {{0x0, 0x0}, {0x1422c00, 0x1280006}, {0x1492a02, 0x228809f}, {0x1502804, 0x3290138}, {0x14050e07, 0x20000225}, {0x3d87806, 0x47982af}, {0x14152a07, 0x2000434e}, {0xdf1e07, 0x519c3c3}, {0x14254607, 0x200484ae}, {0x1672e09, 0x62a4528}, {0x3e97a0a, 0x67a8598}, {0x14356207, 0x2004c607}, {0x26f4e0b, 0x74ac686}, {0x14457e07, 0x20090758}, {0x1b7360d, 0x83347d0}, {0x14559a07, 0x200948a9}, {0x3fe7c0f, 0x97bc90d}, {0x1465b607, 0x200d899a}, {0x1475d207, 0x200dca42}, {0x1485231c, 0x98020af0}, {0x1495931c, 0x980a4be3}, {0x14a52323, 0xba028cd5}, {0x14b59323, 0xba0acdc8}, {0x14c5232a, 0xdc030ebb}, {0x14d5932a, 0xdc0b4f95}, {0x30000000, 0x0}, {0x30000000, 0x0}, {0x30000000, 0x0}, {0x30000000, 0x0}, {0x30000000, 0x0}, {0x30000000, 0x0}, {0x30000000, 0x0}},
    {{0x0, 0x0}, {0x1823400, 0x1300007}, {0x1893202, 0x23080a0}, {0x1903004, 0x3310139}, {0x14061500, 0x31000230}, {0x1592a06, 0x42982c1}, {0x14163100, 0x31004364}, {0x29f5607, 0x551c3d6}, {0x14264d00, 0x310484c4}, {0x2a75609, 0x6524536}, {0x14366900, 0x3104c61c}, {0x12f260b, 0x722c679}, {0xb2140c, 0x71306f2}, {0x14468500, 0x3109076d}, {0x3776e0d, 0x86b47e2}, {0x1456a100, 0x310948be}, {0x1bf360f, 0x933c921}, {0x1466bd00, 0x310d89a4}, {0x1476d900, 0x310dca4d}, {0x14862a1c, 0x98020aff}, {0x14969a1c, 0x980a4bf2}, {0x14a62a23, 0xba028ce5}, {0x14b69a23, 0xba0acdd7}, {0x14c62a2a, 0xdc030eca}, {0x14d69a2a, 0xdc0b4fa3}, {0x30000000, 0x0}, {0x30000000, 0x0}, {0x30000000, 0x0}, {0x30000000, 0x0}, {0x30000000, 0x0}, {0x30000000, 0x0}, {0x30000000, 0x0}},
    {{0x0, 0x0}, {0x1c23c00, 0x1380009}, {0x1c93a02, 0x23880a2}, {0x1d03804, 0x339013b}, {0x14071507, 0x2000023b}, {0x2d95a06, 0x45982d2}, {0x14173107, 0x2000437a}, {0x600808, 0x50a03ea}, {0x14274d07, 0x200484da}, {0x28000a, 0x6028546}, {0x2ea5c0a, 0x65a85b9}, {0x14376907, 0x2004c631}, {0x170280c, 0x72b06a6}, {0x14478507, 0x20090782}, {0xb8100e, 0x81387ef}, {0x1457a107, 0x200948d3}, {0x37f6e0f, 0x96bc933}, {0x1467bd07, 0x200d89af}, {0x1477d907, 0x200dca58}, {0x1487311c, 0x98020b0e}, {0x1497a11c, 0x980a4c01}, {0x14a73123, 0xba028cf4}, {0x14b7a123, 0xba0acde7}, {0x14c7312a, 0xdc030ed9}, {0x14d7a12a, 0xdc0b4fb0}, {0x30000000, 0x0}, {0x30000000, 0x0}, {0x30000000, 0x0}, {0x30000000, 0x0}, {0x30000000, 0x0}, {0x30000000, 0x0}, {0x30000000, 0x0}},
    {{0x0, 0x0}, {0x2024400, 0x140000a}, {0x2094202, 0x24080a3}, {0x2104004, 0x341013c}, {0x1408000e, 0x75000246}, {0x5a0c06, 0x40982e2}, {0x14181c0e, 0x75004390}, {0x2204008, 0x54203fd}, {0x1232608, 0x5220476}, {0x1428380e, 0x750484f0}, {0xe91a0a, 0x61a857a}, {0x1438540e, 0x7504c646}, {0x2f0580c, 0x75b06b6}, {0x1448700e, 0x75090797}, {0x2b8500e, 0x8538804}, {0x14588c0e, 0x750948e8}, {0x1468a80e, 0x750d89b9}, {0x1478c40e, 0x750dca62}, {0x1488381c, 0x98060b1d}, {0x1498a81c, 0x980e4c10}, {0x14a83823, 0xba068d03}, {0x14b8a823, 0xba0ecdf6}, {0x14c8382a, 0xdc070ee9}, {0x14d8a82a, 0xdc0f4fbd}, {0x30000000, 0x0}, {0x30000000, 0x0}, {0x30000000, 0x0}, {0x30000000, 0x0}, {0x30000000, 0x0}, {0x30000000, 0x0}, {0x30000000, 0x0}, {0x30000000, 0x0}},
    {{0x0, 0x0}, {0x2424c00, 0x148000b}, {0x2494a02, 0x24880a4}, {0x2504804, 0x349013d}, {0x14090015, 0x64000251}, {0x2a483833, 0x3a8282f4}, {0x14191c15, 0x640043a6}, {0x3e07808, 0x57a040f}, {0x2e35e08, 0x55a0489}, {0x14293815, 0x64048506}, {0x1a9320a, 0x6328582}, {0x14395415, 0x6404c65b}, {0xf11a0c, 0x71b06cb}, {0x14497015, 0x640907ac}, {0x1792a0e, 0x82b8821}, {0x14598c15, 0x640948fd}, {0x1469a815, 0x640d89c4}, {0x1479c415, 0x640dca6d}, {0x14893f1c, 0x98060b2c}, {0x1499af1c, 0x980e4c1f}, {0x14a93f23, 0xba068d12}, {0x14b9af23, 0xba0ece05}, {0x14c93f2a, 0xdc070ef6}, {0x14d9af2a, 0xdc0f4fca}, {0x30000000, 0x0}, {0x30000000, 0x0}, {0x30000000, 0x0}, {0x30000000, 0x0}, {0x30000000, 0x0}, {0x30000000, 0x0}, {0x30000000, 0x0}, {0x30000000, 0x0}},
    {{0x0, 0x0}, {0x2825400, 0x150000d}, {0x2895202, 0x25080a6}, {0x2905004, 0x351013f}, {0x2a200031, 0x8001cd}, {0x140a070e, 0x7500025d}, {0x1b0606, 0x401830b}, {0x141a230e, 0x750043bc}, {0x3216208, 0x5620434}, {0x142a3f0e, 0x7504851c}, {0x2694a0a, 0x64a8589}, {0x143a5b0e, 0x7504c670}, {0x331620c, 0x76306e3}, {0x144a770e, 0x750907c1}, {0x3b9720e, 0x8738839}, {0x145a930e, 0x75094912}, {0x146aaf0e, 0x750d89cf}, {0x147acb0e, 0x750dca77}, {0x148a461c, 0x98060b3c}, {0x149ab61c, 0x980e4c2e}, {0x14aa4623, 0xba068d21}, {0x14bab623, 0xba0ece14}, {0x14ca462a, 0xdc070f03}, {0x14dab62a, 0xdc0f4fd8}, {0x30000000, 0x0}, {0x30000000, 0x0}, {0x30000000, 0x0}, {0x30000000, 0x0}, {0x30000000, 0x0}, {0x30000000, 0x0}, {0x30000000, 0x0}, {0x30000000, 0x0}},
    {{0x0, 0x0}, {0x2c25c00, 0x158000e}, {0x2c95a02, 0x25880a7}, {0x2d05804, 0x3590140}, {0x2a210032, 0x18001ce}, {0x140b0715, 0x64000273}, {0x19b3606, 0x431831c}, {0x141b2315, 0x640043d2}, {0x1222408, 0x522044a}, {0x142b3f15, 0x64048532}, {0xaa140a, 0x61285a1}, {0x143b5b15, 0x6404c685}, {0x1b2340c, 0x73306fd}, {0x144b7715, 0x640907d6}, {0x1fa3c0e, 0x93b884f}, {0x145b9315, 0x64094927}, {0x146baf15, 0x640d89d9}, {0x147bcb15, 0x640dca82}, {0x148b4d1c, 0x98060b4b}, {0x149bbd1c, 0x980e4c3e}, {0x14ab4d23, 0xba068d30}, {0x14bbbd23, 0xba0ece23}, {0x14cb4d2a, 0xdc070f10}, {0x14dbbd2a, 0xdc0f4fe5}, {0x30000000, 0x0}, {0x30000000, 0x0}, {0x30000000, 0x0}, {0x30000000, 0x0}, {0x30000000, 0x0}, {0x30000000, 0x0}, {0x30000000, 0x0}, {0x30000000, 0x0}},
    {{0x0, 0x0}, {0x3026400, 0x160000f}, {0x3096202, 0x26080a8}, {0x3106004, 0x3610141}, {0x2a220731, 0x78001cf}, {0x140c1c00, 0x31000289}, {0x2db5e06, 0x4598329}, {0x141c3800, 0x310443e8}, {0x3226408, 0x5620460}, {0x142c5400, 0x31048548}, {0x32a640a, 0x66285bc}, {0x143c7000, 0x3108c69a}, {0x3f27c0c, 0x77b0713}, {0x144c8c00, 0x310907eb}, {0x3fa7c0e, 0x97b8864}, {0x145ca800, 0x310d493b}, {0x146cc400, 0x310d89e4}, {0x147cd20e, 0x750dca8c}, {0x148c541c, 0x98060b5a}, {0x149cc41c, 0x980e4c4d}, {0x14ac5423, 0xba068d40}, {0x14bcc423, 0xba0ece33}, {0x14cc542a, 0xdc070f1e}, {0x14dcc42a, 0xdc0f4ff2}, {0x30000000, 0x0}, {0x30000000, 0x0}, {0x30000000, 0x0}, {0x30000000, 0x0}, {0x30000000, 0x0}, {0x30000000, 0x0}, {0x30000000, 0x0}, {0x30000000, 0x0}},
    {{0x0, 0x0}, {0x3426c00, 0x1680011}, {0x3496a02, 0x26880aa}, {0x3506804, 0x3690143}, {0x2a230732, 0x88001d1}, {0x140d1c07, 0x2000029f}, {0x5c0807, 0x409c33a}, {0x141d3807, 0x200443fe}, {0x1632e08, 0x52a0478}, {0x142d5407, 0x2004855e}, {0x16b2e0a, 0x62a85d3}, {0x143d7007, 0x2008c6af}, {0x2734e0c, 0x84b072f}, {0x144d8c07, 0x20090800}, {0x1bb360e, 0x9338878}, {0x145da807, 0x200d4946}, {0x146dc407, 0x200d89ee}, {0x147dd215, 0x640dca97}, {0x148d5b1c, 0x98060b69}, {0x149dcb1c, 0x980e4c5c}, {0x14ad5b23, 0xba068d4f}, {0x14bdcb23, 0xba0ece42}, {0x14cd5b2a, 0xdc070f2b}, {0x14ddcb2a, 0xdc0f5000}, {0x30000000, 0x0}, {0x30000000, 0x0}, {0x30000000, 0x0}, {0x30000000, 0x0}, {0x30000000, 0x0}, {0x30000000, 0x0}, {0x30000000, 0x0}, {0x30000000, 0x0}},
    {{0x0, 0x0}, {0x3827400, 0x1700012}, {0x3897202, 0x27080ab}, {0x3907004, 0x3710144}, {0x2a240e31, 0xe8041d2}, {0x140e2300, 0x310002b5}, {0x19c3007, 0x431c348}, {0x141e3f00, 0x31044414}, {0x3636e08, 0x56a048e}, {0x142e5b00, 0x31048573}, {0x3ab760a, 0x67285eb}, {0x143e7700, 0x3108c6c4}, {0x74080d, 0x80b4744}, {0x144e9300, 0x31090815}, {0x3bb760e, 0x973888d}, {0x145eaf00, 0x310d4950}, {0x146ecb00, 0x310d89f9}, {0x147ed90e, 0x750dcaa1}, {0x148e621c, 0x98060b78}, {0x149ed21c, 0x980e4c6b}, {0x14ae6223, 0xba068d5e}, {0x14bed223, 0xba0ece51}, {0x14ce622a, 0xdc070f38}, {0x14ded22a, 0xdc0f500d}, {0x30000000, 0x0}, {0x30000000, 0x0}, {0x30000000, 0x0}, {0x30000000, 0x0}, {0x30000000, 0x0}, {0x30000000, 0x0}, {0x30000000, 0x0}, {0x30000000, 0x0}},
    {{0x0, 0x0}, {0x3c27c00, 0x1780013}, {0x3c97a02, 0x27880ac}, {0x3d07804, 0x3790145}, {0x2a250e32, 0xf8041d4}, {0x140f2307, 0x200002cb}, {0x2dc5807, 0x459c355}, {0x141f3f07, 0x2004442a}, {0x2244009, 0x54244ad}, {0x142f5b07, 0x20048588}, {0x16c280b, 0x72ac5fd}, {0x143f7707, 0x2008c6d9}, {0x234400d, 0x8434756}, {0x144f9307, 0x2009082a}, {0x17c280f, 0x92bc8a0}, {0x145faf07, 0x200d495b}, {0x146fcb07, 0x200d8a03}, {0x147fd915, 0x640dcaac}, {0x148f691c, 0x98060b87}, {0x149fd91c, 0x980e4c7a}, {0x14af6923, 0xba068d6d}, {0x14bfd923, 0xba0ece60}, {0x14cf692a, 0xdc070f46}, {0x14dfd92a, 0xdc0f501a}, {0x30000000, 0x0}, {0x30000000, 0x0}, {0x30000000, 0x0}, {0x30000000, 0x0}, {0x30000000, 0x0}, {0x30000000, 0x0}, {0x30000000, 0x0}, {0x30000000, 0x0}},
    {{0x0, 0x0}, {0x30600, 0x1000015}, {0xa0402, 0x20080ae}, {0x110204, 0x3010147}, {0x14e00001, 0x310001ef}, {0x170605, 0x401425c}, {0x14f00e0f, 0x750042e3}, {0x9d1207, 0x411c369}, {0x15002a0f, 0x75008443}, {0xa51209, 0x61244c8}, {0x1510460f, 0x7504c5a0}, {0x3ac700b, 0x772c615}, {0x1520620f, 0x750506f1}, {0x35020d, 0x803476b}, {0x15307e0f, 0x75094842}, {0x37c680f, 0x96bc8b5}, {0x15409a0f, 0x75098967}, {0x1550b60f, 0x750dca0f}, {0x1560001d, 0x98020ab8}, {0x1570701d, 0x980a4b99}, {0x15800024, 0xba028c8b}, {0x15907024, 0xba0acd7e}, {0x15a0002b, 0xdc030e71}, {0x15b0702b, 0xdc0b4f55}, {0x30000000, 0x0}, {0x30000000, 0x0}, {0x30000000, 0x0}, {0x30000000, 0x0}, {0x30000000, 0x0}, {0x30000000, 0x0}, {0x30000000, 0x0}, {0x30000000, 0x0}},
    {{0x0, 0x0}, {0x430e00, 0x1080016}, {0x4a0c02, 0x20880af}, {0x510a04, 0x3090148}, {0x14e10008, 0x200001fa}, {0x1d73e05, 0x439426d}, {0x14f10e16, 0x640042f9}, {0x21d4207, 0x441c379}, {0x15012a16, 0x64008459}, {0x2a55209, 0x65244de}, {0x15114616, 0x6404c5b5}, {0x1ad320b, 0x732c62a}, {0x15216216, 0x64050706}, {0x1f53a0d, 0x83b477d}, {0x38000e, 0x80387ea}, {0x15317e16, 0x64094857}, {0x3bd720f, 0x973c8e2}, {0x15419a16, 0x64098971}, {0x1551b616, 0x640dca1a}, {0x1561071d, 0x98020ac2}, {0x1571771d, 0x980a4ba8}, {0x15810724, 0xba028c9b}, {0x15917724, 0xba0acd8d}, {0x15a1072b, 0xdc030e80}, {0x15b1772b, 0xdc0b4f62}, {0x30000000, 0x0}, {0x30000000, 0x0}, {0x30000000, 0x0}, {0x30000000, 0x0}, {0x30000000, 0x0}, {0x30000000, 0x0}, {0x30000000, 0x0}},
    {{0x0, 0x0}, {0x831600, 0x1100017}, {0x8a1402, 0x21080b0}, {0x911204, 0x3110149}, {0x14e20701, 0x31000205}, {0x3576e05, 0x469427f}, {0x14f2150f, 0x7500430f}, {0x3dd7a07, 0x479c38b}, {0x1502310f, 0x7500846f}, {0xa61409, 0x61244f4}, {0x15124d0f, 0x7504c5ca}, {0x3ad720b, 0x772c63f}, {0x1522690f, 0x7505071b}, {0x3b5720d, 0x8734790}, {0x238400e, 0x84387ff}, {0x1532850f, 0x7509486c}, {0xbe140f, 0x913c8ec}, {0x1542a10f, 0x7509897c}, {0x1552bd0f, 0x750dca24}, {0x15620e1d, 0x98020acd}, {0x15727e1d, 0x980a4bb7}, {0x15820e24, 0xba028caa}, {0x15927e24, 0xba0acd9d}, {0x15a20e2b, 0xdc030e8f}, {0x15b27e2b, 0xdc0b4f6f}, {0x30000000, 0x0}, {0x30000000, 0x0}, {0x30000000, 0x0}, {0x30000000, 0x0}, {0x30000000, 0x0}, {0x30000000, 0x0}, {0x30000000, 0x0}},
    {{0x0, 0x0}, {0xc31e00, 0x1180018}, {0xca1c02, 0x21880b1}, {0xd11a04, 0x319014a}, {0x14e30708, 0x20000210}, {0xd81806, 0x4198290}, {0x14f31516, 0x64004325}, {0x15e2c07, 0x529c39d}, {0x15033116, 0x64008485}, {0x2664c09, 0x64a4507}, {0x15134d16, 0x6404c5df}, {0x16e2c0b, 0x72ac652}, {0x15236916, 0x64050730}, {0x1762c0d, 0x82b47a3}, {0x15338516, 0x64094881}, {0x3fd7a0f, 0x97bc8e3}, {0x1543a116, 0x64098986}, {0x1553bd16, 0x640dca2f}, {0x1563151d, 0x98020ad7}, {0x1573851d, 0x980a4bc6}, {0x15831524, 0xba028cb9}, {0x15938524, 0xba0acdac}, {0x15a3152b, 0xdc030e9f}, {0x15b3852b, 0xdc0b4f7d}, {0x30000000, 0x0}, {0x30000000, 0x0}, {0x30000000, 0x0}, {0x30000000, 0x0}, {0x30000000, 0x0}, {0x30000000, 0x0}, {0x30000000, 0x0}, {0x30000000, 0x0}},
    {{0x0, 0x0}, {0x1032600, 0x120001a}, {0x10a2402, 0x22080b3}, {0x1112204, 0x321014c}, {0x14e40e01, 0x3100021b}, {0x2584806, 0x44982a0}, {0x14f42a01, 0x3100433b}, {0x35e6c07, 0x569c3b3}, {0x15044601, 0x3104849b}, {0x270609, 0x602451a}, {0x15146201, 0x3104c5f4}, {0x32e640b, 0x762c664}, {0x15247e01, 0x31090745}, {0x236440d, 0x84347ab}, {0x139220e, 0x823881f}, {0x15349a01, 0x31094896}, {0x27e4c0f, 0x94bc8fe}, {0x1544b601, 0x310d8991}, {0x1554d201, 0x310dca39}, {0x15641c1d, 0x98020ae2}, {0x15748c1d, 0x980a4bd5}, {0x15841c24, 0xba028cc8}, {0x15948c24, 0xba0acdbb}, {0x15a41c2b, 0xdc030eae}, {0x15b48c2b, 0xdc0b4f8a}, {0x30000000, 0x0}, {0x30000000, 0x0}, {0x30000000, 0x0}, {0x30000000, 0x0}, {0x30000000, 0x0}, {0x30000000, 0x0}, {0x30000000, 0x0}},
    {{0x0, 0x0}, {0x1432e00, 0x128001b}, {0x14a2c02, 0x22880b4}, {0x1512a04, 0x329014d}, {0x14e50e08, 0x20000226}, {0x2a454632, 0x478242b2}, {0x14f52a08, 0x20004351}, {0x11f2607, 0x521c3c6}, {0x15054608, 0x200484b1}, {0x1a73609, 0x632452b}, {0x15156208, 0x2004c609}, {0x6f0e0b, 0x70ac671}, {0x3716a0c, 0x76b06e5}, {0x15257e08, 0x2009075a}, {0x1f73e0d, 0x83b47d1}, {0x15359a08, 0x200948ac}, {0x3f060f, 0x903c911}, {0x1545b608, 0x200d899b}, {0x1555d208, 0x200dca44}, {0x1565231d, 0x98020af2}, {0x1575931d, 0x980a4be4}, {0x15852324, 0xba028cd7}, {0x15959324, 0xba0acdca}, {0x15a5232b, 0xdc030ebd}, {0x15b5932b, 0xdc0b4f97}, {0x30000000, 0x0}, {0x30000000, 0x0}, {0x30000000, 0x0}, {0x30000000, 0x0}, {0x30000000, 0x0}, {0x30000000, 0x0}, {0x30000000, 0x0}},
    {{0x0, 0x0}, {0x1833600, 0x130001c}, {0x18a3402, 0x23080b5}, {0x1913204, 0x331014e}, {0x14e61501, 0x31000231}, {0x1993206, 0x43182c4}, {0x14f63101, 0x31004367}, {0x2df5e07, 0x559c3d9}, {0x15064d01, 0x310484c7}, {0x3276609, 0x662453b}, {0x15166901, 0x3104c61e}, {0x16f2e0b, 0x72ac67c}, {0x15268501, 0x3109076f}, {0x3f67c0d, 0x87b47bc}, {0x3796a0e, 0x86b8836}, {0x1536a101, 0x310948c1}, {0x1ff3e0f, 0x93bc922}, {0x1546bd01, 0x310d89a6}, {0x1556d901, 0x310dca4e}, {0x15662a1d, 0x98020b01}, {0x15769a1d, 0x980a4bf4}, {0x15862a24, 0xba028ce6}, {0x15969a24, 0xba0acdd9}, {0x15a62a2b, 0xdc030ecc}, {0x15b69a2b, 0xdc0b4fa4}, {0x30000000, 0x0}, {0x30000000, 0x0}, {0x30000000, 0x0}, {0x30000000, 0x0}, {0x30000000, 0x0}, {0x30000000, 0x0}, {0x30000000, 0x0}},
    {{0x0, 0x0}, {0x1c33e00, 0x138001e}, {0x1ca3c02, 0x23880b7}, {0x1d13a04, 0x3390150}, {0x14e71508, 0x2000023c}, {0x3196206, 0x46182d4}, {0x14f73108, 0x2000437d}, {0xa01008, 0x51203ec}, {0x15074d08, 0x200484dd}, {0x68080a, 0x60a8549}, {0x36a6c0a, 0x66a85be}, {0x15176908, 0x2004c633}, {0x1f0380c, 0x73b06aa}, {0x15278508, 0x20090785}, {0xf8180e, 0x81b87f2}, {0x1537a108, 0x200948d6}, {0x3bf760f, 0x973c936}, {0x1547bd08, 0x200d89b0}, {0x1557d908, 0x200dca59}, {0x1567311d, 0x98020b10}, {0x1577a11d, 0x980a4c03}, {0x15873124, 0xba028cf6}, {0x1597a124, 0xba0acde9}, {0x15a7312b, 0xdc030edb}, {0x15b7a12b, 0xdc0b4fb2}, {0x30000000, 0x0}, {0x30000000, 0x0}, {0x30000000, 0x0}, {0x30000000, 0x0}, {0x30000000, 0x0}, {0x30000000, 0x0}, {0x30000000, 0x0}},
    {{0x0, 0x0}, {0x2034600, 0x140001f}, {0x20a4402, 0x24080b8}, {0x2114204, 0x3410151}, {0x14e8000f, 0x75000247}, {0x9a1406, 0x41182e5}, {0x14f81c0f, 0x75004393}, {0x2604808, 0x54a0400}, {0x1508380f, 0x750484f3}, {0x1e8380a, 0x63a8558}, {0x12b260a, 0x62285d1}, {0x1518540f, 0x7504c648}, {0x370680c, 0x76b06bb}, {0x1528700f, 0x7509079a}, {0x338600e, 0x863880a}, {0x15388c0f, 0x750948eb}, {0x1548a80f, 0x750d89bb}, {0x1558c40f, 0x750dca63}, {0x1568381d, 0x98060b1f}, {0x1578a81d, 0x980e4c12}, {0x15883824, 0xba068d05}, {0x1598a824, 0xba0ecdf8}, {0x15a8382b, 0xdc070eeb}, {0x15b8a82b, 0xdc0f4fbf}, {0x30000000, 0x0}, {0x30000000, 0x0}, {0x30000000, 0x0}, {0x30000000, 0x0}, {0x30000000, 0x0}, {0x30000000, 0x0}, {0x30000000, 0x0}, {0x30000000, 0x0}},
    {{0x0, 0x0}, {0x2434e00, 0x1480020}, {0x24a4c02, 0x24880b9}, {0x2514a04, 0x3490152}, {0x14e90016, 0x64000252}, {0x21a4406, 0x44182f5}, {0x14f91c16, 0x640043a9}, {0x210208, 0x5020413}, {0x3236608, 0x562048c}, {0x15093816, 0x64048509}, {0x1e93a0a, 0x63a8583}, {0x15195416, 0x6404c65e}, {0x131220c, 0x72306cd}, {0x15297016, 0x640907af}, {0x1f93a0e, 0x83b8825}, {0x15398c16, 0x64094900}, {0x1549a816, 0x640d89c5}, {0x1559c416, 0x640dca6e}, {0x15693f1d, 0x98060b2e}, {0x1579af1d, 0x980e4c21}, {0x15893f24, 0xba068d14}, {0x1599af24, 0xba0ece07}, {0x15a93f2b, 0xdc070ef8}, {0x15b9af2b, 0xdc0f4fcc}, {0x30000000, 0x0}, {0x30000000, 0x0}, {0x30000000, 0x0}, {0x30000000, 0x0}, {0x30000000, 0x0}, {0x30000000, 0x0}, {0x30000000, 0x0}, {0x30000000, 0x0}},
    {{0x0, 0x0}, {0x2835600, 0x1500022}, {0x28a5402, 0x25080bb}, {0x2915204, 0x3510154}, {0x2a261531, 0x158041d5}, {0x14ea070f, 0x75000260}, {0x11b2606, 0x4218316}, {0x14fa230f, 0x750043bf}, {0x3a17208, 0x5720439}, {0x150a3f0f, 0x7504851e}, {0x2e95a0a, 0x65a858f}, {0x151a5b0f, 0x7504c673}, {0x3b1720c, 0x77306e8}, {0x152a770f, 0x750907c4}, {0x3a040e, 0x903883e}, {0x153a930f, 0x75094915}, {0x154aaf0f, 0x750d89d0}, {0x155acb0f, 0x750dca78}, {0x156a461d, 0x98060b3d}, {0x157ab61d, 0x980e4c30}, {0x158a4624, 0xba068d23}, {0x159ab624, 0xba0ece16}, {0x15aa462b, 0xdc070f05}, {0x15bab62b, 0xdc0f4fda}, {0x30000000, 0x0}, {0x30000000, 0x0}, {0x30000000, 0x0}, {0x30000000, 0x0}, {0x30000000, 0x0}, {0x30000000, 0x0}, {0x30000000, 0x0}, {0x30000000, 0x0}},
    {{0x0, 0x0}, {0x2c35e00, 0x1580023}, {0x2ca5c02, 0x25880bc}, {0x2d15a04, 0x3590155}, {0x2a271532, 0x168041d6}, {0x14eb0716, 0x64000276}, {0x2a4a3f33, 0x41828320}, {0x14fb2316, 0x640043d5}, {0x1a23408, 0x532044f}, {0x150b3f16, 0x64048534}, {0x16a2c0a, 0x62a85a9}, {0x151b5b16, 0x6404c688}, {0x1f23c0c, 0x73b06fe}, {0x152b7716, 0x640907d9}, {0x23a440e, 0x9438853}, {0x153b9316, 0x6409492a}, {0x154baf16, 0x640d89da}, {0x155bcb16, 0x640dca83}, {0x156b4d1d, 0x98060b4d}, {0x157bbd1d, 0x980e4c40}, {0x158b4d24, 0xba068d32}, {0x159bbd24, 0xba0ece25}, {0x15ab4d2b, 0xdc070f12}, {0x15bbbd2b, 0xdc0f4fe7}, {0x30000000, 0x0}, {0x30000000, 0x0}, {0x30000000, 0x0}, {0x30000000, 0x0}, {0x30000000, 0x0}, {0x30000000, 0x0}, {0x30000000, 0x0}, {0x30000000, 0x0}},
    {{0x0, 0x0}, {0x3036600, 0x1600024}, {0x30a6402, 0x26080bd}, {0x3116204, 0x3610156}, {0x2a280033, 0x28081d8}, {0x14ec1c01, 0x3100028c}, {0x35b6e06, 0x469832f}, {0x14fc3801, 0x310443eb}, {0x3a27408, 0x5720465}, {0x150c5401, 0x3104854a}, {0x3ea7c0a, 0x67a85c2}, {0x151c7001, 0x3108c69d}, {0x33060c, 0x8030717}, {0x152c8c01, 0x310907ee}, {0x3b060e, 0x9038868}, {0x153ca801, 0x310d493c}, {0x154cc401, 0x310d89e5}, {0x155cd20f, 0x750dca8e}, {0x156c541d, 0x98060b5c}, {0x157cc41d, 0x980e4c4f}, {0x158c5424, 0xba068d42}, {0x159cc424, 0xba0ece34}, {0x15ac542b, 0xdc070f20}, {0x15bcc42b, 0xdc0f4ff4}, {0x30000000, 0x0}, {0x30000000, 0x0}, {0x30000000, 0x0}, {0x30000000, 0x0}, {0x30000000, 0x0}, {0x30000000, 0x0}, {0x30000000, 0x0}, {0x30000000, 0x0}},
    {{0x0, 0x0}, {0x3436e00, 0x1680026}, {0x34a6c02, 0x26880bf}, {0x3516a04, 0x3690158}, {0x2a290034, 0x38081d9}, {0x14ed1c08, 0x200002a2}, {0x9c1007, 0x411c33d}, {0x14fd3808, 0x20044401}, {0x1a33608, 0x532047b}, {0x150d5408, 0x20048560}, {0x1ab360a, 0x63285d6}, {0x151d7008, 0x2008c6b2}, {0x2b3560c, 0x8530732}, {0x152d8c08, 0x20090803}, {0x1fb3e0e, 0x93b8879}, {0x153da808, 0x200d4947}, {0x154dc408, 0x200d89ef}, {0x155dd216, 0x640dca98}, {0x156d5b1d, 0x98060b6b}, {0x157dcb1d, 0x980e4c5e}, {0x158d5b24, 0xba068d51}, {0x159dcb24, 0xba0ece44}, {0x15ad5b2b, 0xdc070f2d}, {0x15bdcb2b, 0xdc0f5001}, {0x30000000, 0x0}, {0x30000000, 0x0}, {0x30000000, 0x0}, {0x30000000, 0x0}, {0x30000000, 0x0}, {0x30000000, 0x0}, {0x30000000, 0x0}, {0x30000000, 0x0}},
    {{0x0, 0x0}, {0x3837600, 0x1700027}, {0x38a7402, 0x27080c0}, {0x3917204, 0x3710159}, {0x2a2a0733, 0x98081da}, {0x14ee2301, 0x310002b7}, {0x1dc3807, 0x439c349}, {0x14fe3f01, 0x31044417}, {0x3a37608, 0x5720491}, {0x150e5b01, 0x31048576}, {0x3eb7e0a, 0x67a85ec}, {0x151e7701, 0x3108c6c7}, {0xb4100d, 0x8134747}, {0x152e9301, 0x31090818}, {0x3fb7e0e, 0x97b888f}, {0x153eaf01, 0x310d4951}, {0x154ecb01, 0x310d89fa}, {0x155ed90f, 0x750dcaa3}, {0x156e621d, 0x98060b7a}, {0x157ed21d, 0x980e4c6d}, {0x158e6224, 0xba068d60}, {0x159ed224, 0xba0ece53}, {0x15ae622b, 0xdc070f3a}, {0x15bed22b, 0xdc0f500f}, {0x30000000, 0x0}, {0x30000000, 0x0}, {0x30000000, 0x0}, {0x30000000, 0x0}, {0x30000000, 0x0}, {0x30000000, 0x0}, {0x30000000, 0x0}, {0x30000000, 0x0}},
    {{0x0, 0x0}, {0x3c37e00, 0x1780028}, {0x3ca7c02, 0x27880c1}, {0x3d17a04, 0x379015a}, {0x2a2b0734, 0xa8081dc}, {0x14ef2308, 0x200002cd}, {0x31c6007, 0x461c358}, {0x14ff3f08, 0x2004442d}, {0x2644809, 0x54a44af}, {0x150f5b08, 0x2004858b}, {0x1ac300b, 0x732c600}, {0x151f7708, 0x2008c6dc}, {0x274480d, 0x84b4759}, {0x152f9308, 0x2009082d}, {0x1bc300f, 0x933c8a2}, {0x153faf08, 0x200d495c}, {0x154fcb08, 0x200d8a05}, {0x155fd916, 0x640dcaad}, {0x156f691d, 0x98060b89}, {0x157fd91d, 0x980e4c7c}, {0x158f6924, 0xba068d6f}, {0x159fd924, 0xba0ece62}, {0x15af692b, 0xdc070f48}, {0x15bfd92b, 0xdc0f501c}, {0x30000000, 0x0}, {0x30000000, 0x0}, {0x30000000, 0x0}, {0x30000000, 0x0}, {0x30000000, 0x0}, {0x30000000, 0x0}, {0x30000000, 0x0}, {0x30000000, 0x0}},
    {{0x0, 0x0}, {0x40001, 0x100402a}, {0xb0602, 0x20080c3}, {0x120404, 0x301015c}, {0x15c00002, 0x310001f0}, {0x570e05, 0x409425e}, {0x15d00e10, 0x750042e6}, {0xdd1a07, 0x419c36b}, {0x15e02a10, 0x75008446}, {0x1252209, 0x62244cd}, {0x15f04610, 0x7504c5a3}, {0x3ec780b, 0x77ac616}, {0x16006210, 0x750506f4}, {0x750a0d, 0x80b476e}, {0x16107e10, 0x75094845}, {0x3bc700f, 0x973c8b7}, {0x16209a10, 0x75098968}, {0x1630b610, 0x750dca10}, {0x1640001e, 0x98020ab9}, {0x1650701e, 0x980a4b9a}, {0x16600025, 0xba028c8d}, {0x16707025, 0xba0acd80}, {0x1680002c, 0xdc030e73}, {0x1690702c, 0xdc0b4f57}, {0x30000000, 0x0}, {0x30000000, 0x0}, {0x30000000, 0x0}, {0x30000000, 0x0}, {0x30000000, 0x0}, {0x30000000, 0x0}, {0x30000000, 0x0}, {0x30000000, 0x0}},
    {{0x0, 0x0}, {0x440801, 0x108402b}, {0x4b0e02, 0x20880c4}, {0x520c04, 0x309015d}, {0x15c10009, 0x200001fb}, {0x2a423133, 0x33820270}, {0x15d10e17, 0x640042fc}, {0x25d4a07, 0x449c37c}, {0x15e12a17, 0x6400845c}, {0x2e55a09, 0x65a44e1}, {0x15f14617, 0x6404c5b8}, {0x1ed3a0b, 0x73ac62b}, {0x16016217, 0x64050709}, {0x235420d, 0x8434781}, {0x16117e17, 0x6409485a}, {0x13d220f, 0x923c8c7}, {0x16219a17, 0x64098972}, {0x1631b617, 0x640dca1b}, {0x1641071e, 0x98020ac4}, {0x1651771e, 0x980a4baa}, {0x16610725, 0xba028c9c}, {0x16717725, 0xba0acd8f}, {0x1681072c, 0xdc030e82}, {0x1691772c, 0xdc0b4f64}, {0x30000000, 0x0}, {0x30000000, 0x0}, {0x30000000, 0x0}, {0x30000000, 0x0}, {0x30000000, 0x0}, {0x30000000, 0x0}, {0x30000000, 0x0}, {0x30000000, 0x0}},
    {{0x0, 0x0}, {0x841001, 0x110402c}, {0x8b1602, 0x21080c5}, {0x921404, 0x311015e}, {0x15c20702, 0x31000206}, {0x3977605, 0x4714282}, {0x15d21510, 0x75004312}, {0x2a4f5b32, 0x5c82c38e}, {0x15e23110, 0x75008472}, {0xe61c09, 0x61a44f7}, {0x15f24d10, 0x7504c5cd}, {0x3ed7a0b, 0x77ac641}, {0x16026910, 0x7505071e}, {0x3f57a0d, 0x87b4792}, {0x16128510, 0x7509486f}, {0x27d4a0f, 0x94bc8d4}, {0x1622a110, 0x7509897d}, {0x1632bd10, 0x750dca25}, {0x16420e1e, 0x98020ace}, {0x16527e1e, 0x980a4bb9}, {0x16620e25, 0xba028cac}, {0x16727e25, 0xba0acd9f}, {0x16820e2c, 0xdc030e91}, {0x16927e2c, 0xdc0b4f71}, {0x30000000, 0x0}, {0x30000000, 0x0}, {0x30000000, 0x0}, {0x30000000, 0x0}, {0x30000000, 0x0}, {0x30000000, 0x0}, {0x30000000, 0x0}, {0x30000000, 0x0}},
    {{0x0, 0x0}, {0xc41801, 0x118402d}, {0xcb1e02, 0x21880c6}, {0xd21c04, 0x319015f}, {0x15c30709, 0x20000211}, {0x1182006, 0x4218292}, {0x15d31517, 0x64004328}, {0x19e3407, 0x531c39f}, {0x15e33117, 0x64008487}, {0x2a65409, 0x652450a}, {0x15f34d17, 0x6404c5e2}, {0x1ae340b, 0x732c654}, {0x31020c, 0x70306c3}, {0x16036917, 0x64050733}, {0x2b6540d, 0x85347b0}, {0x16138517, 0x64094884}, {0x13e240f, 0x923c8f1}, {0x1623a117, 0x64098987}, {0x1633bd17, 0x640dca30}, {0x1643151e, 0x98020ad9}, {0x1653851e, 0x980a4bc8}, {0x16631525, 0xba028cbb}, {0x16738525, 0xba0acdae}, {0x1683152c, 0xdc030ea1}, {0x1693852c, 0xdc0b4f7f}, {0x30000000, 0x0}, {0x30000000, 0x0}, {0x30000000, 0x0}, {0x30000000, 0x0}, {0x30000000, 0x0}, {0x30000000, 0x0}, {0x30000000, 0x0}},
    {{0x0, 0x0}, {0x1042001, 0x120402f}, {0x10b2602, 0x22080c8}, {0x1122404, 0x3210161}, {0x15c40e02, 0x3100021c}, {0x2985006, 0x45182a3}, {0x15d42a02, 0x3100433e}, {0x39e7407, 0x571c3b5}, {0x15e44602, 0x3104849d}, {0x670e09, 0x60a451d}, {0x15f46202, 0x3104c5f7}, {0x36e6c0b, 0x76ac667}, {0x16047e02, 0x31090748}, {0x2764c0d, 0x84b47ad}, {0x1b9320e, 0x8338824}, {0x16149a02, 0x31094899}, {0x2be540f, 0x953c901}, {0x1624b602, 0x310d8992}, {0x1634d202, 0x310dca3b}, {0x16441c1e, 0x98020ae4}, {0x16548c1e, 0x980a4bd7}, {0x16641c25, 0xba028cca}, {0x16748c25, 0xba0acdbd}, {0x16841c2c, 0xdc030eb0}, {0x16948c2c, 0xdc0b4f8c}, {0x30000000, 0x0}, {0x30000000, 0x0}, {0x30000000, 0x0}, {0x30000000, 0x0}, {0x30000000, 0x0}, {0x30000000, 0x0}, {0x30000000, 0x0}},
    {{0x0, 0x0}, {0x1442801, 0x1284030}, {0x14b2e02, 0x22880c9}, {0x1522c04, 0x3290162}, {0x15c50e09, 0x20000227}, {0x190206, 0x40182b3}, {0x15d52a09, 0x20004354}, {0x15f2e07, 0x529c3c9}, {0x15e54609, 0x200484b3}, {0x1e73e09, 0x63a452c}, {0x15f56209, 0x2004c60c}, {0xaf160b, 0x712c674}, {0x3f17a0c, 0x77b06e9}, {0x16057e09, 0x2009075d}, {0x237460d, 0x84347d5}, {0x16159a09, 0x200948ae}, {0x7f0e0f, 0x90bc914}, {0x1625b609, 0x200d899d}, {0x1635d209, 0x200dca45}, {0x1645231e, 0x98020af3}, {0x1655931e, 0x980a4be6}, {0x16652325, 0xba028cd9}, {0x16759325, 0xba0acdcc}, {0x1685232c, 0xdc030ebf}, {0x1695932c, 0xdc0b4f99}, {0x30000000, 0x0}, {0x30000000, 0x0}, {0x30000000, 0x0}, {0x30000000, 0x0}, {0x30000000, 0x0}, {0x30000000, 0x0}, {0x30000000, 0x0}},
    {{0x0, 0x0}, {0x1843001, 0x1304031}, {0x18b3602, 0x23080ca}, {0x1923404, 0x3310163}, {0x15c61502, 0x31000232}, {0x1d93a06, 0x43982c5}, {0x15d63102, 0x3100436a}, {0x31f6607, 0x561c3dc}, {0x15e64d02, 0x310484c9}, {0x3676e09, 0x66a453e}, {0x15f66902, 0x3104c621}, {0x1ef3e0b, 0x73ac680}, {0x16068502, 0x31090772}, {0x770e0d, 0x80b47c2}, {0x3f97a0e, 0x87b883a}, {0x1616a102, 0x310948c3}, {0x23f460f, 0x943c926}, {0x1626bd02, 0x310d89a7}, {0x1636d902, 0x310dca50}, {0x16462a1e, 0x98020b03}, {0x16569a1e, 0x980a4bf6}, {0x16662a25, 0xba028ce8}, {0x16769a25, 0xba0acddb}, {0x16862a2c, 0xdc030ece}, {0x16969a2c, 0xdc0b4fa6}, {0x30000000, 0x0}, {0x30000000, 0x0}, {0x30000000, 0x0}, {0x30000000, 0x0}, {0x30000000, 0x0}, {0x30000000, 0x0}, {0x30000000, 0x0}},
    {{0x0, 0x0}, {0x1c43801, 0x1384033}, {0x1cb3e02, 0x23880cc}, {0x1d23c04, 0x3390165}, {0x15c71509, 0x2000023d}, {0x3596a06, 0x46982d7}, {0x15d73109, 0x20004380}, {0xe01808, 0x51a03ef}, {0x15e74d09, 0x200484df}, {0xe8180a, 0x61a854f}, {0x15f76909, 0x2004c636}, {0x2af560b, 0x752c689}, {0x232440c, 0x7430702}, {0x16078509, 0x20090787}, {0x138200e, 0x82387f4}, {0x1617a109, 0x200948d8}, {0x3ff7e0f, 0x97bc937}, {0x1627bd09, 0x200d89b2}, {0x1637d909, 0x200dca5a}, {0x1647311e, 0x98020b12}, {0x1657a11e, 0x980a4c05}, {0x16673125, 0xba028cf8}, {0x1677a125, 0xba0acdea}, {0x1687312c, 0xdc030edd}, {0x1697a12c, 0xdc0b4fb4}, {0x30000000, 0x0}, {0x30000000, 0x0}, {0x30000000, 0x0}, {0x30000000, 0x0}, {0x30000000, 0x0}, {0x30000000, 0x0}, {0x30000000, 0x0}},
    {{0x0, 0x0}, {0x2044001, 0x1404034}, {0x20b4602, 0x24080cd}, {0x2124404, 0x3410166}, {0x15c80010, 0x75000248}, {0xda1c06, 0x41982e8}, {0x15d81c10, 0x75004396}, {0x2a05008, 0x5520402}, {0x1e33e08, 0x53a047d}, {0x15e83810, 0x750484f5}, {0x1692a0a, 0x62a857f}, {0x15f85410, 0x7504c64b}, {0x3b0700c, 0x77306be}, {0x16087010, 0x7509079c}, {0x378680e, 0x86b880c}, {0x16188c10, 0x750948ed}, {0x1628a810, 0x750d89bc}, {0x1638c410, 0x750dca65}, {0x1648381e, 0x98060b21}, {0x1658a81e, 0x980e4c14}, {0x16683825, 0xba068d07}, {0x1678a825, 0xba0ecdfa}, {0x1688382c, 0xdc070eec}, {0x1698a82c, 0xdc0f4fc1}, {0x30000000, 0x0}, {0x30000000, 0x0}, {0x30000000, 0x0}, {0x30000000, 0x0}, {0x30000000, 0x0}, {0x30000000, 0x0}, {0x30000000, 0x0}, {0x30000000, 0x0}},
    {{0x0, 0x0}, {0x2444801, 0x1484035}, {0x24b4e02, 0x24880ce}, {0x2524c04, 0x3490167}, {0x2a2c1c31, 0x1c80c1dd}, {0x15c90017, 0x64000253}, {0x15d91c17, 0x640043ac}, {0x610a08, 0x50a0416}, {0x15e93817, 0x6404850b}, {0x3a8700a, 0x672856d}, {0x32b660a, 0x66285e6}, {0x15f95417, 0x6404c660}, {0x1712a0c, 0x72b06d0}, {0x16097017, 0x640907b1}, {0x239420e, 0x8438829}, {0x16198c17, 0x64094902}, {0x1629a817, 0x640d89c7}, {0x1639c417, 0x640dca6f}, {0x16493f1e, 0x98060b30}, {0x1659af1e, 0x980e4c23}, {0x16693f25, 0xba068d16}, {0x1679af25, 0xba0ece09}, {0x16893f2c, 0xdc070efa}, {0x1699af2c, 0xdc0f4fce}, {0x30000000, 0x0}, {0x30000000, 0x0}, {0x30000000, 0x0}, {0x30000000, 0x0}, {0x30000000, 0x0}, {0x30000000, 0x0}, {0x30000000, 0x0}, {0x30000000, 0x0}},
    {{0x0, 0x0}, {0x2845001, 0x1504037}, {0x28b5602, 0x25080d0}, {0x2925404, 0x3510169}, {0x2a2d1c32, 0x1d80c1df}, {0x15ca0710, 0x75000262}, {0x9b1606, 0x4118311}, {0x15da2310, 0x750043c2}, {0x3e17a08, 0x57a043b}, {0x15ea3f10, 0x75048521}, {0x329620a, 0x6628591}, {0x15fa5b10, 0x7504c675}, {0x32040c, 0x70306ed}, {0x160a7710, 0x750907c6}, {0x7a0c0e, 0x90b8841}, {0x161a9310, 0x75094918}, {0x162aaf10, 0x750d89d1}, {0x163acb10, 0x750dca7a}, {0x164a461e, 0x98060b3f}, {0x165ab61e, 0x980e4c32}, {0x166a4625, 0xba068d25}, {0x167ab625, 0xba0ece18}, {0x168a462c, 0xdc070f07}, {0x169ab62c, 0xdc0f4fdc}, {0x30000000, 0x0}, {0x30000000, 0x0}, {0x30000000, 0x0}, {0x30000000, 0x0}, {0x30000000, 0x0}, {0x30000000, 0x0}, {0x30000000, 0x0}, {0x30000000, 0x0}},
    {{0x0, 0x0}, {0x2c45801, 0x1584038}, {0x2cb5e02, 0x25880d1}, {0x2d25c04, 0x359016a}, {0x2a2e2331, 0x2380c1e0}, {0x15cb0717, 0x64000278}, {0x21b4606, 0x4418321}, {0x15db2317, 0x640043d8}, {0x1e23c08, 0x53a0451}, {0x15eb3f17, 0x64048537}, {0x1aa340a, 0x63285ac}, {0x15fb5b17, 0x6404c68a}, {0x2724c0c, 0x74b0705}, {0x160b7717, 0x640907db}, {0x27a4c0e, 0x94b8856}, {0x161b9317, 0x6409492d}, {0x162baf17, 0x640d89dc}, {0x163bcb17, 0x640dca84}, {0x164b4d1e, 0x98060b4f}, {0x165bbd1e, 0x980e4c41}, {0x166b4d25, 0xba068d34}, {0x167bbd25, 0xba0ece27}, {0x168b4d2c, 0xdc070f14}, {0x169bbd2c, 0xdc0f4fe9}, {0x30000000, 0x0}, {0x30000000, 0x0}, {0x30000000, 0x0}, {0x30000000, 0x0}, {0x30000000, 0x0}, {0x30000000, 0x0}, {0x30000000, 0x0}, {0x30000000, 0x0}},
    {{0x0, 0x0}, {0x3046001, 0x1604039}, {0x30b6602, 0x26080d2}, {0x3126404, 0x361016b}, {0x2a2f2332, 0x2480c1e1}, {0x15cc1c02, 0x3100028e}, {0x39b7606, 0x4718332}, {0x15dc3802, 0x310443ee}, {0x3e27c08, 0x57a0467}, {0x15ec5402, 0x3104854d}, {0x2b060a, 0x60285c6}, {0x15fc7002, 0x3108c69f}, {0xb3160c, 0x813071c}, {0x160c8c02, 0x310907f1}, {0x7b0e0e, 0x90b886b}, {0x161ca802, 0x310d493e}, {0x162cc402, 0x310d89e6}, {0x163cd210, 0x750dca8f}, {0x164c541e, 0x98060b5e}, {0x165cc41e, 0x980e4c51}, {0x166c5425, 0xba068d43}, {0x167cc425, 0xba0ece36}, {0x168c542c, 0xdc070f22}, {0x169cc42c, 0xdc0f4ff6}, {0x30000000, 0x0}, {0x30000000, 0x0}, {0x30000000, 0x0}, {0x30000000, 0x0}, {0x30000000, 0x0}, {0x30000000, 0x0}, {0x30000000, 0x0}, {0x30000000, 0x0}},
    {{0x0, 0x0}, {0x3446801, 0x168403b}, {0x34b6e02, 0x26880d4}, {0x3526c04, 0x369016d}, {0x2a300e33, 0x108101e3}, {0x15cd1c09, 0x200002a4}, {0xdc1807, 0x419c33f}, {0x15dd3809, 0x20044404}, {0x2234608, 0x5420481}, {0x15ed5409, 0x20048563}, {0x22b460a, 0x64285db}, {0x15fd7009, 0x2008c6b4}, {0x333660c, 0x8630737}, {0x160d8c09, 0x20090806}, {0x23b460e, 0x943887d}, {0x161da809, 0x200d4948}, {0x162dc409, 0x200d89f1}, {0x163dd217, 0x640dca99}, {0x164d5b1e, 0x98060b6d}, {0x165dcb1e, 0x980e4c60}, {0x166d5b25, 0xba068d53}, {0x167dcb25, 0xba0ece45}, {0x168d5b2c, 0xdc070f2f}, {0x169dcb2c, 0xdc0f5003}, {0x30000000, 0x0}, {0x30000000, 0x0}, {0x30000000, 0x0}, {0x30000000, 0x0}, {0x30000000, 0x0}, {0x30000000, 0x0}, {0x30000000, 0x0}, {0x30000000, 0x0}},
    {{0x0, 0x0}, {0x3847001, 0x170403c}, {0x38b7602, 0x27080d5}, {0x3927404, 0x371016e}, {0x2a310e34, 0x118101e4}, {0x15ce2302, 0x310002ba}, {0x2a4c5431, 0x5482c34c}, {0x15de3f02, 0x3104441a}, {0x240009, 0x5024497}, {0x15ee5b02, 0x31048578}, {0x2c000b, 0x702c5f0}, {0x15fe7702, 0x3108c6ca}, {0xf4180d, 0x81b4749}, {0x160e9302, 0x3109081b}, {0x3c000f, 0x903c892}, {0x161eaf02, 0x310d4953}, {0x162ecb02, 0x310d89fb}, {0x163ed910, 0x750dcaa4}, {0x164e621e, 0x98060b7c}, {0x165ed21e, 0x980e4c6f}, {0x166e6225, 0xba068d62}, {0x167ed225, 0xba0ece55}, {0x168e622c, 0xdc070f3c}, {0x169ed22c, 0xdc0f5011}, {0x30000000, 0x0}, {0x30000000, 0x0}, {0x30000000, 0x0}, {0x30000000, 0x0}, {0x30000000, 0x0}, {0x30000000, 0x0}, {0x30000000, 0x0}, {0x30000000, 0x0}},
    {{0x0, 0x0}, {0x3c47801, 0x178403d}, {0x3cb7e02, 0x27880d6}, {0x3d27c04, 0x379016f}, {0x2a321533, 0x178101e5}, {0x15cf2309, 0x200002d0}, {0x35c6807, 0x469c35b}, {0x15df3f09, 0x20044430}, {0x2e45809, 0x55a44b5}, {0x15ef5b09, 0x2004858d}, {0x22c400b, 0x742c605}, {0x15ff7709, 0x2008c6df}, {0x2b4500d, 0x853475c}, {0x160f9309, 0x20090830}, {0x1fc380f, 0x93bc8a4}, {0x161faf09, 0x200d495d}, {0x162fcb09, 0x200d8a06}, {0x163fd917, 0x640dcaae}, {0x164f691e, 0x98060b8b}, {0x165fd91e, 0x980e4c7e}, {0x166f6925, 0xba068d71}, {0x167fd925, 0xba0ece64}, {0x168f692c, 0xdc070f49}, {0x169fd92c, 0xdc0f501e}, {0x30000000, 0x0}, {0x30000000, 0x0}, {0x30000000, 0x0}, {0x30000000, 0x0}, {0x30000000, 0x0}, {0x30000000, 0x0}, {0x30000000, 0x0}, {0x30000000, 0x0}},
    {{0x0, 0x0}, {0x50201, 0x100403f}, {0xc0003, 0x200c0d8}, {0x130604, 0x3010171}, {0x16a00003, 0x310001f2}, {0x971605, 0x4114261}, {0x16b00e11, 0x750042e9}, {0x11d2207, 0x421c36e}, {0x16c02a11, 0x75008448}, {0x1652a09, 0x62a44d0}, {0x16d04611, 0x7504c5a5}, {0x2d020b, 0x702c61a}, {0x16e06211, 0x750506f6}, {0xb5120d, 0x8134771}, {0x16f07e11, 0x75094847}, {0x3fc780f, 0x97bc8b9}, {0x17009a11, 0x75098969}, {0x1710b611, 0x750dca12}, {0x1720001f, 0x98020aba}, {0x1730701f, 0x980a4b9c}, {0x17400026, 0xba028c8f}, {0x17507026, 0xba0acd82}, {0x1760002d, 0xdc030e75}, {0x1770702d, 0xdc0b4f59}, {0x30000000, 0x0}, {0x30000000, 0x0}, {0x30000000, 0x0}, {0x30000000, 0x0}, {0x30000000, 0x0}, {0x30000000, 0x0}, {0x30000000, 0x0}, {0x30000000, 0x0}},
    {{0x0, 0x0}, {0x450a01, 0x1084040}, {0x4c0803, 0x208c0d9}, {0x530e04, 0x3090172}, {0x16a1000a, 0x200001fd}, {0x2174605, 0x4414271}, {0x16b10e18, 0x640042ff}, {0x29d5207, 0x451c37f}, {0x16c12a18, 0x6400845e}, {0x3656a09, 0x66a44e6}, {0x16d14618, 0x6404c5ba}, {0x22d420b, 0x742c62f}, {0x16e16218, 0x6405070b}, {0x2754a0d, 0x84b4783}, {0x16f17e18, 0x6409485d}, {0x17d2a0f, 0x92bc8ca}, {0x17019a18, 0x64098974}, {0x1711b618, 0x640dca1c}, {0x1721071f, 0x98020ac5}, {0x1731771f, 0x980a4bac}, {0x17410726, 0xba028c9e}, {0x17517726, 0xba0acd91}, {0x1761072d, 0xdc030e84}, {0x1771772d, 0xdc0b4f66}, {0x30000000, 0x0}, {0x30000000, 0x0}, {0x30000000, 0x0}, {0x30000000, 0x0}, {0x30000000, 0x0}, {0x30000000, 0x0}, {0x30000000, 0x0}, {0x30000000, 0x0}},
    {{0x0, 0x0}, {0x851201, 0x1104041}, {0x8c1003, 0x210c0da}, {0x931604, 0x3110173}, {0x16a20703, 0x31000208}, {0x3d77e05, 0x4794283}, {0x16b21511, 0x75004315}, {0x1e0407, 0x501c38f}, {0x16c23111, 0x75008474}, {0x1262409, 0x62244f9}, {0x16d24d11, 0x7504c5cf}, {0x2e040b, 0x702c644}, {0x16e26911, 0x75050720}, {0x36040d, 0x8034796}, {0x16f28511, 0x75094872}, {0x2bd520f, 0x953c8d7}, {0x1702a111, 0x7509897e}, {0x1712bd11, 0x750dca27}, {0x17220e1f, 0x98020acf}, {0x17327e1f, 0x980a4bbb}, {0x17420e26, 0xba028cae}, {0x17527e26, 0xba0acda0}, {0x17620e2d, 0xdc030e93}, {0x17727e2d, 0xdc0b4f73}, {0x30000000, 0x0}, {0x30000000, 0x0}, {0x30000000, 0x0}, {0x30000000, 0x0}, {0x30000000, 0x0}, {0x30000000, 0x0}, {0x30000000, 0x0}, {0x30000000, 0x0}},
    {{0x0, 0x0}, {0xc51a01, 0x1184042}, {0xcc1803, 0x218c0db}, {0xd31e04, 0x3190174}, {0x16a3070a, 0x20000213}, {0x1582806, 0x4298295}, {0x16b31518, 0x6400432b}, {0x1de3c07, 0x539c3a1}, {0x16c33118, 0x6400848a}, {0x2e65c09, 0x65a450d}, {0x16d34d18, 0x6404c5e4}, {0x1ee3c0b, 0x73ac656}, {0x710a0c, 0x70b06c6}, {0x16e36918, 0x64050736}, {0x2f65c0d, 0x85b47b3}, {0x16f38518, 0x64094887}, {0x17e2c0f, 0x92bc8f4}, {0x1703a118, 0x64098989}, {0x1713bd18, 0x640dca31}, {0x1723151f, 0x98020ada}, {0x1733851f, 0x980a4bca}, {0x17431526, 0xba028cbd}, {0x17538526, 0xba0acdb0}, {0x1763152d, 0xdc030ea2}, {0x1773852d, 0xdc0b4f80}, {0x30000000, 0x0}, {0x30000000, 0x0}, {0x30000000, 0x0}, {0x30000000, 0x0}, {0x30000000, 0x0}, {0x30000000, 0x0}, {0x30000000, 0x0}},
    {{0x0, 0x0}, {0x1052201, 0x1204044}, {0x10c2003, 0x220c0dd}, {0x1132604, 0x3210176}, {0x16a40e03, 0x3100021e}, {0x2d85806, 0x45982a6}, {0x16b42a03, 0x31004341}, {0x3de7c07, 0x579c3b7}, {0x2614a08, 0x54a042c}, {0x16c44603, 0x310484a0}, {0x2e75e09, 0x65a4539}, {0x16d46203, 0x3104c5f9}, {0x1af360b, 0x732c67e}, {0x16e47e03, 0x3109074b}, {0x37060d, 0x80347c0}, {0x16f49a03, 0x3109489c}, {0x2fe5c0f, 0x95bc904}, {0x1704b603, 0x310d8993}, {0x1714d203, 0x310dca3c}, {0x17241c1f, 0x98020ae6}, {0x17348c1f, 0x980a4bd9}, {0x17441c26, 0xba028ccc}, {0x17548c26, 0xba0acdbf}, {0x17641c2d, 0xdc030eb2}, {0x17748c2d, 0xdc0b4f8e}, {0x30000000, 0x0}, {0x30000000, 0x0}, {0x30000000, 0x0}, {0x30000000, 0x0}, {0x30000000, 0x0}, {0x30000000, 0x0}, {0x30000000, 0x0}},
    {{0x0, 0x0}, {0x1452a01, 0x1284045}, {0x14c2803, 0x228c0de}, {0x1532e04, 0x3290177}, {0x16a50e0a, 0x20000229}, {0x590a06, 0x40982b6}, {0x16b52a0a, 0x20004357}, {0x19f3607, 0x531c3cb}, {0x16c5460a, 0x200484b6}, {0x2274609, 0x6424530}, {0x16d5620a, 0x2004c60f}, {0xef1e0b, 0x71ac677}, {0x16e57e0a, 0x20090760}, {0x3766c0d, 0x86b47b8}, {0x2f95a0e, 0x85b8831}, {0x16f59a0a, 0x200948b1}, {0xbf160f, 0x913c916}, {0x1705b60a, 0x200d899e}, {0x1715d20a, 0x200dca46}, {0x1725231f, 0x98020af5}, {0x1735931f, 0x980a4be8}, {0x17452326, 0xba028cdb}, {0x17559326, 0xba0acdce}, {0x1765232d, 0xdc030ec1}, {0x1775932d, 0xdc0b4f9b}, {0x30000000, 0x0}, {0x30000000, 0x0}, {0x30000000, 0x0}, {0x30000000, 0x0}, {0x30000000, 0x0}, {0x30000000, 0x0}, {0x30000000, 0x0}},
    {{0x0, 0x0}, {0x1853201, 0x1304046}, {0x18c3003, 0x230c0df}, {0x1933604, 0x3310178}, {0x16a61503, 0x31000234}, {0x2a464d31, 0x4d8242c8}, {0x16b63103, 0x3100436d}, {0x35f6e07, 0x569c3df}, {0x16c64d03, 0x310484cc}, {0x3a77609, 0x6724541}, {0x16d66903, 0x3104c624}, {0x22f460b, 0x742c684}, {0x16e68503, 0x31090775}, {0xf71e0d, 0x81b47c8}, {0xba140e, 0x9138843}, {0x16f6a103, 0x310948c6}, {0x27f4e0f, 0x94bc929}, {0x1706bd03, 0x310d89a8}, {0x1716d903, 0x310dca51}, {0x17262a1f, 0x98020b05}, {0x17369a1f, 0x980a4bf7}, {0x17462a26, 0xba028cea}, {0x17569a26, 0xba0acddd}, {0x17662a2d, 0xdc030ed0}, {0x17769a2d, 0xdc0b4fa8}, {0x30000000, 0x0}, {0x30000000, 0x0}, {0x30000000, 0x0}, {0x30000000, 0x0}, {0x30000000, 0x0}, {0x30000000, 0x0}, {0x30000000, 0x0}},
    {{0x0, 0x0}, {0x1c53a01, 0x1384048}, {0x1cc3803, 0x238c0e1}, {0x1d33e04, 0x339017a}, {0x16a7150a, 0x2000023f}, {0x3997206, 0x47182da}, {0x16b7310a, 0x20004383}, {0x1202008, 0x52203f2}, {0x16c74d0a, 0x200484e2}, {0x168280a, 0x62a8554}, {0x16d7690a, 0x2004c639}, {0x32f660b, 0x762c68e}, {0x2f25c0c, 0x75b070a}, {0x16e7850a, 0x2009078a}, {0x178280e, 0x82b87f7}, {0x16f7a10a, 0x200948db}, {0x1707bd0a, 0x200d89b3}, {0x1717d90a, 0x200dca5b}, {0x1727311f, 0x98020b14}, {0x1737a11f, 0x980a4c07}, {0x17473126, 0xba028cf9}, {0x1757a126, 0xba0acdec}, {0x1767312d, 0xdc030edf}, {0x1777a12d, 0xdc0b4fb6}, {0x30000000, 0x0}, {0x30000000, 0x0}, {0x30000000, 0x0}, {0x30000000, 0x0}, {0x30000000, 0x0}, {0x30000000, 0x0}, {0x30000000, 0x0}, {0x30000000, 0x0}},
    {{0x0, 0x0}, {0x2054201, 0x1404049}, {0x20c4003, 0x240c0e2}, {0x2134604, 0x341017b}, {0x16a80011, 0x7500024a}, {0x11a2406, 0x42182ea}, {0x16b81c11, 0x75004399}, {0x2e05808, 0x55a0405}, {0x16c83811, 0x750484f8}, {0x2a8500a, 0x6528562}, {0x1eb3e0a, 0x63a85d7}, {0x16d85411, 0x7504c64e}, {0x3f0780c, 0x77b06bf}, {0x16e87011, 0x7509079f}, {0x3b8700e, 0x873880f}, {0x16f88c11, 0x750948f0}, {0x1708a811, 0x750d89bd}, {0x1718c411, 0x750dca66}, {0x1728381f, 0x98060b23}, {0x1738a81f, 0x980e4c16}, {0x17483826, 0xba068d09}, {0x1758a826, 0xba0ecdfb}, {0x1768382d, 0xdc070eee}, {0x1778a82d, 0xdc0f4fc3}, {0x30000000, 0x0}, {0x30000000, 0x0}, {0x30000000, 0x0}, {0x30000000, 0x0}, {0x30000000, 0x0}, {0x30000000, 0x0}, {0x30000000, 0x0}, {0x30000000, 0x0}},
    {{0x0, 0x0}, {0x2454a01, 0x148404a}, {0x24c4803, 0x248c0e3}, {0x2534e04, 0x349017c}, {0x2a331534, 0x188101e7}, {0x16a90018, 0x64000255}, {0x16b91c18, 0x640043af}, {0xa11208, 0x5120418}, {0x3e37e08, 0x57a0492}, {0x16c93818, 0x6404850e}, {0x229420a, 0x6428587}, {0x16d95418, 0x6404c663}, {0x1f13a0c, 0x73b06d4}, {0x16e97018, 0x640907b4}, {0x2794a0e, 0x84b882c}, {0x16f98c18, 0x64094905}, {0x1709a818, 0x640d89c8}, {0x1719c418, 0x640dca71}, {0x17293f1f, 0x98060b32}, {0x1739af1f, 0x980e4c25}, {0x17493f26, 0xba068d18}, {0x1759af26, 0xba0ece0b}, {0x17693f2d, 0xdc070efc}, {0x1779af2d, 0xdc0f4fd0}, {0x30000000, 0x0}, {0x30000000, 0x0}, {0x30000000, 0x0}, {0x30000000, 0x0}, {0x30000000, 0x0}, {0x30000000, 0x0}, {0x30000000, 0x0}, {0x30000000, 0x0}},
    {{0x0, 0x0}, {0x2855201, 0x150404c}, {0x28c5003, 0x250c0e5}, {0x2935604, 0x351017e}, {0x2a342a31, 0x2a8141e8}, {0x16aa0711, 0x75000265}, {0xdb1e06, 0x4198313}, {0x16ba2311, 0x750043c5}, {0x220408, 0x502043f}, {0x16ca3f11, 0x75048524}, {0x3696a0a, 0x66a8594}, {0x16da5b11, 0x7504c678}, {0x720c0c, 0x70b06f0}, {0x16ea7711, 0x750907c9}, {0xfa1c0e, 0x91b8846}, {0x16fa9311, 0x7509491a}, {0x170aaf11, 0x750d89d3}, {0x171acb11, 0x750dca7b}, {0x172a461f, 0x98060b41}, {0x173ab61f, 0x980e4c34}, {0x174a4626, 0xba068d27}, {0x175ab626, 0xba0ece1a}, {0x176a462d, 0xdc070f09}, {0x177ab62d, 0xdc0f4fdd}, {0x30000000, 0x0}, {0x30000000, 0x0}, {0x30000000, 0x0}, {0x30000000, 0x0}, {0x30000000, 0x0}, {0x30000000, 0x0}, {0x30000000, 0x0}, {0x30000000, 0x0}},
    {{0x0, 0x0}, {0x2c55a01, 0x158404d}, {0x2cc5803, 0x258c0e6}, {0x2d35e04, 0x359017f}, {0x2a352a32, 0x2b8141ea}, {0x16ab0718, 0x6400027b}, {0x25b4e06, 0x4498324}, {0x16bb2318, 0x640043db}, {0x2224408, 0x5420455}, {0x16cb3f18, 0x6404853a}, {0x1ea3c0a, 0x63a85ad}, {0x16db5b18, 0x6404c68d}, {0x2b2540c, 0x7530707}, {0x16eb7718, 0x640907de}, {0x2fa5c0e, 0x95b885b}, {0x16fb9318, 0x6409492f}, {0x170baf18, 0x640d89dd}, {0x171bcb18, 0x640dca86}, {0x172b4d1f, 0x98060b50}, {0x173bbd1f, 0x980e4c43}, {0x174b4d26, 0xba068d36}, {0x175bbd26, 0xba0ece29}, {0x176b4d2d, 0xdc070f16}, {0x177bbd2d, 0xdc0f4feb}, {0x30000000, 0x0}, {0x30000000, 0x0}, {0x30000000, 0x0}, {0x30000000, 0x0}, {0x30000000, 0x0}, {0x30000000, 0x0}, {0x30000000, 0x0}, {0x30000000, 0x0}},
    {{0x0, 0x0}, {0x3056201, 0x160404e}, {0x30c6003, 0x260c0e7}, {0x3136604, 0x3610180}, {0x2a363131, 0x318141eb}, {0x16ac1c03, 0x31000291}, {0x3db7e06, 0x4798333}, {0x16bc3803, 0x310443f0}, {0x230608, 0x502046b}, {0x16cc5403, 0x31048550}, {0x6b0e0a, 0x60a85c9}, {0x16dc7003, 0x3108c6a2}, {0xf31e0c, 0x81b071f}, {0x16ec8c03, 0x310907f3}, {0xbb160e, 0x913886e}, {0x16fca803, 0x310d493f}, {0x170cc403, 0x310d89e8}, {0x171cd211, 0x750dca90}, {0x172c541f, 0x98060b60}, {0x173cc41f, 0x980e4c52}, {0x174c5426, 0xba068d45}, {0x175cc426, 0xba0ece38}, {0x176c542d, 0xdc070f23}, {0x177cc42d, 0xdc0f4ff8}, {0x30000000, 0x0}, {0x30000000, 0x0}, {0x30000000, 0x0}, {0x30000000, 0x0}, {0x30000000, 0x0}, {0x30000000, 0x0}, {0x30000000, 0x0}, {0x30000000, 0x0}},
    {{0x0, 0x0}, {0x3456a01, 0x1684050}, {0x34c6803, 0x268c0e9}, {0x3536e04, 0x3690182}, {0x2a373132, 0x328141ec}, {0x16ad1c0a, 0x200002a7}, {0x11c2007, 0x421c342}, {0x16bd380a, 0x20044406}, {0x2634e08, 0x54a0483}, {0x16cd540a, 0x20048566}, {0x26b4e0a, 0x64a85de}, {0x16dd700a, 0x2008c6b7}, {0x3736e0c, 0x86b0739}, {0x16ed8c0a, 0x20090808}, {0x2bb560e, 0x9538883}, {0x16fda80a, 0x200d494a}, {0x170dc40a, 0x200d89f2}, {0x171dd218, 0x640dca9b}, {0x172d5b1f, 0x98060b6f}, {0x173dcb1f, 0x980e4c62}, {0x174d5b26, 0xba068d55}, {0x175dcb26, 0xba0ece47}, {0x176d5b2d, 0xdc070f31}, {0x177dcb2d, 0xdc0f5005}, {0x30000000, 0x0}, {0x30000000, 0x0}, {0x30000000, 0x0}, {0x30000000, 0x0}, {0x30000000, 0x0}, {0x30000000, 0x0}, {0x30000000, 0x0}, {0x30000000, 0x0}},
    {{0x0, 0x0}, {0x3857201, 0x1704051}, {0x38c7003, 0x270c0ea}, {0x3937604, 0x3710183}, {0x2a381c33, 0x1e8181f7}, {0x16ae2303, 0x310002bd}, {0x21c4007, 0x441c34d}, {0x16be3f03, 0x3104441c}, {0x640809, 0x50a4499}, {0x16ce5b03, 0x3104857b}, {0x6c080b, 0x70ac5f3}, {0x16de7703, 0x3108c6cc}, {0x134200d, 0x823474c}, {0x16ee9303, 0x3109081d}, {0x7c080f, 0x90bc895}, {0x16feaf03, 0x310d4954}, {0x170ecb03, 0x310d89fd}, {0x171ed911, 0x750dcaa5}, {0x172e621f, 0x98060b7e}, {0x173ed21f, 0x980e4c71}, {0x174e6226, 0xba068d64}, {0x175ed226, 0xba0ece57}, {0x176e622d, 0xdc070f3e}, {0x177ed22d, 0xdc0f5013}, {0x30000000, 0x0}, {0x30000000, 0x0}, {0x30000000, 0x0}, {0x30000000, 0x0}, {0x30000000, 0x0}, {0x30000000, 0x0}, {0x30000000, 0x0}, {0x30000000, 0x0}},
    {{0x0, 0x0}, {0x3c57a01, 0x1784052}, {0x3cc7803, 0x278c0eb}, {0x3d37e04, 0x3790184}, {0x2a391c34, 0x1f818202}, {0x16af230a, 0x200002d3}, {0x39c7007, 0x471c35e}, {0x16bf3f0a, 0x20044432}, {0x3646809, 0x56a44ba}, {0x16cf5b0a, 0x20048590}, {0x26c480b, 0x74ac608}, {0x16df770a, 0x2008c6e1}, {0x2f4580d, 0x85b475e}, {0x16ef930a, 0x20090832}, {0x23c400f, 0x943c8a8}, {0x16ffaf0a, 0x200d495f}, {0x170fcb0a, 0x200d8a07}, {0x171fd918, 0x640dcab0}, {0x172f691f, 0x98060b8d}, {0x173fd91f, 0x980e4c80}, {0x174f6926, 0xba068d73}, {0x175fd926, 0xba0ece66}, {0x176f692d, 0xdc070f4b}, {0x177fd92d, 0xdc0f5020}, {0x30000000, 0x0}, {0x30000000, 0x0}, {0x30000000, 0x0}, {0x30000000, 0x0}, {0x30000000, 0x0}, {0x30000000, 0x0}, {0x30000000, 0x0}, {0x30000000, 0x0}},
    {{0x0, 0x0}, {0x60401, 0x1004054}, {0xd0203, 0x200c0ed}, {0x140005, 0x3014186}, {0x17800004, 0x310001f3}, {0xd71e05, 0x4194264}, {0x17900e12, 0x750042ec}, {0x15d2a07, 0x429c371}, {0x17a02a12, 0x7500844b}, {0x1a53209, 0x63244d3}, {0x17b04612, 0x7504c5a8}, {0xad120b, 0x712c620}, {0x17c06212, 0x750506f9}, {0xf51a0d, 0x81b4773}, {0x17d07e12, 0x7509484a}, {0x3d020f, 0x903c8bd}, {0x17e09a12, 0x7509896a}, {0x17f0b612, 0x750dca13}, {0x18000020, 0x98020abc}, {0x18107020, 0x980a4b9e}, {0x18200027, 0xba028c91}, {0x18307027, 0xba0acd84}, {0x1840002e, 0xdc030e77}, {0x1850702e, 0xdc0b4f5a}, {0x30000000, 0x0}, {0x30000000, 0x0}, {0x30000000, 0x0}, {0x30000000, 0x0}, {0x30000000, 0x0}, {0x30000000, 0x0}, {0x30000000, 0x0}, {0x30000000, 0x0}},
    {{0x0, 0x0}, {0x460c01, 0x1084055}, {0x4d0a03, 0x208c0ee}, {0x540805, 0x3094187}, {0x1781000b, 0x200001fe}, {0x2574e05, 0x4494274}, {0x17910e19, 0x64004302}, {0x2dd5a07, 0x459c381}, {0x17a12a19, 0x64008461}, {0x3a57209, 0x67244e9}, {0x17b14619, 0x6404c5bd}, {0x26d4a0b, 0x74ac632}, {0x17c16219, 0x6405070e}, {0x2b5520d, 0x8534786}, {0x17d17e19, 0x6409485f}, {0x1bd320f, 0x933c8cc}, {0x17e19a19, 0x64098975}, {0x17f1b619, 0x640dca1e}, {0x18010720, 0x98020ac6}, {0x18117720, 0x980a4bad}, {0x18210727, 0xba028ca0}, {0x18317727, 0xba0acd93}, {0x1841072e, 0xdc030e86}, {0x1851772e, 0xdc0b4f68}, {0x30000000, 0x0}, {0x30000000, 0x0}, {0x30000000, 0x0}, {0x30000000, 0x0}, {0x30000000, 0x0}, {0x30000000, 0x0}, {0x30000000, 0x0}, {0x30000000, 0x0}},
    {{0x0, 0x0}, {0x861401, 0x1104056}, {0x8d1203, 0x210c0ef}, {0x941005, 0x3114188}, {0x17820704, 0x31000209}, {0x2a433134, 0x34820286}, {0x17921512, 0x75004318}, {0x5e0c07, 0x509c392}, {0x17a23112, 0x75008477}, {0x1662c09, 0x62a44fc}, {0x17b24d12, 0x7504c5d2}, {0x6e0c0b, 0x70ac647}, {0x17c26912, 0x75050723}, {0x760c0d, 0x80b4798}, {0x17d28512, 0x75094874}, {0x2fd5a0f, 0x95bc8da}, {0x17e2a112, 0x75098980}, {0x17f2bd12, 0x750dca28}, {0x18020e20, 0x98020ad1}, {0x18127e20, 0x980a4bbd}, {0x18220e27, 0xba028caf}, {0x18327e27, 0xba0acda2}, {0x18420e2e, 0xdc030e95}, {0x18527e2e, 0xdc0b4f75}, {0x30000000, 0x0}, {0x30000000, 0x0}, {0x30000000, 0x0}, {0x30000000, 0x0}, {0x30000000, 0x0}, {0x30000000, 0x0}, {0x30000000, 0x0}, {0x30000000, 0x0}},
    {{0x0, 0x0}, {0xc61c01, 0x1184057}, {0xcd1a03, 0x218c0f0}, {0xd41805, 0x3194189}, {0x1783070b, 0x20000214}, {0x1983006, 0x4318298}, {0x17931519, 0x6400432e}, {0x21e4407, 0x541c3a5}, {0x17a33119, 0x6400848d}, {0x3266409, 0x662450f}, {0x17b34d19, 0x6404c5e7}, {0x22e440b, 0x742c65a}, {0xb1120c, 0x71306c8}, {0x17c36919, 0x64050738}, {0x336640d, 0x86347b5}, {0x17d38519, 0x64094889}, {0x1be340f, 0x933c8f7}, {0x17e3a119, 0x6409898a}, {0x17f3bd19, 0x640dca33}, {0x18031520, 0x98020adb}, {0x18138520, 0x980a4bcc}, {0x18231527, 0xba028cbf}, {0x18338527, 0xba0acdb1}, {0x1843152e, 0xdc030ea4}, {0x1853852e, 0xdc0b4f82}, {0x30000000, 0x0}, {0x30000000, 0x0}, {0x30000000, 0x0}, {0x30000000, 0x0}, {0x30000000, 0x0}, {0x30000000, 0x0}, {0x30000000, 0x0}},
    {{0x0, 0x0}, {0x1062401, 0x1204059}, {0x10d2203, 0x220c0f2}, {0x1142005, 0x321418b}, {0x17840e04, 0x3100021f}, {0x3186006, 0x46182a8}, {0x17942a04, 0x31004344}, {0x1f0607, 0x501c3bb}, {0x17a44604, 0x310484a3}, {0xa71609, 0x6124520}, {0x17b46204, 0x3104c5fc}, {0x3ae740b, 0x772c669}, {0x2714a0c, 0x74b06db}, {0x17c47e04, 0x3109074d}, {0xb7160d, 0x81347c5}, {0x17d49a04, 0x3109489e}, {0x33e640f, 0x963c906}, {0x17e4b604, 0x310d8995}, {0x17f4d204, 0x310dca3d}, {0x18041c20, 0x98020ae8}, {0x18148c20, 0x980a4bdb}, {0x18241c27, 0xba028cce}, {0x18348c27, 0xba0acdc1}, {0x18441c2e, 0xdc030eb4}, {0x18548c2e, 0xdc0b4f90}, {0x30000000, 0x0}, {0x30000000, 0x0}, {0x30000000, 0x0}, {0x30000000, 0x0}, {0x30000000, 0x0}, {0x30000000, 0x0}, {0x30000000, 0x0}},
    {{0x0, 0x0}, {0x1462c01, 0x128405a}, {0x14d2a03, 0x228c0f3}, {0x1542805, 0x329418c}, {0x17850e0b, 0x2000022a}, {0x991206, 0x41182b9}, {0x17952a0b, 0x20004359}, {0x1df3e07, 0x539c3cd}, {0x620c08, 0x50a0441}, {0x17a5460b, 0x200484b9}, {0xa8100a, 0x612854c}, {0x17b5620b, 0x2004c611}, {0x2ef5e0b, 0x75ac68c}, {0x17c57e0b, 0x20090762}, {0x2774e0d, 0x84b47d7}, {0x17d59a0b, 0x200948b3}, {0xff1e0f, 0x91bc919}, {0x17e5b60b, 0x200d899f}, {0x17f5d20b, 0x200dca48}, {0x18052320, 0x98020af7}, {0x18159320, 0x980a4bea}, {0x18252327, 0xba028cdd}, {0x18359327, 0xba0acdd0}, {0x1845232e, 0xdc030ec3}, {0x1855932e, 0xdc0b4f9d}, {0x30000000, 0x0}, {0x30000000, 0x0}, {0x30000000, 0x0}, {0x30000000, 0x0}, {0x30000000, 0x0}, {0x30000000, 0x0}, {0x30000000, 0x0}},
    {{0x0, 0x0}, {0x1863401, 0x130405b}, {0x18d3203, 0x230c0f4}, {0x1943005, 0x331418d}, {0x17861504, 0x31000235}, {0x2194206, 0x44182c9}, {0x17963104, 0x3100436f}, {0x39f7607, 0x571c3e1}, {0x2624c08, 0x54a0457}, {0x17a64d04, 0x310484cf}, {0x228400a, 0x642855c}, {0x17b66904, 0x3104c626}, {0x30000c, 0x7030699}, {0x17c68504, 0x31090777}, {0x3b7760d, 0x87347e5}, {0x17d6a104, 0x310948c8}, {0x2bf560f, 0x953c92b}, {0x17e6bd04, 0x310d89aa}, {0x17f6d904, 0x310dca52}, {0x18062a20, 0x98020b06}, {0x18169a20, 0x980a4bf9}, {0x18262a27, 0xba028cec}, {0x18369a27, 0xba0acddf}, {0x18462a2e, 0xdc030ed2}, {0x18569a2e, 0xdc0b4faa}, {0x30000000, 0x0}, {0x30000000, 0x0}, {0x30000000, 0x0}, {0x30000000, 0x0}, {0x30000000, 0x0}, {0x30000000, 0x0}, {0x30000000, 0x0}},
    {{0x0, 0x0}, {0x1c63c01, 0x138405d}, {0x1cd3a03, 0x238c0f6}, {0x1d43805, 0x339418f}, {0x1787150b, 0x20000240}, {0x3d97a06, 0x47982db}, {0x1797310b, 0x20004385}, {0x1602808, 0x52a03f5}, {0x17a74d0b, 0x200484e5}, {0x1a8300a, 0x6328557}, {0x17b7690b, 0x2004c63b}, {0x3af760b, 0x772c694}, {0x17c7850b, 0x2009078c}, {0x2f75e0d, 0x85b47dd}, {0x2ba540e, 0x9538859}, {0x17d7a10b, 0x200948de}, {0x17e7bd0b, 0x200d89b4}, {0x17f7d90b, 0x200dca5d}, {0x18073120, 0x98020b16}, {0x1817a120, 0x980a4c08}, {0x18273127, 0xba028cfb}, {0x1837a127, 0xba0acdee}, {0x1847312e, 0xdc030ee1}, {0x1857a12e, 0xdc0b4fb7}, {0x30000000, 0x0}, {0x30000000, 0x0}, {0x30000000, 0x0}, {0x30000000, 0x0}, {0x30000000, 0x0}, {0x30000000, 0x0}, {0x30000000, 0x0}, {0x30000000, 0x0}},
    {{0x0, 0x0}, {0x2064401, 0x140405e}, {0x20d4203, 0x240c0f7}, {0x2144005, 0x3414190}, {0x17880012, 0x7500024b}, {0x15a2c06, 0x42982ed}, {0x17981c12, 0x7500439b}, {0x3206008, 0x5620408}, {0x17a83812, 0x750484fb}, {0x2e8580a, 0x65a8565}, {0x17b85412, 0x7504c650}, {0xb0100c, 0x713069e}, {0x730e0c, 0x80b071a}, {0x17c87012, 0x750907a1}, {0x39020e, 0x8038814}, {0x17d88c12, 0x750948f3}, {0x17e8a812, 0x750d89bf}, {0x17f8c412, 0x750dca67}, {0x18083820, 0x98060b25}, {0x1818a820, 0x980e4c18}, {0x18283827, 0xba068d0b}, {0x1838a827, 0xba0ecdfd}, {0x1848382e, 0xdc070ef0}, {0x1858a82e, 0xdc0f4fc5}, {0x30000000, 0x0}, {0x30000000, 0x0}, {0x30000000, 0x0}, {0x30000000, 0x0}, {0x30000000, 0x0}, {0x30000000, 0x0}, {0x30000000, 0x0}, {0x30000000, 0x0}},
    {{0x0, 0x0}, {0x2464c01, 0x148405f}, {0x24d4a03, 0x248c0f8}, {0x2544805, 0x3494191}, {0x17890019, 0x64000256}, {0x25a4c06, 0x44982f8}, {0x17991c19, 0x640043b1}, {0xe11a08, 0x51a041b}, {0x17a93819, 0x64048511}, {0x29020a, 0x6028572}, {0x36b6e0a, 0x66a85e8}, {0x17b95419, 0x6404c665}, {0x231420c, 0x74306d8}, {0x17c97019, 0x640907b7}, {0x2b9520e, 0x853882e}, {0x17d98c19, 0x64094908}, {0x17e9a819, 0x640d89c9}, {0x17f9c419, 0x640dca72}, {0x18093f20, 0x98060b34}, {0x1819af20, 0x980e4c27}, {0x18293f27, 0xba068d1a}, {0x1839af27, 0xba0ece0d}, {0x18493f2e, 0xdc070efe}, {0x1859af2e, 0xdc0f4fd2}, {0x30000000, 0x0}, {0x30000000, 0x0}, {0x30000000, 0x0}, {0x30000000, 0x0}, {0x30000000, 0x0}, {0x30000000, 0x0}, {0x30000000, 0x0}, {0x30000000, 0x0}},
    {{0x0, 0x0}, {0x2865401, 0x1504061}, {0x28d5203, 0x250c0fa}, {0x2945005, 0x3514193}, {0x178a0712, 0x75000268}, {0x31a6406, 0x4618300}, {0x179a2312, 0x750043c7}, {0x1a13208, 0x5320423}, {0x1242009, 0x52244a2}, {0x17aa3f12, 0x75048527}, {0x3a9720a, 0x6728597}, {0x17ba5b12, 0x7504c67a}, {0xf21c0c, 0x71b06f5}, {0x17ca7712, 0x750907cc}, {0x13a240e, 0x9238849}, {0x17da9312, 0x7509491d}, {0x17eaaf12, 0x750d89d4}, {0x17facb12, 0x750dca7c}, {0x180a4620, 0x98060b43}, {0x181ab620, 0x980e4c36}, {0x182a4627, 0xba068d29}, {0x183ab627, 0xba0ece1c}, {0x184a462e, 0xdc070f0b}, {0x185ab62e, 0xdc0f4fdf}, {0x30000000, 0x0}, {0x30000000, 0x0}, {0x30000000, 0x0}, {0x30000000, 0x0}, {0x30000000, 0x0}, {0x30000000, 0x0}, {0x30000000, 0x0}, {0x30000000, 0x0}},
    {{0x0, 0x0}, {0x2c65c01, 0x1584062}, {0x2cd5a03, 0x258c0fb}, {0x2d45805, 0x3594194}, {0x178b0719, 0x6400027e}, {0x3da7c06, 0x4798307}, {0x179b2319, 0x640043dd}, {0x2a15208, 0x552042e}, {0x2a45009, 0x55244b2}, {0x17ab3f19, 0x6404853d}, {0x22a440a, 0x64285b1}, {0x17bb5b19, 0x6404c690}, {0x332640c, 0x763070d}, {0x17cb7719, 0x640907e1}, {0x33a640e, 0x963885e}, {0x17db9319, 0x64094932}, {0x17ebaf19, 0x640d89de}, {0x17fbcb19, 0x640dca87}, {0x180b4d20, 0x98060b52}, {0x181bbd20, 0x980e4c45}, {0x182b4d27, 0xba068d38}, {0x183bbd27, 0xba0ece2b}, {0x184b4d2e, 0xdc070f18}, {0x185bbd2e, 0xdc0f4fed}, {0x30000000, 0x0}, {0x30000000, 0x0}, {0x30000000, 0x0}, {0x30000000, 0x0}, {0x30000000, 0x0}, {0x30000000, 0x0}, {0x30000000, 0x0}, {0x30000000, 0x0}},
    {{0x0, 0x0}, {0x3066401, 0x1604063}, {0x30d6203, 0x260c0fc}, {0x3146005, 0x3614195}, {0x2a3a2333, 0x2581820d}, {0x178c1c04, 0x31000294}, {0x2a4b3f34, 0x42828336}, {0x179c3804, 0x310443f3}, {0x630e08, 0x50a046d}, {0x17ac5404, 0x31048553}, {0xab160a, 0x61285cb}, {0x17bc7004, 0x3108c6a5}, {0x1732e0c, 0x82b0724}, {0x17cc8c04, 0x310907f6}, {0xfb1e0e, 0x91b8870}, {0x17dca804, 0x310d4940}, {0x17ecc404, 0x310d89e9}, {0x17fcd212, 0x750dca91}, {0x180c5420, 0x98060b62}, {0x181cc420, 0x980e4c54}, {0x182c5427, 0xba068d47}, {0x183cc427, 0xba0ece3a}, {0x184c542e, 0xdc070f25}, {0x185cc42e, 0xdc0f4ffa}, {0x30000000, 0x0}, {0x30000000, 0x0}, {0x30000000, 0x0}, {0x30000000, 0x0}, {0x30000000, 0x0}, {0x30000000, 0x0}, {0x30000000, 0x0}, {0x30000000, 0x0}},
    {{0x0, 0x0}, {0x3466c01, 0x1684065}, {0x34d6a03, 0x268c0fe}, {0x3546805, 0x3694197}, {0x2a3b2334, 0x26818218}, {0x178d1c0b, 0x200002aa}, {0x15c2807, 0x429c345}, {0x179d380b, 0x20044409}, {0x2a35608, 0x5520486}, {0x17ad540b, 0x20048569}, {0x2ab560a, 0x65285e0}, {0x17bd700b, 0x2008c6ba}, {0x3b3760c, 0x873073c}, {0x17cd8c0b, 0x2009080b}, {0x2fb5e0e, 0x95b8885}, {0x17dda80b, 0x200d494b}, {0x17edc40b, 0x200d89f3}, {0x17fdd219, 0x640dca9c}, {0x180d5b20, 0x98060b71}, {0x181dcb20, 0x980e4c64}, {0x182d5b27, 0xba068d56}, {0x183dcb27, 0xba0ece49}, {0x184d5b2e, 0xdc070f33}, {0x185dcb2e, 0xdc0f5007}, {0x30000000, 0x0}, {0x30000000, 0x0}, {0x30000000, 0x0}, {0x30000000, 0x0}, {0x30000000, 0x0}, {0x30000000, 0x0}, {0x30000000, 0x0}, {0x30000000, 0x0}},
    {{0x0, 0x0}, {0x3867401, 0x1704066}, {0x38d7203, 0x270c0ff}, {0x3947005, 0x3714198}, {0x2a3c3831, 0x3881c223}, {0x178e2304, 0x310002c0}, {0x25c4807, 0x449c350}, {0x179e3f04, 0x3104441f}, {0xa41009, 0x512449c}, {0x17ae5b04, 0x3104857e}, {0xac100b, 0x712c5f5}, {0x17be7704, 0x3108c6cf}, {0x174280d, 0x82b474f}, {0x17ce9304, 0x31090820}, {0xbc100f, 0x913c898}, {0x17deaf04, 0x310d4955}, {0x17eecb04, 0x310d89fe}, {0x17fed912, 0x750dcaa7}, {0x180e6220, 0x98060b80}, {0x181ed220, 0x980e4c73}, {0x182e6227, 0xba068d66}, {0x183ed227, 0xba0ece58}, {0x184e622e, 0xdc070f40}, {0x185ed22e, 0xdc0f5014}, {0x30000000, 0x0}, {0x30000000, 0x0}, {0x30000000, 0x0}, {0x30000000, 0x0}, {0x30000000, 0x0}, {0x30000000, 0x0}, {0x30000000, 0x0}, {0x30000000, 0x0}},
    {{0x0, 0x0}, {0x3c67c01, 0x1784067}, {0x3cd7a03, 0x278c100}, {0x3d47805, 0x3794199}, {0x2a3d3832, 0x3981c22e}, {0x178f230b, 0x200002d6}, {0x3dc7807, 0x479c35f}, {0x179f3f0b, 0x20044435}, {0x3a47009, 0x57244bd}, {0x17af5b0b, 0x20048593}, {0x2ac500b, 0x752c60b}, {0x17bf770b, 0x2008c6e4}, {0x334600d, 0x8634761}, {0x17cf930b, 0x20090835}, {0x27c480f, 0x94bc8aa}, {0x17dfaf0b, 0x200d4960}, {0x17efcb0b, 0x200d8a09}, {0x17ffd919, 0x640dcab1}, {0x180f6920, 0x98060b8f}, {0x181fd920, 0x980e4c82}, {0x182f6927, 0xba068d75}, {0x183fd927, 0xba0ece68}, {0x184f692e, 0xdc070f4d}, {0x185fd92e, 0xdc0f5022}, {0x30000000, 0x0}, {0x30000000, 0x0}, {0x30000000, 0x0}, {0x30000000, 0x0}, {0x30000000, 0x0}, {0x30000000, 0x0}, {0x30000000, 0x0}, {0x30000000, 0x0}},
    {{0x0, 0x0}, {0x70601, 0x1004069}, {0xe0403, 0x200c102}, {0x150205, 0x301419b}, {0x18600005, 0x310001f5}, {0x1172605, 0x4214267}, {0x18700e13, 0x750042ee}, {0x19d3207, 0x431c374}, {0x18802a13, 0x7500844e}, {0x1e53a09, 0x63a44d4}, {0x18904613, 0x7504c5aa}, {0xed1a0b, 0x71ac622}, {0x18a06213, 0x750506fc}, {0x135220d, 0x8234776}, {0x18b07e13, 0x7509484d}, {0x7d0a0f, 0x90bc8bf}, {0x18c09a13, 0x7509896c}, {0x18d0b613, 0x750dca14}, {0x18e00021, 0x98020abd}, {0x18f07021, 0x980a4ba0}, {0x19000028, 0xba028c93}, {0x19107028, 0xba0acd86}, {0x1920002f, 0xdc030e79}, {0x1930702f, 0xdc0b4f5c}, {0x30000000, 0x0}, {0x30000000, 0x0}, {0x30000000, 0x0}, {0x30000000, 0x0}, {0x30000000, 0x0}, {0x30000000, 0x0}, {0x30000000, 0x0}, {0x30000000, 0x0}},
    {{0x400800, 0x80000}, {0x470e01, 0x108406a}, {0x4e0c03, 0x208c103}, {0x550a05, 0x309419c}, {0x1861000c, 0x20000200}, {0x2975605, 0x4514277}, {0x18710e1a, 0x64004304}, {0x31d6207, 0x461c384}, {0x18812a1a, 0x64008464}, {0x3e57a09, 0x67a44ea}, {0x1891461a, 0x6404c5bf}, {0x2ad520b, 0x752c635}, {0x18a1621a, 0x64050711}, {0x2f55a0d, 0x85b4788}, {0x18b17e1a, 0x64094862}, {0x1fd3a0f, 0x93bc8ce}, {0x18c19a1a, 0x64098976}, {0x18d1b61a, 0x640dca1f}, {0x18e10721, 0x98020ac7}, {0x18f17721, 0x980a4baf}, {0x19010728, 0xba028ca2}, {0x19117728, 0xba0acd95}, {0x1921072f, 0xdc030e88}, {0x1931772f, 0xdc0b4f6a}, {0x30000000, 0x0}, {0x30000000, 0x0}, {0x30000000, 0x0}, {0x30000000, 0x0}, {0x30000000, 0x0}, {0x30000000, 0x0}, {0x30000000, 0x0}, {0x30000000, 0x0}},
    {{0x801000, 0x100000}, {0x871601, 0x110406b}, {0x8e1403, 0x210c104}, {0x951205, 0x311419d}, {0x18620705, 0x3100020b}, {0x180006, 0x4018287}, {0x18721513, 0x7500431a}, {0x9e1407, 0x511c395}, {0x18823113, 0x7500847a}, {0x1a63409, 0x63244ff}, {0x18924d13, 0x7504c5d5}, {0xae140b, 0x712c64a}, {0x18a26913, 0x75050726}, {0xb6140d, 0x813479b}, {0x18b28513, 0x75094877}, {0x33d620f, 0x963c8dc}, {0x18c2a113, 0x75098981}, {0x18d2bd13, 0x750dca29}, {0x18e20e21, 0x98020ad2}, {0x18f27e21, 0x980a4bbe}, {0x19020e28, 0xba028cb1}, {0x19127e28, 0xba0acda4}, {0x19220e2f, 0xdc030e97}, {0x19327e2f, 0xdc0b4f77}, {0x30000000, 0x0}, {0x30000000, 0x0}, {0x30000000, 0x0}, {0x30000000, 0x0}, {0x30000000, 0x0}, {0x30000000, 0x0}, {0x30000000, 0x0}, {0x30000000, 0x0}},
    {{0xc01800, 0x180000}, {0xc71e01, 0x118406c}, {0xce1c03, 0x218c105}, {0xd51a05, 0x319419e}, {0x1863070c, 0x20000216}, {0x1d83806, 0x4398299}, {0x1873151a, 0x64004330}, {0x25e4c07, 0x549c3a8}, {0x1883311a, 0x64008490}, {0x3666c09, 0x66a4512}, {0x18934d1a, 0x6404c5ea}, {0x26e4c0b, 0x74ac65c}, {0x18a3691a, 0x6405073b}, {0x1b6340d, 0x83347a5}, {0xb9120e, 0x8138819}, {0x18b3851a, 0x6409488c}, {0x1fe3c0f, 0x93bc8f8}, {0x18c3a11a, 0x6409898b}, {0x18d3bd1a, 0x640dca34}, {0x18e31521, 0x98020add}, {0x18f38521, 0x980a4bce}, {0x19031528, 0xba028cc1}, {0x19138528, 0xba0acdb3}, {0x1923152f, 0xdc030ea6}, {0x1933852f, 0xdc0b4f84}, {0x30000000, 0x0}, {0x30000000, 0x0}, {0x30000000, 0x0}, {0x30000000, 0x0}, {0x30000000, 0x0}, {0x30000000, 0x0}, {0x30000000, 0x0}},
    {{0x1002000, 0x200000}, {0x1072601, 0x120406e}, {0x10e2403, 0x220c107}, {0x1152205, 0x32141a0}, {0x18640e05, 0x31000220}, {0x3586806, 0x46982ab}, {0x18742a05, 0x31004346}, {0x5f0e07, 0x509c3be}, {0x18844605, 0x310484a6}, {0xe71e09, 0x61a4523}, {0x18946205, 0x3104c5ff}, {0x3ee7c0b, 0x77ac66b}, {0x2b1520c, 0x75306dd}, {0x18a47e05, 0x31090750}, {0x137260d, 0x82347ca}, {0x18b49a05, 0x310948a1}, {0x37e6c0f, 0x96bc909}, {0x18c4b605, 0x310d8996}, {0x18d4d205, 0x310dca3f}, {0x18e41c21, 0x98020aea}, {0x18f48c21, 0x980a4bdd}, {0x19041c28, 0xba028cd0}, {0x19148c28, 0xba0acdc3}, {0x19241c2f, 0xdc030eb5}, {0x19348c2f, 0xdc0b4f92}, {0x30000000, 0x0}, {0x30000000, 0x0}, {0x30000000, 0x0}, {0x30000000, 0x0}, {0x30000000, 0x0}, {0x30000000, 0x0}, {0x30000000, 0x0}},
    {{0x1402800, 0x280000}, {0x1472e01, 0x128406f}, {0x14e2c03, 0x228c108}, {0x1552a05, 0x32941a1}, {0x18650e0c, 0x2000022b}, {0xd91a06, 0x41982bc}, {0x18752a0c, 0x2000435c}, {0x21f4607, 0x541c3d1}, {0xe21c08, 0x51a0447}, {0x1885460c, 0x200484bc}, {0x128200a, 0x6228551}, {0x1895620c, 0x2004c614}, {0x36f6e0b, 0x76ac691}, {0x18a57e0c, 0x20090765}, {0x2b7560d, 0x85347da}, {0x18b59a0c, 0x200948b6}, {0x13f260f, 0x923c91b}, {0x18c5b60c, 0x200d89a0}, {0x18d5d20c, 0x200dca49}, {0x18e52321, 0x98020af9}, {0x18f59321, 0x980a4bec}, {0x19052328, 0xba028cdf}, {0x19159328, 0xba0acdd2}, {0x1925232f, 0xdc030ec5}, {0x1935932f, 0xdc0b4f9f}, {0x30000000, 0x0}, {0x30000000, 0x0}, {0x30000000, 0x0}, {0x30000000, 0x0}, {0x30000000, 0x0}, {0x30000000, 0x0}, {0x30000000, 0x0}},
    {{0x1803000, 0x300000}, {0x1873601, 0x1304070}, {0x18e3403, 0x230c109}, {0x1953205, 0x33141a2}, {0x18661505, 0x31000236}, {0x2594a06, 0x44982cc}, {0x18763105, 0x31004372}, {0x3df7e07, 0x579c3e3}, {0x2a25408, 0x552045a}, {0x18864d05, 0x310484d2}, {0x268480a, 0x64a855f}, {0x18966905, 0x3104c629}, {0x70080c, 0x70b069b}, {0x18a68505, 0x3109077a}, {0x3f77e0d, 0x87b47e6}, {0x18b6a105, 0x310948cb}, {0x2ff5e0f, 0x95bc92e}, {0x18c6bd05, 0x310d89ab}, {0x18d6d905, 0x310dca54}, {0x18e62a21, 0x98020b08}, {0x18f69a21, 0x980a4bfb}, {0x19062a28, 0xba028cee}, {0x19169a28, 0xba0acde1}, {0x19262a2f, 0xdc030ed4}, {0x19369a2f, 0xdc0b4fac}, {0x30000000, 0x0}, {0x30000000, 0x0}, {0x30000000, 0x0}, {0x30000000, 0x0}, {0x30000000, 0x0}, {0x30000000, 0x0}, {0x30000000, 0x0}},
    {{0x1c03800, 0x380000}, {0x1c73e01, 0x1384072}, {0x1ce3c03, 0x238c10b}, {0x1d53a05, 0x33941a4}, {0x1867150c, 0x20000241}, {0x2a474d32, 0x4e8242de}, {0x1877310c, 0x20004388}, {0x1a03008, 0x53203f7}, {0xa31608, 0x5120470}, {0x18874d0c, 0x200484e8}, {0x3e8780a, 0x67a856e}, {0x1897690c, 0x2004c63e}, {0x230400c, 0x74306ae}, {0x18a7850c, 0x2009078f}, {0x1f8380e, 0x83b87fb}, {0x18b7a10c, 0x200948e0}, {0x18c7bd0c, 0x200d89b6}, {0x18d7d90c, 0x200dca5e}, {0x18e73121, 0x98020b18}, {0x18f7a121, 0x980a4c0a}, {0x19073128, 0xba028cfd}, {0x1917a128, 0xba0acdf0}, {0x1927312f, 0xdc030ee3}, {0x1937a12f, 0xdc0b4fb9}, {0x30000000, 0x0}, {0x30000000, 0x0}, {0x30000000, 0x0}, {0x30000000, 0x0}, {0x30000000, 0x0}, {0x30000000, 0x0}, {0x30000000, 0x0}, {0x30000000, 0x0}},
    {{0x2004000, 0x400000}, {0x2074601, 0x1404073}, {0x20e4403, 0x240c10c}, {0x2154205, 0x34141a5}, {0x18680013, 0x7500024c}, {0x19a3406, 0x43182f0}, {0x18781c13, 0x7500439e}, {0x3606808, 0x56a040b}, {0x18883813, 0x750484fe}, {0x328600a, 0x6628567}, {0x18985413, 0x7504c653}, {0x130200c, 0x72306a3}, {0x133260c, 0x8230722}, {0x18a87013, 0x750907a4}, {0x790a0e, 0x80b8817}, {0x18b88c13, 0x750948f5}, {0x18c8a813, 0x750d89c0}, {0x18d8c413, 0x750dca69}, {0x18e83821, 0x98060b27}, {0x18f8a821, 0x980e4c1a}, {0x19083828, 0xba068d0c}, {0x1918a828, 0xba0ecdff}, {0x1928382f, 0xdc070ef2}, {0x1938a82f, 0xdc0f4fc7}, {0x30000000, 0x0}, {0x30000000, 0x0}, {0x30000000, 0x0}, {0x30000000, 0x0}, {0x30000000, 0x0}, {0x30000000, 0x0}, {0x30000000, 0x0}, {0x30000000, 0x0}},
    {{0x2404800, 0x480000}, {0x2474e01, 0x1484074}, {0x24e4c03, 0x248c10d}, {0x2554a05, 0x34941a6}, {0x1869001a, 0x64000257}, {0x29a5406, 0x45182fb}, {0x18791c1a, 0x640043b4}, {0x1212208, 0x522041e}, {0x1889381a, 0x64048514}, {0xa9120a, 0x6128577}, {0x1899541a, 0x6404c668}, {0x2b0500c, 0x75306b3}, {0x2f35e0c, 0x85b0734}, {0x18a9701a, 0x640907b9}, {0x339620e, 0x8638834}, {0x18b98c1a, 0x6409490a}, {0x18c9a81a, 0x640d89cb}, {0x18d9c41a, 0x640dca73}, {0x18e93f21, 0x98060b36}, {0x18f9af21, 0x980e4c29}, {0x19093f28, 0xba068d1c}, {0x1919af28, 0xba0ece0e}, {0x19293f2f, 0xdc070eff}, {0x1939af2f, 0xdc0f4fd4}, {0x30000000, 0x0}, {0x30000000, 0x0}, {0x30000000, 0x0}, {0x30000000, 0x0}, {0x30000000, 0x0}, {0x30000000, 0x0}, {0x30000000, 0x0}, {0x30000000, 0x0}},
    {{0x2805000, 0x500000}, {0x2875601, 0x1504076}, {0x28e5403, 0x250c10f}, {0x2955205, 0x35141a8}, {0x186a0713, 0x7500026b}, {0x35a6c06, 0x4698303}, {0x187a2313, 0x750043ca}, {0x1e13a08, 0x53a0425}, {0x1642809, 0x52a44a4}, {0x188a3f13, 0x75048529}, {0x2a040a, 0x602859c}, {0x189a5b13, 0x7504c67d}, {0x132240c, 0x72306f8}, {0x18aa7713, 0x750907ce}, {0x17a2c0e, 0x92b884b}, {0x18ba9313, 0x7509491f}, {0x18caaf13, 0x750d89d5}, {0x18dacb13, 0x750dca7e}, {0x18ea4621, 0x98060b45}, {0x18fab621, 0x980e4c38}, {0x190a4628, 0xba068d2b}, {0x191ab628, 0xba0ece1e}, {0x192a462f, 0xdc070f0d}, {0x193ab62f, 0xdc0f4fe1}, {0x30000000, 0x0}, {0x30000000, 0x0}, {0x30000000, 0x0}, {0x30000000, 0x0}, {0x30000000, 0x0}, {0x30000000, 0x0}, {0x30000000, 0x0}, {0x30000000, 0x0}},
    {{0x2c05800, 0x580000}, {0x2c75e01, 0x1584077}, {0x2ce5c03, 0x258c110}, {0x2d55a05, 0x35941a9}, {0x186b071a, 0x64000281}, {0x2a493834, 0x3b82830a}, {0x187b231a, 0x640043e0}, {0x2e15a08, 0x55a0431}, {0x3246009, 0x56244b8}, {0x188b3f1a, 0x6404853f}, {0x26a4c0a, 0x64a85b4}, {0x189b5b1a, 0x6404c692}, {0x3726c0c, 0x76b070f}, {0x18ab771a, 0x640907e3}, {0x37a6c0e, 0x96b8860}, {0x18bb931a, 0x64094934}, {0x18cbaf1a, 0x640d89e0}, {0x18dbcb1a, 0x640dca88}, {0x18eb4d21, 0x98060b54}, {0x18fbbd21, 0x980e4c47}, {0x190b4d28, 0xba068d3a}, {0x191bbd28, 0xba0ece2d}, {0x192b4d2f, 0xdc070f1a}, {0x193bbd2f, 0xdc0f4fee}, {0x30000000, 0x0}, {0x30000000, 0x0}, {0x30000000, 0x0}, {0x30000000, 0x0}, {0x30000000, 0x0}, {0x30000000, 0x0}, {0x30000000, 0x0}, {0x30000000, 0x0}},
    {{0x3006000, 0x600000}, {0x3076601, 0x1604078}, {0x30e6403, 0x260c111}, {0x3156205, 0x36141aa}, {0x186c1c05, 0x31000297}, {0x15b2e06, 0x4298319}, {0x187c3805, 0x310443f6}, {0xa21408, 0x5120444}, {0xe51a09, 0x61a44cb}, {0x188c5405, 0x31048555}, {0xeb1e0a, 0x61a85ce}, {0x189c7005, 0x3108c6a7}, {0x1b3360c, 0x8330727}, {0x18ac8c05, 0x310907f8}, {0x13b260e, 0x9238873}, {0x18bca805, 0x310d4942}, {0x18ccc405, 0x310d89ea}, {0x18dcd213, 0x750dca93}, {0x18ec5421, 0x98060b63}, {0x18fcc421, 0x980e4c56}, {0x190c5428, 0xba068d49}, {0x191cc428, 0xba0ece3c}, {0x192c542f, 0xdc070f27}, {0x193cc42f, 0xdc0f4ffc}, {0x30000000, 0x0}, {0x30000000, 0x0}, {0x30000000, 0x0}, {0x30000000, 0x0}, {0x30000000, 0x0}, {0x30000000, 0x0}, {0x30000000, 0x0}, {0x30000000, 0x0}},
    {{0x3406800, 0x680000}, {0x3476e01, 0x168407a}, {0x34e6c03, 0x268c113}, {0x3556a05, 0x36941ac}, {0x186d1c0c, 0x200002ad}, {0x29b5606, 0x4518327}, {0x187d380c, 0x2004440c}, {0x2e25c08, 0x55a045d}, {0x3256209, 0x66244e3}, {0x188d540c, 0x2004856b}, {0x2eb5e0a, 0x65a85e3}, {0x189d700c, 0x2008c6bc}, {0x3f37e0c, 0x87b073d}, {0x18ad8c0c, 0x2009080d}, {0x33b660e, 0x9638888}, {0x18bda80c, 0x200d494c}, {0x18cdc40c, 0x200d89f5}, {0x18ddd21a, 0x640dca9d}, {0x18ed5b21, 0x98060b73}, {0x18fdcb21, 0x980e4c65}, {0x190d5b28, 0xba068d58}, {0x191dcb28, 0xba0ece4b}, {0x192d5b2f, 0xdc070f35}, {0x193dcb2f, 0xdc0f5009}, {0x30000000, 0x0}, {0x30000000, 0x0}, {0x30000000, 0x0}, {0x30000000, 0x0}, {0x30000000, 0x0}, {0x30000000, 0x0}, {0x30000000, 0x0}, {0x30000000, 0x0}},
    {{0x3807000, 0x700000}, {0x3877601, 0x170407b}, {0x38e7403, 0x270c114}, {0x3957205, 0x37141ad}, {0x186e2305, 0x310002c2}, {0x1c0007, 0x401c337}, {0x2de5c07, 0x559c3ad}, {0x187e3f05, 0x31044422}, {0xe41809, 0x51a449f}, {0x188e5b05, 0x31048580}, {0xec180b, 0x71ac5f8}, {0x189e7705, 0x3108c6d1}, {0x1b4300d, 0x8334751}, {0x18ae9305, 0x31090823}, {0xfc180f, 0x91bc89a}, {0x18beaf05, 0x310d4957}, {0x18cecb05, 0x310d89ff}, {0x18ded913, 0x750dcaa8}, {0x18ee6221, 0x98060b82}, {0x18fed221, 0x980e4c75}, {0x190e6228, 0xba068d67}, {0x191ed228, 0xba0ece5a}, {0x192e622f, 0xdc070f42}, {0x193ed22f, 0xdc0f5016}, {0x30000000, 0x0}, {0x30000000, 0x0}, {0x30000000, 0x0}, {0x30000000, 0x0}, {0x30000000, 0x0}, {0x30000000, 0x0}, {0x30000000, 0x0}, {0x30000000, 0x0}},
    {{0x3c07800, 0x780000}, {0x3c77e01, 0x178407c}, {0x3ce7c03, 0x278c115}, {0x3d57a05, 0x37941ae}, {0x2a3e3f31, 0x3f81c239}, {0x186f230c, 0x200002d8}, {0x2a4d5432, 0x5582c362}, {0x187f3f0c, 0x20044438}, {0x3e47809, 0x57a44be}, {0x188f5b0c, 0x20048595}, {0x2ec580b, 0x75ac60d}, {0x189f770c, 0x2008c6e6}, {0x374680d, 0x86b4764}, {0x18af930c, 0x20090838}, {0x2bc500f, 0x953c8ad}, {0x18bfaf0c, 0x200d4961}, {0x18cfcb0c, 0x200d8a0a}, {0x18dfd91a, 0x640dcab2}, {0x18ef6921, 0x98060b91}, {0x18ffd921, 0x980e4c84}, {0x190f6928, 0xba068d77}, {0x191fd928, 0xba0ece6a}, {0x192f692f, 0xdc070f4f}, {0x193fd92f, 0xdc0f5024}, {0x30000000, 0x0}, {0x30000000, 0x0}, {0x30000000, 0x0}, {0x30000000, 0x0}, {0x30000000, 0x0}, {0x30000000, 0x0}, {0x30000000, 0x0}, {0x30000000, 0x0}},
    {{0x10200, 0x0}, {0x80002, 0x100807e}, {0xf0603, 0x200c117}, {0x160405, 0x30141b0}, {0x19400006, 0x310001f6}, {0x1572e05, 0x4294269}, {0x19500e14, 0x750042f3}, {0x1dd3a07, 0x439c375}, {0x19602a14, 0x75008452}, {0x2254209, 0x64244d8}, {0x19704614, 0x7504c5ae}, {0x12d220b, 0x722c625}, {0x19806214, 0x75050700}, {0x1752a0d, 0x82b4779}, {0x19907e14, 0x75094851}, {0xbd120f, 0x913c8c2}, {0x19a09a14, 0x7509896d}, {0x19b0b614, 0x750dca16}, {0x19c00022, 0x98020abe}, {0x19d07022, 0x980a4ba2}, {0x19e00029, 0xba028c95}, {0x19f07029, 0xba0acd88}, {0x1a000030, 0xdc030e7b}, {0x1a107030, 0xdc0b4f5e}, {0x30000000, 0x0}, {0x30000000, 0x0}, {0x30000000, 0x0}, {0x30000000, 0x0}, {0x30000000, 0x0}, {0x30000000, 0x0}, {0x30000000, 0x0}, {0x30000000, 0x0}},
    {{0x410a00, 0x80000}, {0x480802, 0x108807f}, {0x4f0e03, 0x208c118}, {0x560c05, 0x30941b1}, {0x1941000d, 0x20000201}, {0x2d75e05, 0x459427a}, {0x19510e1b, 0x64004308}, {0x35d6a07, 0x469c387}, {0x19612a1b, 0x64008468}, {0x260409, 0x60244ee}, {0x1971461b, 0x6404c5c3}, {0x32d620b, 0x762c63a}, {0x1981621b, 0x64050715}, {0x335620d, 0x863478b}, {0x19917e1b, 0x64094866}, {0x23d420f, 0x943c8d2}, {0x19a19a1b, 0x64098978}, {0x19b1b61b, 0x640dca20}, {0x19c10722, 0x98020ac9}, {0x19d17722, 0x980a4bb1}, {0x19e10729, 0xba028ca4}, {0x19f17729, 0xba0acd97}, {0x1a010730, 0xdc030e8a}, {0x1a117730, 0xdc0b4f6c}, {0x30000000, 0x0}, {0x30000000, 0x0}, {0x30000000, 0x0}, {0x30000000, 0x0}, {0x30000000, 0x0}, {0x30000000, 0x0}, {0x30000000, 0x0}, {0x30000000, 0x0}},
    {{0x811200, 0x100000}, {0x881002, 0x1108080}, {0x8f1603, 0x210c119}, {0x961405, 0x31141b2}, {0x19420706, 0x3100020c}, {0x580806, 0x409828a}, {0x19521514, 0x7500431e}, {0xde1c07, 0x519c397}, {0x19623114, 0x7500847e}, {0x1e63c09, 0x63a4500}, {0x19724d14, 0x7504c5d9}, {0xee1c0b, 0x71ac64c}, {0x19826914, 0x7505072a}, {0xf61c0d, 0x81b479e}, {0x19928514, 0x7509487b}, {0x37d6a0f, 0x96bc8df}, {0x19a2a114, 0x75098982}, {0x19b2bd14, 0x750dca2b}, {0x19c20e22, 0x98020ad3}, {0x19d27e22, 0x980a4bc0}, {0x19e20e29, 0xba028cb3}, {0x19f27e29, 0xba0acda6}, {0x1a020e30, 0xdc030e99}, {0x1a127e30, 0xdc0b4f79}, {0x30000000, 0x0}, {0x30000000, 0x0}, {0x30000000, 0x0}, {0x30000000, 0x0}, {0x30000000, 0x0}, {0x30000000, 0x0}, {0x30000000, 0x0}, {0x30000000, 0x0}},
    {{0xc11a00, 0x180000}, {0xc81802, 0x1188081}, {0xcf1e03, 0x218c11a}, {0xd61c05, 0x31941b3}, {0x1943070d, 0x20000217}, {0x2a444631, 0x4682429c}, {0x1953151b, 0x64004334}, {0x29e5407, 0x551c3aa}, {0x1963311b, 0x64008494}, {0x3a67409, 0x6724515}, {0x19734d1b, 0x6404c5ee}, {0x2ae540b, 0x752c65f}, {0x1983691b, 0x6405073f}, {0x1f63c0d, 0x83b47a7}, {0x1993851b, 0x64094890}, {0x7e0c0f, 0x90bc8e9}, {0x19a3a11b, 0x6409898d}, {0x19b3bd1b, 0x640dca35}, {0x19c31522, 0x98020ade}, {0x19d38522, 0x980a4bd0}, {0x19e31529, 0xba028cc2}, {0x19f38529, 0xba0acdb5}, {0x1a031530, 0xdc030ea8}, {0x1a138530, 0xdc0b4f86}, {0x30000000, 0x0}, {0x30000000, 0x0}, {0x30000000, 0x0}, {0x30000000, 0x0}, {0x30000000, 0x0}, {0x30000000, 0x0}, {0x30000000, 0x0}, {0x30000000, 0x0}},
    {{0x1012200, 0x200000}, {0x1082002, 0x1208083}, {0x10f2603, 0x220c11c}, {0x1162405, 0x32141b5}, {0x19440e06, 0x31000222}, {0x3987006, 0x47182ae}, {0x19542a06, 0x3100434a}, {0x9f1607, 0x511c3c0}, {0x19644606, 0x310484aa}, {0x1272609, 0x6224525}, {0x19746206, 0x3104c603}, {0x2f060b, 0x702c66f}, {0x2f15a0c, 0x75b06e0}, {0x19847e06, 0x31090754}, {0x1772e0d, 0x82b47cd}, {0x19949a06, 0x310948a5}, {0x3be740f, 0x973c90c}, {0x19a4b606, 0x310d8997}, {0x19b4d206, 0x310dca40}, {0x19c41c22, 0x98020aec}, {0x19d48c22, 0x980a4bdf}, {0x19e41c29, 0xba028cd2}, {0x19f48c29, 0xba0acdc4}, {0x1a041c30, 0xdc030eb7}, {0x1a148c30, 0xdc0b4f93}, {0x30000000, 0x0}, {0x30000000, 0x0}, {0x30000000, 0x0}, {0x30000000, 0x0}, {0x30000000, 0x0}, {0x30000000, 0x0}, {0x30000000, 0x0}},
    {{0x1412a00, 0x280000}, {0x1482802, 0x1288084}, {0x14f2e03, 0x228c11d}, {0x1562c05, 0x32941b6}, {0x19450e0d, 0x2000022d}, {0x1192206, 0x42182be}, {0x19552a0d, 0x20004360}, {0x25f4e07, 0x549c3d4}, {0x1965460d, 0x200484c0}, {0x2674e09, 0x64a4533}, {0xea1c0a, 0x61a85a4}, {0x1975620d, 0x2004c618}, {0x3ef7e0b, 0x77ac695}, {0x19857e0d, 0x20090769}, {0x337660d, 0x86347df}, {0x19959a0d, 0x200948ba}, {0x17f2e0f, 0x92bc91e}, {0x19a5b60d, 0x200d89a2}, {0x19b5d20d, 0x200dca4a}, {0x19c52322, 0x98020afb}, {0x19d59322, 0x980a4bee}, {0x19e52329, 0xba028ce1}, {0x19f59329, 0xba0acdd4}, {0x1a052330, 0xdc030ec6}, {0x1a159330, 0xdc0b4fa1}, {0x30000000, 0x0}, {0x30000000, 0x0}, {0x30000000, 0x0}, {0x30000000, 0x0}, {0x30000000, 0x0}, {0x30000000, 0x0}, {0x30000000, 0x0}},
    {{0x1813200, 0x300000}, {0x1883002, 0x1308085}, {0x18f3603, 0x230c11e}, {0x1963405, 0x33141b7}, {0x19461506, 0x31000238}, {0x2995206, 0x45182cf}, {0x19563106, 0x31004376}, {0x200008, 0x50203e7}, {0x19664d06, 0x310484d6}, {0x3e77e09, 0x67a4542}, {0x2aa540a, 0x65285b6}, {0x19766906, 0x3104c62d}, {0xf0180c, 0x71b06a1}, {0x19868506, 0x3109077e}, {0x78080e, 0x80b87ed}, {0x1996a106, 0x310948cf}, {0x33f660f, 0x963c931}, {0x19a6bd06, 0x310d89ac}, {0x19b6d906, 0x310dca55}, {0x19c62a22, 0x98020b0a}, {0x19d69a22, 0x980a4bfd}, {0x19e62a29, 0xba028cf0}, {0x19f69a29, 0xba0acde3}, {0x1a062a30, 0xdc030ed6}, {0x1a169a30, 0xdc0b4fae}, {0x30000000, 0x0}, {0x30000000, 0x0}, {0x30000000, 0x0}, {0x30000000, 0x0}, {0x30000000, 0x0}, {0x30000000, 0x0}, {0x30000000, 0x0}},
    {{0x1c13a00, 0x380000}, {0x1c83802, 0x1388087}, {0x1cf3e03, 0x238c120}, {0x1d63c05, 0x33941b9}, {0x1947150d, 0x20000243}, {0x1a0406, 0x40182df}, {0x1957310d, 0x2000438c}, {0x1e03808, 0x53a03f9}, {0xe31e08, 0x51a0473}, {0x19674d0d, 0x200484ec}, {0x690a0a, 0x60a8574}, {0x1977690d, 0x2004c642}, {0x270480c, 0x74b06b0}, {0x1987850d, 0x20090793}, {0x278480e, 0x84b8802}, {0x1997a10d, 0x200948e4}, {0x19a7bd0d, 0x200d89b7}, {0x19b7d90d, 0x200dca5f}, {0x19c73122, 0x98020b19}, {0x19d7a122, 0x980a4c0c}, {0x19e73129, 0xba028cff}, {0x19f7a129, 0xba0acdf2}, {0x1a073130, 0xdc030ee5}, {0x1a17a130, 0xdc0b4fbb}, {0x30000000, 0x0}, {0x30000000, 0x0}, {0x30000000, 0x0}, {0x30000000, 0x0}, {0x30000000, 0x0}, {0x30000000, 0x0}, {0x30000000, 0x0}, {0x30000000, 0x0}},
    {{0x2014200, 0x400000}, {0x2084002, 0x1408088}, {0x20f4603, 0x240c121}, {0x2164405, 0x34141ba}, {0x19480014, 0x7500024e}, {0x1da3c06, 0x43982f1}, {0x19581c14, 0x750043a2}, {0x3a07008, 0x572040d}, {0x19683814, 0x75048502}, {0x368680a, 0x66a856a}, {0x19785414, 0x7504c657}, {0x1b0300c, 0x73306a9}, {0x1f33e0c, 0x83b0728}, {0x19887014, 0x750907a8}, {0xf91a0e, 0x81b881c}, {0x19988c14, 0x750948f9}, {0x19a8a814, 0x750d89c1}, {0x19b8c414, 0x750dca6a}, {0x19c83822, 0x98060b29}, {0x19d8a822, 0x980e4c1b}, {0x19e83829, 0xba068d0e}, {0x19f8a829, 0xba0ece01}, {0x1a083830, 0xdc070ef4}, {0x1a18a830, 0xdc0f4fc9}, {0x30000000, 0x0}, {0x30000000, 0x0}, {0x30000000, 0x0}, {0x30000000, 0x0}, {0x30000000, 0x0}, {0x30000000, 0x0}, {0x30000000, 0x0}, {0x30000000, 0x0}},
    {{0x2414a00, 0x480000}, {0x2484802, 0x1488089}, {0x24f4e03, 0x248c122}, {0x2564c05, 0x34941bb}, {0x1949001b, 0x64000259}, {0x2da5c06, 0x45982fe}, {0x19591c1b, 0x640043b8}, {0x1612a08, 0x52a0421}, {0x1969381b, 0x64048518}, {0x129220a, 0x622857c}, {0x1979541b, 0x6404c66c}, {0x330600c, 0x76306b8}, {0x1989701b, 0x640907bd}, {0x2f8580e, 0x85b8807}, {0x27b4e0e, 0x94b8880}, {0x19998c1b, 0x6409490e}, {0x19a9a81b, 0x640d89cc}, {0x19b9c41b, 0x640dca75}, {0x19c93f22, 0x98060b38}, {0x19d9af22, 0x980e4c2b}, {0x19e93f29, 0xba068d1d}, {0x19f9af29, 0xba0ece10}, {0x1a093f30, 0xdc070f01}, {0x1a19af30, 0xdc0f4fd6}, {0x30000000, 0x0}, {0x30000000, 0x0}, {0x30000000, 0x0}, {0x30000000, 0x0}, {0x30000000, 0x0}, {0x30000000, 0x0}, {0x30000000, 0x0}, {0x30000000, 0x0}},
    {{0x2815200, 0x500000}, {0x2885002, 0x150808b}, {0x28f5603, 0x250c124}, {0x2965405, 0x35141bd}, {0x194a0714, 0x7500026f}, {0x39a7406, 0x4718306}, {0x195a2314, 0x750043ce}, {0x2214208, 0x5420429}, {0x1e43809, 0x53a44a8}, {0x196a3f14, 0x7504852e}, {0x6a0c0a, 0x60a859f}, {0x197a5b14, 0x7504c681}, {0x1722c0c, 0x72b06fa}, {0x198a7714, 0x750907d2}, {0x1ba340e, 0x933884e}, {0x199a9314, 0x75094923}, {0x19aaaf14, 0x750d89d6}, {0x19bacb14, 0x750dca7f}, {0x19ca4622, 0x98060b47}, {0x19dab622, 0x980e4c3a}, {0x19ea4629, 0xba068d2d}, {0x19fab629, 0xba0ece20}, {0x1a0a4630, 0xdc070f0f}, {0x1a1ab630, 0xdc0f4fe3}, {0x30000000, 0x0}, {0x30000000, 0x0}, {0x30000000, 0x0}, {0x30000000, 0x0}, {0x30000000, 0x0}, {0x30000000, 0x0}, {0x30000000, 0x0}, {0x30000000, 0x0}},
    {{0x2c15a00, 0x580000}, {0x2c85802, 0x158808c}, {0x2cf5e03, 0x258c125}, {0x2d65c05, 0x35941be}, {0x194b071b, 0x64000285}, {0x5b0e06, 0x409830e}, {0x195b231b, 0x640043e4}, {0x3616a08, 0x56a0436}, {0x196b3f1b, 0x64048544}, {0x2a9520a, 0x652858c}, {0x1ec380b, 0x73ac601}, {0x197b5b1b, 0x6404c696}, {0x3b2740c, 0x7730712}, {0x198b771b, 0x640907e7}, {0x3ba740e, 0x9738863}, {0x199b931b, 0x64094938}, {0x19abaf1b, 0x640d89e1}, {0x19bbcb1b, 0x640dca8a}, {0x19cb4d22, 0x98060b56}, {0x19dbbd22, 0x980e4c49}, {0x19eb4d29, 0xba068d3c}, {0x19fbbd29, 0xba0ece2f}, {0x1a0b4d30, 0xdc070f1c}, {0x1a1bbd30, 0xdc0f4ff0}, {0x30000000, 0x0}, {0x30000000, 0x0}, {0x30000000, 0x0}, {0x30000000, 0x0}, {0x30000000, 0x0}, {0x30000000, 0x0}, {0x30000000, 0x0}, {0x30000000, 0x0}},
    {{0x3016200, 0x600000}, {0x3086002, 0x160808d}, {0x30f6603, 0x260c126}, {0x3166405, 0x36141bf}, {0x194c1c06, 0x3100029b}, {0x1db3e06, 0x439831d}, {0x195c3806, 0x310443fa}, {0x1622c08, 0x52a044c}, {0x196c5406, 0x3104855a}, {0x12a240a, 0x62285a6}, {0x6d0a0b, 0x70ac61d}, {0x197c7006, 0x3108c6ab}, {0x233460c, 0x843072c}, {0x198c8c06, 0x310907fc}, {0x17b2e0e, 0x92b8876}, {0x199ca806, 0x310d4943}, {0x19acc406, 0x310d89ec}, {0x19bcd214, 0x750dca94}, {0x19cc5422, 0x98060b65}, {0x19dcc422, 0x980e4c58}, {0x19ec5429, 0xba068d4b}, {0x19fcc429, 0xba0ece3e}, {0x1a0c5430, 0xdc070f29}, {0x1a1cc430, 0xdc0f4ffe}, {0x30000000, 0x0}, {0x30000000, 0x0}, {0x30000000, 0x0}, {0x30000000, 0x0}, {0x30000000, 0x0}, {0x30000000, 0x0}, {0x30000000, 0x0}, {0x30000000, 0x0}},
    {{0x3416a00, 0x680000}, {0x3486802, 0x168808f}, {0x34f6e03, 0x268c128}, {0x3566c05, 0x36941c1}, {0x194d1c0d, 0x200002b1}, {0x31b6606, 0x461832c}, {0x195d380d, 0x20044410}, {0x3626c08, 0x56a0462}, {0x196d540d, 0x2004856f}, {0x3aa740a, 0x67285c1}, {0x2ed5a0b, 0x75ac637}, {0x197d700d, 0x2008c6c0}, {0x34000d, 0x8034741}, {0x198d8c0d, 0x20090811}, {0x37b6e0e, 0x96b888b}, {0x199da80d, 0x200d494e}, {0x19adc40d, 0x200d89f6}, {0x19bdd21b, 0x640dca9f}, {0x19cd5b22, 0x98060b74}, {0x19ddcb22, 0x980e4c67}, {0x19ed5b29, 0xba068d5a}, {0x19fdcb29, 0xba0ece4d}, {0x1a0d5b30, 0xdc070f36}, {0x1a1dcb30, 0xdc0f500b}, {0x30000000, 0x0}, {0x30000000, 0x0}, {0x30000000, 0x0}, {0x30000000, 0x0}, {0x30000000, 0x0}, {0x30000000, 0x0}, {0x30000000, 0x0}, {0x30000000, 0x0}},
    {{0x3817200, 0x700000}, {0x3887002, 0x1708090}, {0x38f7603, 0x270c129}, {0x3967405, 0x37141c2}, {0x2a3f3f32, 0x4081c244}, {0x194e2306, 0x310002c7}, {0x29c5007, 0x451c353}, {0x195e3f06, 0x31044426}, {0x1a43009, 0x53244a7}, {0x196e5b06, 0x31048584}, {0x12c200b, 0x722c5fb}, {0x197e7706, 0x3108c6d5}, {0x1f4380d, 0x83b4752}, {0x198e9306, 0x31090827}, {0x13c200f, 0x923c89d}, {0x199eaf06, 0x310d4958}, {0x19aecb06, 0x310d8a01}, {0x19bed914, 0x750dcaa9}, {0x19ce6222, 0x98060b84}, {0x19ded222, 0x980e4c77}, {0x19ee6229, 0xba068d69}, {0x19fed229, 0xba0ece5c}, {0x1a0e6230, 0xdc070f44}, {0x1a1ed230, 0xdc0f5018}, {0x30000000, 0x0}, {0x30000000, 0x0}, {0x30000000, 0x0}, {0x30000000, 0x0}, {0x30000000, 0x0}, {0x30000000, 0x0}, {0x30000000, 0x0}, {0x30000000, 0x0}},
    {{0x3c17a00, 0x780000}, {0x3c87802, 0x1788091}, {0x3cf7e03, 0x278c12a}, {0x3d67c05, 0x37941c3}, {0x2a402a33, 0x2c82024f}, {0x194f230d, 0x200002dd}, {0x1d0207, 0x401c363}, {0x195f3f0d, 0x2004443c}, {0x250209, 0x60244c3}, {0x196f5b0d, 0x20048599}, {0x32c600b, 0x762c610}, {0x197f770d, 0x2008c6ea}, {0x3b4700d, 0x8734766}, {0x198f930d, 0x2009083c}, {0x2fc580f, 0x95bc8af}, {0x199faf0d, 0x200d4963}, {0x19afcb0d, 0x200d8a0b}, {0x19bfd91b, 0x640dcab4}, {0x19cf6922, 0x98060b93}, {0x19dfd922, 0x980e4c86}, {0x19ef6929, 0xba068d79}, {0x19ffd929, 0xba0ece6b}, {0x1a0f6930, 0xdc070f51}, {0x1a1fd930, 0xdc0f5025}, {0x30000000, 0x0}, {0x30000000, 0x0}, {0x30000000, 0x0}, {0x30000000, 0x0}, {0x30000000, 0x0}, {0x30000000, 0x0}, {0x30000000, 0x0}, {0x30000000, 0x0}}
}};
static_assert(NJOB + NCONV == 32, "");

__device__ __forceinline__ unsigned read_back(const void* p) {
    unsigned v = 0;
    asm volatile("ld.relaxed.gpu.global.u32 %0, [%1];" : "=r"(v) : "l"(p) : "memory");
    return v;
}
__device__ __forceinline__ void publish(unsigned* flag, unsigned seen, unsigned zero) {
    asm volatile("{\n.reg .pred p;\n.reg .u32 t;\nredux.sync.or.b32 t, %1, 0xffffffff;\nand.b32 t, t, %2;\nadd.u32 t, t, 1;\n"
                 "elect.sync _|p, 0xffffffff;\n@p red.relaxed.gpu.global.add.u32 [%0], t;\n}" :: "l"(flag), "r"(seen), "r"(zero) : "memory");
}

__device__ __forceinline__ void load_w(uint2 (&v)[32], const char* g) {
#pragma unroll
    for (int k = 0; k < 32; k++)
        asm volatile("ld.global.nc.L1::no_allocate.v2.b32 {%0,%1}, [%2];" : "=r"(v[k].x), "=r"(v[k].y) : "l"(g + k * (N_ * 4)));
}
__device__ __forceinline__ void store_w(const uint2 (&v)[32], unsigned (&o)[16], char* d) {
#pragma unroll
    for (int i = 0; i < 8; i++) {
        o[i] = pack4(v[4 * i].x, v[4 * i + 1].x, v[4 * i + 2].x, v[4 * i + 3].x);
        o[8 + i] = pack4(v[4 * i].y, v[4 * i + 1].y, v[4 * i + 2].y, v[4 * i + 3].y);
        if ((i & 3) == 3) {
            stg128(d + (i >> 2) * 128, make_uint4(o[i - 3], o[i - 2], o[i - 1], o[i]));
            stg128(d + (i >> 2) * 128 + 256, make_uint4(o[i + 5], o[i + 6], o[i + 7], o[i + 8]));
        }
    }
}
__device__ __forceinline__ unsigned col_sums(const unsigned (&o)[16]) {
    int cs[4];
#pragma unroll
    for (int i = 0; i < 4; i++)
        cs[i] = __dp4a((int)o[4 * i], 0x01010101, __dp4a((int)o[4 * i + 1], 0x01010101,
                __dp4a((int)o[4 * i + 2], 0x01010101, __dp4a((int)o[4 * i + 3], 0x01010101, 0))));
    return cs[0] + cs[1] + (cs[2] + cs[3]) * 65536;
}
__device__ __forceinline__ void wait_until(int due, unsigned t0) {
    for (int rem; (rem = due - (int)(clk() - t0)) > 0;) if (rem > CFG_SLEEP) __nanosleep(CFG_SLEEP / 4);
}

__device__ __forceinline__ uint32_t zero_term(const unsigned (&sv)[4], float zxf) {
    int lo = 0, hi = 0;
#pragma unroll
    for (int h = 0; h < 4; h++) {
        const int l = (int)(short)(sv[h] & 0xFFFF);
        lo += l; hi += ((int)(sv[h] - (unsigned)l)) >> 16;
    }
    const float fl = __bfloat162float(__float2bfloat16_rn((float)lo)) * zxf, fh = __bfloat162float(__float2bfloat16_rn((float)hi)) * zxf;
    uint32_t z;
    asm("cvt.rn.bf16x2.f32 %0, %1, %2;" : "=r"(z) : "f"(fh), "f"(fl));
    return z;
}

__device__ __forceinline__ void load_x(Scratch* scr, uint32_t sb, int b, int lane) {
    const int r = b & 15;
    const unsigned tgt = (*(volatile unsigned*)&scr->epoch[b] + 1) * 4;
    const unsigned* f = scr->flag + r * FS + (lane & 15);
    const uint32_t sa = __shfl_sync(~0u, sb, 0);
    const char* const ga = (const char*)scr->a8 + __shfl_sync(~0u, r * 16 * 8192, 0);
    unsigned todo = 0xFFFF, v = ld_flag(f);
    asm volatile("barrier.cluster.wait.aligned;" ::: "memory");
#pragma unroll 1
    for (int it = 0; todo; it++) {
        unsigned m = __ballot_sync(~0u, (int)(v - tgt) >= 0) & todo;
        v = ld_flag(f);
        todo &= ~m;
        while (m) {
            const int sl = __ffs(m) - 1;
            m &= m - 1;
            asm volatile("{\n.reg .pred p;\nelect.sync _|p, 0xffffffff;\n"
                         "@p cp.async.bulk.shared::cluster.global.mbarrier::complete_tx::bytes [%0], [%1], 8192, [%2];\n}"
                         :: "r"(sa + sl * 8192), "l"(ga + (unsigned)sl * 8192), "r"(sa + SM_BAR + (B_FULL + sl) * 8) : "memory");
        }
        if (it > (1 << 20)) __trap();
    }
}

__device__ __forceinline__ void load_x4(Scratch* scr, uint32_t sb, int b, int h, int lane) {
    const uint32_t bars = sb + SM_BAR;
    const unsigned tgt = (*(volatile unsigned*)&scr->epoch[b] + 1) * 4;
    const unsigned* f = scr->flag + (4 * h + (lane >> 4)) * FS + (lane & 15);
    asm volatile("barrier.cluster.wait.aligned;" ::: "memory");
#pragma unroll 1
    for (int it = 0, sl = 0; sl < 16; it++) {
        const unsigned v0 = ld_flag(f), v1 = ld_flag(f + 2 * FS);
        unsigned m = __ballot_sync(~0u, (int)(v0 - tgt) >= 0 && (int)(v1 - tgt) >= 0);
        m &= m >> 16;
#pragma unroll 1
        for (; m >> sl & 1; sl++) {
            if (sl >= 4) mbar_wait(bars + (B_GO + sl - 4) * 8);
            if (elect_one()) {
#pragma unroll
                for (int k = 0; k < 4; k++)
                    asm volatile("cp.async.bulk.shared::cluster.global.mbarrier::complete_tx::bytes [%0], [%1], %2, [%3];"
                                 :: "r"(sb + SM_A + ((sl & 3) * 4 + k) * 8192), "l"((const char*)scr->a8 + ((4 * h + k) * 16 + sl) * 8192),
                                    "r"(8192), "r"(bars + (B_FULL + (k >> 1) * 16 + sl) * 8) : "memory");
            }
        }
        if (it > (1 << 20)) __trap();
    }
}

__device__ __forceinline__ void store_out(const CUtensorMap* map, uint32_t sb, int b, int agent, int lane, int n, unsigned seq, int col, int dcol, int row, int drow) {
    const uint32_t bars = sb + SM_BAR;
    const uint32_t buf = sb + SM_OUT + agent * 4096, full = bars + (B_OFULL + agent) * 8;
#pragma unroll 1
    for (int t = 0; t < n; t++, seq >>= 4) {
        asm volatile("{\n.reg .pred p;\n.reg .u32 c;\nmov.u32 c, 0;\n"
                     "WAIT_LOOP:\n"
                     "mbarrier.try_wait.parity.shared::cta.b64 p, [%4], %5;\n"
                     "@p bra WAIT_DONE;\n"
                     "add.u32 c, c, 1;\nsetp.lt.u32 p, c, 0x100000;\n"
                     "@p bra WAIT_LOOP;\n"
                     "trap;\n"
                     "WAIT_DONE:\n"
                     "fence.proxy.async.shared::cta;\n"
                     "elect.sync _|p, 0xffffffff;\n"
                     "@p cp.async.bulk.tensor.2d.global.shared::cta.tile.bulk_group [%0, {%1, %2}], [%3];\n"
                     "cp.async.bulk.commit_group;\n}"
                     :: "l"(map), "r"(col + (seq & 7) * dcol), "r"(row + agent * 32 + (seq & 7) * drow), "r"(buf), "r"(full), "r"(t & 1) : "memory");
        asm volatile("cp.async.bulk.wait_group.read 0;" ::: "memory");
        if (elect_one()) mbar_arrive(bars + (B_OFREE + t * 4 + 4 + agent) * 8);
    }
}

template <int V> struct I { static constexpr int v = V; };
template <int MODE>
__device__ __forceinline__ void consume(Scratch* scr, const __nv_bfloat16* __restrict__ scale_w, const __nv_bfloat16* __restrict__ bias,
                                        const __nv_bfloat16* __restrict__ scale_x, uint32_t sb, int b, int warp, int lane) {
    constexpr bool SIDE = MODE != 0;
    constexpr int NR = NRING, NG = SIDE ? 48 : 56;
    const uint32_t bars = sb + SM_BAR;
    const int c = SIDE ? 7 : b >> 4;
    constexpr uint32_t SD = 0x400 >> 4;
    if ((sb & 0xFFFFFF) != 0x400) __trap();
    const int wg = warp >> 2;
    const unsigned short sxr = __ldg((const unsigned short*)scale_x);
    const uint32_t sx2 = (uint32_t)sxr * 0x10001u;
    const int c0 = (warp & 3) * 16 + (lane >> 2) * 2;
    uint32_t sw[4], bi[4];
#pragma unroll
    for (int i = 0; i < 4; i++) {
        const int col = col_of(c, i < 2 ? wg * 2 + i : i == 2 ? 4 + wg : 6) + c0;
        sw[i] = __ldg((const uint32_t*)(scale_w + col));
        bi[i] = __ldg((const uint32_t*)(bias + col));
    }
    const uint32_t st0 = sb + SM_OUT + (lane & 3) * 256 + (((c0 >> 3) ^ ((lane & 3) * 2)) << 4) + (c0 & 7) * 2;
    constexpr uint32_t DX0 = (SD + (SM_A >> 4)) | (1 << 16), DW0 = (SD + (SM_RING >> 4)) | (8 << 16);
    asm volatile("barrier.cluster.wait.aligned;" ::: "memory");
    int a0[64], a1[64];
    constexpr int MUL = SIDE ? 4 : 2, NONE = 64 * MUL, BIAS = NR + 64 - NG;
    const uint32_t go = mapa(bars + B_GO * 8, lane & (SIDE ? 1 : 15)) - (64 - NG) * MUL;
    const int key = SIDE ? (lane < 2 ? lane * 4 : 1) : (lane < 16 ? (lane >> 2) * 2 : 1);
    int pend = NONE;
    uint32_t bb = bars + (B_FULL + wg * 16) * 8;
#define RELEASE() { mbar_arrive_cluster_if(go + (pend & ~7), pend & (NONE + 8 - MUL), key); }
    struct Par { uint32_t a, b, c, d; };
    auto load_par = [&](int blk, uint32_t swv, uint32_t biv) {
        mbar_wait_cluster(bars + (B_PAR + blk) * 8);
        const uint32_t zc = lds32(sb + SM_PAR + (blk * 64 + c0) * 2);
        const float sxf = __uint_as_float(sx2 << 16);
        const float s0 = sxf * __uint_as_float(swv << 16), s1 = sxf * __uint_as_float(swv & 0xFFFF0000u);
        Par P = {__float_as_uint(s0), __float_as_uint(s1), __float_as_uint(fmaf(-__uint_as_float(zc << 16), s0, __uint_as_float(biv << 16))),
                 __float_as_uint(fmaf(-__uint_as_float(zc & 0xFFFF0000u), s1, __uint_as_float(biv & 0xFFFF0000u)))};
        asm volatile("{\n.reg .pred p;\nsetp.ne.u32 p, %3, 0;\n@p st.shared.v2.b32 [%0], {%1, %2};\n}" :: "r"(st0), "r"(P.c), "r"(P.d), "r"(blockIdx.y) : "memory");
        return P;
    };
    auto drain = [&](int (&a)[64], auto Q, int t, const Par& P) {
#pragma unroll
        for (int q = Q.v; q < Q.v + 2; q++) {
#pragma unroll
            for (int j = 0; j < 8; j++) {
                const int o = q * 16 + (j >> 1) * 4 + (j & 1);
                asm("cvt.rn.f32.s32 %0, %0;\n\tcvt.rn.f32.s32 %1, %1;\n\tfma.rn.f32 %0, %0, %2, %4;\n\tfma.rn.f32 %1, %1, %3, %5;\n\t"
                    "cvt.rn.bf16x2.f32 %0, %1, %0;" : "+r"(a[o]), "+r"(a[o + 2]) : "r"(P.a), "r"(P.b), "r"(P.c), "r"(P.d));
            }
            mbar_wait(bars + (B_OFREE + t * 4 + q) * 8);
#pragma unroll
            for (int j = 0; j < 8; j++) sts32((st0 ^ ((j & 1) * 16)) + q * 4096 + (j >> 1) * 1024 + (j & 1) * 128, a[q * 16 + (j >> 1) * 4 + (j & 1)]);
            __syncwarp();
            if (lane == 0) mbar_arrive(bars + (B_OFULL + q) * 8);
        }
    };
    wg_fence();
    if (MODE == 2) {
#pragma unroll 1
        for (int s = 0; s < 16; s++) {
            mbar_wait2(bars + (B_FULL + 48 + (s >> 2) * 2) * 8, bb + s * 8);
            mma_rows2(a0, a1, DW0 + s * 256, DX0 + ((s & 3) * 4 + 2 * wg) * 512, s);
            wg_wait<1>();
            if (s && lane == 0) mbar_arrive(bars + (B_GO + s - 1) * 8);
        }
        const Par P = load_par(6, sw[3], bi[3]);
        wg_wait<0>();
        drain(a0, I<0>(), wg, P); drain(a0, I<2>(), wg, P);
        drain(a1, I<0>(), 2 + wg, P); drain(a1, I<2>(), 2 + wg, P);
    } else {
    {
        uint32_t tbl = wg ? STEPS1 : STEPS0;
        uint32_t ba = bars + B_FULL * 8;
        int u = MUL * (wg * D_ + BIAS);
        uint32_t dw = DW0 + wg * D_ * 512;
        static_assert(D_ < NR, "");
        mbar_wait2(ba, bb);
#pragma unroll 1
        for (uint32_t dx = DX0;;) {
            mma_unit2(a0, a1, dw, dx, dx - DX0);
            dx += 512; ba += 8; bb += 8;
            const bool ready = mbar_test2(ba, bb);
            wg_wait<1>();
            RELEASE()
            pend = u;
            if (dx == DX0 + 16 * 512) break;
            u += MUL + (tbl & 1) * MUL;
            dw += 512 + (tbl & 1) * 512;
            if (dw >= DW0 + NR * 512) dw -= NR * 512;
            tbl >>= 1;
            if (!ready && !mbar_test2(ba, bb)) {
                wg_wait<0>();
                RELEASE()
                pend = NONE;
                mbar_wait(ba);
                if (wg) mbar_wait(bb);
            }
        }
    }
    Par P0 = load_par(2 * wg, sw[0], bi[0]);
    const Par P1 = load_par(2 * wg + 1, sw[1], bi[1]);
#define RELEASE2() { mbar_arrive_cluster_if(go + (pend & ~7), pend & (NONE + 8 - 2 * MUL), key & ~MUL); }
    static_assert(NR % 2 == 0, "");
    wg_wait<0>();
#pragma unroll 1
    for (int ph = 0;; ph++) {
        const int m = ph ? MUL : 0;
        const int u0 = 32 + ph * 16 + wg * 8;
        uint32_t dw = DW0 + (ph ? 48 % NR : wg ? 40 % NR : 32 % NR) * 512;
        bb = bars + (B_FULL + u0) * 8;
        mbar_arrive_cluster_if(go + (pend & ~7), pend & (NONE + 8 - MUL - m), key & ~m);
        drain(a0, I<0>(), ph ? (ph + wg) * 2 + (ph & 2) + SIDE : wg, P0);
        const bool first = mbar_test(bb);
        drain(a0, I<2>(), wg ? 4 * ph + 1 : 3 * ph, P0);
        if (SIDE ? ph + wg == 1 : ph == 1) drain(a1, I<0>(), SIDE ? 4 - 2 * wg : 3 + 2 * wg, P1);
        if (SIDE ? ph == 1 : ph + wg == 2) break;
        pend = NONE;
        if (!first) mbar_wait(bb);
        if (ph + wg) mbar_wait(bars + (B_TURN + ph) * 8);
        wg_fence();
#pragma unroll 1
        for (int n = 0;; n += 2) {
            const bool ready = mma_pair(a0, dw, DX0 + n * 1024, n, bb + n * 8 + 16, go + (pend & ~7), pend & (NONE + 8 - 2 * MUL), key & ~MUL);
            wg_wait<1>();
            pend = n ? MUL * (u0 + BIAS + n - 2) : NONE;
            if (n == 6) break;
            dw += 1024;
            if (dw == DW0 + NR * 512) dw = DW0;
            if (!ready) {
                RELEASE2()
                pend = NONE;
                mbar_wait(bb + n * 8 + 16);
            }
        }
        if (ph == 0 && (threadIdx.x & 127) == 0) mbar_arrive(bars + (B_TURN + wg) * 8);
        RELEASE2()
        pend = MUL * (u0 + BIAS + 6);
        if (ph == 0) drain(a1, I<2>(), 2 + 2 * wg, P1);
        P0 = load_par(4 + 2 * ph + wg, ph ? sw[3] : sw[2], ph ? bi[3] : bi[2]);
        wg_wait<0>();
    }
    }
    if (threadIdx.x == 128) asm volatile("red.relaxed.gpu.global.add.u32 [%0], 1;" :: "l"(scr->epoch + b) : "memory");
}

__global__ void __cluster_dims__(CS, 1, 1) __launch_bounds__(512, 1)
w8a8_kernel(const char* __restrict__ qx, const char* __restrict__ qw, Scratch* scr, const JobTable* __restrict__ jobs, const __nv_bfloat16* __restrict__ scale_w,
            const __nv_bfloat16* __restrict__ bias, const __nv_bfloat16* __restrict__ scale_x, const int* __restrict__ zero_x,
            const __grid_constant__ CUtensorMap map) {
    extern __shared__ __align__(1024) unsigned char smem_raw[];
    const uint32_t sb = (uint32_t)__cvta_generic_to_shared(smem_raw);
    const uint32_t bars = sb + SM_BAR;
    const int warp = __shfl_sync(~0u, threadIdx.x >> 5, 0), lane = threadIdx.x & 31;
    const int b = blockIdx.x, r = b & 15, c = b >> 4;
    const unsigned t0 = clk() + CFG_PF0;
    if (warp < CFG_NINIT) {
#pragma unroll 1
        for (int w = warp; w < 8; w += CFG_NINIT) {
            if (elect_one()) {
                const uint32_t cnt = w < B_GO / 16 ? 1 : 4 * CS + 1;
#pragma unroll
                for (int i = 0; i < 16; i++) mbar_init(bars + (w * 16 + i) * 8, cnt);
            }
            __syncwarp();
            const int i = w * 16 + lane;
            if (lane < 16 && i < B_OFREE + NOUT && (i >> 1) != B_TURN / 2) mbar_expect_tx(bars + i * 8, i >= B_AFREE ? 0 : i >= B_PAR ? 128 : w == 1 ? 8192 : 16384);
            if (w == B_GO / 16 && 4 * lane + (r >> 2) < NRING)
                asm volatile("mbarrier.arrive.shared::cta.b64 _, [%0], %1;" :: "r"(bars + i * 8), "r"(4 * CS) : "memory");
        }
        if (warp == (B_SUM / 16) % CFG_NINIT) {
            if (elect_one()) {
#pragma unroll
                for (int k = 0; k < NOUT; k++) mbar_init(bars + (B_OFULL + k) * 8, 4);
                mbar_init(bars + B_SUM * 8, r < 8 ? 1 : 3);
                mbar_expect_tx(bars + B_SUM * 8, r < 8 ? 32 * 64 : 30 * 64);
            }
        }
        asm volatile("fence.mbarrier_init.release.cluster;" ::: "memory");
    } else if (warp == 7) {
        asm volatile("st.shared.v2.b32 [%0], {%1, %1};" :: "r"(sb + SM_SUM + lane * 8), "r"(0) : "memory");
        asm volatile("fence.release.sync_restrict::shared::cta.cluster;" ::: "memory");
    } else if (warp == 9) {
        asm volatile("griddepcontrol.launch_dependents;");
        if (elect_one()) asm volatile("prefetch.tensormap [%0];" :: "l"(&map) : "memory");
    } else if (warp >= 14) {
        const char* pf = qx + (r * 128 + ((threadIdx.x >> 1) & 31)) * (K_ * 4) + (lane & 1) * 128;
        if (c >= 5) asm volatile("prefetch.global.L2 [%0];" :: "l"(pf + (c - 5) * (32 * K_ * 4)) : "memory");
        asm volatile("prefetch.global.L2 [%0];" :: "l"(pf + ((c + 2) & 3) * (32 * K_ * 4) + ((c + 2) >> 2) * 256) : "memory");
    }
    asm volatile("barrier.cluster.arrive.relaxed.aligned;" ::: "memory");

    if (warp >= 8) {
        asm volatile("setmaxnreg.dec.sync.aligned.u32 88;");
        int agent = -1;
        if (warp >= 16 - NCONV) {
            const int cw = warp - (16 - NCONV);
            const unsigned zero = blockIdx.y;
            const char* const gx = qx + (lane >> 4) * (K_ * 4) + (lane & 15) * 16;
            const char* const gw = qw + lane * 8;
            const int wrB = ((lane >> 3) * 32 + (lane & 7)) * 16;
            uint2 tab;
            asm volatile("ld.global.nc.v2.u32 {%0, %1}, [%2];" : "=r"(tab.x), "=r"(tab.y) : "l"(&jobs->e[b][lane]));
            bool synced = false;
#pragma unroll 1
            for (int p = cw || c >= 5 ? cw : NCONV;; p = p < CFG_PZ ? p + NCONV : p < CFG_PZ + 3 ? 31 : p + 3) {
                uint2 j;
                if (p < 4) {
                    const int g = 7 * p + c - 5;
                    j.x = ((r * 128 + (g & 3) * 32) * 16 + (g >> 2)) | (r * 64 + g) << 16;
                    j.y = max((p - 1) * (CFG_P0 / 4) + b * (CFG_P0 * 4 / NCTA) / 16, 0) | (r * FS + (g >> 2)) << 14 | p << 24;
                } else { j.x = __shfl_sync(~0u, tab.x, p); j.y = __shfl_sync(~0u, tab.y, p); }
                if (j.x >= 3u << 28) break;
                const int kind = j.x >> 28, sig = (j.y >> 14) & 0x3FF;
                char* tile = (char*)scr + ((j.x >> 16) & 0xFFF) * 2048;
                const char* g = (kind ? gw : gx) + (j.x & 0xFFFF) * 256;
                wait_until((j.y & 0x3FFF) * 4, t0);
                if (kind == 0) {
                    uint4 v[16];
#pragma unroll
                    for (int i = 0; i < 16; i++)
                        asm volatile("ld.global.nc.L1::no_allocate.v4.b32 {%0,%1,%2,%3}, [%4];"
                                     : "=r"(v[i].x), "=r"(v[i].y), "=r"(v[i].z), "=r"(v[i].w) : "l"(g + i * (2 * K_ * 4)));
#pragma unroll
                    for (int i = 0; i < 16; i++)
                        asm volatile("st.global.b32 [%0], %1;" :: "l"(tile + ((lane * 4) ^ ((i & 3) * 16)) + i * 128),
                                     "r"(pack4(v[i].x, v[i].y, v[i].z, v[i].w)) : "memory");
                    asm volatile("fence.proxy.async.global;" ::: "memory");
                    __syncwarp();
                    publish(scr->flag + sig, read_back(tile + lane * 64), zero);
                } else {
                    uint2 v[32];
                    unsigned o[16];
                    load_w(v, g);
                    if (!synced) asm volatile("barrier.cluster.wait.aligned;" ::: "memory");
                    synced = true;
                    store_w(v, o, tile + wrB);
                    asm volatile("{\n.reg .pred p;\nsetp.eq.u32 p, %1, 0;\nfence.proxy.async.global;\nbar.warp.sync 0xffffffff;\n"
                                 "@p mbarrier.arrive.shared::cta.b64 _, [%0];\n}" :: "r"(bars + (B_GO + (sig & 15)) * 8), "r"(lane | (kind & 2)) : "memory");
                    const unsigned csv = col_sums(o);
                    if (kind == 1) {
                        const int own = (j.y >> (24 + (lane >> 4) * 4)) & 15;
                        const uint32_t so = SM_SUM + (sig & 48) * 4 + (lane & 15) * 4;
                        if (own != r) {
                            const uint32_t ro = mapa(sb, own);
                            asm volatile("red.async.relaxed.cluster.shared::cluster.mbarrier::complete_tx::bytes.add.u32 [%0], %1, [%2];"
                                         :: "r"(ro + so), "r"(csv), "r"(ro + SM_BAR + B_SUM * 8) : "memory");
                        } else asm volatile("red.relaxed.cluster.shared::cta.add.u32 [%0], %1;" :: "r"(sb + so), "r"(csv) : "memory");
                        __syncwarp();
                        if (own == r && (lane & 15) == 0) mbar_arrive(bars + B_SUM * 8);
                    } else {
                        unsigned* csp = scr->cs + (j.y >> 24) * 32 + lane;
                        asm volatile("st.global.u32 [%0], %1;" :: "l"(csp), "r"(csv) : "memory");
                        publish(scr->flag + sig, read_back(tile + lane * 64) | read_back(csp), zero);
                    }
                }
                __syncwarp();
            }
            if (!synced) asm volatile("barrier.cluster.wait.aligned;" ::: "memory");
            agent = (cw + 6 * NCONV - CFG_PZ) % NCONV + 1;
            if (agent > 3) agent = -1;
        } else if (warp == 9) {
            asm volatile("barrier.cluster.wait.aligned;" ::: "memory");
        } else {
            load_x(scr, sb, b, lane);
            agent = 0;
        }
        const char* src = (const char*)scr->b8 + (c * 224 + r) * 2048;
        const int zxi = __ldg(zero_x);
#pragma unroll 1
        for (int i = 0, slot = r >> 2, end = 8;; end = NG / 4) {
#pragma unroll 1
            for (; warp == 9 && i < end; i++) {
                asm volatile("{\n.reg .pred p;\nWAIT_LOOP:\nmbarrier.try_wait.parity.shared::cta.b64 p, [%4], 0;\n@!p bra WAIT_LOOP;\n"
                             "elect.sync _|p, 0xffffffff;\n"
                             "@p cp.async.bulk.shared::cluster.global.mbarrier::complete_tx::bytes.multicast::cluster [%0], [%1], 2048, [%2], %3;\n}"
                             :: "r"(sb + SM_RING + slot * 8192 + (r & 3) * 2048), "l"(src + i * 32768),
                                "r"(bars + (B_FULL + bar_of(4 * i + (r >> 2))) * 8), "h"((uint16_t)0xFFFF), "r"(bars + (B_GO + i) * 8) : "memory");
                slot += slot >= NRING - 4 ? 4 - NRING : 4;
            }
            if (end != 8) break;
            if (warp == (r < 8 ? 9 : r < 10 ? 8 : r < 14 ? 16 - NCONV + (CFG_PZ + 3) % NCONV : 0)) {
                const float zxf = __bfloat162float(__float2bfloat16_rn((float)zxi));
                const int grp = sum_group(r);
                mbar_wait_cluster(bars + B_SUM * 8);
                unsigned sv[4];
#pragma unroll
                for (int h = 0; h < 4; h++) sv[h] = lds32(sb + SM_SUM + h * 64 + (lane & 15) * 4);
                const uint32_t z = zero_term(sv, zxf);
#pragma unroll 2
                for (int k = 0; k < 8; k++) {
                    const uint32_t rb = mapa(sb, k * 2 + (lane >> 4));
                    st_async32(rb + SM_PAR + grp * 64 + (lane & 15) * 4, z, rb + SM_BAR + (B_PAR + (grp >> 1)) * 8);
                }
            }
        }
        __syncwarp();
        if (agent >= 0) store_out(&map, sb, b, agent, lane, 7, agent < 2 ? 0x6351420 : 0x6534120, c * 64, 7 * 64, r * 128, 0);
    } else {
        asm volatile("setmaxnreg.inc.sync.aligned.u32 168;");
        consume<0>(scr, scale_w, bias, scale_x, sb, b, warp, lane);
    }
}

__global__ void __cluster_dims__(2, 1, 1) __launch_bounds__(512, 1)
w8a8_side(const char* __restrict__ qw, Scratch* scr, const __nv_bfloat16* __restrict__ scale_w, const __nv_bfloat16* __restrict__ bias,
          const __nv_bfloat16* __restrict__ scale_x, const int* __restrict__ zero_x, const __grid_constant__ CUtensorMap map) {
    extern __shared__ __align__(1024) unsigned char smem_raw[];
    const uint32_t sb = (uint32_t)__cvta_generic_to_shared(smem_raw);
    const uint32_t bars = sb + SM_BAR;
    const int warp = __shfl_sync(~0u, threadIdx.x >> 5, 0), lane = threadIdx.x & 31;
    const int b = NCTA + blockIdx.x, rank = b & 1;
    const bool helper = blockIdx.x >= 16;
    constexpr int NR = NRING;
    const unsigned t0 = clk();
    if (warp < 3) {
#pragma unroll 1
        for (int w = warp; w < B_OFULL / 16; w += 3) {
            if (elect_one()) {
                const uint32_t cnt = w < B_GO / 16 ? 1 : !helper ? 9 : w == B_GO / 16 ? 8 : 1;
#pragma unroll
                for (int i = 0; i < 16; i++) mbar_init(bars + (w * 16 + i) * 8, cnt);
            }
            __syncwarp();
            const int i = w * 16 + lane;
            if (lane < 16 && i < B_PAR) mbar_expect_tx(bars + i * 8, w == 1 && !helper ? 8192 : 16384);
            if (lane < 16 && i >= B_OFREE && i < B_OFREE + NOUT) mbar_arrive(bars + i * 8);
            if (w == B_GO / 16 && 2 * lane + rank < NR && !helper)
                asm volatile("mbarrier.arrive.shared::cta.b64 _, [%0], %1;" :: "r"(bars + i * 8), "r"(8) : "memory");
        }
        asm volatile("fence.mbarrier_init.release.cluster;" ::: "memory");
    } else if (warp == 3) {
        if (elect_one()) {
#pragma unroll
            for (int i = 0; i < NOUT; i++) mbar_init(bars + (B_OFULL + i) * 8, 4);
            asm volatile("fence.mbarrier_init.release.cluster;" ::: "memory");
        }
        __syncwarp();
    } else if (warp == 11 && elect_one()) asm volatile("prefetch.tensormap [%0];" :: "l"(&map) : "memory");
    asm volatile("barrier.cluster.arrive.relaxed.aligned;" ::: "memory");

    if (warp >= 8) {
        asm volatile("setmaxnreg.dec.sync.aligned.u32 88;");
        int agent = -1;
        if (warp == 10 || warp >= 12) {
#pragma unroll 1
            for (int i = (0x032401 >> (4 * (warp - 10))) & 7; i < (helper ? 8 : 12 - CFG_NOC / 4); i += 5) {
                const int G = (helper ? 192 - 16 + i * 4 : CFG_NOC * 4 + i * 16) + blockIdx.x, u = G >> 2, f = bar_of(u);
                const int blk = u < 32 ? (f >> 4) * 2 + (G & 1) : u >> 3, step = u < 32 ? (f & 15) * 2 + (G >> 1 & 1) : G & 31;
                char* const tile = (char*)scr->b8 + (7 * 224 + G) * 2048;
                unsigned* const csp = scr->cs + (step * 7 + blk) * 32 + lane;
                uint2 v[32];
                unsigned o[16];
                wait_until(helper ? i * CFG_YH + CFG_YH0 : (G - CFG_NOC * 4) * (CFG_YP / 16) + CFG_Y0, t0);
                load_w(v, qw + step * (32 * N_ * 4) + (49 + blk) * 256 + lane * 8);
                store_w(v, o, tile + ((lane >> 3) * 32 + (lane & 7)) * 16);
                asm volatile("st.global.u32 [%0], %1;" :: "l"(csp), "r"(col_sums(o)) : "memory");
                asm volatile("fence.proxy.async.global;" ::: "memory");
                __syncwarp();
                publish(scr->flag + CS * FS + u, read_back(tile + lane * 64) | read_back(csp), blockIdx.y);
            }
        }
        if (warp == 8) {
            if (helper) load_x4(scr, sb, b, blockIdx.x - 16, lane);
            else load_x(scr, sb, b, lane);
            agent = 0;
        } else if (warp == 11) {
            const unsigned tgt = (*(volatile unsigned*)&scr->epoch[b] + 1) * 4;
            const unsigned* f = scr->flag + CS * FS + lane;
            unsigned todo0 = helper ? 0 : ~0u, todo1 = helper ? 0xFF0000 : 0xFFFF, v0 = ld_flag(f), v1 = ld_flag(f + 32);
            bool par = lane >= 2;
            asm volatile("barrier.cluster.wait.aligned;" ::: "memory");
#pragma unroll 1
            for (int it = 0; todo0 | todo1; it++) {
                const unsigned m0 = __ballot_sync(~0u, (int)(v0 - tgt) >= 0) & todo0, m1 = __ballot_sync(~0u, (int)(v1 - tgt) >= 0) & todo1;
                v0 = ld_flag(f); v1 = ld_flag(f + 32);
                todo0 &= ~m0; todo1 &= ~m1;
                if ((lane & 1) == rank) {
                    if (m0 >> lane & 1) mbar_arrive(bars + (B_GO + (lane >> 1)) * 8);
                    if (m1 >> lane & 1) mbar_arrive(bars + (B_GO + 16 + (lane >> 1)) * 8);
                }
                if (!par && !(lane ? todo1 : todo0)) { par = true; mbar_arrive(bars + (B_AFREE + lane) * 8); }
                if (it > (1 << 20)) __trap();
            }
        } else if (warp == 9) {
            asm volatile("barrier.cluster.wait.aligned;" ::: "memory");
            const char* src = (const char*)scr->b8 + (7 * NG + rank) * 8192;
#pragma unroll 1
            for (int i = helper ? 24 : 0, slot = rank; i < (helper ? 28 : 24); i++) {
                asm volatile("{\n.reg .pred p;\nWAIT_LOOP:\nmbarrier.try_wait.parity.shared::cta.b64 p, [%4], 0;\n@!p bra WAIT_LOOP;\n"
                             "elect.sync _|p, 0xffffffff;\n"
                             "@p cp.async.bulk.shared::cluster.global.mbarrier::complete_tx::bytes.multicast::cluster [%0], [%1], 8192, [%2], %3;\n}"
                             :: "r"(sb + SM_RING + slot * 8192), "l"(src + i * 16384),
                                "r"(bars + (B_FULL + bar_of(2 * i + rank)) * 8), "h"((uint16_t)3), "r"(bars + (B_GO + i) * 8) : "memory");
                slot += slot >= NR - 2 ? 2 - NR : 2;
            }
        } else if (warp == 12 || warp == 15) {
            asm volatile("barrier.cluster.wait.aligned;" ::: "memory");
#pragma unroll 1
            for (int blk = helper ? 6 + (warp & 2) : warp & 2; blk < (helper ? 7 : 6); blk += 4) {
                const int w = min(blk * 32 + lane * 2, TN / 2 - 2);
                mbar_wait(bars + (B_AFREE + (blk >> 2)) * 8);
                uint2 v[32];
                unsigned s0[4], s1[4];
                const float zxf = __bfloat162float(__float2bfloat16_rn((float)__ldcg(zero_x)));
#pragma unroll
                for (int k = 0; k < 32; k++) v[k] = __ldcg((const uint2*)(scr->cs + k * (TN / 2) + w));
#pragma unroll
                for (int h = 0; h < 4; h++) {
                    s0[h] = s1[h] = 0;
#pragma unroll
                    for (int k = 0; k < 8; k++) { s0[h] += v[8 * h + k].x; s1[h] += v[8 * h + k].y; }
                }
                sts32(sb + SM_PAR + w * 4, zero_term(s0, zxf));
                sts32(sb + SM_PAR + w * 4 + 4, zero_term(s1, zxf));
                __syncwarp();
                if (lane < 2) mbar_arrive(bars + (B_PAR + blk + lane) * 8);
            }
        } else {
            asm volatile("barrier.cluster.wait.aligned;" ::: "memory");
            agent = warp == 10 ? 1 : warp - 11;
        }
        if (agent >= 0) {
            if (helper) store_out(&map, sb, b, agent, lane, 4, 0x3120, col_of(7, 6), 0, (blockIdx.x - 16) * 512, 128);
            else store_out(&map, sb, b, agent, lane, 6, agent < 2 ? 0x514320 : 0x534120, col_of(7, 0), 64, blockIdx.x * 128, 0);
        }
    } else {
        asm volatile("setmaxnreg.inc.sync.aligned.u32 168;");
        if (helper) consume<2>(scr, scale_w, bias, scale_x, sb, b, warp, lane);
        else consume<1>(scr, scale_w, bias, scale_x, sb, b, warp, lane);
    }
}

}

typedef CUresult (*EncodeFn)(CUtensorMap*, CUtensorMapDataType, cuuint32_t, void*, const cuuint64_t*, const cuuint64_t*,
                             const cuuint32_t*, const cuuint32_t*, CUtensorMapInterleave, CUtensorMapSwizzle,
                             CUtensorMapL2promotion, CUtensorMapFloatOOBfill);

namespace w8 {

constexpr int M_ = 2048, K_ = 1024, N_ = 3584;
constexpr int WA = 160, WB = 64;
constexpr int TN = 2 * WA + 2 * WB;
static_assert(TN == 448, "");
constexpr int X1 = 13;
constexpr int NSLOT = 7, SLOT = WA * 64;
constexpr int NSTG = 3, PFD = 700, NCONV = 5;
constexpr int NU = 48;
constexpr int UX = 32 + NSLOT;
constexpr int NJOB = 22;
constexpr int NCTA = 128;

constexpr int nA = 64, nWA = WA / 4, nWB = WB / 4;
constexpr int SEG1 = X1 * (nA + 2 * nWA);
constexpr int SEG2 = SEG1 + (16 - X1) * (nA + nWA);
constexpr int SEG3 = SEG2 + (16 - X1) * nWA;
constexpr int SEG4 = SEG3 + 16 * nWB;
constexpr int SEG5 = SEG4 + 16 * nWB;
static_assert(SEG5 == NJOB * NCTA, "");

constexpr int SM_A = 0;
constexpr int SM_RING = 131072;
constexpr int SM_STG = SM_RING + NSLOT * SLOT;
constexpr int SM_PAR = SM_STG + NSTG * 8192;
constexpr int SM_BAR = SM_PAR + 3 * TN * 2;
constexpr int B_FULLB = 0, B_FULLA = 48, B_GO = 64, B_PAR = 88, B_PSTEP = 92, B_AFREE = 100, B_NINIT = 102, B_FULLS = 102, B_END = 108;
constexpr int SM_TOTAL = SM_BAR + B_END * 8;
static_assert(SM_TOTAL <= 232448, "");

__device__ uint4 g_a8[M_ * K_ / 16];
__device__ uint4 g_b8[N_ * K_ / 16];
__device__ uint4 g_cs[16 * N_ * 2 / 16];
__device__ unsigned g_flag[16 * 16 + 8 * 64];
__device__ unsigned g_epoch[NCTA];
__device__ unsigned g_sink;
constexpr int SM_ALLOC = SM_TOTAL;

__device__ __forceinline__ void mbar_init(uint32_t bar, uint32_t cnt) {
    asm volatile("mbarrier.init.shared::cta.b64 [%0], %1;" :: "r"(bar), "r"(cnt) : "memory");
}
__device__ __forceinline__ void mbar_expect_tx(uint32_t bar, uint32_t bytes) {
    asm volatile("mbarrier.arrive.expect_tx.shared::cta.b64 _, [%0], %1;" :: "r"(bar), "r"(bytes) : "memory");
}
__device__ __forceinline__ void mbar_arrive(uint32_t bar) {
    asm volatile("mbarrier.arrive.shared::cta.b64 _, [%0];" :: "r"(bar) : "memory");
}
__device__ __forceinline__ void mbar_arrive_cluster(uint32_t bar) {
    asm volatile("mbarrier.arrive.shared::cluster.b64 _, [%0];" :: "r"(bar) : "memory");
}
__device__ __forceinline__ void mbar_wait(uint32_t bar, uint32_t parity = 0) {
    asm volatile("{\n.reg .pred p;\n.reg .u32 c;\n"
                 "mbarrier.try_wait.parity.shared::cta.b64 p, [%0], %1;\n"
                 "@p bra WAIT_DONE;\n"
                 "mov.u32 c, 0;\n"
                 "WAIT_LOOP:\n"
                 "mbarrier.try_wait.parity.shared::cta.b64 p, [%0], %1;\n"
                 "@p bra WAIT_DONE;\n"
                 "add.u32 c, c, 1;\nsetp.lt.u32 p, c, 0x100000;\n"
                 "@p bra WAIT_LOOP;\n"
                 "trap;\n"
                 "WAIT_DONE:\n}" :: "r"(bar), "r"(parity) : "memory");
}
__device__ __forceinline__ void mbar_wait2(uint32_t bar0, uint32_t bar1) {
    asm volatile("{\n.reg .pred p, q;\n.reg .u32 c;\nmov.u32 c, 0;\n"
                 "WAIT_LOOP:\n"
                 "mbarrier.try_wait.parity.shared::cta.b64 p, [%0], 0;\n"
                 "mbarrier.try_wait.parity.shared::cta.b64 q, [%1], 0;\n"
                 "and.pred p, p, q;\n"
                 "@p bra WAIT_DONE;\n"
                 "add.u32 c, c, 1;\nsetp.lt.u32 p, c, 0x100000;\n"
                 "@p bra WAIT_LOOP;\n"
                 "trap;\n"
                 "WAIT_DONE:\n}" :: "r"(bar0), "r"(bar1) : "memory");
}
__device__ __forceinline__ bool mbar_test(uint32_t bar) {
    uint32_t ok;
    asm volatile("{\n.reg .pred p;\nmbarrier.test_wait.parity.shared::cta.b64 p, [%1], 0;\nselp.u32 %0, 1, 0, p;\n}" : "=r"(ok) : "r"(bar) : "memory");
    return ok;
}
__device__ __forceinline__ bool mbar_test2(uint32_t bar0, uint32_t bar1) {
    uint32_t ok;
    asm volatile("{\n.reg .pred p, q;\nmbarrier.test_wait.parity.shared::cta.b64 p, [%1], 0;\n"
                 "mbarrier.test_wait.parity.shared::cta.b64 q, [%2], 0;\nand.pred p, p, q;\nselp.u32 %0, 1, 0, p;\n}"
                 : "=r"(ok) : "r"(bar0), "r"(bar1) : "memory");
    return ok;
}
__device__ __forceinline__ bool elect_one() {
    uint32_t ok;
    asm volatile("{\n.reg .pred p;\nelect.sync _|p, 0xffffffff;\nselp.u32 %0, 1, 0, p;\n}" : "=r"(ok));
    return ok;
}
__device__ __forceinline__ unsigned ld_acquire(const unsigned* p) {
    unsigned v;
    asm volatile("ld.acquire.gpu.global.u32 %0, [%1];" : "=r"(v) : "l"(p) : "memory");
    return v;
}
__device__ __forceinline__ unsigned ld_flag(const unsigned* p) {
    unsigned v;
    asm volatile("ld.relaxed.gpu.global.u32 %0, [%1];" : "=r"(v) : "l"(p) : "memory");
    return v;
}
__device__ __forceinline__ uint4 lds128(uint32_t a) {
    uint4 v;
    asm volatile("ld.shared.v4.b32 {%0,%1,%2,%3}, [%4];" : "=r"(v.x), "=r"(v.y), "=r"(v.z), "=r"(v.w) : "r"(a) : "memory");
    return v;
}
__device__ __forceinline__ void sts128(uint32_t a, uint4 v) {
    asm volatile("st.shared.v4.b32 [%0], {%1,%2,%3,%4};" :: "r"(a), "r"(v.x), "r"(v.y), "r"(v.z), "r"(v.w) : "memory");
}
__device__ __forceinline__ uint32_t lds32(uint32_t a) {
    uint32_t v;
    asm volatile("ld.shared.b32 %0, [%1];" : "=r"(v) : "r"(a) : "memory");
    return v;
}
__device__ __forceinline__ void sts32(uint32_t a, uint32_t v) {
    asm volatile("st.shared.b32 [%0], %1;" :: "r"(a), "r"(v) : "memory");
}
__device__ __forceinline__ void stg128(void* p, uint4 v) {
    asm volatile("st.global.v4.b32 [%0], {%1,%2,%3,%4};" :: "l"(p), "r"(v.x), "r"(v.y), "r"(v.z), "r"(v.w) : "memory");
}
__device__ __forceinline__ unsigned pack4(unsigned a, unsigned b, unsigned c, unsigned d) {
    unsigned lo, r;
    asm("cvt.pack.sat.s8.s32.b32 %0, %1, %2, 0;" : "=r"(lo) : "r"(d), "r"(c));
    asm("cvt.pack.sat.s8.s32.b32 %0, %1, %2, %3;" : "=r"(r) : "r"(b), "r"(a), "r"(lo));
    return r;
}
__device__ __forceinline__ void cpasync16(uint32_t dst, const void* src) {
    asm volatile("cp.async.cg.shared.global [%0], [%1], 16;" :: "r"(dst), "l"(src) : "memory");
}
__device__ __forceinline__ unsigned pf_l2(const void* p) {
    unsigned v;
    asm volatile("ld.global.cg.L2::128B.u32 %0, [%1];" : "=r"(v) : "l"(p) : "memory");
    return v;
}

constexpr uint32_t DESC_A_HI = 0x80000000u | (512 >> 4);
constexpr uint32_t DESC_B_HI = 128 >> 4;
template <int NR> __device__ __forceinline__ void wgmma_n160(int (&d)[NR], uint32_t alo, uint32_t blo, int scale_d) {
    asm volatile("{\n.reg .pred p;\n.reg .b64 da, db;\nsetp.ne.b32 p, %82, 0;\n"
        "mov.b64 da, {%80, %83};\nmov.b64 db, {%81, %84};\n"
        "wgmma.mma_async.sync.aligned.m64n160k32.s32.s8.s8 "
        "{%0, %1, %2, %3, %4, %5, %6, %7, %8, %9, %10, %11, %12, %13, %14, %15, "
        "%16, %17, %18, %19, %20, %21, %22, %23, %24, %25, %26, %27, %28, %29, %30, %31, "
        "%32, %33, %34, %35, %36, %37, %38, %39, %40, %41, %42, %43, %44, %45, %46, %47, "
        "%48, %49, %50, %51, %52, %53, %54, %55, %56, %57, %58, %59, %60, %61, %62, %63, "
        "%64, %65, %66, %67, %68, %69, %70, %71, %72, %73, %74, %75, %76, %77, %78, %79}, "
        "da, db, p;\n}\n"
        : "+r"(d[0]), "+r"(d[1]), "+r"(d[2]), "+r"(d[3]), "+r"(d[4]), "+r"(d[5]), "+r"(d[6]), "+r"(d[7]),
          "+r"(d[8]), "+r"(d[9]), "+r"(d[10]), "+r"(d[11]), "+r"(d[12]), "+r"(d[13]), "+r"(d[14]), "+r"(d[15]),
          "+r"(d[16]), "+r"(d[17]), "+r"(d[18]), "+r"(d[19]), "+r"(d[20]), "+r"(d[21]), "+r"(d[22]), "+r"(d[23]),
          "+r"(d[24]), "+r"(d[25]), "+r"(d[26]), "+r"(d[27]), "+r"(d[28]), "+r"(d[29]), "+r"(d[30]), "+r"(d[31]),
          "+r"(d[32]), "+r"(d[33]), "+r"(d[34]), "+r"(d[35]), "+r"(d[36]), "+r"(d[37]), "+r"(d[38]), "+r"(d[39]),
          "+r"(d[40]), "+r"(d[41]), "+r"(d[42]), "+r"(d[43]), "+r"(d[44]), "+r"(d[45]), "+r"(d[46]), "+r"(d[47]),
          "+r"(d[48]), "+r"(d[49]), "+r"(d[50]), "+r"(d[51]), "+r"(d[52]), "+r"(d[53]), "+r"(d[54]), "+r"(d[55]),
          "+r"(d[56]), "+r"(d[57]), "+r"(d[58]), "+r"(d[59]), "+r"(d[60]), "+r"(d[61]), "+r"(d[62]), "+r"(d[63]),
          "+r"(d[64]), "+r"(d[65]), "+r"(d[66]), "+r"(d[67]), "+r"(d[68]), "+r"(d[69]), "+r"(d[70]), "+r"(d[71]),
          "+r"(d[72]), "+r"(d[73]), "+r"(d[74]), "+r"(d[75]), "+r"(d[76]), "+r"(d[77]), "+r"(d[78]), "+r"(d[79])
        : "r"(alo), "r"(blo), "r"(scale_d), "r"(DESC_A_HI), "r"(DESC_B_HI));
}
template <int NR> __device__ __forceinline__ void wgmma_t128(int (&d)[NR], uint32_t alo, uint32_t blo, int scale_d) {
    asm volatile("{\n.reg .pred p;\n.reg .b64 da, db;\nsetp.ne.b32 p, %66, 0;\n"
        "mov.b64 da, {%64, %67};\nmov.b64 db, {%65, %68};\n"
        "wgmma.mma_async.sync.aligned.m64n128k32.s32.s8.s8 "
        "{%0, %1, %2, %3, %4, %5, %6, %7, %8, %9, %10, %11, %12, %13, %14, %15, "
        "%16, %17, %18, %19, %20, %21, %22, %23, %24, %25, %26, %27, %28, %29, %30, %31, "
        "%32, %33, %34, %35, %36, %37, %38, %39, %40, %41, %42, %43, %44, %45, %46, %47, "
        "%48, %49, %50, %51, %52, %53, %54, %55, %56, %57, %58, %59, %60, %61, %62, %63}, "
        "da, db, p;\n}\n"
        : "+r"(d[0]), "+r"(d[1]), "+r"(d[2]), "+r"(d[3]), "+r"(d[4]), "+r"(d[5]), "+r"(d[6]), "+r"(d[7]),
          "+r"(d[8]), "+r"(d[9]), "+r"(d[10]), "+r"(d[11]), "+r"(d[12]), "+r"(d[13]), "+r"(d[14]), "+r"(d[15]),
          "+r"(d[16]), "+r"(d[17]), "+r"(d[18]), "+r"(d[19]), "+r"(d[20]), "+r"(d[21]), "+r"(d[22]), "+r"(d[23]),
          "+r"(d[24]), "+r"(d[25]), "+r"(d[26]), "+r"(d[27]), "+r"(d[28]), "+r"(d[29]), "+r"(d[30]), "+r"(d[31]),
          "+r"(d[32]), "+r"(d[33]), "+r"(d[34]), "+r"(d[35]), "+r"(d[36]), "+r"(d[37]), "+r"(d[38]), "+r"(d[39]),
          "+r"(d[40]), "+r"(d[41]), "+r"(d[42]), "+r"(d[43]), "+r"(d[44]), "+r"(d[45]), "+r"(d[46]), "+r"(d[47]),
          "+r"(d[48]), "+r"(d[49]), "+r"(d[50]), "+r"(d[51]), "+r"(d[52]), "+r"(d[53]), "+r"(d[54]), "+r"(d[55]),
          "+r"(d[56]), "+r"(d[57]), "+r"(d[58]), "+r"(d[59]), "+r"(d[60]), "+r"(d[61]), "+r"(d[62]), "+r"(d[63])
        : "r"(alo), "r"(blo), "r"(scale_d), "r"(DESC_B_HI), "r"(DESC_A_HI));
}

__device__ __forceinline__ void wg_fence() { asm volatile("wgmma.fence.sync.aligned;" ::: "memory"); }
__device__ __forceinline__ void wg_commit() { asm volatile("wgmma.commit_group.sync.aligned;" ::: "memory"); }
template <int N> __device__ __forceinline__ void wg_wait() { asm volatile("wgmma.wait_group.sync.aligned %0;" :: "n"(N) : "memory"); }

struct Job { int src; int dst; };
__host__ __device__ constexpr int unit_of(int piece, int slab) {
    return piece < 2 ? (slab < X1 ? 2 * slab + piece : (piece ? 16 : X1) + slab) : 32 + (piece - 2) * 8 + (slab >> 1);
}
__device__ __forceinline__ Job decode_job(int g) {
    int slab, idx, piece;
    if (g < SEG2) {
        int r;
        if (g < SEG1) { slab = g / (nA + 2 * nWA); r = g - slab * (nA + 2 * nWA); }
        else { g -= SEG1; slab = g / (nA + nWA); r = g - slab * (nA + nWA); slab += X1; }
        piece = r < nA ? -1 : (r < nA + nWA ? 0 : 1);
        idx = r < nA ? r : r - nA - piece * nWA;
    } else if (g < SEG3) {
        g -= SEG2; slab = g / nWA; idx = g - slab * nWA; slab += X1; piece = 1;
    } else {
        g -= SEG3; piece = 2 + (g >> 8); slab = (g >> 4) & 15; idx = g & 15;
        static_assert(nWB == 16, "");
    }
    Job j;
    if (piece < 0) {
        const int flag = (idx >> 2) * 16 + slab;
        j.src = idx * 32 + (slab << 12);
        j.dst = (flag * 512 + (idx & 3) * 128) | (flag << 18);
    } else {
        const bool wide = piece < 2;
        const int w = wide ? WA : WB;
        const int nb = wide ? idx / (WA / 32) : idx / (WB / 32);
        const int J = idx - nb * (w / 32);
        const int cb = nb * TN + (wide ? piece * WA : 2 * WA - 2 * WB + piece * WB);
        j.src = cb + J * 32 + (slab << 12) + (wide ? 1 << 16 : 2 << 16);
        j.dst = (cb * (K_ / 16) + slab * w * 4 + J * 32) | ((256 + nb * 64 + unit_of(piece, slab)) << 18);
    }
    return j;
}
struct Coord { const CUtensorMap* m; int x, y, z; };
__device__ __forceinline__ Coord job_coord(const CUtensorMap* maps, int src) {
    const bool w = src >> 16;
    const int c0 = src & 0xFFF, slab = (src >> 12) & 15;
    return {maps + (w ? 1 : 0), w ? c0 : 0, w ? slab * 64 : slab * 2, w ? 0 : c0};
}
__device__ __forceinline__ void raw_load(const Coord& c, uint32_t dst, uint32_t bar) {
    mbar_expect_tx(bar, 8192);
    asm volatile("cp.async.bulk.tensor.3d.shared::cluster.global.tile.mbarrier::complete_tx::bytes [%0], [%1, {%2, %3, %4}], [%5];"
                 :: "r"(dst), "l"(c.m), "r"(c.x), "r"(c.y), "r"(c.z), "r"(bar) : "memory");
}
__device__ __forceinline__ void raw_prefetch(const Coord& c) {
    asm volatile("cp.async.bulk.prefetch.tensor.3d.L2.global.tile [%0, {%1, %2, %3}];"
                 :: "l"(c.m), "r"(c.x), "r"(c.y), "r"(c.z) : "memory");
}
__host__ __device__ constexpr unsigned unit_mask(int piece, int s0, int s1) {
    unsigned m = 0;
    for (int s = s0; s < s1; s++) m |= 1u << (unit_of(piece, s) & 31);
    return m;
}
__host__ __device__ constexpr int slot_of(int u) {
    return u < UX ? (u % NSLOT) * (SLOT / 2048) : u < UX + NSTG ? NSLOT * (SLOT / 2048) + (u - UX) * 4 : ((u - NSTG) % NSLOT) * (SLOT / 2048);
}
__host__ __device__ constexpr uint64_t slot_table(int piece) {
    uint64_t t = 0;
    if (piece < 2) for (int s = 0; s < 16; s++) t |= (uint64_t)(unit_of(piece, s) % NSLOT) << (4 * s);
    else for (int s = 0; s < 8; s++) t |= (uint64_t)slot_of(unit_of(piece, 2 * s)) << (8 * s);
    return t;
}
struct Maps { CUtensorMap m[3]; };

__device__ __forceinline__ uint32_t bf2_op_epi(int a, int b, uint32_t zc, uint32_t sx, uint32_t sw, uint32_t bi) {
    uint32_t v;
    float fa = __int2float_rn(a), fb = __int2float_rn(b);
    asm("cvt.rn.bf16x2.f32 %0, %1, %2;" : "=r"(v) : "f"(fb), "f"(fa));
    asm("sub.rn.bf16x2 %0, %0, %1;" : "+r"(v) : "r"(zc));
    asm("mul.rn.bf16x2 %0, %0, %1;" : "+r"(v) : "r"(sx));
    asm("mul.rn.bf16x2 %0, %0, %1;" : "+r"(v) : "r"(sw));
    asm("add.rn.bf16x2 %0, %0, %1;" : "+r"(v) : "r"(bi));
    return v;
}

struct Par { uint4 zc, sw, bi; };
__device__ __forceinline__ Par ld_par(uint32_t p) { return {lds128(p), lds128(p + TN * 2), lds128(p + TN * 4)}; }
__device__ __forceinline__ void epi_row(const int (&a)[WA / 2], int o, const Par& p, uint32_t sx2, char* out) {
    uint4 r;
    r.x = bf2_op_epi(a[o + 0], a[o + 4], p.zc.x, sx2, p.sw.x, p.bi.x);
    r.y = bf2_op_epi(a[o + 8], a[o + 12], p.zc.y, sx2, p.sw.y, p.bi.y);
    r.z = bf2_op_epi(a[o + 1], a[o + 5], p.zc.z, sx2, p.sw.z, p.bi.z);
    r.w = bf2_op_epi(a[o + 9], a[o + 13], p.zc.w, sx2, p.sw.w, p.bi.w);
    stg128(out, r);
}
template <int J, int JN>
__device__ __forceinline__ void epilogue(const int (&a)[WA / 2], Par& p, uint32_t par, uint32_t sx2, char* out) {
    epi_row(a, J * 16, p, sx2, out + J * 64);
    Par n = p;
    if (JN != J) n = ld_par(par + JN * 64);
    epi_row(a, J * 16 + 2, p, sx2, out + 8 * (N_ * 2) + J * 64);
    p = n;
}

__global__ void __cluster_dims__(2, 1, 1) __launch_bounds__(512, 1)
w8a8_kernel(const __grid_constant__ Maps maps, const char* __restrict__ qx, const char* __restrict__ qw, const __nv_bfloat16* __restrict__ scale_x, const int* __restrict__ zero_x,
            const __nv_bfloat16* __restrict__ scale_w, const __nv_bfloat16* __restrict__ bias,
            __nv_bfloat16* __restrict__ out) {
    extern __shared__ __align__(1024) unsigned char smem_raw[];
    const uint32_t sb = (uint32_t)__cvta_generic_to_shared(smem_raw);
    const uint32_t bars = sb + SM_BAR;
    const int warp = __shfl_sync(~0u, threadIdx.x >> 5, 0), lane = threadIdx.x & 31;
    const int b = blockIdx.x, rank = b & 1, nb = (b >> 1) & 7, mb = (b >> 4) * 2 + rank;

    if (warp >= 8) {
        asm volatile("setmaxnreg.dec.sync.aligned.u32 56;");
        if (warp >= 16 - NCONV) {
            const int cw = warp - (16 - NCONV);
            unsigned t0;
            asm volatile("mov.u32 %0, %clock;" : "=r"(t0));
            t0 += 100;
            asm volatile("barrier.cluster.arrive.relaxed.aligned;" ::: "memory");
            const Job mj = decode_job(min(lane, NJOB - 1) * NCTA + b);
            static_assert(NCONV == NSTG + 2 && NJOB == 22, "");
            const uint32_t s = sb + (cw < NSTG ? SM_STG + cw * 8192 : SM_A + (14 - NSTG + cw) * 8192);
            const uint32_t sbar = bars + (B_FULLS + cw) * 8;
            {
                const Coord c = job_coord(maps.m, __shfl_sync(~0u, mj.src, cw));
                if (elect_one()) {
                    mbar_init(sbar, 1);
                    asm volatile("fence.mbarrier_init.release.cluster;" ::: "memory");
                    unsigned t;
                    do { asm volatile("mov.u32 %0, %clock;" : "=r"(t)); } while ((int)(t - t0) < cw * PFD + (cw ? b * 88 : b * 0) / 16);
                    raw_load(c, s, sbar);
                }
                __syncwarp();
            }
            asm volatile("barrier.cluster.wait.aligned;" ::: "memory");
            t0 += b * 88 / 16;
            const int c4 = lane & 3, ln = (lane >> 2) * 2 + (c4 >> 1);
            const uint32_t rdA = ln * 128 + ((((c4 & 1) << 2) ^ (ln & 7)) << 4);
            const uint32_t rdB = (lane >> 3) * 2048 + (lane & 7) * 16;
            const int wrA = (lane >> 2) * 4 + (c4 ^ ((lane >> 3) & 3));
            uint32_t par = 0;
#pragma unroll 1
            for (int j = cw, jn; j < NJOB; j = jn, par ^= 1) {
                jn = j < 13 ? j + NCONV : (j < 15 ? 31 : j + NSTG);
                const int src = __shfl_sync(~0u, mj.src, j), dst = __shfl_sync(~0u, mj.dst, j);
                const int nsrc = __shfl_sync(~0u, mj.src, jn);
                const int kind = src >> 16;
                uint4 o[4];
                uint4* d;
                int dstep;
                mbar_wait(sbar, par);
                if (kind == 0) {
                    const uint32_t a0 = s + rdA;
                    d = g_a8 + (dst & 0x3FFFF) + wrA;
                    dstep = 32;
#pragma unroll
                    for (int i = 0; i < 4; i++) {
                        uint4 v0 = lds128(a0 + i * 2048), v1 = lds128((a0 ^ 16) + i * 2048);
                        uint4 v2 = lds128((a0 ^ 32) + i * 2048), v3 = lds128((a0 ^ 48) + i * 2048);
                        o[i].x = pack4(v0.x, v0.y, v0.z, v0.w); o[i].y = pack4(v1.x, v1.y, v1.z, v1.w);
                        o[i].z = pack4(v2.x, v2.y, v2.z, v2.w); o[i].w = pack4(v3.x, v3.y, v3.z, v3.w);
                    }
                } else {
                    const uint32_t a0 = s + rdB;
                    d = g_b8 + (dst & 0x3FFFF) + (lane >> 3) * (kind == 1 ? WA : WB) + (lane & 7);
                    dstep = 8;
#define CV_B(m, f)                                                                                    \
                    {                                                                                 \
                        uint4 v0 = lds128(a0 + m * 512), v1 = lds128(a0 + m * 512 + 128);             \
                        uint4 v2 = lds128(a0 + m * 512 + 256), v3 = lds128(a0 + m * 512 + 384);       \
                        o[0].f = pack4(v0.x, v1.x, v2.x, v3.x); o[1].f = pack4(v0.y, v1.y, v2.y, v3.y); \
                        o[2].f = pack4(v0.z, v1.z, v2.z, v3.z); o[3].f = pack4(v0.w, v1.w, v2.w, v3.w); \
                    }
                    CV_B(0, x) CV_B(1, y) CV_B(2, z) CV_B(3, w)
                }
#pragma unroll
                for (int i = 0; i < 4; i++) stg128(d + i * dstep, o[i]);
                unsigned tn;
                asm volatile("mov.u32 %0, %clock;" : "=r"(tn));
                const bool late = jn < NJOB && (int)(tn - t0) < jn * PFD;
                if (!late && elect_one()) {
                    if (jn < NJOB) { raw_load(job_coord(maps.m, nsrc), s, sbar); }
                    else if (jn == 31) mbar_arrive(bars + (B_AFREE - NSTG + cw) * 8);
                    else if (0 != 1) {
                        uint32_t ra;
                        asm("mapa.shared::cluster.u32 %0, %1, %2;" : "=r"(ra) : "r"(bars + (B_GO + ((UX + cw) >> 1)) * 8), "r"((UX + cw) & 1));
                        mbar_arrive_cluster(ra);
                    }
                }
                const int* csp = (const int*)d;
                unsigned csv = o[0].x;
                if (kind != 0) {
                    int cs[4];
#pragma unroll
                    for (int i = 0; i < 4; i++)
                        cs[i] = __dp4a((int)o[i].x, 0x01010101, __dp4a((int)o[i].y, 0x01010101,
                                __dp4a((int)o[i].z, 0x01010101, __dp4a((int)o[i].w, 0x01010101, 0))));
                    const int p01 = cs[0] + cs[1] * 65536, p23 = cs[2] + cs[3] * 65536;
                    const bool odd = lane & 8;
                    int v = (odd ? p23 : p01) + __shfl_xor_sync(~0u, odd ? p01 : p23, 8);
                    v += __shfl_xor_sync(~0u, v, 16);
                    int* p = (int*)g_cs + ((src >> 12) & 15) * (N_ / 2) + ((src & 0xFFF) >> 1) + (lane & 15);
                    if (lane < 16) *p = v;
                    csp = p; csv = v;
                }
#pragma unroll 1
                for (int it = 0; it < 1000; it++) {
                    bool ok = true;
                    if ((lane & 3) == 0) {
                        unsigned rb[5];
#pragma unroll
                        for (int i = 0; i < 4; i++)
                            asm volatile("ld.relaxed.gpu.global.u32 %0, [%1];" : "=r"(rb[i]) : "l"(d + i * dstep) : "memory");
                        asm volatile("ld.relaxed.gpu.global.u32 %0, [%1];" : "=r"(rb[4]) : "l"(csp) : "memory");
                        ok = rb[0] == o[0].x && rb[1] == o[1].x && rb[2] == o[2].x && rb[3] == o[3].x && rb[4] == csv;
                    }
                    if (__all_sync(~0u, ok)) break;
                }
                if (elect_one()) asm volatile("red.relaxed.gpu.global.add.u32 [%0], 1;" :: "l"(g_flag + ((unsigned)dst >> 18)) : "memory");
                __syncwarp();
                if (late && elect_one()) {
                    do { asm volatile("mov.u32 %0, %clock;" : "=r"(tn)); } while ((int)(tn - t0) < jn * PFD);
                    raw_load(job_coord(maps.m, nsrc), s, sbar);
                }
                __syncwarp();
            }
        } else if (warp == 8) {
            asm volatile("barrier.cluster.arrive.relaxed.aligned;" ::: "memory");
            const unsigned ep = *(volatile unsigned*)&g_epoch[b] + 1;
            const unsigned* f1 = g_flag + 256 + nb * 64 + lane;
            const unsigned* f2 = lane < 16 ? f1 + 32 : g_flag + mb * 16 + lane - 16;
            const unsigned t1 = ep * (WA / 32), t2 = ep * 4;
            static_assert(WB / 16 == 4, "");
            const unsigned n1 = lane == 0 ? unit_mask(0, 0, 8) : lane == 1 ? unit_mask(1, 0, 8) : lane == 2 ? unit_mask(0, 8, 16)
                              : lane == 3 ? unit_mask(1, 8, 16) : 0u;
            const unsigned n2 = lane < 4 ? 0u : 0xFFFFu;
            bool d1 = false, d2 = false, d3 = lane >= 5, fr = lane < 30;
            asm volatile("barrier.cluster.wait.aligned;" ::: "memory");
            for (int it = 0; 0 != 1; it++) {
                unsigned v1 = t1, v2 = t2;
                if (!d1) v1 = ld_flag(f1);
                if (!d2) v2 = ld_flag(f2);
                if (!fr) fr = mbar_test(bars + (B_AFREE - 30 + lane) * 8);
                if (!d2 && fr && (int)(v2 - t2) >= 0) {
                    d2 = true;
                    if (lane >= 16) {
                        asm volatile("fence.proxy.async.global;" ::: "memory");
                        asm volatile("cp.async.bulk.shared::cluster.global.mbarrier::complete_tx::bytes [%0], [%1], %2, [%3];"
                                     :: "r"(sb + SM_A + (lane - 16) * 8192), "l"((const char*)g_a8 + (mb * 16 + lane - 16) * 8192),
                                        "r"(8192), "r"(bars + (B_FULLA + lane - 16) * 8) : "memory");
                    } else if ((lane & 1) == rank) mbar_arrive(bars + (B_GO + 16 + (lane >> 1)) * 8);
                }
                if (!d1 && (int)(v1 - t1) >= 0) {
                    d1 = true;
                    if ((lane & 1) == rank) mbar_arrive(bars + (B_GO + (lane >> 1)) * 8);
                }
                const unsigned m1 = __ballot_sync(~0u, d1), m2 = __ballot_sync(~0u, d2);
                if (!d3 && (m1 & n1) == n1 && (m2 & n2) == n2) { d3 = true; mbar_arrive(bars + (B_PSTEP + lane) * 8); }
                if ((m1 & m2) == ~0u) break;
                if (it > (1 << 22)) __trap();
            }
        } else if (warp == 9) {
            asm volatile("barrier.cluster.arrive.relaxed.aligned;" ::: "memory");
            const int u = 2 * lane + rank;
            int so, fb;
            if (u < 2 * X1) { so = (u & 1) * (WA * K_) + (u >> 1) * (WA * 64); fb = (u & 1) * 24 + (u >> 1); }
            else if (u < X1 + 16) { so = (u - X1) * (WA * 64); fb = u - X1; }
            else if (u < 32) { so = WA * K_ + (u - 16) * (WA * 64); fb = 24 + u - 16; }
            else { so = 2 * WA * K_ + (u - 32) * (WB * 128); fb = u < 40 ? u - 16 : u; }
            const char* srcB = (const char*)g_b8 + nb * TN * K_ + so;
            const uint32_t dstB = sb + SM_RING + slot_of(u) * 2048;
            asm volatile("barrier.cluster.wait.aligned;" ::: "memory");
#pragma unroll 1
            for (int i = 0; i < NU / 2 && 0 != 1; i++) {
                mbar_wait(bars + (B_GO + i) * 8);
                if (lane == i) {
                    asm volatile("fence.proxy.async.global;" ::: "memory");
                    asm volatile("cp.async.bulk.shared::cluster.global.mbarrier::complete_tx::bytes.multicast::cluster [%0], [%1], %2, [%3], %4;"
                                 :: "r"(dstB), "l"(srcB), "r"(u < 32 ? WA * 64 : WB * 128), "r"(bars + (B_FULLB + fb) * 8), "h"((uint16_t)3) : "memory");
                }
                __syncwarp();
            }
        } else if (warp == 10) {
            unsigned pv, pv2;
            {
                static_assert(X1 > 0 && nA == 64 && nWA == 40, "");
                const int i = b - (b < 104 ? 64 : 104), q = i / 5;
                const char* p = b < 64 ? qx + (b * 32 + (lane >> 1)) * (K_ * 4) + (lane & 1) * 128
                                       : qw + lane * (N_ * 4) + (q * TN + (b < 104 ? 0 : WA) + (i - q * 5) * 32) * 4;
                pv = pf_l2(p);
                pv2 = pf_l2(p + (b < 64 ? 16 * K_ * 4 : 32 * N_ * 4));
                if (lane < 3) asm volatile("prefetch.tensormap [%0];" :: "l"(maps.m + lane) : "memory");
            }
            asm volatile("barrier.cluster.arrive.relaxed.aligned;" ::: "memory");
            if ((pv ^ pv2) == 0x40000000u) g_sink = pv;
            const float zxf = __bfloat162float(__float2bfloat16_rn((float)__ldg(zero_x)));
#pragma unroll 1
            for (int i = lane; i < TN / 4; i += 32) {
                const bool hi = i >= TN / 8;
                sts128(sb + SM_PAR + TN * 2 + i * 16, __ldg((const uint4*)((hi ? bias : scale_w) + nb * TN) + (hi ? i - TN / 8 : i)));
            }
            asm volatile("barrier.cluster.wait.aligned;" ::: "memory");
            int c[8], cs[8];
#pragma unroll
            for (int i = 0; i < 8; i++) { c[i] = 0; cs[i] = 0; }
#pragma unroll 1
            for (int st = 0; st < 5 && 0 != 1; st++) {
                const bool wide = st < 4;
                const int half = wide ? (st >> 1) : (lane >> 4);
                const int col = wide ? (st & 1) * WA + min(lane, WA / 8 - 1) * 8 : 2 * WA + (lane & 15) * 8;
                const uint4* src = g_cs + (half * 8 * N_ + nb * TN + col) / 8;
                mbar_wait(bars + (B_PSTEP + st) * 8);
                uint4 v[8];
#pragma unroll
                for (int i = 0; i < 8; i++) v[i] = __ldcg(src + i * (N_ / 8));
#pragma unroll
                for (int h = 0; h < 8; h += 4) {
                    const unsigned sv[4] = {v[h].x + v[h + 1].x + v[h + 2].x + v[h + 3].x, v[h].y + v[h + 1].y + v[h + 2].y + v[h + 3].y,
                                            v[h].z + v[h + 1].z + v[h + 2].z + v[h + 3].z, v[h].w + v[h + 1].w + v[h + 2].w + v[h + 3].w};
#pragma unroll
                    for (int i = 0; i < 4; i++) {
                        const int lo = (int)(short)(sv[i] & 0xFFFF);
                        c[2 * i] += lo; c[2 * i + 1] += ((int)(sv[i] - (unsigned)lo)) >> 16;
                    }
                }
                if (st >= 2) {
                    uint32_t z[4];
#pragma unroll
                    for (int i = 0; i < 8; i++) {
                        const int o = __shfl_xor_sync(~0u, c[i], 16);
                        if (!wide) c[i] += o;
                    }
#pragma unroll
                    for (int i = 0; i < 4; i++) {
                        const float lo = __bfloat162float(__float2bfloat16_rn((float)c[2 * i])) * zxf;
                        const float hi = __bfloat162float(__float2bfloat16_rn((float)c[2 * i + 1])) * zxf;
                        asm("cvt.rn.bf16x2.f32 %0, %1, %2;" : "=r"(z[i]) : "f"(hi), "f"(lo));
                    }
                    const uint32_t za = sb + SM_PAR + ((col & ~31) + (col & 8) * 2 + ((col >> 3) & 2)) * 2;
#pragma unroll
                    for (int i = 0; i < 4; i++) sts32(za + i * 8, z[i]);
                    __syncwarp();
                    if (lane == 0) { mbar_arrive(bars + (B_PAR + st - 2) * 8); }
#pragma unroll
                    for (int i = 0; i < 8; i++) c[i] = 0;
                }
#pragma unroll
                for (int i = 0; i < 8; i++) { const int t = c[i]; c[i] = cs[i]; cs[i] = t; }
            }
        } else {
            asm volatile("barrier.cluster.arrive.relaxed.aligned;" ::: "memory");
            asm volatile("barrier.cluster.wait.aligned;" ::: "memory");
        }
    } else {
        asm volatile("setmaxnreg.inc.sync.aligned.u32 200;");
        {
            constexpr int PER = (B_NINIT + 7) / 8;
            if (elect_one()) {
#pragma unroll 1
                for (int i = warp * PER; i < min(warp * PER + PER, B_NINIT); i++)
                    {
                    const int u = 2 * (i - B_GO) + rank;
                    mbar_init(bars + i * 8, (i < B_GO || i >= B_PAR || u < NSLOT) ? 1 : (u >= UX && u < UX + NSTG) ? 3 : 9);
                }
            }
            __syncwarp();
            const int i = warp * PER + lane;
            if (lane < PER && i < B_GO) mbar_expect_tx(bars + i * 8, (i < 16 || (i >= 24 && i < 40)) ? WA * 64 : 8192);
            static_assert(WB * 128 == 8192, "");
            asm volatile("fence.mbarrier_init.release.cluster;" ::: "memory");
        }
        asm volatile("barrier.cluster.arrive.relaxed.aligned;" ::: "memory");
        const int wg = warp >> 2;
        const uint32_t sd = (sb & 0x3FFFF) >> 4;
        const unsigned short sxr = __ldg((const unsigned short*)scale_x);
        const uint32_t sx2 = (uint32_t)sxr * 0x10001u;
        char* orow = (char*)out + (size_t)(mb * 128 + (warp & 3) * 16 + (lane >> 2)) * (N_ * 2) + (nb * TN + (lane & 3) * 8 + wg * WA) * 2;
        const uint32_t par = sb + SM_PAR + (lane & 3) * 16 + wg * WA * 2;
        uint32_t reladdr;
        int rell;
        {
            const int u = lane < 16 ? (lane < X1 ? 2 * lane + wg : (wg ? 16 : X1) + lane) : 16 + wg * 8 + lane;
            const int v = u + (u < 32 ? NSLOT : NSLOT + NSTG);
            rell = (lane < 24 && v < NU) ? lane : 99;
            asm("mapa.shared::cluster.u32 %0, %1, %2;" : "=r"(reladdr) : "r"(bars + (B_GO + (v >> 1)) * 8), "r"(v & 1));
        }
        asm volatile("barrier.cluster.wait.aligned;" ::: "memory");
        int a0[WA / 2], a1[WA / 2];
        uint32_t barB = bars + (B_FULLB + wg * 24) * 8;
        bool ready = false;
#define HAND_BACK(done) if (rell <= (done)) { mbar_arrive_cluster(reladdr); rell = 99; }
        if (0 != 1) {
            wg_fence();
            {
                uint64_t tbl = wg ? slot_table(1) : slot_table(0);
                uint32_t da = (sd + (SM_A >> 4)) | (1 << 16);
#pragma unroll 1
                for (int s = 0; s < 16; s++) {
                    const uint32_t db = ((sd + (SM_RING >> 4)) | (WA << 16)) + ((uint32_t)tbl & 15) * (SLOT >> 4);
                    const bool starved = !ready && !mbar_test2(bars + (B_FULLA + s) * 8, barB);
                    if (starved) {
                        wg_wait<0>();
                        HAND_BACK(s - 1)
                        mbar_wait2(bars + (B_FULLA + s) * 8, barB);
                    }
                    wgmma_n160(a0, da, db, s);
                    wgmma_n160(a1, da + 256, db, s);
                    wgmma_n160(a0, da + 2, db + 2 * WA, 1);
                    wgmma_n160(a1, da + 258, db + 2 * WA, 1);
                    wg_commit();
                    HAND_BACK(s - 2)
                    tbl >>= 4; da += 512; barB += 8;
                    ready = mbar_test2(bars + (B_FULLA + min(s + 1, 15)) * 8, barB);
                    wg_wait<1>();
                }
            }
            HAND_BACK(14)
            wg_wait<0>();
            HAND_BACK(15)
            mbar_wait(bars + (B_PAR + wg) * 8);
            Par P = ld_par(par);
            char* const orow1 = orow + 64 * (N_ * 2);
            epilogue<0, 1>(a0, P, par, sx2, orow); epilogue<1, 2>(a0, P, par, sx2, orow);
            epilogue<2, 3>(a0, P, par, sx2, orow); epilogue<3, 0>(a0, P, par, sx2, orow);
            int t[64];
            wg_fence();
            {
                uint64_t tbl = wg ? slot_table(3) : slot_table(2);
                uint32_t da = (sd + (SM_A >> 4)) | (1 << 16);
#pragma unroll
                for (int i = 16; i < 24; i++) {
                    const uint32_t db = ((sd + (SM_RING >> 4)) | (WB << 16)) + ((uint32_t)tbl & 255) * 128;
                    const bool starved = !ready && !mbar_test(barB);
                    if (starved) {
                        wg_wait<0>();
                        HAND_BACK(i - 1)
                        mbar_wait(barB);
                    }
#pragma unroll
                    for (int k = 0; k < 4; k++) wgmma_t128(t, db + k * 2 * WB, da + (k >> 1) * 512 + (k & 1) * 2, k ? 1 : i - 16);
                    wg_commit();
                    HAND_BACK(i - 2)
                    tbl >>= 8; da += 1024; barB += 8;
                    ready = mbar_test(barB);
                    switch (i) {
                        case 16: epilogue<0, 0>(a1, P, par, sx2, orow1); break;
                        case 17: epilogue<1, 1>(a1, P, par, sx2, orow1); break;
                        case 18: epilogue<2, 2>(a1, P, par, sx2, orow1); break;
                        case 19: epilogue<3, 3>(a1, P, par, sx2, orow1); break;
                        case 20: epilogue<4, 4>(a1, P, par, sx2, orow1); break;
                        case 21: epilogue<4, 4>(a0, P, par, sx2, orow); break;
                        default: break;
                    }
                    if (i < 20) P = ld_par(par + (i - 15) * 64);
                    wg_wait<1>();
                }
            }
            HAND_BACK(22)
            mbar_wait(bars + (B_PAR + 2) * 8);
            const int w = warp & 3, q = lane >> 2, c0 = (w >> 1) * 32 + q * 4 + (w & 1) * 2;
            const uint32_t pp = sb + SM_PAR + (2 * WA + wg * WB + c0) * 2;
            const uint32_t zc = lds32(pp), sw = lds32(pp + TN * 2), bi = lds32(pp + TN * 4);
            const int r0 = (lane & 3) * 2;
            const uint32_t st0 = r0 * 128 + (((c0 >> 3) ^ r0) << 4) + (c0 & 7) * 2, st1 = (st0 ^ 16) + 128;
            wg_wait<0>();
            asm volatile("bar.sync %0, 128;" :: "r"(3 + wg) : "memory");
#pragma unroll
            for (int h = 0; h < 2; h++) {
                const uint32_t buf = sb + SM_RING + (wg ? slot_of(UX + 1 + h) : slot_of(UX - 1 + h)) * 2048;
#pragma unroll
                for (int j = 0; j < 8; j++) {
                    const int o = h * 32 + j * 4;
                    sts32(buf + st0 + j * 1024, bf2_op_epi(t[o], t[o + 2], zc, sx2, sw, bi));
                    sts32(buf + st1 + j * 1024, bf2_op_epi(t[o + 1], t[o + 3], zc, sx2, sw, bi));
                }
                asm volatile("fence.proxy.async.shared::cta;" ::: "memory");
                asm volatile("bar.sync %0, 128;" :: "r"(3 + wg) : "memory");
                if (w == 0 && elect_one())
                    asm volatile("cp.async.bulk.tensor.2d.global.shared::cta.tile.bulk_group [%0, {%1, %2}], [%3];"
                                 :: "l"(maps.m + 2), "r"(nb * TN + 2 * WA + wg * WB), "r"(mb * 128 + h * 64), "r"(buf) : "memory");
            }
            if (w == 0) {
                asm volatile("cp.async.bulk.commit_group;" ::: "memory");
                asm volatile("cp.async.bulk.wait_group.read 0;" ::: "memory");
            }
        }
        if (threadIdx.x == 128) asm volatile("red.relaxed.gpu.global.add.u32 [%0], 1;" :: "l"(g_epoch + b) : "memory");
    }
}

static void launch(EncodeFn encode, void* const* d_in, void* d_out) {
    Maps maps;
    CUtensorMap &mx = maps.m[0], &mw = maps.m[1];
    {
        const cuuint64_t dim[3] = {32, K_ / 32, M_}, str[2] = {128, K_ * 4};
        const cuuint32_t box[3] = {32, 2, 32}, es[3] = {1, 1, 1};
        encode(&mx, CU_TENSOR_MAP_DATA_TYPE_INT32, 3, d_in[0], dim, str, box, es, CU_TENSOR_MAP_INTERLEAVE_NONE,
               CU_TENSOR_MAP_SWIZZLE_128B, CU_TENSOR_MAP_L2_PROMOTION_NONE, CU_TENSOR_MAP_FLOAT_OOB_FILL_NONE);
    }
    {
        const cuuint64_t dim[3] = {N_, K_, 1}, str[2] = {N_ * 4, (cuuint64_t)N_ * K_ * 4};
        const cuuint32_t box[3] = {32, 64, 1}, es[3] = {1, 1, 1};
        encode(&mw, CU_TENSOR_MAP_DATA_TYPE_INT32, 3, d_in[1], dim, str, box, es, CU_TENSOR_MAP_INTERLEAVE_NONE,
               CU_TENSOR_MAP_SWIZZLE_NONE, CU_TENSOR_MAP_L2_PROMOTION_NONE, CU_TENSOR_MAP_FLOAT_OOB_FILL_NONE);
    }
    {
        const cuuint64_t dim[2] = {N_, M_}, str[1] = {N_ * 2};
        const cuuint32_t box[2] = {WB, 64}, es[2] = {1, 1};
        encode(&maps.m[2], CU_TENSOR_MAP_DATA_TYPE_BFLOAT16, 2, d_out, dim, str, box, es, CU_TENSOR_MAP_INTERLEAVE_NONE,
               CU_TENSOR_MAP_SWIZZLE_128B, CU_TENSOR_MAP_L2_PROMOTION_NONE, CU_TENSOR_MAP_FLOAT_OOB_FILL_NONE);
    }
    w8a8_kernel<<<NCTA, 512, SM_ALLOC>>>(maps, (const char*)d_in[0], (const char*)d_in[1], (const __nv_bfloat16*)d_in[2], (const int*)d_in[3],
                                         (const __nv_bfloat16*)d_in[4], (const __nv_bfloat16*)d_in[5],
                                         (__nv_bfloat16*)d_out);
}

}

extern "C" void kernel_launch(void* const* d_in, const int* in_sizes, int n_in, void* d_out, int out_size) {
    using namespace ra;
    static EncodeFn encode = nullptr;
    static Scratch* scr = nullptr;
    static const JobTable* jobs = nullptr;
    static bool fits = false;
    if (!encode) {
        void* fn = nullptr;
        cudaDriverEntryPointQueryResult qr;
        cudaGetDriverEntryPoint("cuTensorMapEncodeTiled", &fn, cudaEnableDefault, &qr);
        encode = (EncodeFn)fn;
        cudaGetSymbolAddress((void**)&scr, g_scratch);
        cudaGetSymbolAddress((void**)&jobs, g_jobs);
        cudaFuncSetAttribute(w8a8_kernel, cudaFuncAttributeMaxDynamicSharedMemorySize, SM_ALLOC);
        cudaFuncSetAttribute(w8a8_kernel, cudaFuncAttributeNonPortableClusterSizeAllowed, 1);
        cudaFuncSetAttribute(w8a8_side, cudaFuncAttributeMaxDynamicSharedMemorySize, SM_ALLOC);
        cudaFuncSetAttribute(w8::w8a8_kernel, cudaFuncAttributeMaxDynamicSharedMemorySize, w8::SM_ALLOC);
        cudaLaunchConfig_t oc = {};
        oc.gridDim = dim3(NCTA); oc.blockDim = dim3(512); oc.dynamicSmemBytes = SM_ALLOC;
        cudaLaunchAttribute oa[1];
        oa[0].id = cudaLaunchAttributeClusterDimension; oa[0].val.clusterDim.x = CS; oa[0].val.clusterDim.y = 1; oa[0].val.clusterDim.z = 1;
        oc.attrs = oa; oc.numAttrs = 1;
        int nc = 0, dev = 0, sms = 0;
        cudaGetDevice(&dev);
        cudaDeviceGetAttribute(&sms, cudaDevAttrMultiProcessorCount, dev);
        fits = cudaOccupancyMaxActiveClusters(&nc, w8a8_kernel, &oc) == cudaSuccess && nc >= NCTA / CS && sms >= NCTA + NSIDE;
        cudaGetLastError();
    }
    if (!fits) { w8::launch(encode, d_in, d_out); return; }
    CUtensorMap map;
    {
        const cuuint64_t dim[2] = {N_, M_}, str[1] = {N_ * 2};
        const cuuint32_t box[2] = {64, 32}, es[2] = {1, 1};
        encode(&map, CU_TENSOR_MAP_DATA_TYPE_BFLOAT16, 2, d_out, dim, str, box, es, CU_TENSOR_MAP_INTERLEAVE_NONE,
               CU_TENSOR_MAP_SWIZZLE_128B, CU_TENSOR_MAP_L2_PROMOTION_NONE, CU_TENSOR_MAP_FLOAT_OOB_FILL_NONE);
    }
    w8a8_kernel<<<NCTA, 512, SM_ALLOC, cudaStreamPerThread>>>((const char*)d_in[0], (const char*)d_in[1], scr, jobs, (const __nv_bfloat16*)d_in[4],
                                                             (const __nv_bfloat16*)d_in[5], (const __nv_bfloat16*)d_in[2], (const int*)d_in[3], map);
    cudaLaunchConfig_t cfg = {};
    cfg.gridDim = dim3(NSIDE); cfg.blockDim = dim3(512); cfg.dynamicSmemBytes = SM_ALLOC; cfg.stream = cudaStreamPerThread;
    cudaLaunchAttribute at[1];
    at[0].id = cudaLaunchAttributeProgrammaticStreamSerialization; at[0].val.programmaticStreamSerializationAllowed = 1;
    cfg.attrs = at; cfg.numAttrs = 1;
    cudaLaunchKernelEx(&cfg, w8a8_side, (const char*)d_in[1], scr, (const __nv_bfloat16*)d_in[4], (const __nv_bfloat16*)d_in[5], (const __nv_bfloat16*)d_in[2],
                       (const int*)d_in[3], map);
}
```

```cpp
#include <cuda_runtime.h>
#include <cuda.h>
#include <cuda_bf16.h>
#include <stdint.h>

namespace ra {

constexpr int CFG_D = 2;
constexpr int CFG_P0 = 615;
constexpr int CFG_PF0 = -270;
constexpr int CFG_SLEEP = 400;
constexpr int CFG_NINIT = 2;
constexpr int CFG_NR = 10;
constexpr int CFG_PZ = 16;
constexpr int CFG_NOC = 12;
constexpr int CFG_YP = 1100;
constexpr int CFG_YH = 1000;
constexpr int CFG_YH0 = 1700;
constexpr int CFG_Y0 = 1000;
constexpr int CFG_IDL = 300;
constexpr int CFG_NG0 = 9;

constexpr int M_ = 2048, K_ = 1024, N_ = 3584;
constexpr int CS = 16, NCTA = 112, NSIDE = 20, TN = 448;
constexpr int NRING = CFG_NR, NCONV = 6, NJOB = 26, NG = 56, NOUT = 4, D_ = CFG_D;

constexpr int SM_A = 0;
constexpr int SM_RING = 131072;
constexpr int SM_OUT = SM_RING + NRING * 8192;
constexpr int SM_PAR = SM_OUT + NOUT * 4096;
constexpr int SM_SUM = SM_PAR + 1024;
constexpr int SM_BAR = SM_SUM + 256;
constexpr int B_FULL = 0, B_PAR = 64, B_AFREE = 72, B_TURN = 74, B_OFREE = 76, B_SUM = 108, B_GO = 112, B_OFULL = 144, B_END = 148;
constexpr int SM_TOTAL = SM_BAR + B_END * 8;

constexpr int FS = 32;
struct __align__(2048) Scratch {
    uint4 a8[M_ * K_ / 16];
    uint4 b8[N_ * K_ / 16];
    unsigned cs[32 * TN / 2];
    unsigned flag[CS * FS + 64];
    unsigned epoch[NCTA + NSIDE];
};
__device__ Scratch g_scratch;
constexpr int SM_ALLOC = SM_TOTAL;
static_assert(SM_ALLOC <= 232448, "");

__device__ __forceinline__ void mbar_init(uint32_t bar, uint32_t cnt) {
    asm volatile("mbarrier.init.shared::cta.b64 [%0], %1;" :: "r"(bar), "r"(cnt) : "memory");
}
__device__ __forceinline__ void mbar_expect_tx(uint32_t bar, uint32_t bytes) {
    asm volatile("mbarrier.arrive.expect_tx.shared::cta.b64 _, [%0], %1;" :: "r"(bar), "r"(bytes) : "memory");
}
__device__ __forceinline__ void mbar_arrive(uint32_t bar) {
    asm volatile("mbarrier.arrive.shared::cta.b64 _, [%0];" :: "r"(bar) : "memory");
}
__device__ __forceinline__ void mbar_arrive_cluster_if(uint32_t bar, int a, int b) {
    asm volatile("{\n.reg .pred p;\nsetp.eq.s32 p, %1, %2;\n@p mbarrier.arrive.shared::cluster.b64 _, [%0];\n}" :: "r"(bar), "r"(a), "r"(b) : "memory");
}
__device__ __forceinline__ void mbar_wait(uint32_t bar) {
    asm volatile("{\n.reg .pred p;\nWAIT_LOOP:\nmbarrier.try_wait.parity.shared::cta.b64 p, [%0], 0;\n@!p bra WAIT_LOOP;\n}" :: "r"(bar) : "memory");
}
__device__ __forceinline__ void mbar_wait_cluster(uint32_t bar) {
    asm volatile("{\n.reg .pred p;\nWAIT_LOOP:\nmbarrier.try_wait.parity.relaxed.cluster.shared::cta.b64 p, [%0], 0;\n@!p bra WAIT_LOOP;\n"
                 "fence.acquire.sync_restrict::shared::cluster.cluster;\n}" :: "r"(bar) : "memory");
}
__device__ __forceinline__ void mbar_wait2(uint32_t bar0, uint32_t bar1) { mbar_wait(bar0); mbar_wait(bar1); }
__device__ __forceinline__ bool mbar_test(uint32_t bar) {
    uint32_t ok;
    asm volatile("{\n.reg .pred p;\nmbarrier.test_wait.parity.shared::cta.b64 p, [%1], 0;\nselp.u32 %0, 1, 0, p;\n}" : "=r"(ok) : "r"(bar) : "memory");
    return ok;
}
__device__ __forceinline__ bool mbar_test2(uint32_t bar0, uint32_t bar1) {
    uint32_t ok;
    asm volatile("{\n.reg .pred p, q;\nmbarrier.test_wait.parity.shared::cta.b64 p, [%1], 0;\n"
                 "mbarrier.test_wait.parity.shared::cta.b64 q, [%2], 0;\nand.pred p, p, q;\nselp.u32 %0, 1, 0, p;\n}"
                 : "=r"(ok) : "r"(bar0), "r"(bar1) : "memory");
    return ok;
}
__device__ __forceinline__ bool elect_one() {
    uint32_t ok;
    asm volatile("{\n.reg .pred p;\nelect.sync _|p, 0xffffffff;\nselp.u32 %0, 1, 0, p;\n}" : "=r"(ok));
    return ok;
}
__device__ __forceinline__ uint32_t mapa(uint32_t a, uint32_t cta) {
    uint32_t r;
    asm("mapa.shared::cluster.u32 %0, %1, %2;" : "=r"(r) : "r"(a), "r"(cta));
    return r;
}
__device__ __forceinline__ void st_async32(uint32_t a, uint32_t v, uint32_t bar) {
    asm volatile("st.async.shared::cluster.mbarrier::complete_tx::bytes.b32 [%0], %1, [%2];" :: "r"(a), "r"(v), "r"(bar) : "memory");
}
__device__ __forceinline__ unsigned ld_flag(const unsigned* p) {
    unsigned v;
    asm volatile("ld.relaxed.gpu.global.u32 %0, [%1];" : "=r"(v) : "l"(p) : "memory");
    return v;
}
__device__ __forceinline__ unsigned clk() { unsigned t; asm volatile("mov.u32 %0, %clock;" : "=r"(t)); return t; }
__device__ __forceinline__ uint32_t lds32(uint32_t a) {
    uint32_t v;
    asm volatile("ld.shared.b32 %0, [%1];" : "=r"(v) : "r"(a) : "memory");
    return v;
}
__device__ __forceinline__ void sts32(uint32_t a, uint32_t v) {
    asm volatile("st.shared.b32 [%0], %1;" :: "r"(a), "r"(v) : "memory");
}
__device__ __forceinline__ void stg128(void* p, uint4 v) {
    asm volatile("st.global.v4.b32 [%0], {%1,%2,%3,%4};" :: "l"(p), "r"(v.x), "r"(v.y), "r"(v.z), "r"(v.w) : "memory");
}
__device__ __forceinline__ unsigned pack4(unsigned a, unsigned b, unsigned c, unsigned d) {
    unsigned lo, r;
    asm("cvt.pack.sat.s8.s32.b32 %0, %1, %2, 0;" : "=r"(lo) : "r"(d), "r"(c));
    asm("cvt.pack.sat.s8.s32.b32 %0, %1, %2, %3;" : "=r"(r) : "r"(b), "r"(a), "r"(lo));
    return r;
}
constexpr uint32_t DESC_A_HI = 256 >> 4;
constexpr uint32_t DESC_B_HI = 0x80000000u | (512 >> 4);
__device__ __forceinline__ void mma_unit2(int (&d)[64], int (&e)[64], uint32_t alo, uint32_t blo, int scale_d) {
    asm volatile("{\n.reg .pred p;\n.reg .b64 da, db;\nsetp.ne.b32 p, %130, 0;\n"
        "mov.b64 da, {%128, %131};\nmov.b64 db, {%129, %132};\n"
        "wgmma.mma_async.sync.aligned.m64n128k32.s32.s8.s8 "
        "{%0, %1, %2, %3, %4, %5, %6, %7, %8, %9, %10, %11, %12, %13, %14, %15, "
        "%16, %17, %18, %19, %20, %21, %22, %23, %24, %25, %26, %27, %28, %29, %30, %31, "
        "%32, %33, %34, %35, %36, %37, %38, %39, %40, %41, %42, %43, %44, %45, %46, %47, "
        "%48, %49, %50, %51, %52, %53, %54, %55, %56, %57, %58, %59, %60, %61, %62, %63}, "
        "da, db, p;\n"
        "add.s64 da, da, 128;\n"
        "wgmma.mma_async.sync.aligned.m64n128k32.s32.s8.s8 "
        "{%64, %65, %66, %67, %68, %69, %70, %71, %72, %73, %74, %75, %76, %77, %78, %79, "
        "%80, %81, %82, %83, %84, %85, %86, %87, %88, %89, %90, %91, %92, %93, %94, %95, "
        "%96, %97, %98, %99, %100, %101, %102, %103, %104, %105, %106, %107, %108, %109, %110, %111, "
        "%112, %113, %114, %115, %116, %117, %118, %119, %120, %121, %122, %123, %124, %125, %126, %127}, "
        "da, db, p;\n"
        "add.s64 da, da, 128;\nadd.s64 db, db, 2;\n"
        "wgmma.mma_async.sync.aligned.m64n128k32.s32.s8.s8 "
        "{%0, %1, %2, %3, %4, %5, %6, %7, %8, %9, %10, %11, %12, %13, %14, %15, "
        "%16, %17, %18, %19, %20, %21, %22, %23, %24, %25, %26, %27, %28, %29, %30, %31, "
        "%32, %33, %34, %35, %36, %37, %38, %39, %40, %41, %42, %43, %44, %45, %46, %47, "
        "%48, %49, %50, %51, %52, %53, %54, %55, %56, %57, %58, %59, %60, %61, %62, %63}, "
        "da, db, 1;\n"
        "add.s64 da, da, 128;\n"
        "wgmma.mma_async.sync.aligned.m64n128k32.s32.s8.s8 "
        "{%64, %65, %66, %67, %68, %69, %70, %71, %72, %73, %74, %75, %76, %77, %78, %79, "
        "%80, %81, %82, %83, %84, %85, %86, %87, %88, %89, %90, %91, %92, %93, %94, %95, "
        "%96, %97, %98, %99, %100, %101, %102, %103, %104, %105, %106, %107, %108, %109, %110, %111, "
        "%112, %113, %114, %115, %116, %117, %118, %119, %120, %121, %122, %123, %124, %125, %126, %127}, "
        "da, db, 1;\n"
        "wgmma.commit_group.sync.aligned;\n}\n"
        : "+r"(d[0]), "+r"(d[1]), "+r"(d[2]), "+r"(d[3]), "+r"(d[4]), "+r"(d[5]), "+r"(d[6]), "+r"(d[7]),
          "+r"(d[8]), "+r"(d[9]), "+r"(d[10]), "+r"(d[11]), "+r"(d[12]), "+r"(d[13]), "+r"(d[14]), "+r"(d[15]),
          "+r"(d[16]), "+r"(d[17]), "+r"(d[18]), "+r"(d[19]), "+r"(d[20]), "+r"(d[21]), "+r"(d[22]), "+r"(d[23]),
          "+r"(d[24]), "+r"(d[25]), "+r"(d[26]), "+r"(d[27]), "+r"(d[28]), "+r"(d[29]), "+r"(d[30]), "+r"(d[31]),
          "+r"(d[32]), "+r"(d[33]), "+r"(d[34]), "+r"(d[35]), "+r"(d[36]), "+r"(d[37]), "+r"(d[38]), "+r"(d[39]),
          "+r"(d[40]), "+r"(d[41]), "+r"(d[42]), "+r"(d[43]), "+r"(d[44]), "+r"(d[45]), "+r"(d[46]), "+r"(d[47]),
          "+r"(d[48]), "+r"(d[49]), "+r"(d[50]), "+r"(d[51]), "+r"(d[52]), "+r"(d[53]), "+r"(d[54]), "+r"(d[55]),
          "+r"(d[56]), "+r"(d[57]), "+r"(d[58]), "+r"(d[59]), "+r"(d[60]), "+r"(d[61]), "+r"(d[62]), "+r"(d[63]),
          "+r"(e[0]), "+r"(e[1]), "+r"(e[2]), "+r"(e[3]), "+r"(e[4]), "+r"(e[5]), "+r"(e[6]), "+r"(e[7]),
          "+r"(e[8]), "+r"(e[9]), "+r"(e[10]), "+r"(e[11]), "+r"(e[12]), "+r"(e[13]), "+r"(e[14]), "+r"(e[15]),
          "+r"(e[16]), "+r"(e[17]), "+r"(e[18]), "+r"(e[19]), "+r"(e[20]), "+r"(e[21]), "+r"(e[22]), "+r"(e[23]),
          "+r"(e[24]), "+r"(e[25]), "+r"(e[26]), "+r"(e[27]), "+r"(e[28]), "+r"(e[29]), "+r"(e[30]), "+r"(e[31]),
          "+r"(e[32]), "+r"(e[33]), "+r"(e[34]), "+r"(e[35]), "+r"(e[36]), "+r"(e[37]), "+r"(e[38]), "+r"(e[39]),
          "+r"(e[40]), "+r"(e[41]), "+r"(e[42]), "+r"(e[43]), "+r"(e[44]), "+r"(e[45]), "+r"(e[46]), "+r"(e[47]),
          "+r"(e[48]), "+r"(e[49]), "+r"(e[50]), "+r"(e[51]), "+r"(e[52]), "+r"(e[53]), "+r"(e[54]), "+r"(e[55]),
          "+r"(e[56]), "+r"(e[57]), "+r"(e[58]), "+r"(e[59]), "+r"(e[60]), "+r"(e[61]), "+r"(e[62]), "+r"(e[63])
        : "r"(alo), "r"(blo), "r"(scale_d), "n"(DESC_A_HI), "n"(DESC_B_HI) : "memory");
}
__device__ __forceinline__ bool mma_pair(int (&d)[64], uint32_t alo, uint32_t blo, int scale_d, uint32_t bar, uint32_t rel, int ka, int kb) {
    uint32_t ok;
    asm volatile("{\n.reg .pred p, q, r;\n.reg .b64 da, db;\nsetp.ne.b32 p, %67, 0;\n"
        "mov.b64 da, {%65, %68};\nmov.b64 db, {%66, %69};\n"
        "wgmma.mma_async.sync.aligned.m64n128k32.s32.s8.s8 "
        "{%0, %1, %2, %3, %4, %5, %6, %7, %8, %9, %10, %11, %12, %13, %14, %15, "
        "%16, %17, %18, %19, %20, %21, %22, %23, %24, %25, %26, %27, %28, %29, %30, %31, "
        "%32, %33, %34, %35, %36, %37, %38, %39, %40, %41, %42, %43, %44, %45, %46, %47, "
        "%48, %49, %50, %51, %52, %53, %54, %55, %56, %57, %58, %59, %60, %61, %62, %63}, "
        "da, db, p;\n"
        "setp.eq.s32 r, %72, %73;\n@r mbarrier.arrive.shared::cluster.b64 _, [%71];\n"
        "add.s64 da, da, 128;\nadd.s64 db, db, 2;\n"
        "wgmma.mma_async.sync.aligned.m64n128k32.s32.s8.s8 "
        "{%0, %1, %2, %3, %4, %5, %6, %7, %8, %9, %10, %11, %12, %13, %14, %15, "
        "%16, %17, %18, %19, %20, %21, %22, %23, %24, %25, %26, %27, %28, %29, %30, %31, "
        "%32, %33, %34, %35, %36, %37, %38, %39, %40, %41, %42, %43, %44, %45, %46, %47, "
        "%48, %49, %50, %51, %52, %53, %54, %55, %56, %57, %58, %59, %60, %61, %62, %63}, "
        "da, db, 1;\n"
        "add.s64 da, da, 128;\nadd.s64 db, db, 510;\n"
        "wgmma.mma_async.sync.aligned.m64n128k32.s32.s8.s8 "
        "{%0, %1, %2, %3, %4, %5, %6, %7, %8, %9, %10, %11, %12, %13, %14, %15, "
        "%16, %17, %18, %19, %20, %21, %22, %23, %24, %25, %26, %27, %28, %29, %30, %31, "
        "%32, %33, %34, %35, %36, %37, %38, %39, %40, %41, %42, %43, %44, %45, %46, %47, "
        "%48, %49, %50, %51, %52, %53, %54, %55, %56, %57, %58, %59, %60, %61, %62, %63}, "
        "da, db, 1;\n"
        "add.s64 da, da, 128;\nadd.s64 db, db, 2;\n"
        "wgmma.mma_async.sync.aligned.m64n128k32.s32.s8.s8 "
        "{%0, %1, %2, %3, %4, %5, %6, %7, %8, %9, %10, %11, %12, %13, %14, %15, "
        "%16, %17, %18, %19, %20, %21, %22, %23, %24, %25, %26, %27, %28, %29, %30, %31, "
        "%32, %33, %34, %35, %36, %37, %38, %39, %40, %41, %42, %43, %44, %45, %46, %47, "
        "%48, %49, %50, %51, %52, %53, %54, %55, %56, %57, %58, %59, %60, %61, %62, %63}, "
        "da, db, 1;\n"
        "add.s64 da, da, 128;\nadd.s64 db, db, 510;\n"
        "wgmma.mma_async.sync.aligned.m64n128k32.s32.s8.s8 "
        "{%0, %1, %2, %3, %4, %5, %6, %7, %8, %9, %10, %11, %12, %13, %14, %15, "
        "%16, %17, %18, %19, %20, %21, %22, %23, %24, %25, %26, %27, %28, %29, %30, %31, "
        "%32, %33, %34, %35, %36, %37, %38, %39, %40, %41, %42, %43, %44, %45, %46, %47, "
        "%48, %49, %50, %51, %52, %53, %54, %55, %56, %57, %58, %59, %60, %61, %62, %63}, "
        "da, db, 1;\n"
        "add.s64 da, da, 128;\nadd.s64 db, db, 2;\n"
        "mbarrier.test_wait.parity.shared::cta.b64 q, [%70], 0;\n"
        "wgmma.mma_async.sync.aligned.m64n128k32.s32.s8.s8 "
        "{%0, %1, %2, %3, %4, %5, %6, %7, %8, %9, %10, %11, %12, %13, %14, %15, "
        "%16, %17, %18, %19, %20, %21, %22, %23, %24, %25, %26, %27, %28, %29, %30, %31, "
        "%32, %33, %34, %35, %36, %37, %38, %39, %40, %41, %42, %43, %44, %45, %46, %47, "
        "%48, %49, %50, %51, %52, %53, %54, %55, %56, %57, %58, %59, %60, %61, %62, %63}, "
        "da, db, 1;\n"
        "add.s64 da, da, 128;\nadd.s64 db, db, 510;\n"
        "wgmma.mma_async.sync.aligned.m64n128k32.s32.s8.s8 "
        "{%0, %1, %2, %3, %4, %5, %6, %7, %8, %9, %10, %11, %12, %13, %14, %15, "
        "%16, %17, %18, %19, %20, %21, %22, %23, %24, %25, %26, %27, %28, %29, %30, %31, "
        "%32, %33, %34, %35, %36, %37, %38, %39, %40, %41, %42, %43, %44, %45, %46, %47, "
        "%48, %49, %50, %51, %52, %53, %54, %55, %56, %57, %58, %59, %60, %61, %62, %63}, "
        "da, db, 1;\n"
        "add.s64 da, da, 128;\nadd.s64 db, db, 2;\n"
        "wgmma.mma_async.sync.aligned.m64n128k32.s32.s8.s8 "
        "{%0, %1, %2, %3, %4, %5, %6, %7, %8, %9, %10, %11, %12, %13, %14, %15, "
        "%16, %17, %18, %19, %20, %21, %22, %23, %24, %25, %26, %27, %28, %29, %30, %31, "
        "%32, %33, %34, %35, %36, %37, %38, %39, %40, %41, %42, %43, %44, %45, %46, %47, "
        "%48, %49, %50, %51, %52, %53, %54, %55, %56, %57, %58, %59, %60, %61, %62, %63}, "
        "da, db, 1;\n"
        "wgmma.commit_group.sync.aligned;\nselp.u32 %64, 1, 0, q;\n}\n"
        : "+r"(d[0]), "+r"(d[1]), "+r"(d[2]), "+r"(d[3]), "+r"(d[4]), "+r"(d[5]), "+r"(d[6]), "+r"(d[7]),
          "+r"(d[8]), "+r"(d[9]), "+r"(d[10]), "+r"(d[11]), "+r"(d[12]), "+r"(d[13]), "+r"(d[14]), "+r"(d[15]),
          "+r"(d[16]), "+r"(d[17]), "+r"(d[18]), "+r"(d[19]), "+r"(d[20]), "+r"(d[21]), "+r"(d[22]), "+r"(d[23]),
          "+r"(d[24]), "+r"(d[25]), "+r"(d[26]), "+r"(d[27]), "+r"(d[28]), "+r"(d[29]), "+r"(d[30]), "+r"(d[31]),
          "+r"(d[32]), "+r"(d[33]), "+r"(d[34]), "+r"(d[35]), "+r"(d[36]), "+r"(d[37]), "+r"(d[38]), "+r"(d[39]),
          "+r"(d[40]), "+r"(d[41]), "+r"(d[42]), "+r"(d[43]), "+r"(d[44]), "+r"(d[45]), "+r"(d[46]), "+r"(d[47]),
          "+r"(d[48]), "+r"(d[49]), "+r"(d[50]), "+r"(d[51]), "+r"(d[52]), "+r"(d[53]), "+r"(d[54]), "+r"(d[55]),
          "+r"(d[56]), "+r"(d[57]), "+r"(d[58]), "+r"(d[59]), "+r"(d[60]), "+r"(d[61]), "+r"(d[62]), "+r"(d[63]), "=r"(ok)
        : "r"(alo), "r"(blo), "r"(scale_d), "n"(DESC_A_HI), "n"(DESC_B_HI), "r"(bar), "r"(rel), "r"(ka), "r"(kb) : "memory");
    return ok;
}
__device__ __forceinline__ void mma_rows2(int (&d)[64], int (&e)[64], uint32_t alo, uint32_t blo, int scale_d) {
    asm volatile("{\n.reg .pred p;\n.reg .b64 da, db;\nsetp.ne.b32 p, %130, 0;\n"
        "mov.b64 da, {%128, %131};\nmov.b64 db, {%129, %132};\n"
        "wgmma.mma_async.sync.aligned.m64n128k32.s32.s8.s8 "
        "{%0, %1, %2, %3, %4, %5, %6, %7, %8, %9, %10, %11, %12, %13, %14, %15, "
        "%16, %17, %18, %19, %20, %21, %22, %23, %24, %25, %26, %27, %28, %29, %30, %31, "
        "%32, %33, %34, %35, %36, %37, %38, %39, %40, %41, %42, %43, %44, %45, %46, %47, "
        "%48, %49, %50, %51, %52, %53, %54, %55, %56, %57, %58, %59, %60, %61, %62, %63}, "
        "da, db, p;\n"
        "add.s64 db, db, 512;\n"
        "wgmma.mma_async.sync.aligned.m64n128k32.s32.s8.s8 "
        "{%64, %65, %66, %67, %68, %69, %70, %71, %72, %73, %74, %75, %76, %77, %78, %79, "
        "%80, %81, %82, %83, %84, %85, %86, %87, %88, %89, %90, %91, %92, %93, %94, %95, "
        "%96, %97, %98, %99, %100, %101, %102, %103, %104, %105, %106, %107, %108, %109, %110, %111, "
        "%112, %113, %114, %115, %116, %117, %118, %119, %120, %121, %122, %123, %124, %125, %126, %127}, "
        "da, db, p;\n"
        "add.s64 da, da, 128;\nadd.s64 db, db, -510;\n"
        "wgmma.mma_async.sync.aligned.m64n128k32.s32.s8.s8 "
        "{%0, %1, %2, %3, %4, %5, %6, %7, %8, %9, %10, %11, %12, %13, %14, %15, "
        "%16, %17, %18, %19, %20, %21, %22, %23, %24, %25, %26, %27, %28, %29, %30, %31, "
        "%32, %33, %34, %35, %36, %37, %38, %39, %40, %41, %42, %43, %44, %45, %46, %47, "
        "%48, %49, %50, %51, %52, %53, %54, %55, %56, %57, %58, %59, %60, %61, %62, %63}, "
        "da, db, 1;\n"
        "add.s64 db, db, 512;\n"
        "wgmma.mma_async.sync.aligned.m64n128k32.s32.s8.s8 "
        "{%64, %65, %66, %67, %68, %69, %70, %71, %72, %73, %74, %75, %76, %77, %78, %79, "
        "%80, %81, %82, %83, %84, %85, %86, %87, %88, %89, %90, %91, %92, %93, %94, %95, "
        "%96, %97, %98, %99, %100, %101, %102, %103, %104, %105, %106, %107, %108, %109, %110, %111, "
        "%112, %113, %114, %115, %116, %117, %118, %119, %120, %121, %122, %123, %124, %125, %126, %127}, "
        "da, db, 1;\n"
        "wgmma.commit_group.sync.aligned;\n}\n"
        : "+r"(d[0]), "+r"(d[1]), "+r"(d[2]), "+r"(d[3]), "+r"(d[4]), "+r"(d[5]), "+r"(d[6]), "+r"(d[7]),
          "+r"(d[8]), "+r"(d[9]), "+r"(d[10]), "+r"(d[11]), "+r"(d[12]), "+r"(d[13]), "+r"(d[14]), "+r"(d[15]),
          "+r"(d[16]), "+r"(d[17]), "+r"(d[18]), "+r"(d[19]), "+r"(d[20]), "+r"(d[21]), "+r"(d[22]), "+r"(d[23]),
          "+r"(d[24]), "+r"(d[25]), "+r"(d[26]), "+r"(d[27]), "+r"(d[28]), "+r"(d[29]), "+r"(d[30]), "+r"(d[31]),
          "+r"(d[32]), "+r"(d[33]), "+r"(d[34]), "+r"(d[35]), "+r"(d[36]), "+r"(d[37]), "+r"(d[38]), "+r"(d[39]),
          "+r"(d[40]), "+r"(d[41]), "+r"(d[42]), "+r"(d[43]), "+r"(d[44]), "+r"(d[45]), "+r"(d[46]), "+r"(d[47]),
          "+r"(d[48]), "+r"(d[49]), "+r"(d[50]), "+r"(d[51]), "+r"(d[52]), "+r"(d[53]), "+r"(d[54]), "+r"(d[55]),
          "+r"(d[56]), "+r"(d[57]), "+r"(d[58]), "+r"(d[59]), "+r"(d[60]), "+r"(d[61]), "+r"(d[62]), "+r"(d[63]),
          "+r"(e[0]), "+r"(e[1]), "+r"(e[2]), "+r"(e[3]), "+r"(e[4]), "+r"(e[5]), "+r"(e[6]), "+r"(e[7]),
          "+r"(e[8]), "+r"(e[9]), "+r"(e[10]), "+r"(e[11]), "+r"(e[12]), "+r"(e[13]), "+r"(e[14]), "+r"(e[15]),
          "+r"(e[16]), "+r"(e[17]), "+r"(e[18]), "+r"(e[19]), "+r"(e[20]), "+r"(e[21]), "+r"(e[22]), "+r"(e[23]),
          "+r"(e[24]), "+r"(e[25]), "+r"(e[26]), "+r"(e[27]), "+r"(e[28]), "+r"(e[29]), "+r"(e[30]), "+r"(e[31]),
          "+r"(e[32]), "+r"(e[33]), "+r"(e[34]), "+r"(e[35]), "+r"(e[36]), "+r"(e[37]), "+r"(e[38]), "+r"(e[39]),
          "+r"(e[40]), "+r"(e[41]), "+r"(e[42]), "+r"(e[43]), "+r"(e[44]), "+r"(e[45]), "+r"(e[46]), "+r"(e[47]),
          "+r"(e[48]), "+r"(e[49]), "+r"(e[50]), "+r"(e[51]), "+r"(e[52]), "+r"(e[53]), "+r"(e[54]), "+r"(e[55]),
          "+r"(e[56]), "+r"(e[57]), "+r"(e[58]), "+r"(e[59]), "+r"(e[60]), "+r"(e[61]), "+r"(e[62]), "+r"(e[63])
        : "r"(alo), "r"(blo), "r"(scale_d), "n"(DESC_A_HI), "n"(DESC_B_HI) : "memory");
}

__device__ __forceinline__ void wg_fence() { asm volatile("wgmma.fence.sync.aligned;" ::: "memory"); }
template <int N> __device__ __forceinline__ void wg_wait() { asm volatile("wgmma.wait_group.sync.aligned %0;" :: "n"(N) : "memory"); }

__host__ __device__ constexpr int unit_of(int wg, int s) { return wg ? (s < 16 - D_ ? D_ + 2 * s : s + 16) : (s < D_ ? s : 2 * s - D_ + 1); }

__host__ __device__ constexpr int bar_of(int u) { return u >= 32 ? u & ~1 : u < D_ || u >= 32 - D_ ? u : ((u - D_) & 1) ? D_ + ((u - D_) >> 1) : 16 + ((u - D_) >> 1); }
constexpr uint32_t step_table(int wg) {
    uint32_t t = 0;
    for (int s = 0; s < 15; s++) t |= (uint32_t)(unit_of(wg, s + 1) - unit_of(wg, s) - 1) << s;
    return t;
}
constexpr uint32_t STEPS0 = step_table(0), STEPS1 = step_table(1);
__device__ __forceinline__ int sum_group(int r) { return r < 8 ? (r & 4) | (~r & 1) << 1 | (r >> 1 & 1) : r; }
__device__ __forceinline__ int col_of(int c, int blk) { return (c < 7 ? blk * 7 + c : 49 + blk) * 64; }

struct JobTable { uint2 e[NCTA][NJOB + NCONV]; };
__device__ const JobTable g_jobs = {{
    {{0x0, 0x0}, {0x20400, 0x1000000}, {0x90202, 0x2008099}, {0x100004, 0x3010132}, {0x14000000, 0x310001ee}, {0x2a412a34, 0x2d82025a}, {0x14100e0e, 0x750042d3}, {0x1dc3807, 0x439c358}, {0x14202a0e, 0x75008432}, {0x2a45009, 0x55244c0}, {0x1430460e, 0x7504c591}, {0x2c000b, 0x702c601}, {0x1440620e, 0x750506eb}, {0xb3160c, 0x8130735}, {0x14507e0e, 0x75094845}, {0x3fa7c0e, 0x97b8887}, {0x14609a0e, 0x7509897f}, {0x1470b60e, 0x750dca2c}, {0x1480001c, 0x98020ae5}, {0x1490701c, 0x980a4bc1}, {0x14a00023, 0xba028c9d}, {0x14b07023, 0xba0acd79}, {0x14c0002a, 0xdc030e55}, {0x14d0702a, 0xdc0b4f23}, {0x30000000, 0x0}, {0x30000000, 0x0}, {0x30000000, 0x0}, {0x30000000, 0x0}, {0x30000000, 0x0}, {0x30000000, 0x0}, {0x30000000, 0x0}, {0x30000000, 0x0}},
    {{0x0, 0x0}, {0x420c00, 0x1080001}, {0x490a02, 0x208809a}, {0x500804, 0x3090133}, {0x14010007, 0x200001f9}, {0x570e05, 0x409426c}, {0x14110e15, 0x640042e9}, {0x2a4e5b31, 0x5b82c36a}, {0x14212a15, 0x64008448}, {0x3246009, 0x56244c4}, {0x14314615, 0x6404c5a7}, {0x22c400b, 0x742c617}, {0x14416215, 0x64050700}, {0x233460c, 0x8430745}, {0x14517e15, 0x6409485a}, {0x17b2e0e, 0x92b8896}, {0x14619a15, 0x6409898a}, {0x1471b615, 0x640dca37}, {0x1481071c, 0x98020af2}, {0x1491771c, 0x980a4bce}, {0x14a10723, 0xba028caa}, {0x14b17723, 0xba0acd86}, {0x14c1072a, 0xdc030e62}, {0x14d1772a, 0xdc0b4f2f}, {0x30000000, 0x0}, {0x30000000, 0x0}, {0x30000000, 0x0}, {0x30000000, 0x0}, {0x30000000, 0x0}, {0x30000000, 0x0}, {0x30000000, 0x0}, {0x30000000, 0x0}},
    {{0x0, 0x0}, {0x821400, 0x1100002}, {0x891202, 0x210809b}, {0x901004, 0x3110134}, {0x14020700, 0x31000204}, {0x2a433134, 0x34820278}, {0x1412150e, 0x750042ff}, {0x5d0a07, 0x409c374}, {0x1422310e, 0x7500845e}, {0x3e47809, 0x57a44cd}, {0x14324d0e, 0x7504c5bc}, {0x36c680b, 0x76ac623}, {0x1442690e, 0x75050716}, {0x3b3760c, 0x8730756}, {0x1452850e, 0x75094870}, {0x1fb3e0e, 0x93b889c}, {0x1462a10e, 0x75098995}, {0x1472bd0e, 0x750dca42}, {0x14820e1c, 0x98020b00}, {0x14927e1c, 0x980a4bdc}, {0x14a20e23, 0xba028cb8}, {0x14b27e23, 0xba0acd94}, {0x14c20e2a, 0xdc030e70}, {0x14d27e2a, 0xdc0b4f3b}, {0x30000000, 0x0}, {0x30000000, 0x0}, {0x30000000, 0x0}, {0x30000000, 0x0}, {0x30000000, 0x0}, {0x30000000, 0x0}, {0x30000000, 0x0}, {0x30000000, 0x0}},
    {{0x0, 0x0}, {0xc21c00, 0x1180003}, {0xc91a02, 0x218809c}, {0xd01804, 0x3190135}, {0x14030707, 0x2000020f}, {0x2975605, 0x4514285}, {0x14131515, 0x64004315}, {0x11d2207, 0x421c37a}, {0x14233115, 0x64008474}, {0x650a09, 0x60a44d3}, {0x14334d15, 0x6404c5d2}, {0xad120b, 0x712c632}, {0x30000c, 0x70306ae}, {0x14436915, 0x6405072c}, {0x14538515, 0x64094885}, {0x2fb5e0e, 0x95b88a6}, {0x1463a115, 0x640989a0}, {0x1473bd15, 0x640dca4c}, {0x1483151c, 0x98020b0e}, {0x1493851c, 0x980a4bea}, {0x14a31523, 0xba028cc6}, {0x14b38523, 0xba0acda2}, {0x14c3152a, 0xdc030e7e}, {0x14d3852a, 0xdc0b4f47}, {0x30000000, 0x0}, {0x30000000, 0x0}, {0x30000000, 0x0}, {0x30000000, 0x0}, {0x30000000, 0x0}, {0x30000000, 0x0}, {0x30000000, 0x0}, {0x30000000, 0x0}},
    {{0x0, 0x0}, {0x1022400, 0x1200005}, {0x1092202, 0x220809e}, {0x1102004, 0x3210137}, {0x14040e00, 0x3100021a}, {0x3977605, 0x4714290}, {0x14142a00, 0x3100432b}, {0x29d5207, 0x451c38c}, {0x14244600, 0x3104848a}, {0x1252209, 0x62244da}, {0x14346200, 0x3104c5e8}, {0x22d420b, 0x742c642}, {0x70080c, 0x70b06b1}, {0x14447e00, 0x31090741}, {0x336640d, 0x86347d0}, {0x14549a00, 0x3109489b}, {0x1464b600, 0x310d89aa}, {0x1474d200, 0x310dca57}, {0x14841c1c, 0x98020b1c}, {0x14948c1c, 0x980a4bf8}, {0x14a41c23, 0xba028cd4}, {0x14b48c23, 0xba0acdb0}, {0x14c41c2a, 0xdc030e8c}, {0x14d48c2a, 0xdc0b4f53}, {0x30000000, 0x0}, {0x30000000, 0x0}, {0x30000000, 0x0}, {0x30000000, 0x0}, {0x30000000, 0x0}, {0x30000000, 0x0}, {0x30000000, 0x0}, {0x30000000, 0x0}},
    {{0x0, 0x0}, {0x1422c00, 0x1280006}, {0x1492a02, 0x228809f}, {0x1502804, 0x3290138}, {0x14050e07, 0x20000225}, {0xd81806, 0x419829c}, {0x14152a07, 0x20004341}, {0x3dd7a07, 0x479c39a}, {0x14254607, 0x200484a0}, {0x1a53209, 0x63244e1}, {0x14356207, 0x2004c5fd}, {0x3ed7a0b, 0x77ac655}, {0x3ef7e0b, 0x77ac6ab}, {0x14457e07, 0x20090757}, {0x137260d, 0x82347e6}, {0x14559a07, 0x200948b1}, {0x1465b607, 0x200d89b5}, {0x1475d207, 0x200dca62}, {0x1485231c, 0x98020b29}, {0x1495931c, 0x980a4c05}, {0x14a52323, 0xba028ce1}, {0x14b59323, 0xba0acdbd}, {0x14c5232a, 0xdc030e99}, {0x14d5932a, 0xdc0b4f5f}, {0x30000000, 0x0}, {0x30000000, 0x0}, {0x30000000, 0x0}, {0x30000000, 0x0}, {0x30000000, 0x0}, {0x30000000, 0x0}, {0x30000000, 0x0}, {0x30000000, 0x0}},
    {{0x0, 0x0}, {0x1823400, 0x1300007}, {0x1893202, 0x23080a0}, {0x1903004, 0x3310139}, {0x14061500, 0x31000230}, {0x1d83806, 0x43982a8}, {0x14163100, 0x31004357}, {0xde1c07, 0x519c3a4}, {0x14264d00, 0x310484b6}, {0x2254209, 0x64244e6}, {0x14366900, 0x3104c613}, {0x1ae340b, 0x732c668}, {0x3af760b, 0x772c6a9}, {0x14468500, 0x3109076c}, {0x2f75e0d, 0x85b47f9}, {0x1456a100, 0x310948c6}, {0x1466bd00, 0x310d89c0}, {0x1476d900, 0x310dca6d}, {0x14862a1c, 0x98020b37}, {0x14969a1c, 0x980a4c13}, {0x14a62a23, 0xba028cef}, {0x14b69a23, 0xba0acdcb}, {0x14c62a2a, 0xdc030ea7}, {0x14d69a2a, 0xdc0b4f6b}, {0x30000000, 0x0}, {0x30000000, 0x0}, {0x30000000, 0x0}, {0x30000000, 0x0}, {0x30000000, 0x0}, {0x30000000, 0x0}, {0x30000000, 0x0}, {0x30000000, 0x0}},
    {{0x0, 0x0}, {0x1c23c00, 0x1380009}, {0x1c93a02, 0x23880a2}, {0x1d03804, 0x339013b}, {0x14071507, 0x2000023b}, {0x3186006, 0x46182b5}, {0x14173107, 0x2000436d}, {0x15e2c07, 0x529c3a9}, {0x1212208, 0x522042a}, {0x14274d07, 0x200484cc}, {0x14376907, 0x2004c628}, {0x32e640b, 0x762c677}, {0xb0100c, 0x71306b3}, {0x14478507, 0x20090782}, {0x1f73e0d, 0x83b47ef}, {0x1457a107, 0x200948dc}, {0x1467bd07, 0x200d89cb}, {0x1477d907, 0x200dca78}, {0x1487311c, 0x98020b45}, {0x1497a11c, 0x980a4c21}, {0x14a73123, 0xba028cfd}, {0x14b7a123, 0xba0acdd9}, {0x14c7312a, 0xdc030eb5}, {0x14d7a12a, 0xdc0b4f77}, {0x30000000, 0x0}, {0x30000000, 0x0}, {0x30000000, 0x0}, {0x30000000, 0x0}, {0x30000000, 0x0}, {0x30000000, 0x0}, {0x30000000, 0x0}, {0x30000000, 0x0}},
    {{0x0, 0x0}, {0x2024400, 0x140000a}, {0x2094202, 0x24080a3}, {0x2104004, 0x341013c}, {0x1408000e, 0x75000246}, {0x190206, 0x40182c1}, {0x11c2007, 0x421c34e}, {0x14181c0e, 0x75004383}, {0x210208, 0x5020421}, {0x1428380e, 0x750484e2}, {0x1438540e, 0x7504c63e}, {0xaf160b, 0x712c688}, {0x232440c, 0x743071a}, {0x1448700e, 0x75090798}, {0x1b7360d, 0x83347ed}, {0x14588c0e, 0x750948f1}, {0x1468a80e, 0x750d89d6}, {0x1478c40e, 0x750dca82}, {0x1488381c, 0x98060b53}, {0x1498a81c, 0x980e4c2f}, {0x14a83823, 0xba068d0b}, {0x14b8a823, 0xba0ecde7}, {0x14c8382a, 0xdc070ec3}, {0x14d8a82a, 0xdc0f4f83}, {0x30000000, 0x0}, {0x30000000, 0x0}, {0x30000000, 0x0}, {0x30000000, 0x0}, {0x30000000, 0x0}, {0x30000000, 0x0}, {0x30000000, 0x0}, {0x30000000, 0x0}},
    {{0x0, 0x0}, {0x2424c00, 0x148000b}, {0x2494a02, 0x24880a4}, {0x2504804, 0x349013d}, {0x14090015, 0x64000251}, {0x1592a06, 0x42982cd}, {0x2a4c5431, 0x5482c33e}, {0x14191c15, 0x64004399}, {0xa11208, 0x5120426}, {0x14293815, 0x640484f8}, {0x14395415, 0x6404c654}, {0x26f4e0b, 0x74ac69b}, {0xb2140c, 0x713070a}, {0x14497015, 0x640907ad}, {0x2774e0d, 0x84b47f5}, {0x14598c15, 0x64094907}, {0x1469a815, 0x640d89e0}, {0x1479c415, 0x640dca8d}, {0x14893f1c, 0x98060b60}, {0x1499af1c, 0x980e4c3c}, {0x14a93f23, 0xba068d18}, {0x14b9af23, 0xba0ecdf4}, {0x14c93f2a, 0xdc070ecf}, {0x14d9af2a, 0xdc0f4f8f}, {0x30000000, 0x0}, {0x30000000, 0x0}, {0x30000000, 0x0}, {0x30000000, 0x0}, {0x30000000, 0x0}, {0x30000000, 0x0}, {0x30000000, 0x0}, {0x30000000, 0x0}},
    {{0x0, 0x0}, {0x2825400, 0x150000d}, {0x2895202, 0x25080a6}, {0x2905004, 0x351013f}, {0x2a200031, 0x8001cd}, {0x140a070e, 0x7500025c}, {0x2a4b3f34, 0x42828328}, {0x141a230e, 0x750043af}, {0x1612a08, 0x52a042d}, {0x142a3f0e, 0x7504850e}, {0xa9120a, 0x6128585}, {0x143a5b0e, 0x7504c669}, {0xf11a0c, 0x71b06e0}, {0x144a770e, 0x750907c3}, {0x3776e0d, 0x86b47fe}, {0x145a930e, 0x7509491d}, {0x3be740f, 0x973c931}, {0x146aaf0e, 0x750d89eb}, {0x147acb0e, 0x750dca98}, {0x148a461c, 0x98060b6e}, {0x149ab61c, 0x980e4c4a}, {0x14aa4623, 0xba068d26}, {0x14bab623, 0xba0ece02}, {0x14ca462a, 0xdc070edb}, {0x14dab62a, 0xdc0f4f9b}, {0x30000000, 0x0}, {0x30000000, 0x0}, {0x30000000, 0x0}, {0x30000000, 0x0}, {0x30000000, 0x0}, {0x30000000, 0x0}, {0x30000000, 0x0}},
    {{0x0, 0x0}, {0x2c25c00, 0x158000e}, {0x2c95a02, 0x25880a7}, {0x2d05804, 0x3590140}, {0x2a210032, 0x18001ce}, {0x140b0715, 0x64000267}, {0x2da5c06, 0x459830a}, {0x141b2315, 0x640043c5}, {0x1a13208, 0x5320431}, {0x142b3f15, 0x64048524}, {0x129220a, 0x6228589}, {0x143b5b15, 0x6404c67f}, {0x2b0500c, 0x75306c9}, {0x144b7715, 0x640907d9}, {0x38000e, 0x8038808}, {0x145b9315, 0x64094932}, {0x7f0e0f, 0x90bc939}, {0x146baf15, 0x640d89f6}, {0x147bcb15, 0x640dcaa3}, {0x148b4d1c, 0x98060b7c}, {0x149bbd1c, 0x980e4c58}, {0x14ab4d23, 0xba068d34}, {0x14bbbd23, 0xba0ece10}, {0x14cb4d2a, 0xdc070ee7}, {0x14dbbd2a, 0xdc0f4fa7}, {0x30000000, 0x0}, {0x30000000, 0x0}, {0x30000000, 0x0}, {0x30000000, 0x0}, {0x30000000, 0x0}, {0x30000000, 0x0}, {0x30000000, 0x0}},
    {{0x0, 0x0}, {0x3026400, 0x160000f}, {0x3096202, 0x26080a8}, {0x3106004, 0x3610141}, {0x2a220731, 0x78001cf}, {0x140c1c00, 0x3100027b}, {0x19a3406, 0x43182fe}, {0x141c3800, 0x310443db}, {0x2214208, 0x5420436}, {0x142c5400, 0x3104853a}, {0x1e93a0a, 0x63a8592}, {0x143c7000, 0x3108c694}, {0x230400c, 0x74306c4}, {0x144c8c00, 0x310907ee}, {0x178280e, 0x82b8814}, {0x37a6c0e, 0x96b8880}, {0x145ca800, 0x310d4948}, {0x146cc400, 0x310d8a01}, {0x147cd20e, 0x750dcaae}, {0x148c541c, 0x98060b8a}, {0x149cc41c, 0x980e4c66}, {0x14ac5423, 0xba068d42}, {0x14bcc423, 0xba0ece1e}, {0x14cc542a, 0xdc070ef3}, {0x14dcc42a, 0xdc0f4fb3}, {0x30000000, 0x0}, {0x30000000, 0x0}, {0x30000000, 0x0}, {0x30000000, 0x0}, {0x30000000, 0x0}, {0x30000000, 0x0}, {0x30000000, 0x0}},
    {{0x0, 0x0}, {0x3426c00, 0x1680011}, {0x3496a02, 0x26880aa}, {0x3506804, 0x3690143}, {0x2a230732, 0x88001d1}, {0x140d1c07, 0x20000291}, {0x9a1406, 0x41182f3}, {0x141d3807, 0x200443f0}, {0x2a15208, 0x552043c}, {0x142d5407, 0x20048550}, {0x2a9520a, 0x652859b}, {0x12b260a, 0x62285df}, {0x143d7007, 0x2008c6aa}, {0x1732e0c, 0x82b073c}, {0x144d8c07, 0x20090804}, {0x7b0e0e, 0x90b888c}, {0x145da807, 0x200d495d}, {0x146dc407, 0x200d8a0c}, {0x147dd215, 0x640dcabb}, {0x148d5b1c, 0x98060b97}, {0x149dcb1c, 0x980e4c73}, {0x14ad5b23, 0xba068d4f}, {0x14bdcb23, 0xba0ece2b}, {0x14cd5b2a, 0xdc070eff}, {0x14ddcb2a, 0xdc0f4fbf}, {0x30000000, 0x0}, {0x30000000, 0x0}, {0x30000000, 0x0}, {0x30000000, 0x0}, {0x30000000, 0x0}, {0x30000000, 0x0}, {0x30000000, 0x0}},
    {{0x0, 0x0}, {0x3827400, 0x1700012}, {0x3897202, 0x27080ab}, {0x3907004, 0x3710144}, {0x2a240e31, 0xe8041d2}, {0x140e2300, 0x310002a7}, {0x3d97a06, 0x47982ea}, {0x141e3f00, 0x31044406}, {0x3616a08, 0x56a0443}, {0xa51209, 0x61244d6}, {0x142e5b00, 0x31048566}, {0xeb1e0a, 0x61a85dd}, {0x143e7700, 0x3108c6c0}, {0x3736e0c, 0x86b0751}, {0x144e9300, 0x31090819}, {0x13b260e, 0x9238893}, {0x145eaf00, 0x310d496a}, {0x146ecb00, 0x310d8a16}, {0x147ed90e, 0x750dcac9}, {0x148e621c, 0x98060ba5}, {0x149ed21c, 0x980e4c81}, {0x14ae6223, 0xba068d5d}, {0x14bed223, 0xba0ece39}, {0x14ce622a, 0xdc070f0b}, {0x14ded22a, 0xdc0f4fcb}, {0x30000000, 0x0}, {0x30000000, 0x0}, {0x30000000, 0x0}, {0x30000000, 0x0}, {0x30000000, 0x0}, {0x30000000, 0x0}, {0x30000000, 0x0}},
    {{0x0, 0x0}, {0x3c27c00, 0x1780013}, {0x3c97a02, 0x27880ac}, {0x3d07804, 0x3790145}, {0x2a250e32, 0xf8041d4}, {0x140f2307, 0x200002bd}, {0x3596a06, 0x46982e3}, {0x2a4f5b32, 0x5c82c380}, {0x141f3f07, 0x2004441c}, {0x3a47009, 0x57244cb}, {0x142f5b07, 0x2004857c}, {0x2ab560a, 0x65285f1}, {0x143f7707, 0x2008c6d5}, {0x2b3560c, 0x853074b}, {0x144f9307, 0x2009082f}, {0xbb160e, 0x913888f}, {0x145faf07, 0x200d4974}, {0x146fcb07, 0x200d8a21}, {0x147fd915, 0x640dcad7}, {0x148f691c, 0x98060bb3}, {0x149fd91c, 0x980e4c8f}, {0x14af6923, 0xba068d6b}, {0x14bfd923, 0xba0ece47}, {0x14cf692a, 0xdc070f17}, {0x14dfd92a, 0xdc0f4fd7}, {0x30000000, 0x0}, {0x30000000, 0x0}, {0x30000000, 0x0}, {0x30000000, 0x0}, {0x30000000, 0x0}, {0x30000000, 0x0}, {0x30000000, 0x0}},
    {{0x0, 0x0}, {0x30600, 0x1000015}, {0xa0402, 0x20080ae}, {0x110204, 0x3010147}, {0x14e00001, 0x310001ef}, {0x14f00e0f, 0x750042d6}, {0x2995206, 0x45182dd}, {0x15d2a07, 0x429c37d}, {0x15002a0f, 0x75008435}, {0x250209, 0x60244d0}, {0x1510460f, 0x7504c594}, {0xac100b, 0x712c607}, {0x1520620f, 0x750506ee}, {0x333660c, 0x863074f}, {0x15307e0f, 0x75094847}, {0x1bb360e, 0x933889a}, {0x15409a0f, 0x75098981}, {0x1550b60f, 0x750dca2d}, {0x1560001d, 0x98020ae6}, {0x1570701d, 0x980a4bc2}, {0x15800024, 0xba028c9e}, {0x15907024, 0xba0acd7a}, {0x15a0002b, 0xdc030e56}, {0x15b0702b, 0xdc0b4f25}, {0x30000000, 0x0}, {0x30000000, 0x0}, {0x30000000, 0x0}, {0x30000000, 0x0}, {0x30000000, 0x0}, {0x30000000, 0x0}, {0x30000000, 0x0}, {0x30000000, 0x0}},
    {{0x0, 0x0}, {0x430e00, 0x1080016}, {0x4a0c02, 0x20880af}, {0x510a04, 0x3090148}, {0x14e10008, 0x200001fa}, {0x971605, 0x411426f}, {0x14f10e16, 0x640042ec}, {0x21d4207, 0x441c387}, {0x15012a16, 0x6400844b}, {0xe51a09, 0x61a44d7}, {0x15114616, 0x6404c5a9}, {0x26c480b, 0x74ac61a}, {0x15216216, 0x64050703}, {0x34000d, 0x803475b}, {0x15317e16, 0x6409485d}, {0x23b460e, 0x943889f}, {0x15419a16, 0x6409898b}, {0x1551b616, 0x640dca38}, {0x1561071d, 0x98020af4}, {0x1571771d, 0x980a4bd0}, {0x15810724, 0xba028cac}, {0x15917724, 0xba0acd88}, {0x15a1072b, 0xdc030e64}, {0x15b1772b, 0xdc0b4f31}, {0x30000000, 0x0}, {0x30000000, 0x0}, {0x30000000, 0x0}, {0x30000000, 0x0}, {0x30000000, 0x0}, {0x30000000, 0x0}, {0x30000000, 0x0}, {0x30000000, 0x0}},
    {{0x0, 0x0}, {0x831600, 0x1100017}, {0x8a1402, 0x21080b0}, {0x911204, 0x3110149}, {0x14e20701, 0x31000205}, {0x1973605, 0x431427a}, {0x14f2150f, 0x75004302}, {0x31d6207, 0x461c390}, {0x1502310f, 0x75008461}, {0x1652a09, 0x62a44dd}, {0x15124d0f, 0x7504c5bf}, {0x3ac700b, 0x772c627}, {0x1522690f, 0x75050719}, {0xb4100d, 0x8134760}, {0x1532850f, 0x75094872}, {0x37b6e0e, 0x96b88ab}, {0x1542a10f, 0x75098996}, {0x1552bd0f, 0x750dca43}, {0x15620e1d, 0x98020b02}, {0x15727e1d, 0x980a4bde}, {0x15820e24, 0xba028cba}, {0x15927e24, 0xba0acd96}, {0x15a20e2b, 0xdc030e72}, {0x15b27e2b, 0xdc0b4f3d}, {0x30000000, 0x0}, {0x30000000, 0x0}, {0x30000000, 0x0}, {0x30000000, 0x0}, {0x30000000, 0x0}, {0x30000000, 0x0}, {0x30000000, 0x0}, {0x30000000, 0x0}},
    {{0x0, 0x0}, {0xc31e00, 0x1180018}, {0xca1c02, 0x21880b1}, {0xd11a04, 0x319014a}, {0x14e30708, 0x20000210}, {0x2d75e05, 0x4594286}, {0x14f31516, 0x64004318}, {0x5e0c07, 0x509c39f}, {0x15033116, 0x64008477}, {0x1e53a09, 0x63a44e3}, {0x15134d16, 0x6404c5d5}, {0xed1a0b, 0x71ac633}, {0x15236916, 0x6405072e}, {0x1f4380d, 0x83b476e}, {0x15338516, 0x64094888}, {0x3c000f, 0x903c8b5}, {0x1543a116, 0x640989a1}, {0x1553bd16, 0x640dca4e}, {0x1563151d, 0x98020b10}, {0x1573851d, 0x980a4bec}, {0x15831524, 0xba028cc8}, {0x15938524, 0xba0acda4}, {0x15a3152b, 0xdc030e80}, {0x15b3852b, 0xdc0b4f49}, {0x30000000, 0x0}, {0x30000000, 0x0}, {0x30000000, 0x0}, {0x30000000, 0x0}, {0x30000000, 0x0}, {0x30000000, 0x0}, {0x30000000, 0x0}, {0x30000000, 0x0}},
    {{0x0, 0x0}, {0x1032600, 0x120001a}, {0x10a2402, 0x22080b3}, {0x1112204, 0x321014c}, {0x14e40e01, 0x3100021b}, {0x3d77e05, 0x4794292}, {0x14f42a01, 0x3100432e}, {0x11e2407, 0x521c3a6}, {0x15044601, 0x3104848d}, {0x2e55a09, 0x65a44ed}, {0x15146201, 0x3104c5ea}, {0x2ad520b, 0x752c647}, {0x15247e01, 0x31090744}, {0x2f4580d, 0x85b4777}, {0x15349a01, 0x3109489e}, {0x13c200f, 0x923c8be}, {0x1544b601, 0x310d89ac}, {0x1554d201, 0x310dca59}, {0x15641c1d, 0x98020b1d}, {0x15748c1d, 0x980a4bf9}, {0x15841c24, 0xba028cd5}, {0x15948c24, 0xba0acdb1}, {0x15a41c2b, 0xdc030e8d}, {0x15b48c2b, 0xdc0b4f55}, {0x30000000, 0x0}, {0x30000000, 0x0}, {0x30000000, 0x0}, {0x30000000, 0x0}, {0x30000000, 0x0}, {0x30000000, 0x0}, {0x30000000, 0x0}, {0x30000000, 0x0}},
    {{0x0, 0x0}, {0x1432e00, 0x128001b}, {0x14a2c02, 0x22880b4}, {0x1512a04, 0x329014d}, {0x14e50e08, 0x20000226}, {0x1182006, 0x421829f}, {0x14f52a08, 0x20004344}, {0x1de3c07, 0x539c3b0}, {0x15054608, 0x200484a3}, {0x3a57209, 0x67244f7}, {0x15156208, 0x2004c600}, {0x2e040b, 0x702c658}, {0x15257e08, 0x2009075a}, {0x3f4780d, 0x87b4783}, {0xb8100e, 0x813880d}, {0x15359a08, 0x200948b3}, {0x1545b608, 0x200d89b7}, {0x1555d208, 0x200dca63}, {0x1565231d, 0x98020b2b}, {0x1575931d, 0x980a4c07}, {0x15852324, 0xba028ce3}, {0x15959324, 0xba0acdbf}, {0x15a5232b, 0xdc030e9b}, {0x15b5932b, 0xdc0b4f61}, {0x30000000, 0x0}, {0x30000000, 0x0}, {0x30000000, 0x0}, {0x30000000, 0x0}, {0x30000000, 0x0}, {0x30000000, 0x0}, {0x30000000, 0x0}, {0x30000000, 0x0}},
    {{0x0, 0x0}, {0x1833600, 0x130001c}, {0x18a3402, 0x23080b5}, {0x1913204, 0x331014e}, {0x14e61501, 0x31000231}, {0x2184006, 0x44182ab}, {0x14f63101, 0x31004359}, {0x29e5407, 0x551c3b8}, {0x15064d01, 0x310484b9}, {0x260409, 0x60244fc}, {0x15166901, 0x3104c615}, {0x1ee3c0b, 0x73ac66b}, {0x270480c, 0x74b06c6}, {0x15268501, 0x3109076f}, {0x337660d, 0x86347fc}, {0x1536a101, 0x310948c9}, {0x1546bd01, 0x310d89c1}, {0x1556d901, 0x310dca6e}, {0x15662a1d, 0x98020b39}, {0x15769a1d, 0x980a4c15}, {0x15862a24, 0xba028cf1}, {0x15969a24, 0xba0acdcd}, {0x15a62a2b, 0xdc030ea9}, {0x15b69a2b, 0xdc0b4f6d}, {0x30000000, 0x0}, {0x30000000, 0x0}, {0x30000000, 0x0}, {0x30000000, 0x0}, {0x30000000, 0x0}, {0x30000000, 0x0}, {0x30000000, 0x0}, {0x30000000, 0x0}},
    {{0x0, 0x0}, {0x1c33e00, 0x138001e}, {0x1ca3c02, 0x23880b7}, {0x1d13a04, 0x3390150}, {0x14e71508, 0x2000023c}, {0x3586806, 0x46982b7}, {0x14f73108, 0x2000436f}, {0x31e6407, 0x561c3bc}, {0x15074d08, 0x200484cf}, {0xa61409, 0x6124502}, {0x15176908, 0x2004c62b}, {0x3ae740b, 0x772c67d}, {0xf0180c, 0x71b06b5}, {0x15278508, 0x20090785}, {0x138200e, 0x8238811}, {0x1537a108, 0x200948de}, {0x1547bd08, 0x200d89cc}, {0x1557d908, 0x200dca79}, {0x1567311d, 0x98020b47}, {0x1577a11d, 0x980a4c23}, {0x15873124, 0xba028cff}, {0x1597a124, 0xba0acddb}, {0x15a7312b, 0xdc030eb7}, {0x15b7a12b, 0xdc0b4f79}, {0x30000000, 0x0}, {0x30000000, 0x0}, {0x30000000, 0x0}, {0x30000000, 0x0}, {0x30000000, 0x0}, {0x30000000, 0x0}, {0x30000000, 0x0}, {0x30000000, 0x0}},
    {{0x0, 0x0}, {0x2034600, 0x140001f}, {0x20a4402, 0x24080b8}, {0x2114204, 0x3410151}, {0x14e8000f, 0x75000247}, {0x590a06, 0x40982c4}, {0x14f81c0f, 0x75004385}, {0x39e7407, 0x571c3c3}, {0x2e15a08, 0x55a043d}, {0x1508380f, 0x750484e5}, {0x1518540f, 0x7504c641}, {0xef1e0b, 0x71ac68a}, {0x2f0580c, 0x75b06ca}, {0x1528700f, 0x7509079a}, {0x3f77e0d, 0x87b4805}, {0x15388c0f, 0x750948f4}, {0x1548a80f, 0x750d89d7}, {0x1558c40f, 0x750dca84}, {0x1568381d, 0x98060b54}, {0x1578a81d, 0x980e4c30}, {0x15883824, 0xba068d0c}, {0x1598a824, 0xba0ecde8}, {0x15a8382b, 0xdc070ec4}, {0x15b8a82b, 0xdc0f4f85}, {0x30000000, 0x0}, {0x30000000, 0x0}, {0x30000000, 0x0}, {0x30000000, 0x0}, {0x30000000, 0x0}, {0x30000000, 0x0}, {0x30000000, 0x0}, {0x30000000, 0x0}},
    {{0x0, 0x0}, {0x2434e00, 0x1480020}, {0x24a4c02, 0x24880b9}, {0x2514a04, 0x3490152}, {0x14e90016, 0x64000252}, {0x2a474d32, 0x4e8242d0}, {0x3db7e06, 0x4798342}, {0x14f91c16, 0x6400439b}, {0x1e13a08, 0x53a0434}, {0x15093816, 0x640484fb}, {0x15195416, 0x6404c656}, {0x2af560b, 0x752c69e}, {0x1722c0c, 0x72b0711}, {0x15297016, 0x640907b0}, {0x3b7760d, 0x8734802}, {0x15398c16, 0x6409490a}, {0x1549a816, 0x640d89e2}, {0x1559c416, 0x640dca8f}, {0x15693f1d, 0x98060b62}, {0x1579af1d, 0x980e4c3e}, {0x15893f24, 0xba068d1a}, {0x1599af24, 0xba0ecdf6}, {0x15a93f2b, 0xdc070ed0}, {0x15b9af2b, 0xdc0f4f91}, {0x30000000, 0x0}, {0x30000000, 0x0}, {0x30000000, 0x0}, {0x30000000, 0x0}, {0x30000000, 0x0}, {0x30000000, 0x0}, {0x30000000, 0x0}, {0x30000000, 0x0}},
    {{0x0, 0x0}, {0x2835600, 0x1500022}, {0x28a5402, 0x25080bb}, {0x2915204, 0x3510154}, {0x2a261531, 0x158041d5}, {0x14ea070f, 0x7500025d}, {0x29b5606, 0x4518334}, {0x14fa230f, 0x750043b1}, {0x2614a08, 0x54a0439}, {0x150a3f0f, 0x75048511}, {0x1692a0a, 0x62a858c}, {0x151a5b0f, 0x7504c66c}, {0x1f13a0c, 0x73b06ec}, {0x152a770f, 0x750907c6}, {0x78080e, 0x80b880a}, {0x153a930f, 0x7509491f}, {0x3f060f, 0x903c936}, {0x154aaf0f, 0x750d89ed}, {0x155acb0f, 0x750dca99}, {0x156a461d, 0x98060b70}, {0x157ab61d, 0x980e4c4c}, {0x158a4624, 0xba068d28}, {0x159ab624, 0xba0ece04}, {0x15aa462b, 0xdc070edc}, {0x15bab62b, 0xdc0f4f9d}, {0x30000000, 0x0}, {0x30000000, 0x0}, {0x30000000, 0x0}, {0x30000000, 0x0}, {0x30000000, 0x0}, {0x30000000, 0x0}, {0x30000000, 0x0}},
    {{0x0, 0x0}, {0x2c35e00, 0x1580023}, {0x2ca5c02, 0x25880bc}, {0x2d15a04, 0x3590155}, {0x2a271532, 0x168041d6}, {0x14eb0716, 0x64000268}, {0x1b0606, 0x4018319}, {0x14fb2316, 0x640043c7}, {0x3216208, 0x5620440}, {0x150b3f16, 0x64048527}, {0x229420a, 0x6428595}, {0x151b5b16, 0x6404c681}, {0x3f0780c, 0x77b06d7}, {0x152b7716, 0x640907db}, {0x1b8300e, 0x8338818}, {0x153b9316, 0x64094935}, {0xff1e0f, 0x91bc93d}, {0x154baf16, 0x640d89f7}, {0x155bcb16, 0x640dcaa4}, {0x156b4d1d, 0x98060b7e}, {0x157bbd1d, 0x980e4c5a}, {0x158b4d24, 0xba068d36}, {0x159bbd24, 0xba0ece12}, {0x15ab4d2b, 0xdc070ee9}, {0x15bbbd2b, 0xdc0f4fa9}, {0x30000000, 0x0}, {0x30000000, 0x0}, {0x30000000, 0x0}, {0x30000000, 0x0}, {0x30000000, 0x0}, {0x30000000, 0x0}, {0x30000000, 0x0}},
    {{0x0, 0x0}, {0x3036600, 0x1600024}, {0x30a6402, 0x26080bd}, {0x3116204, 0x3610156}, {0x2a280033, 0x28081d8}, {0x14ec1c01, 0x3100027e}, {0x35a6c06, 0x469830f}, {0x14fc3801, 0x310443dd}, {0x3e17a08, 0x57a044a}, {0x150c5401, 0x3104853d}, {0x2e95a0a, 0x65a859c}, {0x151c7001, 0x3108c697}, {0x370680c, 0x76b06d0}, {0x152c8c01, 0x310907f1}, {0x2b8500e, 0x8538823}, {0x7c080f, 0x90bc8b7}, {0x153ca801, 0x310d494b}, {0x154cc401, 0x310d8a02}, {0x155cd20f, 0x750dcaaf}, {0x156c541d, 0x98060b8b}, {0x157cc41d, 0x980e4c67}, {0x158c5424, 0xba068d43}, {0x159cc424, 0xba0ece1f}, {0x15ac542b, 0xdc070ef5}, {0x15bcc42b, 0xdc0f4fb5}, {0x30000000, 0x0}, {0x30000000, 0x0}, {0x30000000, 0x0}, {0x30000000, 0x0}, {0x30000000, 0x0}, {0x30000000, 0x0}, {0x30000000, 0x0}},
    {{0x0, 0x0}, {0x3436e00, 0x1680026}, {0x34a6c02, 0x26880bf}, {0x3516a04, 0x3690158}, {0x2a290034, 0x38081d9}, {0x14ed1c08, 0x20000294}, {0x21a4406, 0x4418303}, {0x14fd3808, 0x200443f3}, {0x620c08, 0x50a044f}, {0x150d5408, 0x20048553}, {0x3a9720a, 0x67285a5}, {0x12c200b, 0x722c60b}, {0x151d7008, 0x2008c6ad}, {0x74080d, 0x80b475e}, {0x152d8c08, 0x20090806}, {0xfb1e0e, 0x91b8890}, {0x153da808, 0x200d4960}, {0x154dc408, 0x200d8a0d}, {0x155dd216, 0x640dcabd}, {0x156d5b1d, 0x98060b99}, {0x157dcb1d, 0x980e4c75}, {0x158d5b24, 0xba068d51}, {0x159dcb24, 0xba0ece2d}, {0x15ad5b2b, 0xdc070f01}, {0x15bdcb2b, 0xdc0f4fc1}, {0x30000000, 0x0}, {0x30000000, 0x0}, {0x30000000, 0x0}, {0x30000000, 0x0}, {0x30000000, 0x0}, {0x30000000, 0x0}, {0x30000000, 0x0}},
    {{0x0, 0x0}, {0x3837600, 0x1700027}, {0x38a7402, 0x27080c0}, {0x3917204, 0x3710159}, {0x2a2a0733, 0x98081da}, {0x14ee2301, 0x310002aa}, {0x15a2c06, 0x42982f9}, {0x14fe3f01, 0x31044409}, {0xe21c08, 0x51a0453}, {0x150e5b01, 0x31048569}, {0xaa140a, 0x61285b0}, {0x26b4e0a, 0x64a85ee}, {0x151e7701, 0x3108c6c2}, {0x3f37e0c, 0x87b0758}, {0x152e9301, 0x3109081c}, {0x27b4e0e, 0x94b88a2}, {0x153eaf01, 0x310d496b}, {0x154ecb01, 0x310d8a18}, {0x155ed90f, 0x750dcacb}, {0x156e621d, 0x98060ba7}, {0x157ed21d, 0x980e4c83}, {0x158e6224, 0xba068d5f}, {0x159ed224, 0xba0ece3b}, {0x15ae622b, 0xdc070f0d}, {0x15bed22b, 0xdc0f4fcd}, {0x30000000, 0x0}, {0x30000000, 0x0}, {0x30000000, 0x0}, {0x30000000, 0x0}, {0x30000000, 0x0}, {0x30000000, 0x0}, {0x30000000, 0x0}},
    {{0x0, 0x0}, {0x3c37e00, 0x1780028}, {0x3ca7c02, 0x27880c1}, {0x3d17a04, 0x379015a}, {0x2a2b0734, 0xa8081dc}, {0x2a402a33, 0x2c82024f}, {0x14ef2308, 0x200002c0}, {0x14ff3f08, 0x2004441f}, {0x1a23408, 0x532045d}, {0x2a55209, 0x65244ec}, {0x150f5b08, 0x2004857e}, {0x36b6e0a, 0x66a85f8}, {0x151f7708, 0x2008c6d8}, {0xf4180d, 0x81b4762}, {0x152f9308, 0x20090832}, {0x2bb560e, 0x95388a4}, {0x153faf08, 0x200d4976}, {0x154fcb08, 0x200d8a23}, {0x155fd916, 0x640dcad9}, {0x156f691d, 0x98060bb5}, {0x157fd91d, 0x980e4c91}, {0x158f6924, 0xba068d6d}, {0x159fd924, 0xba0ece49}, {0x15af692b, 0xdc070f19}, {0x15bfd92b, 0xdc0f4fd9}, {0x30000000, 0x0}, {0x30000000, 0x0}, {0x30000000, 0x0}, {0x30000000, 0x0}, {0x30000000, 0x0}, {0x30000000, 0x0}, {0x30000000, 0x0}},
    {{0x0, 0x0}, {0x40001, 0x100402a}, {0xb0602, 0x20080c3}, {0x120404, 0x301015c}, {0x15c00002, 0x310001f0}, {0x15d00e10, 0x750042d8}, {0x3997206, 0x47182e8}, {0x15e02a10, 0x75008438}, {0x2624c08, 0x54a0465}, {0x3256209, 0x66244f0}, {0x15f04610, 0x7504c597}, {0xec180b, 0x71ac608}, {0x16006210, 0x750506f0}, {0x2b4500d, 0x8534776}, {0x16107e10, 0x7509484a}, {0x3fb7e0e, 0x97b88b2}, {0x16209a10, 0x75098982}, {0x1630b610, 0x750dca2f}, {0x1640001e, 0x98020ae8}, {0x1650701e, 0x980a4bc4}, {0x16600025, 0xba028ca0}, {0x16707025, 0xba0acd7c}, {0x1680002c, 0xdc030e58}, {0x1690702c, 0xdc0b4f26}, {0x30000000, 0x0}, {0x30000000, 0x0}, {0x30000000, 0x0}, {0x30000000, 0x0}, {0x30000000, 0x0}, {0x30000000, 0x0}, {0x30000000, 0x0}, {0x30000000, 0x0}},
    {{0x0, 0x0}, {0x440801, 0x108402b}, {0x4b0e02, 0x20880c4}, {0x520c04, 0x309015d}, {0x15c10009, 0x200001fb}, {0xd71e05, 0x4194270}, {0x15d10e17, 0x640042ee}, {0x21e4407, 0x541c3b3}, {0x15e12a17, 0x6400844e}, {0x2654a09, 0x64a44e9}, {0x15f14617, 0x6404c5ac}, {0x2ac500b, 0x752c61c}, {0x16016217, 0x64050706}, {0x234400d, 0x8434771}, {0x16117e17, 0x64094860}, {0x3bb760e, 0x97388af}, {0x16219a17, 0x6409898d}, {0x1631b617, 0x640dca3a}, {0x1641071e, 0x98020af6}, {0x1651771e, 0x980a4bd2}, {0x16610725, 0xba028cae}, {0x16717725, 0xba0acd8a}, {0x1681072c, 0xdc030e66}, {0x1691772c, 0xdc0b4f32}, {0x30000000, 0x0}, {0x30000000, 0x0}, {0x30000000, 0x0}, {0x30000000, 0x0}, {0x30000000, 0x0}, {0x30000000, 0x0}, {0x30000000, 0x0}, {0x30000000, 0x0}},
    {{0x0, 0x0}, {0x841001, 0x110402c}, {0x8b1602, 0x21080c5}, {0x921404, 0x311015e}, {0x15c20702, 0x31000206}, {0x1d73e05, 0x439427c}, {0x15d21510, 0x75004304}, {0x19e3407, 0x531c3ad}, {0x15e23110, 0x75008464}, {0x3656a09, 0x66a44f3}, {0x15f24d10, 0x7504c5c2}, {0x3ec780b, 0x77ac62a}, {0x16026910, 0x7505071b}, {0x274480d, 0x84b4773}, {0x16128510, 0x75094875}, {0xbc100f, 0x913c8ba}, {0x1622a110, 0x75098998}, {0x1632bd10, 0x750dca44}, {0x16420e1e, 0x98020b04}, {0x16527e1e, 0x980a4be0}, {0x16620e25, 0xba028cbc}, {0x16727e25, 0xba0acd98}, {0x16820e2c, 0xdc030e74}, {0x16927e2c, 0xdc0b4f3e}, {0x30000000, 0x0}, {0x30000000, 0x0}, {0x30000000, 0x0}, {0x30000000, 0x0}, {0x30000000, 0x0}, {0x30000000, 0x0}, {0x30000000, 0x0}, {0x30000000, 0x0}},
    {{0x0, 0x0}, {0xc41801, 0x118402d}, {0xcb1e02, 0x21880c6}, {0xd21c04, 0x319015f}, {0x15c30709, 0x20000211}, {0x3176605, 0x4614289}, {0x15d31517, 0x6400431a}, {0x25e4c07, 0x549c3b5}, {0x15e33117, 0x6400847a}, {0x3e57a09, 0x67a44f9}, {0x15f34d17, 0x6404c5d7}, {0x12d220b, 0x722c636}, {0x16036917, 0x64050731}, {0x3b4700d, 0x8734781}, {0x16138517, 0x6409488b}, {0x1bc300f, 0x933c8c5}, {0x1623a117, 0x640989a2}, {0x1633bd17, 0x640dca4f}, {0x1643151e, 0x98020b11}, {0x1653851e, 0x980a4bed}, {0x16631525, 0xba028cc9}, {0x16738525, 0xba0acda5}, {0x1683152c, 0xdc030e81}, {0x1693852c, 0xdc0b4f4a}, {0x30000000, 0x0}, {0x30000000, 0x0}, {0x30000000, 0x0}, {0x30000000, 0x0}, {0x30000000, 0x0}, {0x30000000, 0x0}, {0x30000000, 0x0}, {0x30000000, 0x0}},
    {{0x0, 0x0}, {0x1042001, 0x120402f}, {0x10b2602, 0x22080c8}, {0x1122404, 0x3210161}, {0x15c40e02, 0x3100021c}, {0x180006, 0x4018295}, {0x15d42a02, 0x31004330}, {0x2de5c07, 0x559c3ba}, {0x15e44602, 0x31048490}, {0x660c09, 0x60a44ff}, {0x15f46202, 0x3104c5ed}, {0x2ed5a0b, 0x75ac649}, {0x16047e02, 0x31090747}, {0x35020d, 0x8034786}, {0x16149a02, 0x310948a0}, {0x2bc500f, 0x953c8d0}, {0x1624b602, 0x310d89ad}, {0x1634d202, 0x310dca5a}, {0x16441c1e, 0x98020b1f}, {0x16548c1e, 0x980a4bfb}, {0x16641c25, 0xba028cd7}, {0x16748c25, 0xba0acdb3}, {0x16841c2c, 0xdc030e8f}, {0x16948c2c, 0xdc0b4f57}, {0x30000000, 0x0}, {0x30000000, 0x0}, {0x30000000, 0x0}, {0x30000000, 0x0}, {0x30000000, 0x0}, {0x30000000, 0x0}, {0x30000000, 0x0}, {0x30000000, 0x0}},
    {{0x0, 0x0}, {0x1442801, 0x1284030}, {0x14b2e02, 0x22880c9}, {0x1522c04, 0x3290162}, {0x15c50e09, 0x20000227}, {0x1582806, 0x42982a2}, {0x15d52a09, 0x20004346}, {0x35e6c07, 0x569c3bf}, {0x15e54609, 0x200484a6}, {0x1262409, 0x6224506}, {0x15f56209, 0x2004c603}, {0xae140b, 0x712c65d}, {0x16057e09, 0x2009075c}, {0x135220d, 0x8234790}, {0x16159a09, 0x200948b6}, {0x37c680f, 0x96bc8d6}, {0x1625b609, 0x200d89b8}, {0x1635d209, 0x200dca65}, {0x1645231e, 0x98020b2d}, {0x1655931e, 0x980a4c09}, {0x16652325, 0xba028ce5}, {0x16759325, 0xba0acdc1}, {0x1685232c, 0xdc030e9d}, {0x1695932c, 0xdc0b4f63}, {0x30000000, 0x0}, {0x30000000, 0x0}, {0x30000000, 0x0}, {0x30000000, 0x0}, {0x30000000, 0x0}, {0x30000000, 0x0}, {0x30000000, 0x0}, {0x30000000, 0x0}},
    {{0x0, 0x0}, {0x1843001, 0x1304031}, {0x18b3602, 0x23080ca}, {0x1923404, 0x3310163}, {0x15c61502, 0x31000232}, {0x2584806, 0x44982ae}, {0x15d63102, 0x3100435c}, {0x1f0607, 0x501c3c9}, {0x15e64d02, 0x310484bc}, {0x2264409, 0x6424512}, {0x15f66902, 0x3104c618}, {0x22e440b, 0x742c66d}, {0x16068502, 0x31090772}, {0x235420d, 0x843479c}, {0x338600e, 0x8638827}, {0x1616a102, 0x310948cc}, {0x1626bd02, 0x310d89c3}, {0x1636d902, 0x310dca70}, {0x16462a1e, 0x98020b3b}, {0x16569a1e, 0x980a4c17}, {0x16662a25, 0xba028cf3}, {0x16769a25, 0xba0acdcf}, {0x16862a2c, 0xdc030eab}, {0x16969a2c, 0xdc0b4f6f}, {0x30000000, 0x0}, {0x30000000, 0x0}, {0x30000000, 0x0}, {0x30000000, 0x0}, {0x30000000, 0x0}, {0x30000000, 0x0}, {0x30000000, 0x0}, {0x30000000, 0x0}},
    {{0x0, 0x0}, {0x1c43801, 0x1384033}, {0x1cb3e02, 0x23880cc}, {0x1d23c04, 0x3390165}, {0x15c71509, 0x2000023d}, {0x2a464d31, 0x4d8242ba}, {0x15d73109, 0x20004372}, {0xdf1e07, 0x519c3d0}, {0x15e74d09, 0x200484d2}, {0x2a65409, 0x6524518}, {0x15f76909, 0x2004c62e}, {0x3ee7c0b, 0x77ac680}, {0x16078509, 0x20090787}, {0x335620d, 0x86347a5}, {0x278480e, 0x84b8820}, {0x1617a109, 0x200948e1}, {0x1627bd09, 0x200d89ce}, {0x1637d909, 0x200dca7a}, {0x1647311e, 0x98020b48}, {0x1657a11e, 0x980a4c24}, {0x16673125, 0xba028d00}, {0x1677a125, 0xba0acddc}, {0x1687312c, 0xdc030eb8}, {0x1697a12c, 0xdc0b4f7b}, {0x30000000, 0x0}, {0x30000000, 0x0}, {0x30000000, 0x0}, {0x30000000, 0x0}, {0x30000000, 0x0}, {0x30000000, 0x0}, {0x30000000, 0x0}, {0x30000000, 0x0}},
    {{0x0, 0x0}, {0x2044001, 0x1404034}, {0x20b4602, 0x24080cd}, {0x2124404, 0x3410166}, {0x15c80010, 0x75000248}, {0x991206, 0x41182c7}, {0x15d81c10, 0x75004388}, {0x15f2e07, 0x529c3d5}, {0x1222408, 0x5220456}, {0x15e83810, 0x750484e8}, {0x15f85410, 0x7504c643}, {0x16f2e0b, 0x72ac68f}, {0x330600c, 0x76306cd}, {0x16087010, 0x7509079d}, {0x1f8380e, 0x83b881b}, {0x16188c10, 0x750948f7}, {0x1628a810, 0x750d89d8}, {0x1638c410, 0x750dca85}, {0x1648381e, 0x98060b56}, {0x1658a81e, 0x980e4c32}, {0x16683825, 0xba068d0e}, {0x1678a825, 0xba0ecdea}, {0x1688382c, 0xdc070ec6}, {0x1698a82c, 0xdc0f4f87}, {0x30000000, 0x0}, {0x30000000, 0x0}, {0x30000000, 0x0}, {0x30000000, 0x0}, {0x30000000, 0x0}, {0x30000000, 0x0}, {0x30000000, 0x0}, {0x30000000, 0x0}},
    {{0x0, 0x0}, {0x2444801, 0x1484035}, {0x24b4e02, 0x24880ce}, {0x2524c04, 0x3490167}, {0x2a2c1c31, 0x1c80c1dd}, {0x15c90017, 0x64000253}, {0x15c2807, 0x429c351}, {0x15d91c17, 0x6400439e}, {0x3a17208, 0x5720447}, {0x15e93817, 0x640484fe}, {0x1a9320a, 0x6328590}, {0x15f95417, 0x6404c659}, {0x1b2340c, 0x7330715}, {0x16097017, 0x640907b3}, {0xf8180e, 0x81b880f}, {0x16198c17, 0x6409490c}, {0x3fe7c0f, 0x97bc934}, {0x1629a817, 0x640d89e3}, {0x1639c417, 0x640dca90}, {0x16493f1e, 0x98060b64}, {0x1659af1e, 0x980e4c40}, {0x16693f25, 0xba068d1c}, {0x1679af25, 0xba0ecdf8}, {0x16893f2c, 0xdc070ed2}, {0x1699af2c, 0xdc0f4f93}, {0x30000000, 0x0}, {0x30000000, 0x0}, {0x30000000, 0x0}, {0x30000000, 0x0}, {0x30000000, 0x0}, {0x30000000, 0x0}, {0x30000000, 0x0}},
    {{0x0, 0x0}, {0x2845001, 0x1504037}, {0x28b5602, 0x25080d0}, {0x2925404, 0x3510169}, {0x2a2d1c32, 0x1d80c1df}, {0x15ca0710, 0x7500025e}, {0x39b7606, 0x471833f}, {0x15da2310, 0x750043b4}, {0x220408, 0x502044c}, {0x15ea3f10, 0x75048514}, {0x2694a0a, 0x64a8598}, {0x15fa5b10, 0x7504c66f}, {0x2f15a0c, 0x75b06f6}, {0x160a7710, 0x750907c8}, {0x238400e, 0x843881d}, {0x161a9310, 0x75094922}, {0xbf160f, 0x913c93c}, {0x162aaf10, 0x750d89ee}, {0x163acb10, 0x750dca9b}, {0x164a461e, 0x98060b72}, {0x165ab61e, 0x980e4c4e}, {0x166a4625, 0xba068d2a}, {0x167ab625, 0xba0ece06}, {0x168a462c, 0xdc070ede}, {0x169ab62c, 0xdc0f4f9f}, {0x30000000, 0x0}, {0x30000000, 0x0}, {0x30000000, 0x0}, {0x30000000, 0x0}, {0x30000000, 0x0}, {0x30000000, 0x0}, {0x30000000, 0x0}},
    {{0x0, 0x0}, {0x2c45801, 0x1584038}, {0x2cb5e02, 0x25880d1}, {0x2d25c04, 0x359016a}, {0x2a2e2331, 0x2380c1e0}, {0x15cb0717, 0x6400026b}, {0x21b4606, 0x441832f}, {0x15db2317, 0x640043ca}, {0xa21408, 0x5120452}, {0x15eb3f17, 0x64048529}, {0x329620a, 0x662859f}, {0x15fb5b17, 0x6404c684}, {0x2714a0c, 0x74b06f2}, {0x160b7717, 0x640907de}, {0x2f8580e, 0x85b8824}, {0x161b9317, 0x64094938}, {0x1bf360f, 0x933c946}, {0x162baf17, 0x640d89f9}, {0x163bcb17, 0x640dcaa6}, {0x164b4d1e, 0x98060b7f}, {0x165bbd1e, 0x980e4c5b}, {0x166b4d25, 0xba068d37}, {0x167bbd25, 0xba0ece13}, {0x168b4d2c, 0xdc070eea}, {0x169bbd2c, 0xdc0f4fab}, {0x30000000, 0x0}, {0x30000000, 0x0}, {0x30000000, 0x0}, {0x30000000, 0x0}, {0x30000000, 0x0}, {0x30000000, 0x0}, {0x30000000, 0x0}},
    {{0x0, 0x0}, {0x3046001, 0x1604039}, {0x30b6602, 0x26080d2}, {0x3126404, 0x361016b}, {0x2a2f2332, 0x2480c1e1}, {0x15cc1c02, 0x31000281}, {0x5b0e06, 0x409831c}, {0x15dc3802, 0x310443e0}, {0x1622c08, 0x52a0459}, {0x15ec5402, 0x3104853f}, {0x3e97a0a, 0x67a85a8}, {0x15fc7002, 0x3108c69a}, {0x131220c, 0x72306e3}, {0x160c8c02, 0x310907f4}, {0x3b8700e, 0x873882e}, {0x13f260f, 0x923c940}, {0x161ca802, 0x310d494d}, {0x162cc402, 0x310d8a04}, {0x163cd210, 0x750dcab1}, {0x164c541e, 0x98060b8d}, {0x165cc41e, 0x980e4c69}, {0x166c5425, 0xba068d45}, {0x167cc425, 0xba0ece21}, {0x168c542c, 0xdc070ef6}, {0x169cc42c, 0xdc0f4fb7}, {0x30000000, 0x0}, {0x30000000, 0x0}, {0x30000000, 0x0}, {0x30000000, 0x0}, {0x30000000, 0x0}, {0x30000000, 0x0}, {0x30000000, 0x0}},
    {{0x0, 0x0}, {0x3446801, 0x168403b}, {0x34b6e02, 0x26880d4}, {0x3526c04, 0x369016d}, {0x2a300e33, 0x108101e3}, {0x15cd1c09, 0x20000297}, {0x2a4a3f33, 0x41828312}, {0x15dd3809, 0x200443f6}, {0x2224408, 0x5420462}, {0x15ed5409, 0x20048555}, {0xea1c0a, 0x61a85b2}, {0x15fd7009, 0x2008c6af}, {0xb1120c, 0x71306df}, {0x160d8c09, 0x20090809}, {0x790a0e, 0x80b8836}, {0x27c480f, 0x94bc8cd}, {0x161da809, 0x200d4961}, {0x162dc409, 0x200d8a0e}, {0x163dd217, 0x640dcabf}, {0x164d5b1e, 0x98060b9b}, {0x165dcb1e, 0x980e4c77}, {0x166d5b25, 0xba068d53}, {0x167dcb25, 0xba0ece2f}, {0x168d5b2c, 0xdc070f02}, {0x169dcb2c, 0xdc0f4fc3}, {0x30000000, 0x0}, {0x30000000, 0x0}, {0x30000000, 0x0}, {0x30000000, 0x0}, {0x30000000, 0x0}, {0x30000000, 0x0}, {0x30000000, 0x0}},
    {{0x0, 0x0}, {0x3847001, 0x170403c}, {0x38b7602, 0x27080d5}, {0x3927404, 0x371016e}, {0x2a310e34, 0x118101e4}, {0x15ce2302, 0x310002ad}, {0x29a5406, 0x4518308}, {0x15de3f02, 0x3104440c}, {0x2e25c08, 0x55a0469}, {0x15ee5b02, 0x3104856b}, {0x16a2c0a, 0x62a85b7}, {0x2eb5e0a, 0x65a85f2}, {0x15fe7702, 0x3108c6c5}, {0x134200d, 0x8234764}, {0x160e9302, 0x3109081f}, {0x33b660e, 0x96388a8}, {0x161eaf02, 0x310d496c}, {0x162ecb02, 0x310d8a19}, {0x163ed910, 0x750dcacd}, {0x164e621e, 0x98060ba9}, {0x165ed21e, 0x980e4c85}, {0x166e6225, 0xba068d61}, {0x167ed225, 0xba0ece3d}, {0x168e622c, 0xdc070f0e}, {0x169ed22c, 0xdc0f4fcf}, {0x30000000, 0x0}, {0x30000000, 0x0}, {0x30000000, 0x0}, {0x30000000, 0x0}, {0x30000000, 0x0}, {0x30000000, 0x0}, {0x30000000, 0x0}},
    {{0x0, 0x0}, {0x3c47801, 0x178403d}, {0x3cb7e02, 0x27880d6}, {0x3d27c04, 0x379016f}, {0x2a321533, 0x178101e5}, {0x15cf2309, 0x200002c2}, {0x2a493834, 0x3b8282fc}, {0x15df3f09, 0x20044422}, {0x3626c08, 0x56a046f}, {0x15ef5b09, 0x20048581}, {0x1ea3c0a, 0x63a85be}, {0x3eb7e0a, 0x67a85fe}, {0x15ff7709, 0x2008c6db}, {0x174280d, 0x82b4767}, {0x160f9309, 0x20090834}, {0xfc180f, 0x91bc8bb}, {0x161faf09, 0x200d4977}, {0x162fcb09, 0x200d8a24}, {0x163fd917, 0x640dcada}, {0x164f691e, 0x98060bb6}, {0x165fd91e, 0x980e4c92}, {0x166f6925, 0xba068d6e}, {0x167fd925, 0xba0ece4a}, {0x168f692c, 0xdc070f1a}, {0x169fd92c, 0xdc0f4fdb}, {0x30000000, 0x0}, {0x30000000, 0x0}, {0x30000000, 0x0}, {0x30000000, 0x0}, {0x30000000, 0x0}, {0x30000000, 0x0}, {0x30000000, 0x0}},
    {{0x0, 0x0}, {0x50201, 0x100403f}, {0xc0003, 0x200c0d8}, {0x130604, 0x3010171}, {0x16a00003, 0x310001f2}, {0x2a423133, 0x33820265}, {0x16b00e11, 0x750042db}, {0x16c02a11, 0x7500843b}, {0x3e27c08, 0x57a0476}, {0x1662c09, 0x62a4509}, {0x16d04611, 0x7504c599}, {0x16c280b, 0x72ac60d}, {0x16e06211, 0x750506f3}, {0x334600d, 0x863477a}, {0x16f07e11, 0x7509484d}, {0x17c280f, 0x92bc8c1}, {0x17009a11, 0x75098983}, {0x1710b611, 0x750dca30}, {0x1720001f, 0x98020aea}, {0x1730701f, 0x980a4bc6}, {0x17400026, 0xba028ca2}, {0x17507026, 0xba0acd7e}, {0x1760002d, 0xdc030e5a}, {0x1770702d, 0xdc0b4f28}, {0x30000000, 0x0}, {0x30000000, 0x0}, {0x30000000, 0x0}, {0x30000000, 0x0}, {0x30000000, 0x0}, {0x30000000, 0x0}, {0x30000000, 0x0}, {0x30000000, 0x0}},
    {{0x0, 0x0}, {0x450a01, 0x1084040}, {0x4c0803, 0x208c0d9}, {0x530e04, 0x3090172}, {0x16a1000a, 0x200001fd}, {0x1172605, 0x4214273}, {0x16b10e18, 0x640042f1}, {0x16c12a18, 0x64008451}, {0xa31608, 0x512047e}, {0x1a63409, 0x632450d}, {0x16d14618, 0x6404c5af}, {0x2ec580b, 0x75ac61e}, {0x16e16218, 0x64050709}, {0xf51a0d, 0x81b478d}, {0x16f17e18, 0x64094862}, {0x23c400f, 0x943c8ca}, {0x17019a18, 0x6409898e}, {0x1711b618, 0x640dca3b}, {0x1721071f, 0x98020af8}, {0x1731771f, 0x980a4bd4}, {0x17410726, 0xba028cb0}, {0x17517726, 0xba0acd8c}, {0x1761072d, 0xdc030e68}, {0x1771772d, 0xdc0b4f34}, {0x30000000, 0x0}, {0x30000000, 0x0}, {0x30000000, 0x0}, {0x30000000, 0x0}, {0x30000000, 0x0}, {0x30000000, 0x0}, {0x30000000, 0x0}, {0x30000000, 0x0}},
    {{0x0, 0x0}, {0x851201, 0x1104041}, {0x8c1003, 0x210c0da}, {0x931604, 0x3110173}, {0x16a20703, 0x31000208}, {0x2174605, 0x441427f}, {0x16b21511, 0x75004307}, {0x5f0e07, 0x509c3cb}, {0x16c23111, 0x75008467}, {0xe61c09, 0x61a4503}, {0x16d24d11, 0x7504c5c4}, {0x2d020b, 0x702c62c}, {0x16e26911, 0x7505071e}, {0x750a0d, 0x80b4789}, {0x16f28511, 0x75094878}, {0x1fc380f, 0x93bc8c8}, {0x1702a111, 0x75098999}, {0x1712bd11, 0x750dca46}, {0x17220e1f, 0x98020b05}, {0x17327e1f, 0x980a4be1}, {0x17420e26, 0xba028cbd}, {0x17527e26, 0xba0acd99}, {0x17620e2d, 0xdc030e75}, {0x17727e2d, 0xdc0b4f40}, {0x30000000, 0x0}, {0x30000000, 0x0}, {0x30000000, 0x0}, {0x30000000, 0x0}, {0x30000000, 0x0}, {0x30000000, 0x0}, {0x30000000, 0x0}, {0x30000000, 0x0}},
    {{0x0, 0x0}, {0xc51a01, 0x1184042}, {0xcc1803, 0x218c0db}, {0xd31e04, 0x3190174}, {0x16a3070a, 0x20000213}, {0x3576e05, 0x469428c}, {0x16b31518, 0x6400431d}, {0x3de7c07, 0x579c3c6}, {0x16c33118, 0x6400847d}, {0x1e63c09, 0x63a450f}, {0x16d34d18, 0x6404c5da}, {0x16d2a0b, 0x72ac639}, {0x16e36918, 0x64050734}, {0xb5120d, 0x813478c}, {0x16f38518, 0x6409488d}, {0x33c600f, 0x963c8d4}, {0x1703a118, 0x640989a4}, {0x1713bd18, 0x640dca51}, {0x1723151f, 0x98020b13}, {0x1733851f, 0x980a4bef}, {0x17431526, 0xba028ccb}, {0x17538526, 0xba0acda7}, {0x1763152d, 0xdc030e83}, {0x1773852d, 0xdc0b4f4c}, {0x30000000, 0x0}, {0x30000000, 0x0}, {0x30000000, 0x0}, {0x30000000, 0x0}, {0x30000000, 0x0}, {0x30000000, 0x0}, {0x30000000, 0x0}, {0x30000000, 0x0}},
    {{0x0, 0x0}, {0x1052201, 0x1204044}, {0x10c2003, 0x220c0dd}, {0x1132604, 0x3210176}, {0x16a40e03, 0x3100021e}, {0x580806, 0x4098298}, {0x16b42a03, 0x31004333}, {0x9f1607, 0x511c3ce}, {0x16c44603, 0x31048492}, {0x2664c09, 0x64a4515}, {0x16d46203, 0x3104c5f0}, {0x32d620b, 0x762c64b}, {0x16e47e03, 0x31090749}, {0x1f53a0d, 0x83b4799}, {0x16f49a03, 0x310948a3}, {0x3fc780f, 0x97bc8dd}, {0x1704b603, 0x310d89ae}, {0x1714d203, 0x310dca5b}, {0x17241c1f, 0x98020b21}, {0x17348c1f, 0x980a4bfd}, {0x17441c26, 0xba028cd9}, {0x17548c26, 0xba0acdb5}, {0x17641c2d, 0xdc030e91}, {0x17748c2d, 0xdc0b4f58}, {0x30000000, 0x0}, {0x30000000, 0x0}, {0x30000000, 0x0}, {0x30000000, 0x0}, {0x30000000, 0x0}, {0x30000000, 0x0}, {0x30000000, 0x0}, {0x30000000, 0x0}},
    {{0x0, 0x0}, {0x1452a01, 0x1284045}, {0x14c2803, 0x228c0de}, {0x1532e04, 0x3290177}, {0x16a50e0a, 0x20000229}, {0x2a454632, 0x478242a4}, {0x16b52a0a, 0x20004349}, {0x11f2607, 0x521c3d2}, {0x16c5460a, 0x200484a8}, {0x2e65c09, 0x65a4519}, {0x16d5620a, 0x2004c605}, {0x12e240b, 0x722c661}, {0x16e57e0a, 0x2009075f}, {0x2b5520d, 0x85347a1}, {0x16f59a0a, 0x200948b9}, {0xfd1a0f, 0x91bc8e7}, {0x1705b60a, 0x200d89b9}, {0x1715d20a, 0x200dca66}, {0x1725231f, 0x98020b2f}, {0x1735931f, 0x980a4c0b}, {0x17452326, 0xba028ce7}, {0x17559326, 0xba0acdc3}, {0x1765232d, 0xdc030e9f}, {0x1775932d, 0xdc0b4f64}, {0x30000000, 0x0}, {0x30000000, 0x0}, {0x30000000, 0x0}, {0x30000000, 0x0}, {0x30000000, 0x0}, {0x30000000, 0x0}, {0x30000000, 0x0}, {0x30000000, 0x0}},
    {{0x0, 0x0}, {0x1853201, 0x1304046}, {0x18c3003, 0x230c0df}, {0x1933604, 0x3310178}, {0x16a61503, 0x31000234}, {0x2985006, 0x45182b1}, {0x16b63103, 0x3100435f}, {0x19f3607, 0x531c3d9}, {0x16c64d03, 0x310484be}, {0x3666c09, 0x66a451e}, {0x16d66903, 0x3104c61b}, {0x26e4c0b, 0x74ac670}, {0x16e68503, 0x31090775}, {0x3b5720d, 0x87347ac}, {0x16f6a103, 0x310948ce}, {0x17d2a0f, 0x92bc8ec}, {0x1706bd03, 0x310d89c4}, {0x1716d903, 0x310dca71}, {0x17262a1f, 0x98020b3c}, {0x17369a1f, 0x980a4c18}, {0x17462a26, 0xba028cf4}, {0x17569a26, 0xba0acdd0}, {0x17662a2d, 0xdc030eac}, {0x17769a2d, 0xdc0b4f70}, {0x30000000, 0x0}, {0x30000000, 0x0}, {0x30000000, 0x0}, {0x30000000, 0x0}, {0x30000000, 0x0}, {0x30000000, 0x0}, {0x30000000, 0x0}, {0x30000000, 0x0}},
    {{0x0, 0x0}, {0x1c53a01, 0x1384048}, {0x1cc3803, 0x238c0e1}, {0x1d33e04, 0x339017a}, {0x16a7150a, 0x2000023f}, {0x3987006, 0x47182bc}, {0x16b7310a, 0x20004375}, {0x25f4e07, 0x549c3e1}, {0x16c74d0a, 0x200484d4}, {0x670e09, 0x60a452b}, {0x16d7690a, 0x2004c630}, {0x2f060b, 0x702c683}, {0x16e7850a, 0x2009078a}, {0xb6140d, 0x81347b7}, {0xf91a0e, 0x81b883a}, {0x16f7a10a, 0x200948e4}, {0x1707bd0a, 0x200d89cf}, {0x1717d90a, 0x200dca7c}, {0x1727311f, 0x98020b4a}, {0x1737a11f, 0x980a4c26}, {0x17473126, 0xba028d02}, {0x1757a126, 0xba0acdde}, {0x1767312d, 0xdc030eba}, {0x1777a12d, 0xdc0b4f7c}, {0x30000000, 0x0}, {0x30000000, 0x0}, {0x30000000, 0x0}, {0x30000000, 0x0}, {0x30000000, 0x0}, {0x30000000, 0x0}, {0x30000000, 0x0}, {0x30000000, 0x0}},
    {{0x0, 0x0}, {0x2054201, 0x1404049}, {0x20c4003, 0x240c0e2}, {0x2134604, 0x341017b}, {0x16a80011, 0x7500024a}, {0xd91a06, 0x41982c8}, {0x16b81c11, 0x7500438b}, {0x2df5e07, 0x559c3e6}, {0x16c83811, 0x750484ea}, {0x1272609, 0x6224532}, {0x16d85411, 0x7504c646}, {0x1af360b, 0x732c693}, {0x16e87011, 0x750907a0}, {0x1762c0d, 0x82b47bd}, {0x3f8780e, 0x87b8830}, {0x16f88c11, 0x750948fa}, {0x1708a811, 0x750d89da}, {0x1718c411, 0x750dca87}, {0x1728381f, 0x98060b58}, {0x1738a81f, 0x980e4c34}, {0x17483826, 0xba068d10}, {0x1758a826, 0xba0ecdec}, {0x1768382d, 0xdc070ec8}, {0x1778a82d, 0xdc0f4f88}, {0x30000000, 0x0}, {0x30000000, 0x0}, {0x30000000, 0x0}, {0x30000000, 0x0}, {0x30000000, 0x0}, {0x30000000, 0x0}, {0x30000000, 0x0}, {0x30000000, 0x0}},
    {{0x0, 0x0}, {0x2454a01, 0x148404a}, {0x24c4803, 0x248c0e3}, {0x2534e04, 0x349017c}, {0x2a331534, 0x188101e7}, {0x16a90018, 0x64000255}, {0x16b91c18, 0x640043a1}, {0x35f6e07, 0x569c3eb}, {0x16c93818, 0x64048500}, {0x1a73609, 0x6324539}, {0x6a0c0a, 0x60a85ad}, {0x16d95418, 0x6404c65c}, {0x710a0c, 0x70b06dc}, {0x16e97018, 0x640907b5}, {0x1792a0e, 0x82b883f}, {0x16f98c18, 0x6409490f}, {0x1ff3e0f, 0x93bc949}, {0x1709a818, 0x640d89e4}, {0x1719c418, 0x640dca91}, {0x17293f1f, 0x98060b66}, {0x1739af1f, 0x980e4c42}, {0x17493f26, 0xba068d1e}, {0x1759af26, 0xba0ecdfa}, {0x17693f2d, 0xdc070ed4}, {0x1779af2d, 0xdc0f4f94}, {0x30000000, 0x0}, {0x30000000, 0x0}, {0x30000000, 0x0}, {0x30000000, 0x0}, {0x30000000, 0x0}, {0x30000000, 0x0}, {0x30000000, 0x0}},
    {{0x0, 0x0}, {0x2855201, 0x150404c}, {0x28c5003, 0x250c0e5}, {0x2935604, 0x351017e}, {0x2a342a31, 0x2a8141e8}, {0x16aa0711, 0x75000260}, {0x9c1007, 0x411c34a}, {0x16ba2311, 0x750043b7}, {0x1e23c08, 0x53a0460}, {0x16ca3f11, 0x75048516}, {0x3696a0a, 0x66a85a1}, {0x16da5b11, 0x7504c671}, {0x720c0c, 0x70b0707}, {0x16ea7711, 0x750907cb}, {0x378680e, 0x86b882a}, {0x16fa9311, 0x75094925}, {0x17f2e0f, 0x92bc942}, {0x170aaf11, 0x750d89ef}, {0x171acb11, 0x750dca9c}, {0x172a461f, 0x98060b73}, {0x173ab61f, 0x980e4c4f}, {0x174a4626, 0xba068d2b}, {0x175ab626, 0xba0ece07}, {0x176a462d, 0xdc070ee0}, {0x177ab62d, 0xdc0f4fa0}, {0x30000000, 0x0}, {0x30000000, 0x0}, {0x30000000, 0x0}, {0x30000000, 0x0}, {0x30000000, 0x0}, {0x30000000, 0x0}, {0x30000000, 0x0}},
    {{0x0, 0x0}, {0x2c55a01, 0x158404d}, {0x2cc5803, 0x258c0e6}, {0x2d35e04, 0x359017f}, {0x2a352a32, 0x2b8141ea}, {0x16ab0718, 0x6400026d}, {0x35b6e06, 0x469833b}, {0x16bb2318, 0x640043cd}, {0x2a25408, 0x5520468}, {0x16cb3f18, 0x6404852c}, {0x2a040a, 0x60285ab}, {0x16db5b18, 0x6404c687}, {0x3f17a0c, 0x77b0702}, {0x16eb7718, 0x640907e1}, {0x39020e, 0x8038833}, {0x16fb9318, 0x6409493a}, {0x23f460f, 0x943c94c}, {0x170baf18, 0x640d89fa}, {0x171bcb18, 0x640dcaa7}, {0x172b4d1f, 0x98060b81}, {0x173bbd1f, 0x980e4c5d}, {0x174b4d26, 0xba068d39}, {0x175bbd26, 0xba0ece15}, {0x176b4d2d, 0xdc070eec}, {0x177bbd2d, 0xdc0f4fac}, {0x30000000, 0x0}, {0x30000000, 0x0}, {0x30000000, 0x0}, {0x30000000, 0x0}, {0x30000000, 0x0}, {0x30000000, 0x0}, {0x30000000, 0x0}},
    {{0x0, 0x0}, {0x3056201, 0x160404e}, {0x30c6003, 0x260c0e7}, {0x3136604, 0x3610180}, {0x2a363131, 0x318141eb}, {0x16ac1c03, 0x31000283}, {0x19b3606, 0x4318329}, {0x16bc3803, 0x310443e3}, {0x3226408, 0x562046c}, {0x16cc5403, 0x31048542}, {0x12a240a, 0x62285b4}, {0x16dc7003, 0x3108c69d}, {0x2b1520c, 0x75306f4}, {0x16ec8c03, 0x310907f6}, {0xb9120e, 0x8138838}, {0x16fca803, 0x310d4950}, {0x2ff5e0f, 0x95bc953}, {0x170cc403, 0x310d8a05}, {0x171cd211, 0x750dcab3}, {0x172c541f, 0x98060b8f}, {0x173cc41f, 0x980e4c6b}, {0x174c5426, 0xba068d47}, {0x175cc426, 0xba0ece23}, {0x176c542d, 0xdc070ef8}, {0x177cc42d, 0xdc0f4fb8}, {0x30000000, 0x0}, {0x30000000, 0x0}, {0x30000000, 0x0}, {0x30000000, 0x0}, {0x30000000, 0x0}, {0x30000000, 0x0}, {0x30000000, 0x0}},
    {{0x0, 0x0}, {0x3456a01, 0x1684050}, {0x34c6803, 0x268c0e9}, {0x3536e04, 0x3690182}, {0x2a373132, 0x328141ec}, {0x16ad1c0a, 0x20000299}, {0xdb1e06, 0x4198320}, {0x16bd380a, 0x200443f9}, {0x3a27408, 0x5720473}, {0x16cd540a, 0x20048558}, {0x1aa340a, 0x63285bb}, {0x16dd700a, 0x2008c6b2}, {0x231420c, 0x74306ef}, {0x16ed8c0a, 0x2009080c}, {0x239420e, 0x8438849}, {0x37e6c0f, 0x96bc92d}, {0x16fda80a, 0x200d4963}, {0x170dc40a, 0x200d8a10}, {0x171dd218, 0x640dcac1}, {0x172d5b1f, 0x98060b9d}, {0x173dcb1f, 0x980e4c79}, {0x174d5b26, 0xba068d55}, {0x175dcb26, 0xba0ece31}, {0x176d5b2d, 0xdc070f04}, {0x177dcb2d, 0xdc0f4fc5}, {0x30000000, 0x0}, {0x30000000, 0x0}, {0x30000000, 0x0}, {0x30000000, 0x0}, {0x30000000, 0x0}, {0x30000000, 0x0}, {0x30000000, 0x0}},
    {{0x0, 0x0}, {0x3857201, 0x1704051}, {0x38c7003, 0x270c0ea}, {0x3937604, 0x3710183}, {0x2a381c33, 0x1e8181f7}, {0x16ae2303, 0x310002af}, {0x39a7406, 0x4718313}, {0x16be3f03, 0x3104440f}, {0x630e08, 0x50a047b}, {0x16ce5b03, 0x3104856e}, {0x22a440a, 0x64285c0}, {0x3ab760a, 0x67285fc}, {0x16de7703, 0x3108c6c8}, {0x16ee9303, 0x31090821}, {0x2b9520e, 0x853884e}, {0x1bd320f, 0x933c8f0}, {0x16feaf03, 0x310d496e}, {0x170ecb03, 0x310d8a1a}, {0x171ed911, 0x750dcace}, {0x172e621f, 0x98060baa}, {0x173ed21f, 0x980e4c86}, {0x174e6226, 0xba068d62}, {0x175ed226, 0xba0ece3e}, {0x176e622d, 0xdc070f10}, {0x177ed22d, 0xdc0f4fd1}, {0x30000000, 0x0}, {0x30000000, 0x0}, {0x30000000, 0x0}, {0x30000000, 0x0}, {0x30000000, 0x0}, {0x30000000, 0x0}, {0x30000000, 0x0}},
    {{0x0, 0x0}, {0x3c57a01, 0x1784052}, {0x3cc7803, 0x278c0eb}, {0x3d37e04, 0x3790184}, {0x2a391c34, 0x1f818202}, {0x16af230a, 0x200002c5}, {0x31a6406, 0x461830d}, {0x16bf3f0a, 0x20044425}, {0x1232608, 0x5220482}, {0x16cf5b0a, 0x20048584}, {0x32a640a, 0x66285ca}, {0x6c080b, 0x70ac604}, {0x16df770a, 0x2008c6dd}, {0x1b4300d, 0x833476b}, {0x16ef930a, 0x20090837}, {0x2fc580f, 0x95bc8d1}, {0x16ffaf0a, 0x200d4978}, {0x170fcb0a, 0x200d8a25}, {0x171fd918, 0x640dcadc}, {0x172f691f, 0x98060bb8}, {0x173fd91f, 0x980e4c94}, {0x174f6926, 0xba068d70}, {0x175fd926, 0xba0ece4c}, {0x176f692d, 0xdc070f1c}, {0x177fd92d, 0xdc0f4fdd}, {0x30000000, 0x0}, {0x30000000, 0x0}, {0x30000000, 0x0}, {0x30000000, 0x0}, {0x30000000, 0x0}, {0x30000000, 0x0}, {0x30000000, 0x0}},
    {{0x0, 0x0}, {0x60401, 0x1004054}, {0xd0203, 0x200c0ed}, {0x140005, 0x3014186}, {0x17800004, 0x310001f3}, {0x170605, 0x4014269}, {0x17900e12, 0x750042df}, {0x17a02a12, 0x7500843f}, {0x1e33e08, 0x53a048c}, {0xa71609, 0x612452e}, {0x17b04612, 0x7504c59d}, {0x1ec380b, 0x73ac614}, {0x17c06212, 0x750506f7}, {0x374680d, 0x86b477d}, {0x17d07e12, 0x75094851}, {0x3d020f, 0x903c8e0}, {0x17e09a12, 0x75098985}, {0x17f0b612, 0x750dca31}, {0x18000020, 0x98020aec}, {0x18107020, 0x980a4bc8}, {0x18200027, 0xba028ca4}, {0x18307027, 0xba0acd80}, {0x1840002e, 0xdc030e5c}, {0x1850702e, 0xdc0b4f2a}, {0x30000000, 0x0}, {0x30000000, 0x0}, {0x30000000, 0x0}, {0x30000000, 0x0}, {0x30000000, 0x0}, {0x30000000, 0x0}, {0x30000000, 0x0}, {0x30000000, 0x0}},
    {{0x0, 0x0}, {0x460c01, 0x1084055}, {0x4d0a03, 0x208c0ee}, {0x540805, 0x3094187}, {0x1781000b, 0x200001fe}, {0x1572e05, 0x4294276}, {0x17910e19, 0x640042f5}, {0x17a12a19, 0x64008455}, {0x2634e08, 0x54a0491}, {0x3a67409, 0x6724523}, {0x17b14619, 0x6404c5b3}, {0x32c600b, 0x762c620}, {0x17c16219, 0x6405070d}, {0x1752a0d, 0x82b4792}, {0x17d17e19, 0x64094866}, {0x3bc700f, 0x973c8da}, {0x17e19a19, 0x6409898f}, {0x17f1b619, 0x640dca3c}, {0x18010720, 0x98020af9}, {0x18117720, 0x980a4bd5}, {0x18210727, 0xba028cb1}, {0x18317727, 0xba0acd8d}, {0x1841072e, 0xdc030e69}, {0x1851772e, 0xdc0b4f36}, {0x30000000, 0x0}, {0x30000000, 0x0}, {0x30000000, 0x0}, {0x30000000, 0x0}, {0x30000000, 0x0}, {0x30000000, 0x0}, {0x30000000, 0x0}, {0x30000000, 0x0}},
    {{0x0, 0x0}, {0x861401, 0x1104056}, {0x8d1203, 0x210c0ef}, {0x941005, 0x3114188}, {0x17820704, 0x31000209}, {0x2574e05, 0x4494282}, {0x17921512, 0x7500430b}, {0x17a23112, 0x7500846b}, {0x3236608, 0x5620498}, {0x3e67c09, 0x67a4525}, {0x17b24d12, 0x7504c5c8}, {0x6d0a0b, 0x70ac62f}, {0x17c26912, 0x75050722}, {0x3756a0d, 0x86b47a8}, {0x17d28512, 0x7509487c}, {0xbd120f, 0x913c8e5}, {0x17e2a112, 0x7509899a}, {0x17f2bd12, 0x750dca47}, {0x18020e20, 0x98020b07}, {0x18127e20, 0x980a4be3}, {0x18220e27, 0xba028cbf}, {0x18327e27, 0xba0acd9b}, {0x18420e2e, 0xdc030e77}, {0x18527e2e, 0xdc0b4f42}, {0x30000000, 0x0}, {0x30000000, 0x0}, {0x30000000, 0x0}, {0x30000000, 0x0}, {0x30000000, 0x0}, {0x30000000, 0x0}, {0x30000000, 0x0}, {0x30000000, 0x0}},
    {{0x0, 0x0}, {0xc61c01, 0x1184057}, {0xcd1a03, 0x218c0f0}, {0xd41805, 0x3194189}, {0x1783070b, 0x20000214}, {0x2a444631, 0x4682428e}, {0x17931519, 0x64004321}, {0x1df3e07, 0x539c3dc}, {0x17a33119, 0x64008481}, {0x3266409, 0x662451c}, {0x17b34d19, 0x6404c5de}, {0x1ad320b, 0x732c63d}, {0x17c36919, 0x64050738}, {0x2754a0d, 0x84b479e}, {0x17d38519, 0x64094892}, {0x7d0a0f, 0x90bc8e3}, {0x17e3a119, 0x640989a5}, {0x17f3bd19, 0x640dca52}, {0x18031520, 0x98020b15}, {0x18138520, 0x980a4bf1}, {0x18231527, 0xba028ccd}, {0x18338527, 0xba0acda9}, {0x1843152e, 0xdc030e85}, {0x1853852e, 0xdc0b4f4e}, {0x30000000, 0x0}, {0x30000000, 0x0}, {0x30000000, 0x0}, {0x30000000, 0x0}, {0x30000000, 0x0}, {0x30000000, 0x0}, {0x30000000, 0x0}, {0x30000000, 0x0}},
    {{0x0, 0x0}, {0x1062401, 0x1204059}, {0x10d2203, 0x220c0f2}, {0x1142005, 0x321418b}, {0x17840e04, 0x3100021f}, {0x981006, 0x411829b}, {0x17942a04, 0x31004337}, {0x21f4607, 0x541c3df}, {0x17a44604, 0x31048497}, {0x270609, 0x6024528}, {0x17b46204, 0x3104c5f4}, {0x3ad720b, 0x772c652}, {0x17c47e04, 0x3109074d}, {0x2f55a0d, 0x85b47a2}, {0x17d49a04, 0x310948a7}, {0x13d220f, 0x923c8e9}, {0x17e4b604, 0x310d89b0}, {0x17f4d204, 0x310dca5d}, {0x18041c20, 0x98020b23}, {0x18148c20, 0x980a4bff}, {0x18241c27, 0xba028cdb}, {0x18348c27, 0xba0acdb7}, {0x18441c2e, 0xdc030e93}, {0x18548c2e, 0xdc0b4f5a}, {0x30000000, 0x0}, {0x30000000, 0x0}, {0x30000000, 0x0}, {0x30000000, 0x0}, {0x30000000, 0x0}, {0x30000000, 0x0}, {0x30000000, 0x0}, {0x30000000, 0x0}},
    {{0x0, 0x0}, {0x1462c01, 0x128405a}, {0x14d2a03, 0x228c0f3}, {0x1542805, 0x329418c}, {0x17850e0b, 0x2000022a}, {0x1983006, 0x43182a6}, {0x17952a0b, 0x2000434d}, {0x29f5607, 0x551c3e4}, {0x17a5460b, 0x200484ad}, {0xe71e09, 0x61a452f}, {0x17b5620b, 0x2004c609}, {0x16e2c0b, 0x72ac664}, {0x17c57e0b, 0x20090763}, {0x36040d, 0x80347b1}, {0x17d59a0b, 0x200948bd}, {0x1fd3a0f, 0x93bc8f3}, {0x17e5b60b, 0x200d89bb}, {0x17f5d20b, 0x200dca67}, {0x18052320, 0x98020b30}, {0x18159320, 0x980a4c0c}, {0x18252327, 0xba028ce8}, {0x18359327, 0xba0acdc4}, {0x1845232e, 0xdc030ea0}, {0x1855932e, 0xdc0b4f66}, {0x30000000, 0x0}, {0x30000000, 0x0}, {0x30000000, 0x0}, {0x30000000, 0x0}, {0x30000000, 0x0}, {0x30000000, 0x0}, {0x30000000, 0x0}, {0x30000000, 0x0}},
    {{0x0, 0x0}, {0x1863401, 0x130405b}, {0x18d3203, 0x230c0f4}, {0x1943005, 0x331418d}, {0x17861504, 0x31000235}, {0x2d85806, 0x45982b2}, {0x17963104, 0x31004363}, {0x31f6607, 0x561c3e8}, {0x17a64d04, 0x310484c3}, {0x1672e09, 0x62a4534}, {0x17b66904, 0x3104c61f}, {0x2ae540b, 0x752c673}, {0x17c68504, 0x31090779}, {0xf61c0d, 0x81b47b8}, {0x17d6a104, 0x310948d2}, {0x33d620f, 0x963c8ff}, {0x17e6bd04, 0x310d89c5}, {0x17f6d904, 0x310dca72}, {0x18062a20, 0x98020b3e}, {0x18169a20, 0x980a4c1a}, {0x18262a27, 0xba028cf6}, {0x18369a27, 0xba0acdd2}, {0x18462a2e, 0xdc030eae}, {0x18569a2e, 0xdc0b4f72}, {0x30000000, 0x0}, {0x30000000, 0x0}, {0x30000000, 0x0}, {0x30000000, 0x0}, {0x30000000, 0x0}, {0x30000000, 0x0}, {0x30000000, 0x0}, {0x30000000, 0x0}},
    {{0x0, 0x0}, {0x1c63c01, 0x138405d}, {0x1cd3a03, 0x238c0f6}, {0x1d43805, 0x339418f}, {0x1787150b, 0x20000240}, {0x3d87806, 0x47982be}, {0x1797310b, 0x20004379}, {0x39f7607, 0x571c3ef}, {0x17a74d0b, 0x200484d8}, {0x2274609, 0x642453e}, {0x17b7690b, 0x2004c635}, {0x6f0e0b, 0x70ac686}, {0x17c7850b, 0x2009078e}, {0x1b6340d, 0x83347c2}, {0x17d7a10b, 0x200948e8}, {0x3fd7a0f, 0x97bc908}, {0x17e7bd0b, 0x200d89d0}, {0x17f7d90b, 0x200dca7d}, {0x18073120, 0x98020b4c}, {0x1817a120, 0x980a4c28}, {0x18273127, 0xba028d04}, {0x1837a127, 0xba0acde0}, {0x1847312e, 0xdc030ebc}, {0x1857a12e, 0xdc0b4f7e}, {0x30000000, 0x0}, {0x30000000, 0x0}, {0x30000000, 0x0}, {0x30000000, 0x0}, {0x30000000, 0x0}, {0x30000000, 0x0}, {0x30000000, 0x0}, {0x30000000, 0x0}},
    {{0x0, 0x0}, {0x2064401, 0x140405e}, {0x20d4203, 0x240c0f7}, {0x2144005, 0x3414190}, {0x17880012, 0x7500024b}, {0x1192206, 0x42182cb}, {0x17981c12, 0x7500438f}, {0x3df7e07, 0x579c3f2}, {0x17a83812, 0x750484ee}, {0x3276609, 0x6624548}, {0x17b85412, 0x7504c64a}, {0x22f460b, 0x742c698}, {0x17c87012, 0x750907a4}, {0x2f65c0d, 0x85b47ce}, {0x2f95a0e, 0x85b884f}, {0x17d88c12, 0x750948fe}, {0x17e8a812, 0x750d89db}, {0x17f8c412, 0x750dca88}, {0x18083820, 0x98060b5a}, {0x1818a820, 0x980e4c36}, {0x18283827, 0xba068d12}, {0x1838a827, 0xba0ecdee}, {0x1848382e, 0xdc070eca}, {0x1858a82e, 0xdc0f4f8a}, {0x30000000, 0x0}, {0x30000000, 0x0}, {0x30000000, 0x0}, {0x30000000, 0x0}, {0x30000000, 0x0}, {0x30000000, 0x0}, {0x30000000, 0x0}, {0x30000000, 0x0}},
    {{0x0, 0x0}, {0x2464c01, 0x148405f}, {0x24d4a03, 0x248c0f8}, {0x2544805, 0x3494191}, {0x17890019, 0x64000256}, {0x1993206, 0x43182d2}, {0x17991c19, 0x640043a5}, {0x200008, 0x50203f5}, {0x17a93819, 0x64048504}, {0x3a77609, 0x672454f}, {0x17b95419, 0x6404c660}, {0x2ef5e0b, 0x75ac69f}, {0x2724c0c, 0x74b071d}, {0x17c97019, 0x640907b9}, {0x1f93a0e, 0x83b8846}, {0x17d98c19, 0x64094913}, {0x17e9a819, 0x640d89e6}, {0x17f9c419, 0x640dca93}, {0x18093f20, 0x98060b67}, {0x1819af20, 0x980e4c43}, {0x18293f27, 0xba068d1f}, {0x1839af27, 0xba0ecdfb}, {0x18493f2e, 0xdc070ed6}, {0x1859af2e, 0xdc0f4f96}, {0x30000000, 0x0}, {0x30000000, 0x0}, {0x30000000, 0x0}, {0x30000000, 0x0}, {0x30000000, 0x0}, {0x30000000, 0x0}, {0x30000000, 0x0}, {0x30000000, 0x0}},
    {{0x0, 0x0}, {0x2865401, 0x1504061}, {0x28d5203, 0x250c0fa}, {0x2945005, 0x3514193}, {0x178a0712, 0x75000261}, {0x1d93a06, 0x43982d4}, {0x179a2312, 0x750043bb}, {0xe01808, 0x51a03fb}, {0x1632e08, 0x52a0485}, {0x17aa3f12, 0x7504851a}, {0x3aa740a, 0x67285d1}, {0x17ba5b12, 0x7504c675}, {0x32040c, 0x7030704}, {0x17ca7712, 0x750907cf}, {0x1b9320e, 0x8338843}, {0x17da9312, 0x75094929}, {0x3bf760f, 0x973c95c}, {0x17eaaf12, 0x750d89f1}, {0x17facb12, 0x750dca9d}, {0x180a4620, 0x98060b75}, {0x181ab620, 0x980e4c51}, {0x182a4627, 0xba068d2d}, {0x183ab627, 0xba0ece09}, {0x184a462e, 0xdc070ee2}, {0x185ab62e, 0xdc0f4fa2}, {0x30000000, 0x0}, {0x30000000, 0x0}, {0x30000000, 0x0}, {0x30000000, 0x0}, {0x30000000, 0x0}, {0x30000000, 0x0}, {0x30000000, 0x0}},
    {{0x0, 0x0}, {0x2c65c01, 0x1584062}, {0x2cd5a03, 0x258c0fb}, {0x2d45805, 0x3594194}, {0x178b0719, 0x64000271}, {0x2194206, 0x44182d7}, {0x1c0007, 0x401c345}, {0x179b2319, 0x640043d1}, {0x230608, 0x5020478}, {0x17ab3f19, 0x64048530}, {0x26a4c0a, 0x64a85c3}, {0x17bb5b19, 0x6404c68b}, {0xf21c0c, 0x71b070b}, {0x17cb7719, 0x640907e5}, {0x139220e, 0x823883c}, {0x17db9319, 0x6409493e}, {0x37f6e0f, 0x96bc958}, {0x17ebaf19, 0x640d89fb}, {0x17fbcb19, 0x640dcaa8}, {0x180b4d20, 0x98060b83}, {0x181bbd20, 0x980e4c5f}, {0x182b4d27, 0xba068d3b}, {0x183bbd27, 0xba0ece17}, {0x184b4d2e, 0xdc070eee}, {0x185bbd2e, 0xdc0f4fae}, {0x30000000, 0x0}, {0x30000000, 0x0}, {0x30000000, 0x0}, {0x30000000, 0x0}, {0x30000000, 0x0}, {0x30000000, 0x0}, {0x30000000, 0x0}},
    {{0x0, 0x0}, {0x3066401, 0x1604063}, {0x30d6203, 0x260c0fc}, {0x3146005, 0x3614195}, {0x2a3a2333, 0x2581820d}, {0x178c1c04, 0x31000287}, {0x25b4e06, 0x4498332}, {0x179c3804, 0x310443e7}, {0xe31e08, 0x51a047f}, {0x17ac5404, 0x31048546}, {0x2aa540a, 0x65285c6}, {0x17bc7004, 0x3108c6a1}, {0x331620c, 0x76306f8}, {0x17cc8c04, 0x310907fa}, {0x2794a0e, 0x84b884b}, {0x17dca804, 0x310d4954}, {0x3ff7e0f, 0x97bc95f}, {0x17ecc404, 0x310d8a06}, {0x17fcd212, 0x750dcab5}, {0x180c5420, 0x98060b91}, {0x181cc420, 0x980e4c6d}, {0x182c5427, 0xba068d49}, {0x183cc427, 0xba0ece25}, {0x184c542e, 0xdc070efa}, {0x185cc42e, 0xdc0f4fba}, {0x30000000, 0x0}, {0x30000000, 0x0}, {0x30000000, 0x0}, {0x30000000, 0x0}, {0x30000000, 0x0}, {0x30000000, 0x0}, {0x30000000, 0x0}},
    {{0x0, 0x0}, {0x3466c01, 0x1684065}, {0x34d6a03, 0x268c0fe}, {0x3546805, 0x3694197}, {0x2a3b2334, 0x26818218}, {0x178d1c0b, 0x2000029d}, {0x1db3e06, 0x439832c}, {0x179d380b, 0x200443fd}, {0x1a33608, 0x5320489}, {0x17ad540b, 0x2004855c}, {0x36a6c0a, 0x66a85cd}, {0x17bd700b, 0x2008c6b6}, {0x3b1720c, 0x77306ff}, {0x17cd8c0b, 0x20090810}, {0x339620e, 0x8638852}, {0x17dda80b, 0x200d4964}, {0x17edc40b, 0x200d8a11}, {0x17fdd219, 0x640dcac2}, {0x180d5b20, 0x98060b9e}, {0x181dcb20, 0x980e4c7a}, {0x182d5b27, 0xba068d56}, {0x183dcb27, 0xba0ece32}, {0x184d5b2e, 0xdc070f06}, {0x185dcb2e, 0xdc0f4fc6}, {0x30000000, 0x0}, {0x30000000, 0x0}, {0x30000000, 0x0}, {0x30000000, 0x0}, {0x30000000, 0x0}, {0x30000000, 0x0}, {0x30000000, 0x0}, {0x30000000, 0x0}},
    {{0x0, 0x0}, {0x3867401, 0x1704066}, {0x38d7203, 0x270c0ff}, {0x3947005, 0x3714198}, {0x2a3c3831, 0x3881c223}, {0x178e2304, 0x310002b3}, {0x15b2e06, 0x4298325}, {0x179e3f04, 0x31044413}, {0x2234608, 0x542048e}, {0x17ae5b04, 0x31048572}, {0x6b0e0a, 0x60a85d9}, {0x17be7704, 0x3108c6cc}, {0x3716a0c, 0x76b06fb}, {0x17ce9304, 0x31090825}, {0x3f97a0e, 0x87b885b}, {0x2bf560f, 0x953c951}, {0x17deaf04, 0x310d496f}, {0x17eecb04, 0x310d8a1c}, {0x17fed912, 0x750dcad0}, {0x180e6220, 0x98060bac}, {0x181ed220, 0x980e4c88}, {0x182e6227, 0xba068d64}, {0x183ed227, 0xba0ece40}, {0x184e622e, 0xdc070f12}, {0x185ed22e, 0xdc0f4fd2}, {0x30000000, 0x0}, {0x30000000, 0x0}, {0x30000000, 0x0}, {0x30000000, 0x0}, {0x30000000, 0x0}, {0x30000000, 0x0}, {0x30000000, 0x0}},
    {{0x0, 0x0}, {0x3c67c01, 0x1784067}, {0x3cd7a03, 0x278c100}, {0x3d47805, 0x3794199}, {0x2a3d3832, 0x3981c22e}, {0x178f230b, 0x200002c9}, {0x3da7c06, 0x4798316}, {0x179f3f0b, 0x20044429}, {0x2e35e08, 0x55a0495}, {0x17af5b0b, 0x20048588}, {0x16b2e0a, 0x62a85e2}, {0x1ac300b, 0x732c611}, {0x17bf770b, 0x2008c6e1}, {0x17cf930b, 0x2009083b}, {0x7a0c0e, 0x90b8861}, {0x27f4e0f, 0x94bc94f}, {0x17dfaf0b, 0x200d497a}, {0x17efcb0b, 0x200d8a27}, {0x17ffd919, 0x640dcade}, {0x180f6920, 0x98060bba}, {0x181fd920, 0x980e4c96}, {0x182f6927, 0xba068d72}, {0x183fd927, 0xba0ece4e}, {0x184f692e, 0xdc070f1e}, {0x185fd92e, 0xdc0f4fde}, {0x30000000, 0x0}, {0x30000000, 0x0}, {0x30000000, 0x0}, {0x30000000, 0x0}, {0x30000000, 0x0}, {0x30000000, 0x0}, {0x30000000, 0x0}},
    {{0x0, 0x0}, {0x70601, 0x1004069}, {0xe0403, 0x200c102}, {0x150205, 0x301419b}, {0x18600005, 0x310001f5}, {0x18700e13, 0x750042e2}, {0x2dc5807, 0x459c362}, {0x18802a13, 0x75008441}, {0x3a37608, 0x572049f}, {0xe8180a, 0x61a855b}, {0x18904613, 0x7504c5a0}, {0x18a06213, 0x750506fa}, {0x1b3360c, 0x8330740}, {0x18b07e13, 0x75094853}, {0x1fa3c0e, 0x93b8871}, {0x3bd720f, 0x973c906}, {0x18c09a13, 0x75098986}, {0x18d0b613, 0x750dca33}, {0x18e00021, 0x98020aed}, {0x18f07021, 0x980a4bc9}, {0x19000028, 0xba028ca5}, {0x19107028, 0xba0acd81}, {0x1920002f, 0xdc030e5d}, {0x1930702f, 0xdc0b4f2c}, {0x30000000, 0x0}, {0x30000000, 0x0}, {0x30000000, 0x0}, {0x30000000, 0x0}, {0x30000000, 0x0}, {0x30000000, 0x0}, {0x30000000, 0x0}, {0x30000000, 0x0}},
    {{0x400800, 0x80000}, {0x470e01, 0x108406a}, {0x4e0c03, 0x208c103}, {0x550a05, 0x309419c}, {0x1861000c, 0x20000200}, {0x18710e1a, 0x640042f8}, {0x3dc7807, 0x479c36e}, {0x18812a1a, 0x64008457}, {0x240009, 0x50244a4}, {0x3e77e09, 0x67a4551}, {0x1891461a, 0x6404c5b6}, {0x36d6a0b, 0x76ac64e}, {0x18a1621a, 0x6405070f}, {0x1b5320d, 0x8334796}, {0x18b17e1a, 0x64094869}, {0x2fd5a0f, 0x95bc8fc}, {0x18c19a1a, 0x64098991}, {0x18d1b61a, 0x640dca3e}, {0x18e10721, 0x98020afb}, {0x18f17721, 0x980a4bd7}, {0x19010728, 0xba028cb3}, {0x19117728, 0xba0acd8f}, {0x1921072f, 0xdc030e6b}, {0x1931772f, 0xdc0b4f38}, {0x30000000, 0x0}, {0x30000000, 0x0}, {0x30000000, 0x0}, {0x30000000, 0x0}, {0x30000000, 0x0}, {0x30000000, 0x0}, {0x30000000, 0x0}, {0x30000000, 0x0}},
    {{0x801000, 0x100000}, {0x871601, 0x110406b}, {0x8e1403, 0x210c104}, {0x951205, 0x311419d}, {0x18620705, 0x3100020b}, {0x18721513, 0x7500430e}, {0x9d1207, 0x411c376}, {0x18823113, 0x7500846d}, {0xa41009, 0x51244aa}, {0x2a75609, 0x6524544}, {0x18924d13, 0x7504c5cb}, {0x1ed3a0b, 0x73ac63f}, {0x18a26913, 0x75050725}, {0x3f57a0d, 0x87b47af}, {0x18b28513, 0x7509487f}, {0x23d420f, 0x943c8f5}, {0x18c2a113, 0x7509899c}, {0x18d2bd13, 0x750dca48}, {0x18e20e21, 0x98020b09}, {0x18f27e21, 0x980a4be5}, {0x19020e28, 0xba028cc1}, {0x19127e28, 0xba0acd9d}, {0x19220e2f, 0xdc030e79}, {0x19327e2f, 0xdc0b4f44}, {0x30000000, 0x0}, {0x30000000, 0x0}, {0x30000000, 0x0}, {0x30000000, 0x0}, {0x30000000, 0x0}, {0x30000000, 0x0}, {0x30000000, 0x0}, {0x30000000, 0x0}},
    {{0xc01800, 0x180000}, {0xc71e01, 0x118406c}, {0xce1c03, 0x218c105}, {0xd51a05, 0x319419e}, {0x1863070c, 0x20000216}, {0x1873151a, 0x64004324}, {0x19d3207, 0x431c381}, {0x1883311a, 0x64008483}, {0x1642809, 0x52a44b1}, {0x2674e09, 0x64a4541}, {0x18934d1a, 0x6404c5e1}, {0x6e0c0b, 0x70ac65a}, {0x18a3691a, 0x6405073b}, {0x1f63c0d, 0x83b47c4}, {0x18b3851a, 0x64094894}, {0x27d4a0f, 0x94bc8f8}, {0x18c3a11a, 0x640989a6}, {0x18d3bd1a, 0x640dca53}, {0x18e31521, 0x98020b17}, {0x18f38521, 0x980a4bf3}, {0x19031528, 0xba028ccf}, {0x19138528, 0xba0acdab}, {0x1923152f, 0xdc030e87}, {0x1933852f, 0xdc0b4f50}, {0x30000000, 0x0}, {0x30000000, 0x0}, {0x30000000, 0x0}, {0x30000000, 0x0}, {0x30000000, 0x0}, {0x30000000, 0x0}, {0x30000000, 0x0}, {0x30000000, 0x0}},
    {{0x1002000, 0x200000}, {0x1072601, 0x120406e}, {0x10e2403, 0x220c107}, {0x1152205, 0x32141a0}, {0x18640e05, 0x31000220}, {0x18742a05, 0x3100433a}, {0x25d4a07, 0x449c38a}, {0xa01008, 0x51203fa}, {0x18844605, 0x31048499}, {0x1e73e09, 0x63a453b}, {0x18946205, 0x3104c5f6}, {0x2ee5c0b, 0x75ac674}, {0x18a47e05, 0x31090750}, {0x136240d, 0x82347bb}, {0x18b49a05, 0x310948aa}, {0x2bd520f, 0x953c8fb}, {0x18c4b605, 0x310d89b1}, {0x18d4d205, 0x310dca5e}, {0x18e41c21, 0x98020b24}, {0x18f48c21, 0x980a4c00}, {0x19041c28, 0xba028cdc}, {0x19148c28, 0xba0acdb8}, {0x19241c2f, 0xdc030e94}, {0x19348c2f, 0xdc0b4f5c}, {0x30000000, 0x0}, {0x30000000, 0x0}, {0x30000000, 0x0}, {0x30000000, 0x0}, {0x30000000, 0x0}, {0x30000000, 0x0}, {0x30000000, 0x0}, {0x30000000, 0x0}},
    {{0x1402800, 0x280000}, {0x1472e01, 0x128406f}, {0x14e2c03, 0x228c108}, {0x1552a05, 0x32941a1}, {0x18650e0c, 0x2000022b}, {0x18752a0c, 0x20004350}, {0x35d6a07, 0x469c393}, {0x1202008, 0x52203fe}, {0x1885460c, 0x200484af}, {0x2e75e09, 0x65a4545}, {0x1895620c, 0x2004c60c}, {0x12f260b, 0x722c68c}, {0x18a57e0c, 0x20090766}, {0x236440d, 0x84347c7}, {0x18b59a0c, 0x200948bf}, {0x37d6a0f, 0x96bc902}, {0x18c5b60c, 0x200d89bc}, {0x18d5d20c, 0x200dca69}, {0x18e52321, 0x98020b32}, {0x18f59321, 0x980a4c0e}, {0x19052328, 0xba028cea}, {0x19159328, 0xba0acdc6}, {0x1925232f, 0xdc030ea2}, {0x1935932f, 0xdc0b4f68}, {0x30000000, 0x0}, {0x30000000, 0x0}, {0x30000000, 0x0}, {0x30000000, 0x0}, {0x30000000, 0x0}, {0x30000000, 0x0}, {0x30000000, 0x0}, {0x30000000, 0x0}},
    {{0x1803000, 0x300000}, {0x1873601, 0x1304070}, {0x18e3403, 0x230c109}, {0x1953205, 0x33141a2}, {0x18661505, 0x31000236}, {0x18763105, 0x31004366}, {0x1e0407, 0x501c39d}, {0x1a03008, 0x5320405}, {0x18864d05, 0x310484c5}, {0x3676e09, 0x66a454a}, {0x18966905, 0x3104c622}, {0x32f660b, 0x762c6a2}, {0x18a68505, 0x3109077b}, {0x3766c0d, 0x86b47d3}, {0x18b6a105, 0x310948d5}, {0x3e040f, 0x903c90b}, {0x18c6bd05, 0x310d89c7}, {0x18d6d905, 0x310dca74}, {0x18e62a21, 0x98020b40}, {0x18f69a21, 0x980a4c1c}, {0x19062a28, 0xba028cf8}, {0x19169a28, 0xba0acdd4}, {0x19262a2f, 0xdc030eb0}, {0x19369a2f, 0xdc0b4f74}, {0x30000000, 0x0}, {0x30000000, 0x0}, {0x30000000, 0x0}, {0x30000000, 0x0}, {0x30000000, 0x0}, {0x30000000, 0x0}, {0x30000000, 0x0}, {0x30000000, 0x0}},
    {{0x1c03800, 0x380000}, {0x1c73e01, 0x1384072}, {0x1ce3c03, 0x238c10b}, {0x1d53a05, 0x33941a4}, {0x1867150c, 0x20000241}, {0xdc1807, 0x419c34c}, {0x1877310c, 0x2000437c}, {0x600808, 0x50a03f7}, {0x18874d0c, 0x200484db}, {0x28000a, 0x6028554}, {0x1897690c, 0x2004c637}, {0x1f23c0c, 0x73b0717}, {0x18a7850c, 0x20090791}, {0x2b6540d, 0x85347cc}, {0x18b7a10c, 0x200948eb}, {0x13e240f, 0x923c915}, {0x18c7bd0c, 0x200d89d2}, {0x18d7d90c, 0x200dca7e}, {0x18e73121, 0x98020b4e}, {0x18f7a121, 0x980a4c2a}, {0x19073128, 0xba028d06}, {0x1917a128, 0xba0acde2}, {0x1927312f, 0xdc030ebe}, {0x1937a12f, 0xdc0b4f80}, {0x30000000, 0x0}, {0x30000000, 0x0}, {0x30000000, 0x0}, {0x30000000, 0x0}, {0x30000000, 0x0}, {0x30000000, 0x0}, {0x30000000, 0x0}, {0x30000000, 0x0}},
    {{0x2004000, 0x400000}, {0x2074601, 0x1404073}, {0x20e4403, 0x240c10c}, {0x2154205, 0x34141a5}, {0x18680013, 0x7500024c}, {0x31b6606, 0x4618339}, {0x18781c13, 0x75004392}, {0x1602808, 0x52a0401}, {0x18883813, 0x750484f1}, {0xa8100a, 0x612855a}, {0x18985413, 0x7504c64d}, {0x1b1320c, 0x73306e9}, {0x18a87013, 0x750907a7}, {0x3f67c0d, 0x87b47da}, {0x18b88c13, 0x75094900}, {0x1fe3c0f, 0x93bc91e}, {0x18c8a813, 0x750d89dc}, {0x18d8c413, 0x750dca89}, {0x18e83821, 0x98060b5b}, {0x18f8a821, 0x980e4c37}, {0x19083828, 0xba068d13}, {0x1918a828, 0xba0ecdef}, {0x1928382f, 0xdc070ecb}, {0x1938a82f, 0xdc0f4f8c}, {0x30000000, 0x0}, {0x30000000, 0x0}, {0x30000000, 0x0}, {0x30000000, 0x0}, {0x30000000, 0x0}, {0x30000000, 0x0}, {0x30000000, 0x0}, {0x30000000, 0x0}},
    {{0x2404800, 0x480000}, {0x2474e01, 0x1484074}, {0x24e4c03, 0x248c10d}, {0x2554a05, 0x34941a6}, {0x1869001a, 0x64000257}, {0x11b2606, 0x4218323}, {0x18791c1a, 0x640043a8}, {0x1e03808, 0x53a0408}, {0x1889381a, 0x64048507}, {0x1a8300a, 0x6328565}, {0x1899541a, 0x6404c662}, {0x31020c, 0x70306d9}, {0x18a9701a, 0x640907bc}, {0xf71e0d, 0x81b47e3}, {0xba140e, 0x9138864}, {0x18b98c1a, 0x64094916}, {0x18c9a81a, 0x640d89e7}, {0x18d9c41a, 0x640dca94}, {0x18e93f21, 0x98060b69}, {0x18f9af21, 0x980e4c45}, {0x19093f28, 0xba068d21}, {0x1919af28, 0xba0ecdfd}, {0x19293f2f, 0xdc070ed7}, {0x1939af2f, 0xdc0f4f98}, {0x30000000, 0x0}, {0x30000000, 0x0}, {0x30000000, 0x0}, {0x30000000, 0x0}, {0x30000000, 0x0}, {0x30000000, 0x0}, {0x30000000, 0x0}, {0x30000000, 0x0}},
    {{0x2805000, 0x500000}, {0x2875601, 0x1504076}, {0x28e5403, 0x250c10f}, {0x2955205, 0x35141a8}, {0x186a0713, 0x75000262}, {0x25a4c06, 0x4498306}, {0x187a2313, 0x750043be}, {0x2604808, 0x54a040d}, {0x188a3f13, 0x7504851d}, {0x268480a, 0x64a856d}, {0x189a5b13, 0x7504c678}, {0x1f0380c, 0x73b06c1}, {0x2734e0c, 0x84b0748}, {0x18aa7713, 0x750907d2}, {0x3b9720e, 0x8738859}, {0x18ba9313, 0x7509492b}, {0x18caaf13, 0x750d89f2}, {0x18dacb13, 0x750dca9f}, {0x18ea4621, 0x98060b77}, {0x18fab621, 0x980e4c53}, {0x190a4628, 0xba068d2f}, {0x191ab628, 0xba0ece0b}, {0x192a462f, 0xdc070ee3}, {0x193ab62f, 0xdc0f4fa4}, {0x30000000, 0x0}, {0x30000000, 0x0}, {0x30000000, 0x0}, {0x30000000, 0x0}, {0x30000000, 0x0}, {0x30000000, 0x0}, {0x30000000, 0x0}, {0x30000000, 0x0}},
    {{0x2c05800, 0x580000}, {0x2c75e01, 0x1584077}, {0x2ce5c03, 0x258c110}, {0x2d55a05, 0x35941a9}, {0x186b071a, 0x64000274}, {0x11a2406, 0x42182f7}, {0x187b231a, 0x640043d4}, {0x3606808, 0x56a0417}, {0x188b3f1a, 0x64048533}, {0x328600a, 0x6628573}, {0x189b5b1a, 0x6404c68e}, {0x170280c, 0x72b06ba}, {0x2b2540c, 0x753071f}, {0x18ab771a, 0x640907e7}, {0x17a2c0e, 0x92b886a}, {0x18bb931a, 0x64094941}, {0x18cbaf1a, 0x640d89fd}, {0x18dbcb1a, 0x640dcaaa}, {0x18eb4d21, 0x98060b85}, {0x18fbbd21, 0x980e4c61}, {0x190b4d28, 0xba068d3d}, {0x191bbd28, 0xba0ece19}, {0x192b4d2f, 0xdc070eef}, {0x193bbd2f, 0xdc0f4fb0}, {0x30000000, 0x0}, {0x30000000, 0x0}, {0x30000000, 0x0}, {0x30000000, 0x0}, {0x30000000, 0x0}, {0x30000000, 0x0}, {0x30000000, 0x0}, {0x30000000, 0x0}},
    {{0x3006000, 0x600000}, {0x3076601, 0x1604078}, {0x30e6403, 0x260c111}, {0x3156205, 0x36141aa}, {0x186c1c05, 0x3100028a}, {0x5a0c06, 0x40982f0}, {0x39c7007, 0x471c36b}, {0x187c3805, 0x310443ea}, {0x2a35608, 0x5520494}, {0x188c5405, 0x31048549}, {0x2ea5c0a, 0x65a85c7}, {0x189c7005, 0x3108c6a3}, {0x730e0c, 0x80b0732}, {0x18ac8c05, 0x310907fd}, {0x3796a0e, 0x86b8855}, {0x18bca805, 0x310d4957}, {0x18ccc405, 0x310d8a08}, {0x18dcd213, 0x750dcab6}, {0x18ec5421, 0x98060b92}, {0x18fcc421, 0x980e4c6e}, {0x190c5428, 0xba068d4a}, {0x191cc428, 0xba0ece26}, {0x192c542f, 0xdc070efb}, {0x193cc42f, 0xdc0f4fbc}, {0x30000000, 0x0}, {0x30000000, 0x0}, {0x30000000, 0x0}, {0x30000000, 0x0}, {0x30000000, 0x0}, {0x30000000, 0x0}, {0x30000000, 0x0}, {0x30000000, 0x0}},
    {{0x3406800, 0x680000}, {0x3476e01, 0x168407a}, {0x34e6c03, 0x268c113}, {0x3556a05, 0x36941ac}, {0x186d1c0c, 0x200002a0}, {0x2a483833, 0x3a8282e6}, {0x35c6807, 0x469c367}, {0x187d380c, 0x20044400}, {0x3636e08, 0x56a049b}, {0x188d540c, 0x2004855f}, {0x2b060a, 0x60285d6}, {0x189d700c, 0x2008c6b9}, {0xf31e0c, 0x81b0736}, {0x18ad8c0c, 0x20090813}, {0x3a040e, 0x903885e}, {0x18bda80c, 0x200d4966}, {0x18cdc40c, 0x200d8a12}, {0x18ddd21a, 0x640dcac4}, {0x18ed5b21, 0x98060ba0}, {0x18fdcb21, 0x980e4c7c}, {0x190d5b28, 0xba068d58}, {0x191dcb28, 0xba0ece34}, {0x192d5b2f, 0xdc070f07}, {0x193dcb2f, 0xdc0f4fc8}, {0x30000000, 0x0}, {0x30000000, 0x0}, {0x30000000, 0x0}, {0x30000000, 0x0}, {0x30000000, 0x0}, {0x30000000, 0x0}, {0x30000000, 0x0}, {0x30000000, 0x0}},
    {{0x3807000, 0x700000}, {0x3877601, 0x170407b}, {0x38e7403, 0x270c114}, {0x3957205, 0x37141ad}, {0x186e2305, 0x310002b6}, {0x2d95a06, 0x45982de}, {0x25c4807, 0x449c35e}, {0x187e3f05, 0x31044416}, {0x3e37e08, 0x57a04a2}, {0x188e5b05, 0x31048575}, {0x1ab360a, 0x63285e6}, {0x189e7705, 0x3108c6ce}, {0x33060c, 0x8030730}, {0x18ae9305, 0x31090828}, {0xfa1c0e, 0x91b8865}, {0x18beaf05, 0x310d4970}, {0x18cecb05, 0x310d8a1d}, {0x18ded913, 0x750dcad2}, {0x18ee6221, 0x98060bae}, {0x18fed221, 0x980e4c8a}, {0x190e6228, 0xba068d66}, {0x191ed228, 0xba0ece42}, {0x192e622f, 0xdc070f13}, {0x193ed22f, 0xdc0f4fd4}, {0x30000000, 0x0}, {0x30000000, 0x0}, {0x30000000, 0x0}, {0x30000000, 0x0}, {0x30000000, 0x0}, {0x30000000, 0x0}, {0x30000000, 0x0}, {0x30000000, 0x0}},
    {{0x3c07800, 0x780000}, {0x3c77e01, 0x178407c}, {0x3ce7c03, 0x278c115}, {0x3d57a05, 0x37941ae}, {0x2a3e3f31, 0x3f81c239}, {0x186f230c, 0x200002cc}, {0x2a4d5432, 0x5582c354}, {0x187f3f0c, 0x2004442c}, {0x640809, 0x50a44a7}, {0x188f5b0c, 0x2004858a}, {0x1eb3e0a, 0x63a85e9}, {0x189f770c, 0x2008c6e4}, {0x332640c, 0x7630724}, {0x18af930c, 0x2009083e}, {0x23a440e, 0x9438874}, {0x33f660f, 0x963c955}, {0x18bfaf0c, 0x200d497b}, {0x18cfcb0c, 0x200d8a28}, {0x18dfd91a, 0x640dcae0}, {0x18ef6921, 0x98060bbc}, {0x18ffd921, 0x980e4c98}, {0x190f6928, 0xba068d74}, {0x191fd928, 0xba0ece50}, {0x192f692f, 0xdc070f20}, {0x193fd92f, 0xdc0f4fe0}, {0x30000000, 0x0}, {0x30000000, 0x0}, {0x30000000, 0x0}, {0x30000000, 0x0}, {0x30000000, 0x0}, {0x30000000, 0x0}, {0x30000000, 0x0}},
    {{0x10200, 0x0}, {0x80002, 0x100807e}, {0xf0603, 0x200c117}, {0x160405, 0x30141b0}, {0x19400006, 0x310001f6}, {0x19500e14, 0x750042e5}, {0x31c6007, 0x461c364}, {0x19602a14, 0x75008444}, {0x1242009, 0x52244ae}, {0x29020a, 0x6028580}, {0x19704614, 0x7504c5a3}, {0x19806214, 0x750506fc}, {0x1f33e0c, 0x83b0743}, {0x19907e14, 0x75094856}, {0x2fa5c0e, 0x95b887b}, {0x2be540f, 0x953c926}, {0x19a09a14, 0x75098987}, {0x19b0b614, 0x750dca34}, {0x19c00022, 0x98020aef}, {0x19d07022, 0x980a4bcb}, {0x19e00029, 0xba028ca7}, {0x19f07029, 0xba0acd83}, {0x1a000030, 0xdc030e5f}, {0x1a107030, 0xdc0b4f2d}, {0x30000000, 0x0}, {0x30000000, 0x0}, {0x30000000, 0x0}, {0x30000000, 0x0}, {0x30000000, 0x0}, {0x30000000, 0x0}, {0x30000000, 0x0}, {0x30000000, 0x0}},
    {{0x410a00, 0x80000}, {0x480802, 0x108807f}, {0x4f0e03, 0x208c118}, {0x560c05, 0x30941b1}, {0x1941000d, 0x20000201}, {0x19510e1b, 0x640042fb}, {0x1d0207, 0x401c371}, {0x19612a1b, 0x6400845a}, {0x1e43809, 0x53a44b8}, {0x3a8700a, 0x672857a}, {0x1971461b, 0x6404c5b8}, {0x1981621b, 0x64050712}, {0x2f35e0c, 0x85b074c}, {0x19917e1b, 0x6409486c}, {0x3b060e, 0x9038889}, {0x23e440f, 0x943c921}, {0x19a19a1b, 0x64098992}, {0x19b1b61b, 0x640dca3f}, {0x19c10722, 0x98020afd}, {0x19d17722, 0x980a4bd9}, {0x19e10729, 0xba028cb5}, {0x19f17729, 0xba0acd91}, {0x1a010730, 0xdc030e6d}, {0x1a117730, 0xdc0b4f39}, {0x30000000, 0x0}, {0x30000000, 0x0}, {0x30000000, 0x0}, {0x30000000, 0x0}, {0x30000000, 0x0}, {0x30000000, 0x0}, {0x30000000, 0x0}, {0x30000000, 0x0}},
    {{0x811200, 0x100000}, {0x881002, 0x1108080}, {0x8f1603, 0x210c119}, {0x961405, 0x31141b2}, {0x19420706, 0x3100020c}, {0x19521514, 0x75004311}, {0xdd1a07, 0x419c378}, {0x19623114, 0x75008470}, {0x2644809, 0x54a44bd}, {0x2e8580a, 0x65a8571}, {0x19724d14, 0x7504c5ce}, {0x26d4a0b, 0x74ac645}, {0x19826914, 0x75050728}, {0x760c0d, 0x80b47b4}, {0x19928514, 0x75094881}, {0x17e2c0f, 0x92bc917}, {0x19a2a114, 0x7509899d}, {0x19b2bd14, 0x750dca4a}, {0x19c20e22, 0x98020b0b}, {0x19d27e22, 0x980a4be7}, {0x19e20e29, 0xba028cc3}, {0x19f27e29, 0xba0acd9f}, {0x1a020e30, 0xdc030e7b}, {0x1a127e30, 0xdc0b4f45}, {0x30000000, 0x0}, {0x30000000, 0x0}, {0x30000000, 0x0}, {0x30000000, 0x0}, {0x30000000, 0x0}, {0x30000000, 0x0}, {0x30000000, 0x0}, {0x30000000, 0x0}},
    {{0xc11a00, 0x180000}, {0xc81802, 0x1188081}, {0xcf1e03, 0x218c11a}, {0xd61c05, 0x31941b3}, {0x1943070d, 0x20000217}, {0x1953151b, 0x64004327}, {0x1dd3a07, 0x439c384}, {0x1963311b, 0x64008486}, {0x2e45809, 0x55a44c1}, {0x1e8380a, 0x63a8567}, {0x19734d1b, 0x6404c5e3}, {0xee1c0b, 0x71ac65e}, {0x1983691b, 0x6405073d}, {0x2764c0d, 0x84b47ca}, {0x1993851b, 0x64094897}, {0xfe1c0f, 0x91bc912}, {0x19a3a11b, 0x640989a8}, {0x19b3bd1b, 0x640dca55}, {0x19c31522, 0x98020b18}, {0x19d38522, 0x980a4bf4}, {0x19e31529, 0xba028cd0}, {0x19f38529, 0xba0acdac}, {0x1a031530, 0xdc030e88}, {0x1a138530, 0xdc0b4f51}, {0x30000000, 0x0}, {0x30000000, 0x0}, {0x30000000, 0x0}, {0x30000000, 0x0}, {0x30000000, 0x0}, {0x30000000, 0x0}, {0x30000000, 0x0}, {0x30000000, 0x0}},
    {{0x1012200, 0x200000}, {0x1082002, 0x1208083}, {0x10f2603, 0x220c11c}, {0x1162405, 0x32141b5}, {0x19440e06, 0x31000222}, {0x19542a06, 0x3100433d}, {0x2dd5a07, 0x459c38e}, {0x19644606, 0x3104849c}, {0x3646809, 0x56a44c7}, {0x128200a, 0x622855e}, {0x19746206, 0x3104c5f9}, {0x36e6c0b, 0x76ac679}, {0x19847e06, 0x31090753}, {0xb7160d, 0x81347e2}, {0x19949a06, 0x310948ad}, {0xbe140f, 0x913c910}, {0x19a4b606, 0x310d89b3}, {0x19b4d206, 0x310dca5f}, {0x19c41c22, 0x98020b26}, {0x19d48c22, 0x980a4c02}, {0x19e41c29, 0xba028cde}, {0x19f48c29, 0xba0acdba}, {0x1a041c30, 0xdc030e96}, {0x1a148c30, 0xdc0b4f5d}, {0x30000000, 0x0}, {0x30000000, 0x0}, {0x30000000, 0x0}, {0x30000000, 0x0}, {0x30000000, 0x0}, {0x30000000, 0x0}, {0x30000000, 0x0}, {0x30000000, 0x0}},
    {{0x1412a00, 0x280000}, {0x1482802, 0x1288084}, {0x14f2e03, 0x228c11d}, {0x1562c05, 0x32941b6}, {0x19450e0d, 0x2000022d}, {0x19552a0d, 0x20004353}, {0x39d7207, 0x471c397}, {0x2a05008, 0x5520410}, {0x1965460d, 0x200484b2}, {0x68080a, 0x60a8557}, {0x1975620d, 0x2004c60f}, {0x1ef3e0b, 0x73ac696}, {0x19857e0d, 0x20090768}, {0x3b6740d, 0x87347d7}, {0x19959a0d, 0x200948c2}, {0x7e0c0f, 0x90bc90e}, {0x19a5b60d, 0x200d89bd}, {0x19b5d20d, 0x200dca6a}, {0x19c52322, 0x98020b34}, {0x19d59322, 0x980a4c10}, {0x19e52329, 0xba028cec}, {0x19f59329, 0xba0acdc8}, {0x1a052330, 0xdc030ea4}, {0x1a159330, 0xdc0b4f69}, {0x30000000, 0x0}, {0x30000000, 0x0}, {0x30000000, 0x0}, {0x30000000, 0x0}, {0x30000000, 0x0}, {0x30000000, 0x0}, {0x30000000, 0x0}, {0x30000000, 0x0}},
    {{0x1813200, 0x300000}, {0x1883002, 0x1308085}, {0x18f3603, 0x230c11e}, {0x1963405, 0x33141b7}, {0x19461506, 0x31000238}, {0x19563106, 0x31004369}, {0x9e1407, 0x511c3a2}, {0x3206008, 0x5620414}, {0x19664d06, 0x310484c8}, {0x168280a, 0x62a8560}, {0x19766906, 0x3104c624}, {0x36f6e0b, 0x76ac6a5}, {0x19868506, 0x3109077e}, {0x770e0d, 0x80b47df}, {0x1996a106, 0x310948d8}, {0x1be340f, 0x933c91b}, {0x19a6bd06, 0x310d89c8}, {0x19b6d906, 0x310dca75}, {0x19c62a22, 0x98020b42}, {0x19d69a22, 0x980a4c1e}, {0x19e62a29, 0xba028cfa}, {0x19f69a29, 0xba0acdd6}, {0x1a062a30, 0xdc030eb2}, {0x1a169a30, 0xdc0b4f75}, {0x30000000, 0x0}, {0x30000000, 0x0}, {0x30000000, 0x0}, {0x30000000, 0x0}, {0x30000000, 0x0}, {0x30000000, 0x0}, {0x30000000, 0x0}, {0x30000000, 0x0}},
    {{0x1c13a00, 0x380000}, {0x1c83802, 0x1388087}, {0x1cf3e03, 0x238c120}, {0x1d63c05, 0x33941b9}, {0x1947150d, 0x20000243}, {0x5c0807, 0x409c348}, {0x1957310d, 0x2000437f}, {0x2204008, 0x542040b}, {0x19674d0d, 0x200484de}, {0x228400a, 0x642856a}, {0x1977690d, 0x2004c63a}, {0x132240c, 0x723070e}, {0x1987850d, 0x20090794}, {0x37060d, 0x80347dd}, {0x1997a10d, 0x200948ed}, {0x27e4c0f, 0x94bc923}, {0x19a7bd0d, 0x200d89d3}, {0x19b7d90d, 0x200dca80}, {0x19c73122, 0x98020b4f}, {0x19d7a122, 0x980a4c2b}, {0x19e73129, 0xba028d07}, {0x19f7a129, 0xba0acde3}, {0x1a073130, 0xdc030ebf}, {0x1a17a130, 0xdc0b4f81}, {0x30000000, 0x0}, {0x30000000, 0x0}, {0x30000000, 0x0}, {0x30000000, 0x0}, {0x30000000, 0x0}, {0x30000000, 0x0}, {0x30000000, 0x0}, {0x30000000, 0x0}},
    {{0x2014200, 0x400000}, {0x2084002, 0x1408088}, {0x20f4603, 0x240c121}, {0x2164405, 0x34141ba}, {0x19480014, 0x7500024e}, {0x2db5e06, 0x4598336}, {0x19581c14, 0x75004395}, {0x2e05808, 0x55a0411}, {0x19683814, 0x750484f4}, {0x2a8500a, 0x652856f}, {0x19785414, 0x7504c650}, {0x1712a0c, 0x72b06e5}, {0x19887014, 0x750907a9}, {0x1772e0d, 0x82b47e9}, {0x19988c14, 0x75094903}, {0x2fe5c0f, 0x95bc927}, {0x19a8a814, 0x750d89de}, {0x19b8c414, 0x750dca8b}, {0x19c83822, 0x98060b5d}, {0x19d8a822, 0x980e4c39}, {0x19e83829, 0xba068d15}, {0x19f8a829, 0xba0ecdf1}, {0x1a083830, 0xdc070ecd}, {0x1a18a830, 0xdc0f4f8e}, {0x30000000, 0x0}, {0x30000000, 0x0}, {0x30000000, 0x0}, {0x30000000, 0x0}, {0x30000000, 0x0}, {0x30000000, 0x0}, {0x30000000, 0x0}, {0x30000000, 0x0}},
    {{0x2414a00, 0x480000}, {0x2484802, 0x1488089}, {0x24f4e03, 0x248c122}, {0x2564c05, 0x34941bb}, {0x1949001b, 0x64000259}, {0x9b1606, 0x411831e}, {0x19591c1b, 0x640043aa}, {0x3a07008, 0x572041b}, {0x1969381b, 0x6404850a}, {0x368680a, 0x66a8576}, {0x1979541b, 0x6404c665}, {0x3b0700c, 0x77306d4}, {0x1989701b, 0x640907bf}, {0x237460d, 0x84347f2}, {0x19998c1b, 0x64094919}, {0x33e640f, 0x963c92a}, {0x19a9a81b, 0x640d89e9}, {0x19b9c41b, 0x640dca95}, {0x19c93f22, 0x98060b6b}, {0x19d9af22, 0x980e4c47}, {0x19e93f29, 0xba068d23}, {0x19f9af29, 0xba0ecdff}, {0x1a093f30, 0xdc070ed9}, {0x1a19af30, 0xdc0f4f9a}, {0x30000000, 0x0}, {0x30000000, 0x0}, {0x30000000, 0x0}, {0x30000000, 0x0}, {0x30000000, 0x0}, {0x30000000, 0x0}, {0x30000000, 0x0}, {0x30000000, 0x0}},
    {{0x2815200, 0x500000}, {0x2885002, 0x150808b}, {0x28f5603, 0x250c124}, {0x2965405, 0x35141bd}, {0x194a0714, 0x75000264}, {0x1da3c06, 0x4398300}, {0x195a2314, 0x750043c0}, {0x3e07808, 0x57a041e}, {0x196a3f14, 0x75048520}, {0x3e8780a, 0x67a857d}, {0x197a5b14, 0x7504c67b}, {0x1b0300c, 0x73306be}, {0x198a7714, 0x750907d4}, {0x2b7560d, 0x85347f8}, {0x2ba540e, 0x9538879}, {0x199a9314, 0x7509492e}, {0x19aaaf14, 0x750d89f3}, {0x19bacb14, 0x750dcaa0}, {0x19ca4622, 0x98060b79}, {0x19dab622, 0x980e4c55}, {0x19ea4629, 0xba068d31}, {0x19fab629, 0xba0ece0d}, {0x1a0a4630, 0xdc070ee5}, {0x1a1ab630, 0xdc0f4fa6}, {0x30000000, 0x0}, {0x30000000, 0x0}, {0x30000000, 0x0}, {0x30000000, 0x0}, {0x30000000, 0x0}, {0x30000000, 0x0}, {0x30000000, 0x0}, {0x30000000, 0x0}},
    {{0x2c15a00, 0x580000}, {0x2c85802, 0x158808c}, {0x2cf5e03, 0x258c125}, {0x2d65c05, 0x35941be}, {0x194b071b, 0x64000277}, {0xda1c06, 0x41982f4}, {0x195b231b, 0x640043d6}, {0x610a08, 0x50a0423}, {0x196b3f1b, 0x64048536}, {0x690a0a, 0x60a8582}, {0x197b5b1b, 0x6404c690}, {0x130200c, 0x72306b8}, {0x2f25c0c, 0x75b0721}, {0x198b771b, 0x640907ea}, {0x1ba340e, 0x933886e}, {0x199b931b, 0x64094944}, {0x19abaf1b, 0x640d89fe}, {0x19bbcb1b, 0x640dcaab}, {0x19cb4d22, 0x98060b86}, {0x19dbbd22, 0x980e4c62}, {0x19eb4d29, 0xba068d3e}, {0x19fbbd29, 0xba0ece1a}, {0x1a0b4d30, 0xdc070ef1}, {0x1a1bbd30, 0xdc0f4fb2}, {0x30000000, 0x0}, {0x30000000, 0x0}, {0x30000000, 0x0}, {0x30000000, 0x0}, {0x30000000, 0x0}, {0x30000000, 0x0}, {0x30000000, 0x0}, {0x30000000, 0x0}},
    {{0x3016200, 0x600000}, {0x3086002, 0x160808d}, {0x30f6603, 0x260c126}, {0x3166405, 0x36141bf}, {0x194c1c06, 0x3100028d}, {0x1a0406, 0x40182ed}, {0x195c3806, 0x310443ec}, {0xe11a08, 0x51a0427}, {0x196c5406, 0x3104854c}, {0xe91a0a, 0x61a8586}, {0x3ea7c0a, 0x67a85d3}, {0x197c7006, 0x3108c6a6}, {0x133260c, 0x8230739}, {0x198c8c06, 0x31090800}, {0x3ba740e, 0x9738884}, {0x199ca806, 0x310d4959}, {0x19acc406, 0x310d8a09}, {0x19bcd214, 0x750dcab8}, {0x19cc5422, 0x98060b94}, {0x19dcc422, 0x980e4c70}, {0x19ec5429, 0xba068d4c}, {0x19fcc429, 0xba0ece28}, {0x1a0c5430, 0xdc070efd}, {0x1a1cc430, 0xdc0f4fbe}, {0x30000000, 0x0}, {0x30000000, 0x0}, {0x30000000, 0x0}, {0x30000000, 0x0}, {0x30000000, 0x0}, {0x30000000, 0x0}, {0x30000000, 0x0}, {0x30000000, 0x0}},
    {{0x3416a00, 0x680000}, {0x3486802, 0x168808f}, {0x34f6e03, 0x268c128}, {0x3566c05, 0x36941c1}, {0x194d1c0d, 0x200002a3}, {0x3196206, 0x46182e1}, {0x29c5007, 0x451c360}, {0x195d380d, 0x20044402}, {0xe41809, 0x51a44ab}, {0x196d540d, 0x20048562}, {0xab160a, 0x61285db}, {0x197d700d, 0x2008c6bc}, {0x3726c0c, 0x76b0726}, {0x198d8c0d, 0x20090815}, {0x13a240e, 0x9238868}, {0x199da80d, 0x200d4967}, {0x19adc40d, 0x200d8a14}, {0x19bdd21b, 0x640dcac6}, {0x19cd5b22, 0x98060ba2}, {0x19ddcb22, 0x980e4c7e}, {0x19ed5b29, 0xba068d5a}, {0x19fdcb29, 0xba0ece36}, {0x1a0d5b30, 0xdc070f09}, {0x1a1dcb30, 0xdc0f4fca}, {0x30000000, 0x0}, {0x30000000, 0x0}, {0x30000000, 0x0}, {0x30000000, 0x0}, {0x30000000, 0x0}, {0x30000000, 0x0}, {0x30000000, 0x0}, {0x30000000, 0x0}},
    {{0x3817200, 0x700000}, {0x3887002, 0x1708090}, {0x38f7603, 0x270c129}, {0x3967405, 0x37141c2}, {0x194e2306, 0x310002b9}, {0x2594a06, 0x44982da}, {0x21c4007, 0x441c35b}, {0x195e3f06, 0x31044418}, {0x1a43009, 0x53244b5}, {0x196e5b06, 0x31048577}, {0x22b460a, 0x64285ec}, {0x197e7706, 0x3108c6d1}, {0x3b2740c, 0x773072a}, {0x198e9306, 0x3109082b}, {0x27a4c0e, 0x94b8877}, {0x199eaf06, 0x310d4972}, {0x19aecb06, 0x310d8a1f}, {0x19bed914, 0x750dcad4}, {0x19ce6222, 0x98060bb0}, {0x19ded222, 0x980e4c8c}, {0x19ee6229, 0xba068d68}, {0x19fed229, 0xba0ece44}, {0x1a0e6230, 0xdc070f15}, {0x1a1ed230, 0xdc0f4fd6}, {0x30000000, 0x0}, {0x30000000, 0x0}, {0x30000000, 0x0}, {0x30000000, 0x0}, {0x30000000, 0x0}, {0x30000000, 0x0}, {0x30000000, 0x0}, {0x30000000, 0x0}},
    {{0x3c17a00, 0x780000}, {0x3c87802, 0x1788091}, {0x3cf7e03, 0x278c12a}, {0x3d67c05, 0x37941c3}, {0x2a3f3f32, 0x4081c244}, {0x194f230d, 0x200002cf}, {0x19c3007, 0x431c355}, {0x195f3f0d, 0x2004442e}, {0x2244009, 0x54244ba}, {0x196f5b0d, 0x2004858d}, {0x32b660a, 0x66285f5}, {0x197f770d, 0x2008c6e7}, {0x3f27c0c, 0x77b072d}, {0x198f930d, 0x20090840}, {0x33a640e, 0x963887d}, {0x199faf0d, 0x200d497c}, {0x19afcb0d, 0x200d8a29}, {0x19bfd91b, 0x640dcae1}, {0x19cf6922, 0x98060bbd}, {0x19dfd922, 0x980e4c99}, {0x19ef6929, 0xba068d75}, {0x19ffd929, 0xba0ece51}, {0x1a0f6930, 0xdc070f21}, {0x1a1fd930, 0xdc0f4fe2}, {0x30000000, 0x0}, {0x30000000, 0x0}, {0x30000000, 0x0}, {0x30000000, 0x0}, {0x30000000, 0x0}, {0x30000000, 0x0}, {0x30000000, 0x0}, {0x30000000, 0x0}}
}};
static_assert(NJOB + NCONV == 32, "");

__device__ __forceinline__ unsigned read_back(const void* p) {
    unsigned v = 0;
    asm volatile("ld.relaxed.gpu.global.u32 %0, [%1];" : "=r"(v) : "l"(p) : "memory");
    return v;
}
__device__ __forceinline__ void publish(unsigned* flag, unsigned seen, unsigned zero) {
    asm volatile("{\n.reg .pred p;\n.reg .u32 t;\nredux.sync.or.b32 t, %1, 0xffffffff;\nand.b32 t, t, %2;\nadd.u32 t, t, 1;\n"
                 "elect.sync _|p, 0xffffffff;\n@p red.relaxed.gpu.global.add.u32 [%0], t;\n}" :: "l"(flag), "r"(seen), "r"(zero) : "memory");
}

__device__ __forceinline__ void load_w(uint2 (&v)[32], const char* g) {
#pragma unroll
    for (int k = 0; k < 32; k++)
        asm volatile("ld.global.nc.L1::no_allocate.v2.b32 {%0,%1}, [%2];" : "=r"(v[k].x), "=r"(v[k].y) : "l"(g + k * (N_ * 4)));
}
__device__ __forceinline__ void store_w(const uint2 (&v)[32], unsigned (&o)[16], char* d) {
#pragma unroll
    for (int i = 0; i < 8; i++) {
        o[i] = pack4(v[4 * i].x, v[4 * i + 1].x, v[4 * i + 2].x, v[4 * i + 3].x);
        o[8 + i] = pack4(v[4 * i].y, v[4 * i + 1].y, v[4 * i + 2].y, v[4 * i + 3].y);
        if ((i & 3) == 3) {
            stg128(d + (i >> 2) * 128, make_uint4(o[i - 3], o[i - 2], o[i - 1], o[i]));
            stg128(d + (i >> 2) * 128 + 256, make_uint4(o[i + 5], o[i + 6], o[i + 7], o[i + 8]));
        }
    }
}
__device__ __forceinline__ unsigned col_sums(const unsigned (&o)[16]) {
    int cs[4];
#pragma unroll
    for (int i = 0; i < 4; i++)
        cs[i] = __dp4a((int)o[4 * i], 0x01010101, __dp4a((int)o[4 * i + 1], 0x01010101,
                __dp4a((int)o[4 * i + 2], 0x01010101, __dp4a((int)o[4 * i + 3], 0x01010101, 0))));
    return cs[0] + cs[1] + (cs[2] + cs[3]) * 65536;
}
__device__ __forceinline__ void wait_until(int due, unsigned t0) {
    for (int rem; (rem = due - (int)(clk() - t0)) > 0;) if (rem > CFG_SLEEP) __nanosleep(CFG_SLEEP / 4);
}

__device__ __forceinline__ uint32_t zero_term(const unsigned (&sv)[4], float zxf) {
    int lo = 0, hi = 0;
#pragma unroll
    for (int h = 0; h < 4; h++) {
        const int l = (int)(short)(sv[h] & 0xFFFF);
        lo += l; hi += ((int)(sv[h] - (unsigned)l)) >> 16;
    }
    const float fl = __bfloat162float(__float2bfloat16_rn((float)lo)) * zxf, fh = __bfloat162float(__float2bfloat16_rn((float)hi)) * zxf;
    uint32_t z;
    asm("cvt.rn.bf16x2.f32 %0, %1, %2;" : "=r"(z) : "f"(fh), "f"(fl));
    return z;
}

__device__ __forceinline__ void load_x(Scratch* scr, uint32_t sb, int b, int lane) {
    const int r = b & 15;
    const unsigned tgt = (*(volatile unsigned*)&scr->epoch[b] + 1) * 4;
    const unsigned* f = scr->flag + r * FS + (lane & 15);
    const uint32_t sa = __shfl_sync(~0u, sb, 0);
    const char* const ga = (const char*)scr->a8 + __shfl_sync(~0u, r * 16 * 8192, 0);
    unsigned todo = 0xFFFF, v = ld_flag(f);
    asm volatile("barrier.cluster.wait.aligned;" ::: "memory");
#pragma unroll 1
    for (int it = 0; todo; it++) {
        unsigned m = __ballot_sync(~0u, (int)(v - tgt) >= 0) & todo;
        v = ld_flag(f);
        todo &= ~m;
        while (m) {
            const int sl = __ffs(m) - 1;
            m &= m - 1;
            asm volatile("{\n.reg .pred p;\nelect.sync _|p, 0xffffffff;\n"
                         "@p cp.async.bulk.shared::cluster.global.mbarrier::complete_tx::bytes [%0], [%1], 8192, [%2];\n}"
                         :: "r"(sa + sl * 8192), "l"(ga + (unsigned)sl * 8192), "r"(sa + SM_BAR + (B_FULL + sl) * 8) : "memory");
        }
        if (it > (1 << 20)) __trap();
    }
}

__device__ __forceinline__ void load_x4(Scratch* scr, uint32_t sb, int b, int h, int lane) {
    const uint32_t bars = sb + SM_BAR;
    const unsigned tgt = (*(volatile unsigned*)&scr->epoch[b] + 1) * 4;
    const unsigned* f = scr->flag + (4 * h + (lane >> 4)) * FS + (lane & 15);
    asm volatile("barrier.cluster.wait.aligned;" ::: "memory");
#pragma unroll 1
    for (int it = 0, sl = 0; sl < 16; it++) {
        const unsigned v0 = ld_flag(f), v1 = ld_flag(f + 2 * FS);
        unsigned m = __ballot_sync(~0u, (int)(v0 - tgt) >= 0 && (int)(v1 - tgt) >= 0);
        m &= m >> 16;
#pragma unroll 1
        for (; m >> sl & 1; sl++) {
            if (sl >= 4) mbar_wait(bars + (B_GO + sl - 4) * 8);
            if (elect_one()) {
#pragma unroll
                for (int k = 0; k < 4; k++)
                    asm volatile("cp.async.bulk.shared::cluster.global.mbarrier::complete_tx::bytes [%0], [%1], %2, [%3];"
                                 :: "r"(sb + SM_A + ((sl & 3) * 4 + k) * 8192), "l"((const char*)scr->a8 + ((4 * h + k) * 16 + sl) * 8192),
                                    "r"(8192), "r"(bars + (B_FULL + (k >> 1) * 16 + sl) * 8) : "memory");
            }
        }
        if (it > (1 << 20)) __trap();
    }
}

__device__ __forceinline__ void store_out(const CUtensorMap* map, uint32_t sb, int b, int agent, int lane, int n, unsigned seq, int col, int dcol, int row, int drow) {
    const uint32_t bars = sb + SM_BAR;
    const uint32_t buf = sb + SM_OUT + agent * 4096, full = bars + (B_OFULL + agent) * 8;
#pragma unroll 1
    for (int t = 0; t < n; t++, seq >>= 4) {
        asm volatile("{\n.reg .pred p;\n.reg .u32 c;\nmov.u32 c, 0;\n"
                     "WAIT_LOOP:\n"
                     "mbarrier.try_wait.parity.shared::cta.b64 p, [%4], %5;\n"
                     "@p bra WAIT_DONE;\n"
                     "add.u32 c, c, 1;\nsetp.lt.u32 p, c, 0x100000;\n"
                     "@p bra WAIT_LOOP;\n"
                     "trap;\n"
                     "WAIT_DONE:\n"
                     "fence.proxy.async.shared::cta;\n"
                     "elect.sync _|p, 0xffffffff;\n"
                     "@p cp.async.bulk.tensor.2d.global.shared::cta.tile.bulk_group [%0, {%1, %2}], [%3];\n"
                     "cp.async.bulk.commit_group;\n}"
                     :: "l"(map), "r"(col + (seq & 7) * dcol), "r"(row + agent * 32 + (seq & 7) * drow), "r"(buf), "r"(full), "r"(t & 1) : "memory");
        asm volatile("cp.async.bulk.wait_group.read 0;" ::: "memory");
        if (elect_one()) mbar_arrive(bars + (B_OFREE + t * 4 + 4 + agent) * 8);
    }
}

template <int V> struct I { static constexpr int v = V; };
template <int MODE>
__device__ __forceinline__ void consume(Scratch* scr, const __nv_bfloat16* __restrict__ scale_w, const __nv_bfloat16* __restrict__ bias,
                                        const __nv_bfloat16* __restrict__ scale_x, uint32_t sb, int b, int warp, int lane) {
    constexpr bool SIDE = MODE != 0;
    constexpr int NR = NRING, NG = SIDE ? 48 : 56;
    const uint32_t bars = sb + SM_BAR;
    const int c = SIDE ? 7 : b >> 4;
    constexpr uint32_t SD = 0x400 >> 4;
    if ((sb & 0xFFFFFF) != 0x400) __trap();
    const int wg = warp >> 2;
    const unsigned short sxr = __ldg((const unsigned short*)scale_x);
    const uint32_t sx2 = (uint32_t)sxr * 0x10001u;
    const int c0 = (warp & 3) * 16 + (lane >> 2) * 2;
    uint32_t sw[4], bi[4];
#pragma unroll
    for (int i = 0; i < 4; i++) {
        const int col = col_of(c, i < 2 ? wg * 2 + i : i == 2 ? 4 + wg : 6) + c0;
        sw[i] = __ldg((const uint32_t*)(scale_w + col));
        bi[i] = __ldg((const uint32_t*)(bias + col));
    }
    const uint32_t st0 = sb + SM_OUT + (lane & 3) * 256 + (((c0 >> 3) ^ ((lane & 3) * 2)) << 4) + (c0 & 7) * 2;
    constexpr uint32_t DX0 = (SD + (SM_A >> 4)) | (1 << 16), DW0 = (SD + (SM_RING >> 4)) | (8 << 16);
    asm volatile("barrier.cluster.wait.aligned;" ::: "memory");
    int a0[64], a1[64];
    constexpr int MUL = SIDE ? 4 : 2, NONE = 64 * MUL, BIAS = NR + 64 - NG;
    const uint32_t go = mapa(bars + B_GO * 8, lane & (SIDE ? 1 : 15)) - (64 - NG) * MUL;
    const int key = SIDE ? (lane < 2 ? lane * 4 : 1) : (lane < 16 ? (lane >> 2) * 2 : 1);
    int pend = NONE;
    uint32_t bb = bars + (B_FULL + wg * 16) * 8;
#define RELEASE() { mbar_arrive_cluster_if(go + (pend & ~7), pend & (NONE + 8 - MUL), key); }
    struct Par { uint32_t a, b, c, d; };
    auto load_par = [&](int blk, uint32_t swv, uint32_t biv) {
        mbar_wait_cluster(bars + (B_PAR + blk) * 8);
        const uint32_t zc = lds32(sb + SM_PAR + (blk * 64 + c0) * 2);
        const float sxf = __uint_as_float(sx2 << 16);
        const float s0 = sxf * __uint_as_float(swv << 16), s1 = sxf * __uint_as_float(swv & 0xFFFF0000u);
        Par P = {__float_as_uint(s0), __float_as_uint(s1), __float_as_uint(fmaf(-__uint_as_float(zc << 16), s0, __uint_as_float(biv << 16))),
                 __float_as_uint(fmaf(-__uint_as_float(zc & 0xFFFF0000u), s1, __uint_as_float(biv & 0xFFFF0000u)))};
        asm volatile("{\n.reg .pred p;\nsetp.ne.u32 p, %3, 0;\n@p st.shared.v2.b32 [%0], {%1, %2};\n}" :: "r"(st0), "r"(P.c), "r"(P.d), "r"(blockIdx.y) : "memory");
        return P;
    };
    auto drain = [&](int (&a)[64], auto Q, int t, const Par& P) {
#pragma unroll
        for (int q = Q.v; q < Q.v + 2; q++) {
#pragma unroll
            for (int j = 0; j < 8; j++) {
                const int o = q * 16 + (j >> 1) * 4 + (j & 1);
                asm("cvt.rn.f32.s32 %0, %0;\n\tcvt.rn.f32.s32 %1, %1;\n\tfma.rn.f32 %0, %0, %2, %4;\n\tfma.rn.f32 %1, %1, %3, %5;\n\t"
                    "cvt.rn.bf16x2.f32 %0, %1, %0;" : "+r"(a[o]), "+r"(a[o + 2]) : "r"(P.a), "r"(P.b), "r"(P.c), "r"(P.d));
            }
            mbar_wait(bars + (B_OFREE + t * 4 + q) * 8);
#pragma unroll
            for (int j = 0; j < 8; j++) sts32((st0 ^ ((j & 1) * 16)) + q * 4096 + (j >> 1) * 1024 + (j & 1) * 128, a[q * 16 + (j >> 1) * 4 + (j & 1)]);
            __syncwarp();
            if (lane == 0) mbar_arrive(bars + (B_OFULL + q) * 8);
        }
    };
    wg_fence();
    if (MODE == 2) {
#pragma unroll 1
        for (int s = 0; s < 16; s++) {
            mbar_wait2(bars + (B_FULL + 48 + (s >> 2) * 2) * 8, bb + s * 8);
            mma_rows2(a0, a1, DW0 + s * 256, DX0 + ((s & 3) * 4 + 2 * wg) * 512, s);
            wg_wait<1>();
            if (s && lane == 0) mbar_arrive(bars + (B_GO + s - 1) * 8);
        }
        const Par P = load_par(6, sw[3], bi[3]);
        wg_wait<0>();
        drain(a0, I<0>(), wg, P); drain(a0, I<2>(), wg, P);
        drain(a1, I<0>(), 2 + wg, P); drain(a1, I<2>(), 2 + wg, P);
    } else {
    {
        uint32_t tbl = wg ? STEPS1 : STEPS0;
        uint32_t ba = bars + B_FULL * 8;
        int u = MUL * (wg * D_ + BIAS);
        uint32_t dw = DW0 + wg * D_ * 512;
        static_assert(D_ < NR, "");
        mbar_wait2(ba, bb);
#pragma unroll 1
        for (uint32_t dx = DX0;;) {
            mma_unit2(a0, a1, dw, dx, dx - DX0);
            dx += 512; ba += 8; bb += 8;
            const bool ready = mbar_test2(ba, bb);
            wg_wait<1>();
            RELEASE()
            pend = u;
            if (dx == DX0 + 16 * 512) break;
            u += MUL + (tbl & 1) * MUL;
            dw += 512 + (tbl & 1) * 512;
            if (dw >= DW0 + NR * 512) dw -= NR * 512;
            tbl >>= 1;
            if (!ready && !mbar_test2(ba, bb)) {
                wg_wait<0>();
                RELEASE()
                pend = NONE;
                mbar_wait(ba);
                if (wg) mbar_wait(bb);
            }
        }
    }
    Par P0 = load_par(2 * wg, sw[0], bi[0]);
    const Par P1 = load_par(2 * wg + 1, sw[1], bi[1]);
#define RELEASE2() { mbar_arrive_cluster_if(go + (pend & ~7), pend & (NONE + 8 - 2 * MUL), key & ~MUL); }
    static_assert(NR % 2 == 0, "");
    wg_wait<0>();
#pragma unroll 1
    for (int ph = 0;; ph++) {
        const int m = ph ? MUL : 0;
        const int u0 = 32 + ph * 16 + wg * 8;
        uint32_t dw = DW0 + (ph ? 48 % NR : wg ? 40 % NR : 32 % NR) * 512;
        bb = bars + (B_FULL + u0) * 8;
        mbar_arrive_cluster_if(go + (pend & ~7), pend & (NONE + 8 - MUL - m), key & ~m);
        drain(a0, I<0>(), ph ? (ph + wg) * 2 + (ph & 2) + SIDE : wg, P0);
        const bool first = mbar_test(bb);
        drain(a0, I<2>(), wg ? 4 * ph + 1 : 3 * ph, P0);
        if (SIDE ? ph + wg == 1 : ph == 1) drain(a1, I<0>(), SIDE ? 4 - 2 * wg : 3 + 2 * wg, P1);
        if (SIDE ? ph == 1 : ph + wg == 2) break;
        pend = NONE;
        if (!first) mbar_wait(bb);
        if (ph + wg) mbar_wait(bars + (B_TURN + ph) * 8);
        wg_fence();
#pragma unroll 1
        for (int n = 0;; n += 2) {
            const bool ready = mma_pair(a0, dw, DX0 + n * 1024, n, bb + n * 8 + 16, go + (pend & ~7), pend & (NONE + 8 - 2 * MUL), key & ~MUL);
            wg_wait<1>();
            pend = n ? MUL * (u0 + BIAS + n - 2) : NONE;
            if (n == 6) break;
            dw += 1024;
            if (dw == DW0 + NR * 512) dw = DW0;
            if (!ready) {
                RELEASE2()
                pend = NONE;
                mbar_wait(bb + n * 8 + 16);
            }
        }
        if (ph == 0 && (threadIdx.x & 127) == 0) mbar_arrive(bars + (B_TURN + wg) * 8);
        RELEASE2()
        pend = MUL * (u0 + BIAS + 6);
        if (ph == 0) drain(a1, I<2>(), 2 + 2 * wg, P1);
        P0 = load_par(4 + 2 * ph + wg, ph ? sw[3] : sw[2], ph ? bi[3] : bi[2]);
        wg_wait<0>();
    }
    }
    if (threadIdx.x == 128) asm volatile("red.relaxed.gpu.global.add.u32 [%0], 1;" :: "l"(scr->epoch + b) : "memory");
}

__global__ void __cluster_dims__(CS, 1, 1) __launch_bounds__(512, 1)
w8a8_kernel(const char* __restrict__ qx, const char* __restrict__ qw, Scratch* scr, const JobTable* __restrict__ jobs, const __nv_bfloat16* __restrict__ scale_w,
            const __nv_bfloat16* __restrict__ bias, const __nv_bfloat16* __restrict__ scale_x, const int* __restrict__ zero_x,
            const __grid_constant__ CUtensorMap map) {
    extern __shared__ __align__(1024) unsigned char smem_raw[];
    const uint32_t sb = (uint32_t)__cvta_generic_to_shared(smem_raw);
    const uint32_t bars = sb + SM_BAR;
    const int b = blockIdx.x, r = b & 15, c = b >> 4;
    const int warp = __shfl_sync(~0u, threadIdx.x >> 5, 0), lane = threadIdx.x & 31;
    {
        const int g = (int)(threadIdx.x >> 6) * 7 + c - 12;
        asm volatile("{\n.reg .pred p;\nsetp.lt.u32 p, %1, %2;\n@p prefetch.global.L2 [%0];\n}"
                     :: "l"(qx + (r * 128 + (g & 3) * 32 + ((threadIdx.x >> 1) & 31)) * (K_ * 4) + (g >> 2) * 256 + (threadIdx.x & 1) * 128), "r"(g), "n"(CFG_NG0) : "memory");
    }
    const unsigned t0 = clk() + CFG_PF0;
    if (warp >= 8) {
        asm volatile("barrier.cluster.arrive.relaxed.aligned;" ::: "memory");
        asm volatile("setmaxnreg.dec.sync.aligned.u32 88;");
        int agent = -1;
        if (warp >= 16 - NCONV) {
            const int cw = warp - (16 - NCONV);
            const unsigned zero = blockIdx.y;
            const char* const gx = qx + (lane >> 4) * (K_ * 4) + (lane & 15) * 16;
            const char* const gw = qw + lane * 8;
            const int wrB = ((lane >> 3) * 32 + (lane & 7)) * 16;
            uint2 tab;
            asm volatile("ld.global.nc.v2.u32 {%0, %1}, [%2];" : "=r"(tab.x), "=r"(tab.y) : "l"(&jobs->e[b][lane]));
            bool synced = false;
#pragma unroll 1
            for (int p = cw || c >= 5 ? cw : NCONV;; p = p < CFG_PZ ? p + NCONV : p < CFG_PZ + 3 ? 31 : p + 3) {
                uint2 j;
                if (p < 4) {
                    const int g = 7 * p + c - 5;
                    j.x = ((r * 128 + (g & 3) * 32) * 16 + (g >> 2)) | (r * 64 + g) << 16;
                    j.y = max((p - 1) * (CFG_P0 / 4) + b * (CFG_P0 * 4 / NCTA) / 16, 0) | (r * FS + (g >> 2)) << 14 | p << 24;
                } else { j.x = __shfl_sync(~0u, tab.x, p); j.y = __shfl_sync(~0u, tab.y, p); }
                if (j.x >= 3u << 28) break;
                const int kind = j.x >> 28, sig = (j.y >> 14) & 0x3FF;
                char* tile = (char*)scr + ((j.x >> 16) & 0xFFF) * 2048;
                const char* g = (kind ? gw : gx) + (j.x & 0xFFFF) * 256;
                wait_until((j.y & 0x3FFF) * 4, t0);
                if (kind == 0) {
                    uint4 v[16];
#pragma unroll
                    for (int i = 0; i < 16; i++)
                        asm volatile("ld.global.nc.L1::no_allocate.v4.b32 {%0,%1,%2,%3}, [%4];"
                                     : "=r"(v[i].x), "=r"(v[i].y), "=r"(v[i].z), "=r"(v[i].w) : "l"(g + i * (2 * K_ * 4)));
#pragma unroll
                    for (int i = 0; i < 16; i++)
                        asm volatile("st.global.b32 [%0], %1;" :: "l"(tile + ((lane * 4) ^ ((i & 3) * 16)) + i * 128),
                                     "r"(pack4(v[i].x, v[i].y, v[i].z, v[i].w)) : "memory");
                    asm volatile("fence.proxy.async.global;" ::: "memory");
                    __syncwarp();
                    publish(scr->flag + sig, read_back(tile + lane * 64), zero);
                } else {
                    uint2 v[32];
                    unsigned o[16];
                    load_w(v, g);
                    if (!synced) asm volatile("barrier.cluster.wait.aligned;" ::: "memory");
                    synced = true;
                    store_w(v, o, tile + wrB);
                    asm volatile("{\n.reg .pred p;\nsetp.eq.u32 p, %1, 0;\nfence.proxy.async.global;\nbar.warp.sync 0xffffffff;\n"
                                 "@p mbarrier.arrive.shared::cta.b64 _, [%0];\n}" :: "r"(bars + (B_GO + (sig & 15)) * 8), "r"(lane | (kind & 2)) : "memory");
                    const unsigned csv = col_sums(o);
                    if (kind == 1) {
                        const int own = (j.y >> (24 + (lane >> 4) * 4)) & 15;
                        const uint32_t so = SM_SUM + (sig & 48) * 4 + (lane & 15) * 4;
                        if (own != r) {
                            const uint32_t ro = mapa(sb, own);
                            asm volatile("red.async.relaxed.cluster.shared::cluster.mbarrier::complete_tx::bytes.add.u32 [%0], %1, [%2];"
                                         :: "r"(ro + so), "r"(csv), "r"(ro + SM_BAR + B_SUM * 8) : "memory");
                        } else asm volatile("red.relaxed.cluster.shared::cta.add.u32 [%0], %1;" :: "r"(sb + so), "r"(csv) : "memory");
                        __syncwarp();
                        if (own == r && (lane & 15) == 0) mbar_arrive(bars + B_SUM * 8);
                    } else {
                        unsigned* csp = scr->cs + (j.y >> 24) * 32 + lane;
                        asm volatile("st.global.u32 [%0], %1;" :: "l"(csp), "r"(csv) : "memory");
                        publish(scr->flag + sig, read_back(tile + lane * 64) | read_back(csp), zero);
                    }
                }
                __syncwarp();
            }
            if (!synced) asm volatile("barrier.cluster.wait.aligned;" ::: "memory");
            agent = (cw + 6 * NCONV - CFG_PZ) % NCONV + 1;
            if (agent > 3) agent = -1;
        } else if (warp == 9) {
            if (elect_one()) asm volatile("prefetch.tensormap [%0];" :: "l"(&map) : "memory");
            asm volatile("barrier.cluster.wait.aligned;" ::: "memory");
        } else {
            load_x(scr, sb, b, lane);
            agent = 0;
        }
        const char* src = (const char*)scr->b8 + (c * 224 + r) * 2048;
        const int zxi = __ldg(zero_x);
#pragma unroll 1
        for (int i = 0, slot = r >> 2, end = r < 8 ? 8 : 10;; end = NG / 4) {
#pragma unroll 1
            for (; warp == 9 && i < end; i++) {
                asm volatile("{\n.reg .pred p;\nWAIT_LOOP:\nmbarrier.try_wait.parity.shared::cta.b64 p, [%4], 0;\n@!p bra WAIT_LOOP;\n"
                             "elect.sync _|p, 0xffffffff;\n"
                             "@p cp.async.bulk.shared::cluster.global.mbarrier::complete_tx::bytes.multicast::cluster [%0], [%1], 2048, [%2], %3;\n}"
                             :: "r"(sb + SM_RING + slot * 8192 + (r & 3) * 2048), "l"(src + i * 32768),
                                "r"(bars + (B_FULL + bar_of(4 * i + (r >> 2))) * 8), "h"((uint16_t)0xFFFF), "r"(bars + (B_GO + i) * 8) : "memory");
                slot += slot >= NRING - 4 ? 4 - NRING : 4;
            }
            if (end == NG / 4) break;
            if (warp == (r < 10 ? 9 : r < 14 ? 16 - NCONV + (CFG_PZ + 3) % NCONV : 0)) {
                const float zxf = __bfloat162float(__float2bfloat16_rn((float)zxi));
                const int grp = sum_group(r);
                mbar_wait_cluster(bars + B_SUM * 8);
                unsigned sv[4];
#pragma unroll
                for (int h = 0; h < 4; h++) sv[h] = lds32(sb + SM_SUM + h * 64 + (lane & 15) * 4);
                const uint32_t z = zero_term(sv, zxf);
#pragma unroll 2
                for (int k = 0; k < 8; k++) {
                    const uint32_t rb = mapa(sb, k * 2 + (lane >> 4));
                    st_async32(rb + SM_PAR + grp * 64 + (lane & 15) * 4, z, rb + SM_BAR + (B_PAR + (grp >> 1)) * 8);
                }
            }
        }
        __syncwarp();
        if (agent >= 0) store_out(&map, sb, b, agent, lane, 7, agent < 2 ? 0x6351420 : 0x6534120, c * 64, 7 * 64, r * 128, 0);
    } else {
        if (warp == 6) asm volatile("griddepcontrol.launch_dependents;");
        if (warp < CFG_NINIT) {
            wait_until(CFG_IDL, t0);
#pragma unroll 1
            for (int w = warp; w < 8; w += CFG_NINIT) {
                if (elect_one()) {
                    const uint32_t cnt = w < B_GO / 16 ? 1 : 4 * CS + 1;
#pragma unroll
                    for (int i = 0; i < 16; i++) mbar_init(bars + (w * 16 + i) * 8, cnt);
                }
                __syncwarp();
                const int i = w * 16 + lane;
                if (lane < 16 && i < B_OFREE + NOUT && (i >> 1) != B_TURN / 2) mbar_expect_tx(bars + i * 8, i >= B_AFREE ? 0 : i >= B_PAR ? 128 : w == 1 ? 8192 : 16384);
                if (w == B_GO / 16 && 4 * lane + (r >> 2) < NRING)
                    asm volatile("mbarrier.arrive.shared::cta.b64 _, [%0], %1;" :: "r"(bars + i * 8), "r"(4 * CS) : "memory");
            }
            if (warp == (B_SUM / 16) % CFG_NINIT) {
                if (elect_one()) {
#pragma unroll
                    for (int k = 0; k < NOUT; k++) mbar_init(bars + (B_OFULL + k) * 8, 4);
                    mbar_init(bars + B_SUM * 8, r < 8 ? 1 : 3);
                    mbar_expect_tx(bars + B_SUM * 8, r < 8 ? 32 * 64 : 30 * 64);
                }
            }
            asm volatile("fence.mbarrier_init.release.cluster;" ::: "memory");
        } else if (warp == 7) {
            asm volatile("st.shared.v2.b32 [%0], {%1, %1};" :: "r"(sb + SM_SUM + lane * 8), "r"(0) : "memory");
            asm volatile("fence.release.sync_restrict::shared::cta.cluster;" ::: "memory");
        }
        asm volatile("barrier.cluster.arrive.relaxed.aligned;" ::: "memory");
        asm volatile("setmaxnreg.inc.sync.aligned.u32 168;");
        consume<0>(scr, scale_w, bias, scale_x, sb, b, warp, lane);
    }
}

__global__ void __cluster_dims__(2, 1, 1) __launch_bounds__(512, 1)
w8a8_side(const char* __restrict__ qw, Scratch* scr, const __nv_bfloat16* __restrict__ scale_w, const __nv_bfloat16* __restrict__ bias,
          const __nv_bfloat16* __restrict__ scale_x, const int* __restrict__ zero_x, const __grid_constant__ CUtensorMap map) {
    extern __shared__ __align__(1024) unsigned char smem_raw[];
    const uint32_t sb = (uint32_t)__cvta_generic_to_shared(smem_raw);
    const uint32_t bars = sb + SM_BAR;
    const int warp = __shfl_sync(~0u, threadIdx.x >> 5, 0), lane = threadIdx.x & 31;
    const int b = NCTA + blockIdx.x, rank = b & 1;
    const bool helper = blockIdx.x >= 16;
    constexpr int NR = NRING;
    const unsigned t0 = clk();
    if (warp < 3) {
#pragma unroll 1
        for (int w = warp; w < B_OFULL / 16; w += 3) {
            if (elect_one()) {
                const uint32_t cnt = w < B_GO / 16 ? 1 : !helper ? 9 : w == B_GO / 16 ? 8 : 1;
#pragma unroll
                for (int i = 0; i < 16; i++) mbar_init(bars + (w * 16 + i) * 8, cnt);
            }
            __syncwarp();
            const int i = w * 16 + lane;
            if (lane < 16 && i < B_PAR) mbar_expect_tx(bars + i * 8, w == 1 && !helper ? 8192 : 16384);
            if (lane < 16 && i >= B_OFREE && i < B_OFREE + NOUT) mbar_arrive(bars + i * 8);
            if (w == B_GO / 16 && 2 * lane + rank < NR && !helper)
                asm volatile("mbarrier.arrive.shared::cta.b64 _, [%0], %1;" :: "r"(bars + i * 8), "r"(8) : "memory");
        }
        asm volatile("fence.mbarrier_init.release.cluster;" ::: "memory");
    } else if (warp == 3) {
        if (elect_one()) {
#pragma unroll
            for (int i = 0; i < NOUT; i++) mbar_init(bars + (B_OFULL + i) * 8, 4);
            asm volatile("fence.mbarrier_init.release.cluster;" ::: "memory");
        }
        __syncwarp();
    } else if (warp == 11 && elect_one()) asm volatile("prefetch.tensormap [%0];" :: "l"(&map) : "memory");
    asm volatile("barrier.cluster.arrive.relaxed.aligned;" ::: "memory");

    if (warp >= 8) {
        asm volatile("setmaxnreg.dec.sync.aligned.u32 88;");
        int agent = -1;
        if (warp == 10 || warp >= 12) {
#pragma unroll 1
            for (int i = (0x032401 >> (4 * (warp - 10))) & 7; i < (helper ? 8 : 12 - CFG_NOC / 4); i += 5) {
                const int G = (helper ? 192 - 16 + i * 4 : CFG_NOC * 4 + i * 16) + blockIdx.x, u = G >> 2, f = bar_of(u);
                const int blk = u < 32 ? (f >> 4) * 2 + (G & 1) : u >> 3, step = u < 32 ? (f & 15) * 2 + (G >> 1 & 1) : G & 31;
                char* const tile = (char*)scr->b8 + (7 * 224 + G) * 2048;
                unsigned* const csp = scr->cs + (step * 7 + blk) * 32 + lane;
                uint2 v[32];
                unsigned o[16];
                wait_until(helper ? i * CFG_YH + CFG_YH0 : (G - CFG_NOC * 4) * (CFG_YP / 16) + CFG_Y0, t0);
                load_w(v, qw + step * (32 * N_ * 4) + (49 + blk) * 256 + lane * 8);
                store_w(v, o, tile + ((lane >> 3) * 32 + (lane & 7)) * 16);
                asm volatile("st.global.u32 [%0], %1;" :: "l"(csp), "r"(col_sums(o)) : "memory");
                asm volatile("fence.proxy.async.global;" ::: "memory");
                __syncwarp();
                publish(scr->flag + CS * FS + u, read_back(tile + lane * 64) | read_back(csp), blockIdx.y);
            }
        }
        if (warp == 8) {
            if (helper) load_x4(scr, sb, b, blockIdx.x - 16, lane);
            else load_x(scr, sb, b, lane);
            agent = 0;
        } else if (warp == 11) {
            const unsigned tgt = (*(volatile unsigned*)&scr->epoch[b] + 1) * 4;
            const unsigned* f = scr->flag + CS * FS + lane;
            unsigned todo0 = helper ? 0 : ~0u, todo1 = helper ? 0xFF0000 : 0xFFFF, v0 = ld_flag(f), v1 = ld_flag(f + 32);
            bool par = lane >= 2;
            asm volatile("barrier.cluster.wait.aligned;" ::: "memory");
#pragma unroll 1
            for (int it = 0; todo0 | todo1; it++) {
                const unsigned m0 = __ballot_sync(~0u, (int)(v0 - tgt) >= 0) & todo0, m1 = __ballot_sync(~0u, (int)(v1 - tgt) >= 0) & todo1;
                v0 = ld_flag(f); v1 = ld_flag(f + 32);
                todo0 &= ~m0; todo1 &= ~m1;
                if ((lane & 1) == rank) {
                    if (m0 >> lane & 1) mbar_arrive(bars + (B_GO + (lane >> 1)) * 8);
                    if (m1 >> lane & 1) mbar_arrive(bars + (B_GO + 16 + (lane >> 1)) * 8);
                }
                if (!par && !(lane ? todo1 : todo0)) { par = true; mbar_arrive(bars + (B_AFREE + lane) * 8); }
                if (it > (1 << 20)) __trap();
            }
        } else if (warp == 9) {
            asm volatile("barrier.cluster.wait.aligned;" ::: "memory");
            const char* src = (const char*)scr->b8 + (7 * NG + rank) * 8192;
#pragma unroll 1
            for (int i = helper ? 24 : 0, slot = rank; i < (helper ? 28 : 24); i++) {
                asm volatile("{\n.reg .pred p;\nWAIT_LOOP:\nmbarrier.try_wait.parity.shared::cta.b64 p, [%4], 0;\n@!p bra WAIT_LOOP;\n"
                             "elect.sync _|p, 0xffffffff;\n"
                             "@p cp.async.bulk.shared::cluster.global.mbarrier::complete_tx::bytes.multicast::cluster [%0], [%1], 8192, [%2], %3;\n}"
                             :: "r"(sb + SM_RING + slot * 8192), "l"(src + i * 16384),
                                "r"(bars + (B_FULL + bar_of(2 * i + rank)) * 8), "h"((uint16_t)3), "r"(bars + (B_GO + i) * 8) : "memory");
                slot += slot >= NR - 2 ? 2 - NR : 2;
            }
        } else if (warp == 12 || warp == 15) {
            asm volatile("barrier.cluster.wait.aligned;" ::: "memory");
#pragma unroll 1
            for (int blk = helper ? 6 + (warp & 2) : warp & 2; blk < (helper ? 7 : 6); blk += 4) {
                const int w = min(blk * 32 + lane * 2, TN / 2 - 2);
                mbar_wait(bars + (B_AFREE + (blk >> 2)) * 8);
                uint2 v[32];
                unsigned s0[4], s1[4];
                const float zxf = __bfloat162float(__float2bfloat16_rn((float)__ldcg(zero_x)));
#pragma unroll
                for (int k = 0; k < 32; k++) v[k] = __ldcg((const uint2*)(scr->cs + k * (TN / 2) + w));
#pragma unroll
                for (int h = 0; h < 4; h++) {
                    s0[h] = s1[h] = 0;
#pragma unroll
                    for (int k = 0; k < 8; k++) { s0[h] += v[8 * h + k].x; s1[h] += v[8 * h + k].y; }
                }
                sts32(sb + SM_PAR + w * 4, zero_term(s0, zxf));
                sts32(sb + SM_PAR + w * 4 + 4, zero_term(s1, zxf));
                __syncwarp();
                if (lane < 2) mbar_arrive(bars + (B_PAR + blk + lane) * 8);
            }
        } else {
            asm volatile("barrier.cluster.wait.aligned;" ::: "memory");
            agent = warp == 10 ? 1 : warp - 11;
        }
        if (agent >= 0) {
            if (helper) store_out(&map, sb, b, agent, lane, 4, 0x3120, col_of(7, 6), 0, (blockIdx.x - 16) * 512, 128);
            else store_out(&map, sb, b, agent, lane, 6, agent < 2 ? 0x514320 : 0x534120, col_of(7, 0), 64, blockIdx.x * 128, 0);
        }
    } else {
        asm volatile("setmaxnreg.inc.sync.aligned.u32 168;");
        if (helper) consume<2>(scr, scale_w, bias, scale_x, sb, b, warp, lane);
        else consume<1>(scr, scale_w, bias, scale_x, sb, b, warp, lane);
    }
}

}

typedef CUresult (*EncodeFn)(CUtensorMap*, CUtensorMapDataType, cuuint32_t, void*, const cuuint64_t*, const cuuint64_t*,
                             const cuuint32_t*, const cuuint32_t*, CUtensorMapInterleave, CUtensorMapSwizzle,
                             CUtensorMapL2promotion, CUtensorMapFloatOOBfill);

namespace w8 {

constexpr int M_ = 2048, K_ = 1024, N_ = 3584;
constexpr int WA = 160, WB = 64;
constexpr int TN = 2 * WA + 2 * WB;
static_assert(TN == 448, "");
constexpr int X1 = 13;
constexpr int NSLOT = 7, SLOT = WA * 64;
constexpr int NSTG = 3, PFD = 700, NCONV = 5;
constexpr int NU = 48;
constexpr int UX = 32 + NSLOT;
constexpr int NJOB = 22;
constexpr int NCTA = 128;

constexpr int nA = 64, nWA = WA / 4, nWB = WB / 4;
constexpr int SEG1 = X1 * (nA + 2 * nWA);
constexpr int SEG2 = SEG1 + (16 - X1) * (nA + nWA);
constexpr int SEG3 = SEG2 + (16 - X1) * nWA;
constexpr int SEG4 = SEG3 + 16 * nWB;
constexpr int SEG5 = SEG4 + 16 * nWB;
static_assert(SEG5 == NJOB * NCTA, "");

constexpr int SM_A = 0;
constexpr int SM_RING = 131072;
constexpr int SM_STG = SM_RING + NSLOT * SLOT;
constexpr int SM_PAR = SM_STG + NSTG * 8192;
constexpr int SM_BAR = SM_PAR + 3 * TN * 2;
constexpr int B_FULLB = 0, B_FULLA = 48, B_GO = 64, B_PAR = 88, B_PSTEP = 92, B_AFREE = 100, B_NINIT = 102, B_FULLS = 102, B_END = 108;
constexpr int SM_TOTAL = SM_BAR + B_END * 8;
static_assert(SM_TOTAL <= 232448, "");

__device__ uint4 g_a8[M_ * K_ / 16];
__device__ uint4 g_b8[N_ * K_ / 16];
__device__ uint4 g_cs[16 * N_ * 2 / 16];
__device__ unsigned g_flag[16 * 16 + 8 * 64];
__device__ unsigned g_epoch[NCTA];
__device__ unsigned g_sink;
constexpr int SM_ALLOC = SM_TOTAL;

__device__ __forceinline__ void mbar_init(uint32_t bar, uint32_t cnt) {
    asm volatile("mbarrier.init.shared::cta.b64 [%0], %1;" :: "r"(bar), "r"(cnt) : "memory");
}
__device__ __forceinline__ void mbar_expect_tx(uint32_t bar, uint32_t bytes) {
    asm volatile("mbarrier.arrive.expect_tx.shared::cta.b64 _, [%0], %1;" :: "r"(bar), "r"(bytes) : "memory");
}
__device__ __forceinline__ void mbar_arrive(uint32_t bar) {
    asm volatile("mbarrier.arrive.shared::cta.b64 _, [%0];" :: "r"(bar) : "memory");
}
__device__ __forceinline__ void mbar_arrive_cluster(uint32_t bar) {
    asm volatile("mbarrier.arrive.shared::cluster.b64 _, [%0];" :: "r"(bar) : "memory");
}
__device__ __forceinline__ void mbar_wait(uint32_t bar, uint32_t parity = 0) {
    asm volatile("{\n.reg .pred p;\n.reg .u32 c;\n"
                 "mbarrier.try_wait.parity.shared::cta.b64 p, [%0], %1;\n"
                 "@p bra WAIT_DONE;\n"
                 "mov.u32 c, 0;\n"
                 "WAIT_LOOP:\n"
                 "mbarrier.try_wait.parity.shared::cta.b64 p, [%0], %1;\n"
                 "@p bra WAIT_DONE;\n"
                 "add.u32 c, c, 1;\nsetp.lt.u32 p, c, 0x100000;\n"
                 "@p bra WAIT_LOOP;\n"
                 "trap;\n"
                 "WAIT_DONE:\n}" :: "r"(bar), "r"(parity) : "memory");
}
__device__ __forceinline__ void mbar_wait2(uint32_t bar0, uint32_t bar1) {
    asm volatile("{\n.reg .pred p, q;\n.reg .u32 c;\nmov.u32 c, 0;\n"
                 "WAIT_LOOP:\n"
                 "mbarrier.try_wait.parity.shared::cta.b64 p, [%0], 0;\n"
                 "mbarrier.try_wait.parity.shared::cta.b64 q, [%1], 0;\n"
                 "and.pred p, p, q;\n"
                 "@p bra WAIT_DONE;\n"
                 "add.u32 c, c, 1;\nsetp.lt.u32 p, c, 0x100000;\n"
                 "@p bra WAIT_LOOP;\n"
                 "trap;\n"
                 "WAIT_DONE:\n}" :: "r"(bar0), "r"(bar1) : "memory");
}
__device__ __forceinline__ bool mbar_test(uint32_t bar) {
    uint32_t ok;
    asm volatile("{\n.reg .pred p;\nmbarrier.test_wait.parity.shared::cta.b64 p, [%1], 0;\nselp.u32 %0, 1, 0, p;\n}" : "=r"(ok) : "r"(bar) : "memory");
    return ok;
}
__device__ __forceinline__ bool mbar_test2(uint32_t bar0, uint32_t bar1) {
    uint32_t ok;
    asm volatile("{\n.reg .pred p, q;\nmbarrier.test_wait.parity.shared::cta.b64 p, [%1], 0;\n"
                 "mbarrier.test_wait.parity.shared::cta.b64 q, [%2], 0;\nand.pred p, p, q;\nselp.u32 %0, 1, 0, p;\n}"
                 : "=r"(ok) : "r"(bar0), "r"(bar1) : "memory");
    return ok;
}
__device__ __forceinline__ bool elect_one() {
    uint32_t ok;
    asm volatile("{\n.reg .pred p;\nelect.sync _|p, 0xffffffff;\nselp.u32 %0, 1, 0, p;\n}" : "=r"(ok));
    return ok;
}
__device__ __forceinline__ unsigned ld_acquire(const unsigned* p) {
    unsigned v;
    asm volatile("ld.acquire.gpu.global.u32 %0, [%1];" : "=r"(v) : "l"(p) : "memory");
    return v;
}
__device__ __forceinline__ unsigned ld_flag(const unsigned* p) {
    unsigned v;
    asm volatile("ld.relaxed.gpu.global.u32 %0, [%1];" : "=r"(v) : "l"(p) : "memory");
    return v;
}
__device__ __forceinline__ uint4 lds128(uint32_t a) {
    uint4 v;
    asm volatile("ld.shared.v4.b32 {%0,%1,%2,%3}, [%4];" : "=r"(v.x), "=r"(v.y), "=r"(v.z), "=r"(v.w) : "r"(a) : "memory");
    return v;
}
__device__ __forceinline__ void sts128(uint32_t a, uint4 v) {
    asm volatile("st.shared.v4.b32 [%0], {%1,%2,%3,%4};" :: "r"(a), "r"(v.x), "r"(v.y), "r"(v.z), "r"(v.w) : "memory");
}
__device__ __forceinline__ uint32_t lds32(uint32_t a) {
    uint32_t v;
    asm volatile("ld.shared.b32 %0, [%1];" : "=r"(v) : "r"(a) : "memory");
    return v;
}
__device__ __forceinline__ void sts32(uint32_t a, uint32_t v) {
    asm volatile("st.shared.b32 [%0], %1;" :: "r"(a), "r"(v) : "memory");
}
__device__ __forceinline__ void stg128(void* p, uint4 v) {
    asm volatile("st.global.v4.b32 [%0], {%1,%2,%3,%4};" :: "l"(p), "r"(v.x), "r"(v.y), "r"(v.z), "r"(v.w) : "memory");
}
__device__ __forceinline__ unsigned pack4(unsigned a, unsigned b, unsigned c, unsigned d) {
    unsigned lo, r;
    asm("cvt.pack.sat.s8.s32.b32 %0, %1, %2, 0;" : "=r"(lo) : "r"(d), "r"(c));
    asm("cvt.pack.sat.s8.s32.b32 %0, %1, %2, %3;" : "=r"(r) : "r"(b), "r"(a), "r"(lo));
    return r;
}
__device__ __forceinline__ void cpasync16(uint32_t dst, const void* src) {
    asm volatile("cp.async.cg.shared.global [%0], [%1], 16;" :: "r"(dst), "l"(src) : "memory");
}
__device__ __forceinline__ unsigned pf_l2(const void* p) {
    unsigned v;
    asm volatile("ld.global.cg.L2::128B.u32 %0, [%1];" : "=r"(v) : "l"(p) : "memory");
    return v;
}

constexpr uint32_t DESC_A_HI = 0x80000000u | (512 >> 4);
constexpr uint32_t DESC_B_HI = 128 >> 4;
template <int NR> __device__ __forceinline__ void wgmma_n160(int (&d)[NR], uint32_t alo, uint32_t blo, int scale_d) {
    asm volatile("{\n.reg .pred p;\n.reg .b64 da, db;\nsetp.ne.b32 p, %82, 0;\n"
        "mov.b64 da, {%80, %83};\nmov.b64 db, {%81, %84};\n"
        "wgmma.mma_async.sync.aligned.m64n160k32.s32.s8.s8 "
        "{%0, %1, %2, %3, %4, %5, %6, %7, %8, %9, %10, %11, %12, %13, %14, %15, "
        "%16, %17, %18, %19, %20, %21, %22, %23, %24, %25, %26, %27, %28, %29, %30, %31, "
        "%32, %33, %34, %35, %36, %37, %38, %39, %40, %41, %42, %43, %44, %45, %46, %47, "
        "%48, %49, %50, %51, %52, %53, %54, %55, %56, %57, %58, %59, %60, %61, %62, %63, "
        "%64, %65, %66, %67, %68, %69, %70, %71, %72, %73, %74, %75, %76, %77, %78, %79}, "
        "da, db, p;\n}\n"
        : "+r"(d[0]), "+r"(d[1]), "+r"(d[2]), "+r"(d[3]), "+r"(d[4]), "+r"(d[5]), "+r"(d[6]), "+r"(d[7]),
          "+r"(d[8]), "+r"(d[9]), "+r"(d[10]), "+r"(d[11]), "+r"(d[12]), "+r"(d[13]), "+r"(d[14]), "+r"(d[15]),
          "+r"(d[16]), "+r"(d[17]), "+r"(d[18]), "+r"(d[19]), "+r"(d[20]), "+r"(d[21]), "+r"(d[22]), "+r"(d[23]),
          "+r"(d[24]), "+r"(d[25]), "+r"(d[26]), "+r"(d[27]), "+r"(d[28]), "+r"(d[29]), "+r"(d[30]), "+r"(d[31]),
          "+r"(d[32]), "+r"(d[33]), "+r"(d[34]), "+r"(d[35]), "+r"(d[36]), "+r"(d[37]), "+r"(d[38]), "+r"(d[39]),
          "+r"(d[40]), "+r"(d[41]), "+r"(d[42]), "+r"(d[43]), "+r"(d[44]), "+r"(d[45]), "+r"(d[46]), "+r"(d[47]),
          "+r"(d[48]), "+r"(d[49]), "+r"(d[50]), "+r"(d[51]), "+r"(d[52]), "+r"(d[53]), "+r"(d[54]), "+r"(d[55]),
          "+r"(d[56]), "+r"(d[57]), "+r"(d[58]), "+r"(d[59]), "+r"(d[60]), "+r"(d[61]), "+r"(d[62]), "+r"(d[63]),
          "+r"(d[64]), "+r"(d[65]), "+r"(d[66]), "+r"(d[67]), "+r"(d[68]), "+r"(d[69]), "+r"(d[70]), "+r"(d[71]),
          "+r"(d[72]), "+r"(d[73]), "+r"(d[74]), "+r"(d[75]), "+r"(d[76]), "+r"(d[77]), "+r"(d[78]), "+r"(d[79])
        : "r"(alo), "r"(blo), "r"(scale_d), "r"(DESC_A_HI), "r"(DESC_B_HI));
}
template <int NR> __device__ __forceinline__ void wgmma_t128(int (&d)[NR], uint32_t alo, uint32_t blo, int scale_d) {
    asm volatile("{\n.reg .pred p;\n.reg .b64 da, db;\nsetp.ne.b32 p, %66, 0;\n"
        "mov.b64 da, {%64, %67};\nmov.b64 db, {%65, %68};\n"
        "wgmma.mma_async.sync.aligned.m64n128k32.s32.s8.s8 "
        "{%0, %1, %2, %3, %4, %5, %6, %7, %8, %9, %10, %11, %12, %13, %14, %15, "
        "%16, %17, %18, %19, %20, %21, %22, %23, %24, %25, %26, %27, %28, %29, %30, %31, "
        "%32, %33, %34, %35, %36, %37, %38, %39, %40, %41, %42, %43, %44, %45, %46, %47, "
        "%48, %49, %50, %51, %52, %53, %54, %55, %56, %57, %58, %59, %60, %61, %62, %63}, "
        "da, db, p;\n}\n"
        : "+r"(d[0]), "+r"(d[1]), "+r"(d[2]), "+r"(d[3]), "+r"(d[4]), "+r"(d[5]), "+r"(d[6]), "+r"(d[7]),
          "+r"(d[8]), "+r"(d[9]), "+r"(d[10]), "+r"(d[11]), "+r"(d[12]), "+r"(d[13]), "+r"(d[14]), "+r"(d[15]),
          "+r"(d[16]), "+r"(d[17]), "+r"(d[18]), "+r"(d[19]), "+r"(d[20]), "+r"(d[21]), "+r"(d[22]), "+r"(d[23]),
          "+r"(d[24]), "+r"(d[25]), "+r"(d[26]), "+r"(d[27]), "+r"(d[28]), "+r"(d[29]), "+r"(d[30]), "+r"(d[31]),
          "+r"(d[32]), "+r"(d[33]), "+r"(d[34]), "+r"(d[35]), "+r"(d[36]), "+r"(d[37]), "+r"(d[38]), "+r"(d[39]),
          "+r"(d[40]), "+r"(d[41]), "+r"(d[42]), "+r"(d[43]), "+r"(d[44]), "+r"(d[45]), "+r"(d[46]), "+r"(d[47]),
          "+r"(d[48]), "+r"(d[49]), "+r"(d[50]), "+r"(d[51]), "+r"(d[52]), "+r"(d[53]), "+r"(d[54]), "+r"(d[55]),
          "+r"(d[56]), "+r"(d[57]), "+r"(d[58]), "+r"(d[59]), "+r"(d[60]), "+r"(d[61]), "+r"(d[62]), "+r"(d[63])
        : "r"(alo), "r"(blo), "r"(scale_d), "r"(DESC_B_HI), "r"(DESC_A_HI));
}

__device__ __forceinline__ void wg_fence() { asm volatile("wgmma.fence.sync.aligned;" ::: "memory"); }
__device__ __forceinline__ void wg_commit() { asm volatile("wgmma.commit_group.sync.aligned;" ::: "memory"); }
template <int N> __device__ __forceinline__ void wg_wait() { asm volatile("wgmma.wait_group.sync.aligned %0;" :: "n"(N) : "memory"); }

struct Job { int src; int dst; };
__host__ __device__ constexpr int unit_of(int piece, int slab) {
    return piece < 2 ? (slab < X1 ? 2 * slab + piece : (piece ? 16 : X1) + slab) : 32 + (piece - 2) * 8 + (slab >> 1);
}
__device__ __forceinline__ Job decode_job(int g) {
    int slab, idx, piece;
    if (g < SEG2) {
        int r;
        if (g < SEG1) { slab = g / (nA + 2 * nWA); r = g - slab * (nA + 2 * nWA); }
        else { g -= SEG1; slab = g / (nA + nWA); r = g - slab * (nA + nWA); slab += X1; }
        piece = r < nA ? -1 : (r < nA + nWA ? 0 : 1);
        idx = r < nA ? r : r - nA - piece * nWA;
    } else if (g < SEG3) {
        g -= SEG2; slab = g / nWA; idx = g - slab * nWA; slab += X1; piece = 1;
    } else {
        g -= SEG3; piece = 2 + (g >> 8); slab = (g >> 4) & 15; idx = g & 15;
        static_assert(nWB == 16, "");
    }
    Job j;
    if (piece < 0) {
        const int flag = (idx >> 2) * 16 + slab;
        j.src = idx * 32 + (slab << 12);
        j.dst = (flag * 512 + (idx & 3) * 128) | (flag << 18);
    } else {
        const bool wide = piece < 2;
        const int w = wide ? WA : WB;
        const int nb = wide ? idx / (WA / 32) : idx / (WB / 32);
        const int J = idx - nb * (w / 32);
        const int cb = nb * TN + (wide ? piece * WA : 2 * WA - 2 * WB + piece * WB);
        j.src = cb + J * 32 + (slab << 12) + (wide ? 1 << 16 : 2 << 16);
        j.dst = (cb * (K_ / 16) + slab * w * 4 + J * 32) | ((256 + nb * 64 + unit_of(piece, slab)) << 18);
    }
    return j;
}
struct Coord { const CUtensorMap* m; int x, y, z; };
__device__ __forceinline__ Coord job_coord(const CUtensorMap* maps, int src) {
    const bool w = src >> 16;
    const int c0 = src & 0xFFF, slab = (src >> 12) & 15;
    return {maps + (w ? 1 : 0), w ? c0 : 0, w ? slab * 64 : slab * 2, w ? 0 : c0};
}
__device__ __forceinline__ void raw_load(const Coord& c, uint32_t dst, uint32_t bar) {
    mbar_expect_tx(bar, 8192);
    asm volatile("cp.async.bulk.tensor.3d.shared::cluster.global.tile.mbarrier::complete_tx::bytes [%0], [%1, {%2, %3, %4}], [%5];"
                 :: "r"(dst), "l"(c.m), "r"(c.x), "r"(c.y), "r"(c.z), "r"(bar) : "memory");
}
__device__ __forceinline__ void raw_prefetch(const Coord& c) {
    asm volatile("cp.async.bulk.prefetch.tensor.3d.L2.global.tile [%0, {%1, %2, %3}];"
                 :: "l"(c.m), "r"(c.x), "r"(c.y), "r"(c.z) : "memory");
}
__host__ __device__ constexpr unsigned unit_mask(int piece, int s0, int s1) {
    unsigned m = 0;
    for (int s = s0; s < s1; s++) m |= 1u << (unit_of(piece, s) & 31);
    return m;
}
__host__ __device__ constexpr int slot_of(int u) {
    return u < UX ? (u % NSLOT) * (SLOT / 2048) : u < UX + NSTG ? NSLOT * (SLOT / 2048) + (u - UX) * 4 : ((u - NSTG) % NSLOT) * (SLOT / 2048);
}
__host__ __device__ constexpr uint64_t slot_table(int piece) {
    uint64_t t = 0;
    if (piece < 2) for (int s = 0; s < 16; s++) t |= (uint64_t)(unit_of(piece, s) % NSLOT) << (4 * s);
    else for (int s = 0; s < 8; s++) t |= (uint64_t)slot_of(unit_of(piece, 2 * s)) << (8 * s);
    return t;
}
struct Maps { CUtensorMap m[3]; };

__device__ __forceinline__ uint32_t bf2_op_epi(int a, int b, uint32_t zc, uint32_t sx, uint32_t sw, uint32_t bi) {
    uint32_t v;
    float fa = __int2float_rn(a), fb = __int2float_rn(b);
    asm("cvt.rn.bf16x2.f32 %0, %1, %2;" : "=r"(v) : "f"(fb), "f"(fa));
    asm("sub.rn.bf16x2 %0, %0, %1;" : "+r"(v) : "r"(zc));
    asm("mul.rn.bf16x2 %0, %0, %1;" : "+r"(v) : "r"(sx));
    asm("mul.rn.bf16x2 %0, %0, %1;" : "+r"(v) : "r"(sw));
    asm("add.rn.bf16x2 %0, %0, %1;" : "+r"(v) : "r"(bi));
    return v;
}

struct Par { uint4 zc, sw, bi; };
__device__ __forceinline__ Par ld_par(uint32_t p) { return {lds128(p), lds128(p + TN * 2), lds128(p + TN * 4)}; }
__device__ __forceinline__ void epi_row(const int (&a)[WA / 2], int o, const Par& p, uint32_t sx2, char* out) {
    uint4 r;
    r.x = bf2_op_epi(a[o + 0], a[o + 4], p.zc.x, sx2, p.sw.x, p.bi.x);
    r.y = bf2_op_epi(a[o + 8], a[o + 12], p.zc.y, sx2, p.sw.y, p.bi.y);
    r.z = bf2_op_epi(a[o + 1], a[o + 5], p.zc.z, sx2, p.sw.z, p.bi.z);
    r.w = bf2_op_epi(a[o + 9], a[o + 13], p.zc.w, sx2, p.sw.w, p.bi.w);
    stg128(out, r);
}
template <int J, int JN>
__device__ __forceinline__ void epilogue(const int (&a)[WA / 2], Par& p, uint32_t par, uint32_t sx2, char* out) {
    epi_row(a, J * 16, p, sx2, out + J * 64);
    Par n = p;
    if (JN != J) n = ld_par(par + JN * 64);
    epi_row(a, J * 16 + 2, p, sx2, out + 8 * (N_ * 2) + J * 64);
    p = n;
}

__global__ void __cluster_dims__(2, 1, 1) __launch_bounds__(512, 1)
w8a8_kernel(const __grid_constant__ Maps maps, const char* __restrict__ qx, const char* __restrict__ qw, const __nv_bfloat16* __restrict__ scale_x, const int* __restrict__ zero_x,
            const __nv_bfloat16* __restrict__ scale_w, const __nv_bfloat16* __restrict__ bias,
            __nv_bfloat16* __restrict__ out) {
    extern __shared__ __align__(1024) unsigned char smem_raw[];
    const uint32_t sb = (uint32_t)__cvta_generic_to_shared(smem_raw);
    const uint32_t bars = sb + SM_BAR;
    const int warp = __shfl_sync(~0u, threadIdx.x >> 5, 0), lane = threadIdx.x & 31;
    const int b = blockIdx.x, rank = b & 1, nb = (b >> 1) & 7, mb = (b >> 4) * 2 + rank;

    if (warp >= 8) {
        asm volatile("setmaxnreg.dec.sync.aligned.u32 56;");
        if (warp >= 16 - NCONV) {
            const int cw = warp - (16 - NCONV);
            unsigned t0;
            asm volatile("mov.u32 %0, %clock;" : "=r"(t0));
            t0 += 100;
            asm volatile("barrier.cluster.arrive.relaxed.aligned;" ::: "memory");
            const Job mj = decode_job(min(lane, NJOB - 1) * NCTA + b);
            static_assert(NCONV == NSTG + 2 && NJOB == 22, "");
            const uint32_t s = sb + (cw < NSTG ? SM_STG + cw * 8192 : SM_A + (14 - NSTG + cw) * 8192);
            const uint32_t sbar = bars + (B_FULLS + cw) * 8;
            {
                const Coord c = job_coord(maps.m, __shfl_sync(~0u, mj.src, cw));
                if (elect_one()) {
                    mbar_init(sbar, 1);
                    asm volatile("fence.mbarrier_init.release.cluster;" ::: "memory");
                    unsigned t;
                    do { asm volatile("mov.u32 %0, %clock;" : "=r"(t)); } while ((int)(t - t0) < cw * PFD + (cw ? b * 88 : b * 0) / 16);
                    raw_load(c, s, sbar);
                }
                __syncwarp();
            }
            asm volatile("barrier.cluster.wait.aligned;" ::: "memory");
            t0 += b * 88 / 16;
            const int c4 = lane & 3, ln = (lane >> 2) * 2 + (c4 >> 1);
            const uint32_t rdA = ln * 128 + ((((c4 & 1) << 2) ^ (ln & 7)) << 4);
            const uint32_t rdB = (lane >> 3) * 2048 + (lane & 7) * 16;
            const int wrA = (lane >> 2) * 4 + (c4 ^ ((lane >> 3) & 3));
            uint32_t par = 0;
#pragma unroll 1
            for (int j = cw, jn; j < NJOB; j = jn, par ^= 1) {
                jn = j < 13 ? j + NCONV : (j < 15 ? 31 : j + NSTG);
                const int src = __shfl_sync(~0u, mj.src, j), dst = __shfl_sync(~0u, mj.dst, j);
                const int nsrc = __shfl_sync(~0u, mj.src, jn);
                const int kind = src >> 16;
                uint4 o[4];
                uint4* d;
                int dstep;
                mbar_wait(sbar, par);
                if (kind == 0) {
                    const uint32_t a0 = s + rdA;
                    d = g_a8 + (dst & 0x3FFFF) + wrA;
                    dstep = 32;
#pragma unroll
                    for (int i = 0; i < 4; i++) {
                        uint4 v0 = lds128(a0 + i * 2048), v1 = lds128((a0 ^ 16) + i * 2048);
                        uint4 v2 = lds128((a0 ^ 32) + i * 2048), v3 = lds128((a0 ^ 48) + i * 2048);
                        o[i].x = pack4(v0.x, v0.y, v0.z, v0.w); o[i].y = pack4(v1.x, v1.y, v1.z, v1.w);
                        o[i].z = pack4(v2.x, v2.y, v2.z, v2.w); o[i].w = pack4(v3.x, v3.y, v3.z, v3.w);
                    }
                } else {
                    const uint32_t a0 = s + rdB;
                    d = g_b8 + (dst & 0x3FFFF) + (lane >> 3) * (kind == 1 ? WA : WB) + (lane & 7);
                    dstep = 8;
#define CV_B(m, f)                                                                                    \
                    {                                                                                 \
                        uint4 v0 = lds128(a0 + m * 512), v1 = lds128(a0 + m * 512 + 128);             \
                        uint4 v2 = lds128(a0 + m * 512 + 256), v3 = lds128(a0 + m * 512 + 384);       \
                        o[0].f = pack4(v0.x, v1.x, v2.x, v3.x); o[1].f = pack4(v0.y, v1.y, v2.y, v3.y); \
                        o[2].f = pack4(v0.z, v1.z, v2.z, v3.z); o[3].f = pack4(v0.w, v1.w, v2.w, v3.w); \
                    }
                    CV_B(0, x) CV_B(1, y) CV_B(2, z) CV_B(3, w)
                }
#pragma unroll
                for (int i = 0; i < 4; i++) stg128(d + i * dstep, o[i]);
                unsigned tn;
                asm volatile("mov.u32 %0, %clock;" : "=r"(tn));
                const bool late = jn < NJOB && (int)(tn - t0) < jn * PFD;
                if (!late && elect_one()) {
                    if (jn < NJOB) { raw_load(job_coord(maps.m, nsrc), s, sbar); }
                    else if (jn == 31) mbar_arrive(bars + (B_AFREE - NSTG + cw) * 8);
                    else if (0 != 1) {
                        uint32_t ra;
                        asm("mapa.shared::cluster.u32 %0, %1, %2;" : "=r"(ra) : "r"(bars + (B_GO + ((UX + cw) >> 1)) * 8), "r"((UX + cw) & 1));
                        mbar_arrive_cluster(ra);
                    }
                }
                const int* csp = (const int*)d;
                unsigned csv = o[0].x;
                if (kind != 0) {
                    int cs[4];
#pragma unroll
                    for (int i = 0; i < 4; i++)
                        cs[i] = __dp4a((int)o[i].x, 0x01010101, __dp4a((int)o[i].y, 0x01010101,
                                __dp4a((int)o[i].z, 0x01010101, __dp4a((int)o[i].w, 0x01010101, 0))));
                    const int p01 = cs[0] + cs[1] * 65536, p23 = cs[2] + cs[3] * 65536;
                    const bool odd = lane & 8;
                    int v = (odd ? p23 : p01) + __shfl_xor_sync(~0u, odd ? p01 : p23, 8);
                    v += __shfl_xor_sync(~0u, v, 16);
                    int* p = (int*)g_cs + ((src >> 12) & 15) * (N_ / 2) + ((src & 0xFFF) >> 1) + (lane & 15);
                    if (lane < 16) *p = v;
                    csp = p; csv = v;
                }
#pragma unroll 1
                for (int it = 0; it < 1000; it++) {
                    bool ok = true;
                    if ((lane & 3) == 0) {
                        unsigned rb[5];
#pragma unroll
                        for (int i = 0; i < 4; i++)
                            asm volatile("ld.relaxed.gpu.global.u32 %0, [%1];" : "=r"(rb[i]) : "l"(d + i * dstep) : "memory");
                        asm volatile("ld.relaxed.gpu.global.u32 %0, [%1];" : "=r"(rb[4]) : "l"(csp) : "memory");
                        ok = rb[0] == o[0].x && rb[1] == o[1].x && rb[2] == o[2].x && rb[3] == o[3].x && rb[4] == csv;
                    }
                    if (__all_sync(~0u, ok)) break;
                }
                if (elect_one()) asm volatile("red.relaxed.gpu.global.add.u32 [%0], 1;" :: "l"(g_flag + ((unsigned)dst >> 18)) : "memory");
                __syncwarp();
                if (late && elect_one()) {
                    do { asm volatile("mov.u32 %0, %clock;" : "=r"(tn)); } while ((int)(tn - t0) < jn * PFD);
                    raw_load(job_coord(maps.m, nsrc), s, sbar);
                }
                __syncwarp();
            }
        } else if (warp == 8) {
            asm volatile("barrier.cluster.arrive.relaxed.aligned;" ::: "memory");
            const unsigned ep = *(volatile unsigned*)&g_epoch[b] + 1;
            const unsigned* f1 = g_flag + 256 + nb * 64 + lane;
            const unsigned* f2 = lane < 16 ? f1 + 32 : g_flag + mb * 16 + lane - 16;
            const unsigned t1 = ep * (WA / 32), t2 = ep * 4;
            static_assert(WB / 16 == 4, "");
            const unsigned n1 = lane == 0 ? unit_mask(0, 0, 8) : lane == 1 ? unit_mask(1, 0, 8) : lane == 2 ? unit_mask(0, 8, 16)
                              : lane == 3 ? unit_mask(1, 8, 16) : 0u;
            const unsigned n2 = lane < 4 ? 0u : 0xFFFFu;
            bool d1 = false, d2 = false, d3 = lane >= 5, fr = lane < 30;
            asm volatile("barrier.cluster.wait.aligned;" ::: "memory");
            for (int it = 0; 0 != 1; it++) {
                unsigned v1 = t1, v2 = t2;
                if (!d1) v1 = ld_flag(f1);
                if (!d2) v2 = ld_flag(f2);
                if (!fr) fr = mbar_test(bars + (B_AFREE - 30 + lane) * 8);
                if (!d2 && fr && (int)(v2 - t2) >= 0) {
                    d2 = true;
                    if (lane >= 16) {
                        asm volatile("fence.proxy.async.global;" ::: "memory");
                        asm volatile("cp.async.bulk.shared::cluster.global.mbarrier::complete_tx::bytes [%0], [%1], %2, [%3];"
                                     :: "r"(sb + SM_A + (lane - 16) * 8192), "l"((const char*)g_a8 + (mb * 16 + lane - 16) * 8192),
                                        "r"(8192), "r"(bars + (B_FULLA + lane - 16) * 8) : "memory");
                    } else if ((lane & 1) == rank) mbar_arrive(bars + (B_GO + 16 + (lane >> 1)) * 8);
                }
                if (!d1 && (int)(v1 - t1) >= 0) {
                    d1 = true;
                    if ((lane & 1) == rank) mbar_arrive(bars + (B_GO + (lane >> 1)) * 8);
                }
                const unsigned m1 = __ballot_sync(~0u, d1), m2 = __ballot_sync(~0u, d2);
                if (!d3 && (m1 & n1) == n1 && (m2 & n2) == n2) { d3 = true; mbar_arrive(bars + (B_PSTEP + lane) * 8); }
                if ((m1 & m2) == ~0u) break;
                if (it > (1 << 22)) __trap();
            }
        } else if (warp == 9) {
            asm volatile("barrier.cluster.arrive.relaxed.aligned;" ::: "memory");
            const int u = 2 * lane + rank;
            int so, fb;
            if (u < 2 * X1) { so = (u & 1) * (WA * K_) + (u >> 1) * (WA * 64); fb = (u & 1) * 24 + (u >> 1); }
            else if (u < X1 + 16) { so = (u - X1) * (WA * 64); fb = u - X1; }
            else if (u < 32) { so = WA * K_ + (u - 16) * (WA * 64); fb = 24 + u - 16; }
            else { so = 2 * WA * K_ + (u - 32) * (WB * 128); fb = u < 40 ? u - 16 : u; }
            const char* srcB = (const char*)g_b8 + nb * TN * K_ + so;
            const uint32_t dstB = sb + SM_RING + slot_of(u) * 2048;
            asm volatile("barrier.cluster.wait.aligned;" ::: "memory");
#pragma unroll 1
            for (int i = 0; i < NU / 2 && 0 != 1; i++) {
                mbar_wait(bars + (B_GO + i) * 8);
                if (lane == i) {
                    asm volatile("fence.proxy.async.global;" ::: "memory");
                    asm volatile("cp.async.bulk.shared::cluster.global.mbarrier::complete_tx::bytes.multicast::cluster [%0], [%1], %2, [%3], %4;"
                                 :: "r"(dstB), "l"(srcB), "r"(u < 32 ? WA * 64 : WB * 128), "r"(bars + (B_FULLB + fb) * 8), "h"((uint16_t)3) : "memory");
                }
                __syncwarp();
            }
        } else if (warp == 10) {
            unsigned pv, pv2;
            {
                static_assert(X1 > 0 && nA == 64 && nWA == 40, "");
                const int i = b - (b < 104 ? 64 : 104), q = i / 5;
                const char* p = b < 64 ? qx + (b * 32 + (lane >> 1)) * (K_ * 4) + (lane & 1) * 128
                                       : qw + lane * (N_ * 4) + (q * TN + (b < 104 ? 0 : WA) + (i - q * 5) * 32) * 4;
                pv = pf_l2(p);
                pv2 = pf_l2(p + (b < 64 ? 16 * K_ * 4 : 32 * N_ * 4));
                if (lane < 3) asm volatile("prefetch.tensormap [%0];" :: "l"(maps.m + lane) : "memory");
            }
            asm volatile("barrier.cluster.arrive.relaxed.aligned;" ::: "memory");
            if ((pv ^ pv2) == 0x40000000u) g_sink = pv;
            const float zxf = __bfloat162float(__float2bfloat16_rn((float)__ldg(zero_x)));
#pragma unroll 1
            for (int i = lane; i < TN / 4; i += 32) {
                const bool hi = i >= TN / 8;
                sts128(sb + SM_PAR + TN * 2 + i * 16, __ldg((const uint4*)((hi ? bias : scale_w) + nb * TN) + (hi ? i - TN / 8 : i)));
            }
            asm volatile("barrier.cluster.wait.aligned;" ::: "memory");
            int c[8], cs[8];
#pragma unroll
            for (int i = 0; i < 8; i++) { c[i] = 0; cs[i] = 0; }
#pragma unroll 1
            for (int st = 0; st < 5 && 0 != 1; st++) {
                const bool wide = st < 4;
                const int half = wide ? (st >> 1) : (lane >> 4);
                const int col = wide ? (st & 1) * WA + min(lane, WA / 8 - 1) * 8 : 2 * WA + (lane & 15) * 8;
                const uint4* src = g_cs + (half * 8 * N_ + nb * TN + col) / 8;
                mbar_wait(bars + (B_PSTEP + st) * 8);
                uint4 v[8];
#pragma unroll
                for (int i = 0; i < 8; i++) v[i] = __ldcg(src + i * (N_ / 8));
#pragma unroll
                for (int h = 0; h < 8; h += 4) {
                    const unsigned sv[4] = {v[h].x + v[h + 1].x + v[h + 2].x + v[h + 3].x, v[h].y + v[h + 1].y + v[h + 2].y + v[h + 3].y,
                                            v[h].z + v[h + 1].z + v[h + 2].z + v[h + 3].z, v[h].w + v[h + 1].w + v[h + 2].w + v[h + 3].w};
#pragma unroll
                    for (int i = 0; i < 4; i++) {
                        const int lo = (int)(short)(sv[i] & 0xFFFF);
                        c[2 * i] += lo; c[2 * i + 1] += ((int)(sv[i] - (unsigned)lo)) >> 16;
                    }
                }
                if (st >= 2) {
                    uint32_t z[4];
#pragma unroll
                    for (int i = 0; i < 8; i++) {
                        const int o = __shfl_xor_sync(~0u, c[i], 16);
                        if (!wide) c[i] += o;
                    }
#pragma unroll
                    for (int i = 0; i < 4; i++) {
                        const float lo = __bfloat162float(__float2bfloat16_rn((float)c[2 * i])) * zxf;
                        const float hi = __bfloat162float(__float2bfloat16_rn((float)c[2 * i + 1])) * zxf;
                        asm("cvt.rn.bf16x2.f32 %0, %1, %2;" : "=r"(z[i]) : "f"(hi), "f"(lo));
                    }
                    const uint32_t za = sb + SM_PAR + ((col & ~31) + (col & 8) * 2 + ((col >> 3) & 2)) * 2;
#pragma unroll
                    for (int i = 0; i < 4; i++) sts32(za + i * 8, z[i]);
                    __syncwarp();
                    if (lane == 0) { mbar_arrive(bars + (B_PAR + st - 2) * 8); }
#pragma unroll
                    for (int i = 0; i < 8; i++) c[i] = 0;
                }
#pragma unroll
                for (int i = 0; i < 8; i++) { const int t = c[i]; c[i] = cs[i]; cs[i] = t; }
            }
        } else {
            asm volatile("barrier.cluster.arrive.relaxed.aligned;" ::: "memory");
            asm volatile("barrier.cluster.wait.aligned;" ::: "memory");
        }
    } else {
        asm volatile("setmaxnreg.inc.sync.aligned.u32 200;");
        {
            constexpr int PER = (B_NINIT + 7) / 8;
            if (elect_one()) {
#pragma unroll 1
                for (int i = warp * PER; i < min(warp * PER + PER, B_NINIT); i++)
                    {
                    const int u = 2 * (i - B_GO) + rank;
                    mbar_init(bars + i * 8, (i < B_GO || i >= B_PAR || u < NSLOT) ? 1 : (u >= UX && u < UX + NSTG) ? 3 : 9);
                }
            }
            __syncwarp();
            const int i = warp * PER + lane;
            if (lane < PER && i < B_GO) mbar_expect_tx(bars + i * 8, (i < 16 || (i >= 24 && i < 40)) ? WA * 64 : 8192);
            static_assert(WB * 128 == 8192, "");
            asm volatile("fence.mbarrier_init.release.cluster;" ::: "memory");
        }
        asm volatile("barrier.cluster.arrive.relaxed.aligned;" ::: "memory");
        const int wg = warp >> 2;
        const uint32_t sd = (sb & 0x3FFFF) >> 4;
        const unsigned short sxr = __ldg((const unsigned short*)scale_x);
        const uint32_t sx2 = (uint32_t)sxr * 0x10001u;
        char* orow = (char*)out + (size_t)(mb * 128 + (warp & 3) * 16 + (lane >> 2)) * (N_ * 2) + (nb * TN + (lane & 3) * 8 + wg * WA) * 2;
        const uint32_t par = sb + SM_PAR + (lane & 3) * 16 + wg * WA * 2;
        uint32_t reladdr;
        int rell;
        {
            const int u = lane < 16 ? (lane < X1 ? 2 * lane + wg : (wg ? 16 : X1) + lane) : 16 + wg * 8 + lane;
            const int v = u + (u < 32 ? NSLOT : NSLOT + NSTG);
            rell = (lane < 24 && v < NU) ? lane : 99;
            asm("mapa.shared::cluster.u32 %0, %1, %2;" : "=r"(reladdr) : "r"(bars + (B_GO + (v >> 1)) * 8), "r"(v & 1));
        }
        asm volatile("barrier.cluster.wait.aligned;" ::: "memory");
        int a0[WA / 2], a1[WA / 2];
        uint32_t barB = bars + (B_FULLB + wg * 24) * 8;
        bool ready = false;
#define HAND_BACK(done) if (rell <= (done)) { mbar_arrive_cluster(reladdr); rell = 99; }
        if (0 != 1) {
            wg_fence();
            {
                uint64_t tbl = wg ? slot_table(1) : slot_table(0);
                uint32_t da = (sd + (SM_A >> 4)) | (1 << 16);
#pragma unroll 1
                for (int s = 0; s < 16; s++) {
                    const uint32_t db = ((sd + (SM_RING >> 4)) | (WA << 16)) + ((uint32_t)tbl & 15) * (SLOT >> 4);
                    const bool starved = !ready && !mbar_test2(bars + (B_FULLA + s) * 8, barB);
                    if (starved) {
                        wg_wait<0>();
                        HAND_BACK(s - 1)
                        mbar_wait2(bars + (B_FULLA + s) * 8, barB);
                    }
                    wgmma_n160(a0, da, db, s);
                    wgmma_n160(a1, da + 256, db, s);
                    wgmma_n160(a0, da + 2, db + 2 * WA, 1);
                    wgmma_n160(a1, da + 258, db + 2 * WA, 1);
                    wg_commit();
                    HAND_BACK(s - 2)
                    tbl >>= 4; da += 512; barB += 8;
                    ready = mbar_test2(bars + (B_FULLA + min(s + 1, 15)) * 8, barB);
                    wg_wait<1>();
                }
            }
            HAND_BACK(14)
            wg_wait<0>();
            HAND_BACK(15)
            mbar_wait(bars + (B_PAR + wg) * 8);
            Par P = ld_par(par);
            char* const orow1 = orow + 64 * (N_ * 2);
            epilogue<0, 1>(a0, P, par, sx2, orow); epilogue<1, 2>(a0, P, par, sx2, orow);
            epilogue<2, 3>(a0, P, par, sx2, orow); epilogue<3, 0>(a0, P, par, sx2, orow);
            int t[64];
            wg_fence();
            {
                uint64_t tbl = wg ? slot_table(3) : slot_table(2);
                uint32_t da = (sd + (SM_A >> 4)) | (1 << 16);
#pragma unroll
                for (int i = 16; i < 24; i++) {
                    const uint32_t db = ((sd + (SM_RING >> 4)) | (WB << 16)) + ((uint32_t)tbl & 255) * 128;
                    const bool starved = !ready && !mbar_test(barB);
                    if (starved) {
                        wg_wait<0>();
                        HAND_BACK(i - 1)
                        mbar_wait(barB);
                    }
#pragma unroll
                    for (int k = 0; k < 4; k++) wgmma_t128(t, db + k * 2 * WB, da + (k >> 1) * 512 + (k & 1) * 2, k ? 1 : i - 16);
                    wg_commit();
                    HAND_BACK(i - 2)
                    tbl >>= 8; da += 1024; barB += 8;
                    ready = mbar_test(barB);
                    switch (i) {
                        case 16: epilogue<0, 0>(a1, P, par, sx2, orow1); break;
                        case 17: epilogue<1, 1>(a1, P, par, sx2, orow1); break;
                        case 18: epilogue<2, 2>(a1, P, par, sx2, orow1); break;
                        case 19: epilogue<3, 3>(a1, P, par, sx2, orow1); break;
                        case 20: epilogue<4, 4>(a1, P, par, sx2, orow1); break;
                        case 21: epilogue<4, 4>(a0, P, par, sx2, orow); break;
                        default: break;
                    }
                    if (i < 20) P = ld_par(par + (i - 15) * 64);
                    wg_wait<1>();
                }
            }
            HAND_BACK(22)
            mbar_wait(bars + (B_PAR + 2) * 8);
            const int w = warp & 3, q = lane >> 2, c0 = (w >> 1) * 32 + q * 4 + (w & 1) * 2;
            const uint32_t pp = sb + SM_PAR + (2 * WA + wg * WB + c0) * 2;
            const uint32_t zc = lds32(pp), sw = lds32(pp + TN * 2), bi = lds32(pp + TN * 4);
            const int r0 = (lane & 3) * 2;
            const uint32_t st0 = r0 * 128 + (((c0 >> 3) ^ r0) << 4) + (c0 & 7) * 2, st1 = (st0 ^ 16) + 128;
            wg_wait<0>();
            asm volatile("bar.sync %0, 128;" :: "r"(3 + wg) : "memory");
#pragma unroll
            for (int h = 0; h < 2; h++) {
                const uint32_t buf = sb + SM_RING + (wg ? slot_of(UX + 1 + h) : slot_of(UX - 1 + h)) * 2048;
#pragma unroll
                for (int j = 0; j < 8; j++) {
                    const int o = h * 32 + j * 4;
                    sts32(buf + st0 + j * 1024, bf2_op_epi(t[o], t[o + 2], zc, sx2, sw, bi));
                    sts32(buf + st1 + j * 1024, bf2_op_epi(t[o + 1], t[o + 3], zc, sx2, sw, bi));
                }
                asm volatile("fence.proxy.async.shared::cta;" ::: "memory");
                asm volatile("bar.sync %0, 128;" :: "r"(3 + wg) : "memory");
                if (w == 0 && elect_one())
                    asm volatile("cp.async.bulk.tensor.2d.global.shared::cta.tile.bulk_group [%0, {%1, %2}], [%3];"
                                 :: "l"(maps.m + 2), "r"(nb * TN + 2 * WA + wg * WB), "r"(mb * 128 + h * 64), "r"(buf) : "memory");
            }
            if (w == 0) {
                asm volatile("cp.async.bulk.commit_group;" ::: "memory");
                asm volatile("cp.async.bulk.wait_group.read 0;" ::: "memory");
            }
        }
        if (threadIdx.x == 128) asm volatile("red.relaxed.gpu.global.add.u32 [%0], 1;" :: "l"(g_epoch + b) : "memory");
    }
}

static void launch(EncodeFn encode, void* const* d_in, void* d_out) {
    Maps maps;
    CUtensorMap &mx = maps.m[0], &mw = maps.m[1];
    {
        const cuuint64_t dim[3] = {32, K_ / 32, M_}, str[2] = {128, K_ * 4};
        const cuuint32_t box[3] = {32, 2, 32}, es[3] = {1, 1, 1};
        encode(&mx, CU_TENSOR_MAP_DATA_TYPE_INT32, 3, d_in[0], dim, str, box, es, CU_TENSOR_MAP_INTERLEAVE_NONE,
               CU_TENSOR_MAP_SWIZZLE_128B, CU_TENSOR_MAP_L2_PROMOTION_NONE, CU_TENSOR_MAP_FLOAT_OOB_FILL_NONE);
    }
    {
        const cuuint64_t dim[3] = {N_, K_, 1}, str[2] = {N_ * 4, (cuuint64_t)N_ * K_ * 4};
        const cuuint32_t box[3] = {32, 64, 1}, es[3] = {1, 1, 1};
        encode(&mw, CU_TENSOR_MAP_DATA_TYPE_INT32, 3, d_in[1], dim, str, box, es, CU_TENSOR_MAP_INTERLEAVE_NONE,
               CU_TENSOR_MAP_SWIZZLE_NONE, CU_TENSOR_MAP_L2_PROMOTION_NONE, CU_TENSOR_MAP_FLOAT_OOB_FILL_NONE);
    }
    {
        const cuuint64_t dim[2] = {N_, M_}, str[1] = {N_ * 2};
        const cuuint32_t box[2] = {WB, 64}, es[2] = {1, 1};
        encode(&maps.m[2], CU_TENSOR_MAP_DATA_TYPE_BFLOAT16, 2, d_out, dim, str, box, es, CU_TENSOR_MAP_INTERLEAVE_NONE,
               CU_TENSOR_MAP_SWIZZLE_128B, CU_TENSOR_MAP_L2_PROMOTION_NONE, CU_TENSOR_MAP_FLOAT_OOB_FILL_NONE);
    }
    w8a8_kernel<<<NCTA, 512, SM_ALLOC>>>(maps, (const char*)d_in[0], (const char*)d_in[1], (const __nv_bfloat16*)d_in[2], (const int*)d_in[3],
                                         (const __nv_bfloat16*)d_in[4], (const __nv_bfloat16*)d_in[5],
                                         (__nv_bfloat16*)d_out);
}

}

extern "C" void kernel_launch(void* const* d_in, const int* in_sizes, int n_in, void* d_out, int out_size) {
    using namespace ra;
    static EncodeFn encode = nullptr;
    static Scratch* scr = nullptr;
    static const JobTable* jobs = nullptr;
    static bool fits = false;
    if (!encode) {
        void* fn = nullptr;
        cudaDriverEntryPointQueryResult qr;
        cudaGetDriverEntryPoint("cuTensorMapEncodeTiled", &fn, cudaEnableDefault, &qr);
        encode = (EncodeFn)fn;
        cudaGetSymbolAddress((void**)&scr, g_scratch);
        cudaGetSymbolAddress((void**)&jobs, g_jobs);
        cudaFuncSetAttribute(w8a8_kernel, cudaFuncAttributeMaxDynamicSharedMemorySize, SM_ALLOC);
        cudaFuncSetAttribute(w8a8_kernel, cudaFuncAttributeNonPortableClusterSizeAllowed, 1);
        cudaFuncSetAttribute(w8a8_side, cudaFuncAttributeMaxDynamicSharedMemorySize, SM_ALLOC);
        cudaFuncSetAttribute(w8::w8a8_kernel, cudaFuncAttributeMaxDynamicSharedMemorySize, w8::SM_ALLOC);
        cudaLaunchConfig_t oc = {};
        oc.gridDim = dim3(NCTA); oc.blockDim = dim3(512); oc.dynamicSmemBytes = SM_ALLOC;
        cudaLaunchAttribute oa[1];
        oa[0].id = cudaLaunchAttributeClusterDimension; oa[0].val.clusterDim.x = CS; oa[0].val.clusterDim.y = 1; oa[0].val.clusterDim.z = 1;
        oc.attrs = oa; oc.numAttrs = 1;
        int nc = 0, dev = 0, sms = 0;
        cudaGetDevice(&dev);
        cudaDeviceGetAttribute(&sms, cudaDevAttrMultiProcessorCount, dev);
        fits = cudaOccupancyMaxActiveClusters(&nc, w8a8_kernel, &oc) == cudaSuccess && nc >= NCTA / CS && sms >= NCTA + NSIDE;
        cudaGetLastError();
    }
    if (!fits) { w8::launch(encode, d_in, d_out); return; }
    CUtensorMap map;
    {
        const cuuint64_t dim[2] = {N_, M_}, str[1] = {N_ * 2};
        const cuuint32_t box[2] = {64, 32}, es[2] = {1, 1};
        encode(&map, CU_TENSOR_MAP_DATA_TYPE_BFLOAT16, 2, d_out, dim, str, box, es, CU_TENSOR_MAP_INTERLEAVE_NONE,
               CU_TENSOR_MAP_SWIZZLE_128B, CU_TENSOR_MAP_L2_PROMOTION_NONE, CU_TENSOR_MAP_FLOAT_OOB_FILL_NONE);
    }
    w8a8_kernel<<<NCTA, 512, SM_ALLOC, cudaStreamPerThread>>>((const char*)d_in[0], (const char*)d_in[1], scr, jobs, (const __nv_bfloat16*)d_in[4],
                                                             (const __nv_bfloat16*)d_in[5], (const __nv_bfloat16*)d_in[2], (const int*)d_in[3], map);
    cudaLaunchConfig_t cfg = {};
    cfg.gridDim = dim3(NSIDE); cfg.blockDim = dim3(512); cfg.dynamicSmemBytes = SM_ALLOC; cfg.stream = cudaStreamPerThread;
    cudaLaunchAttribute at[1];
    at[0].id = cudaLaunchAttributeProgrammaticStreamSerialization; at[0].val.programmaticStreamSerializationAllowed = 1;
    cfg.attrs = at; cfg.numAttrs = 1;
    cudaLaunchKernelEx(&cfg, w8a8_side, (const char*)d_in[1], scr, (const __nv_bfloat16*)d_in[4], (const __nv_bfloat16*)d_in[5], (const __nv_bfloat16*)d_in[2],
                       (const int*)d_in[3], map);
}
```
